```python
import torch

def _softmax(x, axis=-1):
    return torch.softmax(x, dim=axis)
def _gelu(x):
    return torch.nn.functional.gelu(x, approximate="tanh")
def _silu(x):
    return torch.nn.functional.silu(x)
def _sigmoid(x):
    return torch.sigmoid(x)
def _layernorm(x, axis=-1, eps=1e-5):
    m = x.mean(dim=axis, keepdim=True)
    v = x.var(dim=axis, keepdim=True, unbiased=False)
    return (x - m) / torch.sqrt(v + eps)
def _scatter_add(tgt, idx, src, axis=0):
    return tgt.clone().index_add_(axis, idx, src)
def _segment_sum(src, seg, n):
    out = torch.zeros((n,) + src.shape[1:], dtype=src.dtype)
    return out.index_add_(0, seg, src)
def _pad(x, pw):
    flat = tuple(v for pair in reversed(pw) for v in pair)
    return torch.nn.functional.pad(x, flat)

kernel_name = 'standalone__edge_featured_mpnn_gatedgcn__graph'

def setup_inputs():

    _w = (lambda a: (lambda t: t.to(torch.bfloat16) if t.is_floating_point() else t)(torch.as_tensor(a)))
    N, deg, D, De = 50000, 16, 64, max(16, 1)
    E = N * deg
    return {
        "x": _w((lambda *s: torch.randn(*s, dtype=torch.bfloat16) * 0.4)(N, D)),
        "e_attr": _w((lambda *s: torch.randn(*s, dtype=torch.bfloat16) * 0.8)(E, De)),
        "src": _w((lambda lo, hi, *s: torch.randint(lo, hi, s))(0, N, E).to(torch.int64)),
        "dst": _w((lambda lo, hi, *s: torch.randint(lo, hi, s))(0, N, E).to(torch.int64)),
        "w_a": _w((lambda *s: torch.randn(*s, dtype=torch.bfloat16) * 0.8)(D, D)),
        "w_b": _w((lambda *s: torch.randn(*s, dtype=torch.bfloat16) * 0.4)(D, D)),
        "w_c": _w((lambda *s: torch.randn(*s, dtype=torch.bfloat16) * 0.8)(De, D)),
        "w_u": _w((lambda *s: torch.randn(*s, dtype=torch.bfloat16) * 0.05)(D, D)),
        "w_v": _w((lambda *s: torch.randn(*s, dtype=torch.bfloat16) * 0.05)(D, D)),
    }

def reference(x, e_attr, src, dst, w_a, w_b, w_c, w_u, w_v):
    N, D = x.shape
    hv = x @ w_v
    g = x[dst] @ w_a + x[src] @ w_b + e_attr @ w_c
    eta = _sigmoid(g)
    denom = _segment_sum(eta, dst, N) + 1e-6
    eta_n = eta / denom[dst]
    agg = _segment_sum(eta_n * hv[src], dst, N)
    z = x @ w_u + agg
    relu_z = torch.where(z > 0, z, 0 * z)
    return x + relu_z
```

```cpp
#include <cuda_runtime.h>
#include <cuda.h>
#include <cuda_bf16.h>
#include <stdint.h>

namespace {

constexpr int N_MAX = 65536;
constexpr int NPMAX = 11;
constexpr int NPMIN = 4;
constexpr int THREADS = 512;
constexpr int EPT = 12;
constexpr int CH_MAX = THREADS * EPT;
constexpr int NB_MAX = 134, NB_MIN = 120;
constexpr int CE = 64;
constexpr int P1B = NB_MAX * CE * 2;
constexpr int P2B = NB_MAX * CE * 4;
constexpr int HB = NB_MAX * 64;
constexpr int G_H1 = NB_MAX * (P1B + P2B), G_H2 = G_H1 + HB, G_L = G_H2 + HB, G_END = G_L + NB_MAX * 512;
constexpr int NPB_MAX = 384;
constexpr int SLOT_CAP = 6784;
constexpr int TILE_CAP = 124;
constexpr int TILE_X = 8;
constexpr int NCLS = 64;
constexpr int NSTAGE = 2;
constexpr int TR = 2;
constexpr float LOG2E = 1.4426950408889634f;

__device__ __align__(256) uint4 g_str[G_END / 16];
__device__ __align__(128) unsigned g_bar[96 + 32 * NB_MAX];
__device__ float g_slow[N_MAX * 128];

#define WS(k)
#define WS1(k)
#define WSG(k)
#define WGD()
#define WG0()
#define WG1()
#define CG(k)
#define SMEM_LAUNCH SMEM_BYTES
#define EPOLL 0
#define WSPL 1
#define XT0 1000
#define XDT 800
#define D3 0
#define XMID 0
#define SRCE 0
#define XA 1
#define XC 0
#define XW 1
#define XE 0
#define XEW 1
#define XAFT 1
#define WDET 1
#define H1F 0
#define TSRC 1000
#define G3F 1
#define TLBW 0
#define OWNE 0
#define XPF 0
#define XLD 4
#define XSPL 1
#define P2W 1
#define H2M 0
#define D1 0
#define D2 0
#define FORCE64 0
#define EDHI ((16ull << 32) | (3ull << 62))
template<int NP> struct TileMMA;
template<> struct TileMMA<1> {
  static __device__ __forceinline__ void issue(float* g, float* h, const uint32_t* w, uint64_t dx, uint64_t de, uint64_t dh, uint64_t dc) {
    asm volatile(
      "{\n.reg .b64 dx1, dx2, dx3;\n"
      "add.s64 dx1, %48, 2;\nadd.s64 dx2, %48, 4;\nadd.s64 dx3, %48, 6;\n"
      "wgmma.fence.sync.aligned;\n"
      "wgmma.mma_async.sync.aligned.m64n8k16.f32.bf16.bf16 {%0, %1, %2, %3}, {%44, %45, %46, %47}, %50, 0, 1, 1, 0;\n"
      "wgmma.mma_async.sync.aligned.m64n8k16.f32.bf16.bf16 {%0, %1, %2, %3}, {%24, %25, %26, %27}, %49, 1, 1, 1, 0;\n"
      "wgmma.mma_async.sync.aligned.m64n8k16.f32.bf16.bf16 {%0, %1, %2, %3}, {%8, %9, %10, %11}, %48, 1, 1, 1, 0;\n"
      "wgmma.mma_async.sync.aligned.m64n8k16.f32.bf16.bf16 {%0, %1, %2, %3}, {%12, %13, %14, %15}, dx1, 1, 1, 1, 0;\n"
      "wgmma.mma_async.sync.aligned.m64n8k16.f32.bf16.bf16 {%0, %1, %2, %3}, {%16, %17, %18, %19}, dx2, 1, 1, 1, 0;\n"
      "wgmma.mma_async.sync.aligned.m64n8k16.f32.bf16.bf16 {%0, %1, %2, %3}, {%20, %21, %22, %23}, dx3, 1, 1, 1, 0;\n"
      "wgmma.commit_group.sync.aligned;\n"
      "wgmma.mma_async.sync.aligned.m64n8k16.f32.bf16.bf16 {%4, %5, %6, %7}, {%28, %29, %30, %31}, %48, 0, 1, 1, 0;\n"
      "wgmma.mma_async.sync.aligned.m64n8k16.f32.bf16.bf16 {%4, %5, %6, %7}, {%32, %33, %34, %35}, dx1, 1, 1, 1, 0;\n"
      "wgmma.mma_async.sync.aligned.m64n8k16.f32.bf16.bf16 {%4, %5, %6, %7}, {%36, %37, %38, %39}, dx2, 1, 1, 1, 0;\n"
      "wgmma.mma_async.sync.aligned.m64n8k16.f32.bf16.bf16 {%4, %5, %6, %7}, {%40, %41, %42, %43}, dx3, 1, 1, 1, 0;\n"
      "wgmma.commit_group.sync.aligned;\n}\n"
      : "=f"(g[0]), "=f"(g[1]), "=f"(g[2]), "=f"(g[3]),
        "=f"(h[0]), "=f"(h[1]), "=f"(h[2]), "=f"(h[3])
      : "r"(w[0]), "r"(w[1]), "r"(w[2]), "r"(w[3]), "r"(w[4]), "r"(w[5]), "r"(w[6]), "r"(w[7]), "r"(w[8]), "r"(w[9]), "r"(w[10]), "r"(w[11]), "r"(w[12]), "r"(w[13]), "r"(w[14]), "r"(w[15]), "r"(w[16]), "r"(w[17]), "r"(w[18]), "r"(w[19]), "r"(w[20]), "r"(w[21]), "r"(w[22]), "r"(w[23]), "r"(w[24]), "r"(w[25]), "r"(w[26]), "r"(w[27]), "r"(w[28]), "r"(w[29]), "r"(w[30]), "r"(w[31]), "r"(w[32]), "r"(w[33]), "r"(w[34]), "r"(w[35]), "r"(w[36]), "r"(w[37]), "r"(w[38]), "r"(w[39]), "l"(dx), "l"(de), "l"(dh)
      : "memory");
  }
  static __device__ __forceinline__ void wait_g(float* g) {
    asm volatile("wgmma.wait_group.sync.aligned 1;\n"
      : "+f"(g[0]), "+f"(g[1]), "+f"(g[2]), "+f"(g[3])
      :: "memory");
  }
  static __device__ __forceinline__ void wait_h(float* h) {
    asm volatile("wgmma.wait_group.sync.aligned 0;\n"
      : "+f"(h[0]), "+f"(h[1]), "+f"(h[2]), "+f"(h[3])
      :: "memory");
  }
};
template<> struct TileMMA<2> {
  static __device__ __forceinline__ void issue(float* g, float* h, const uint32_t* w, uint64_t dx, uint64_t de, uint64_t dh, uint64_t dc) {
    asm volatile(
      "{\n.reg .b64 dx1, dx2, dx3;\n"
      "add.s64 dx1, %56, 2;\nadd.s64 dx2, %56, 4;\nadd.s64 dx3, %56, 6;\n"
      "wgmma.fence.sync.aligned;\n"
      "wgmma.mma_async.sync.aligned.m64n16k16.f32.bf16.bf16 {%0, %1, %2, %3, %4, %5, %6, %7}, {%52, %53, %54, %55}, %58, 0, 1, 1, 0;\n"
      "wgmma.mma_async.sync.aligned.m64n16k16.f32.bf16.bf16 {%0, %1, %2, %3, %4, %5, %6, %7}, {%32, %33, %34, %35}, %57, 1, 1, 1, 0;\n"
      "wgmma.mma_async.sync.aligned.m64n16k16.f32.bf16.bf16 {%0, %1, %2, %3, %4, %5, %6, %7}, {%16, %17, %18, %19}, %56, 1, 1, 1, 0;\n"
      "wgmma.mma_async.sync.aligned.m64n16k16.f32.bf16.bf16 {%0, %1, %2, %3, %4, %5, %6, %7}, {%20, %21, %22, %23}, dx1, 1, 1, 1, 0;\n"
      "wgmma.mma_async.sync.aligned.m64n16k16.f32.bf16.bf16 {%0, %1, %2, %3, %4, %5, %6, %7}, {%24, %25, %26, %27}, dx2, 1, 1, 1, 0;\n"
      "wgmma.mma_async.sync.aligned.m64n16k16.f32.bf16.bf16 {%0, %1, %2, %3, %4, %5, %6, %7}, {%28, %29, %30, %31}, dx3, 1, 1, 1, 0;\n"
      "wgmma.commit_group.sync.aligned;\n"
      "wgmma.mma_async.sync.aligned.m64n16k16.f32.bf16.bf16 {%8, %9, %10, %11, %12, %13, %14, %15}, {%36, %37, %38, %39}, %56, 0, 1, 1, 0;\n"
      "wgmma.mma_async.sync.aligned.m64n16k16.f32.bf16.bf16 {%8, %9, %10, %11, %12, %13, %14, %15}, {%40, %41, %42, %43}, dx1, 1, 1, 1, 0;\n"
      "wgmma.mma_async.sync.aligned.m64n16k16.f32.bf16.bf16 {%8, %9, %10, %11, %12, %13, %14, %15}, {%44, %45, %46, %47}, dx2, 1, 1, 1, 0;\n"
      "wgmma.mma_async.sync.aligned.m64n16k16.f32.bf16.bf16 {%8, %9, %10, %11, %12, %13, %14, %15}, {%48, %49, %50, %51}, dx3, 1, 1, 1, 0;\n"
      "wgmma.commit_group.sync.aligned;\n}\n"
      : "=f"(g[0]), "=f"(g[1]), "=f"(g[2]), "=f"(g[3]), "=f"(g[4]), "=f"(g[5]), "=f"(g[6]), "=f"(g[7]),
        "=f"(h[0]), "=f"(h[1]), "=f"(h[2]), "=f"(h[3]), "=f"(h[4]), "=f"(h[5]), "=f"(h[6]), "=f"(h[7])
      : "r"(w[0]), "r"(w[1]), "r"(w[2]), "r"(w[3]), "r"(w[4]), "r"(w[5]), "r"(w[6]), "r"(w[7]), "r"(w[8]), "r"(w[9]), "r"(w[10]), "r"(w[11]), "r"(w[12]), "r"(w[13]), "r"(w[14]), "r"(w[15]), "r"(w[16]), "r"(w[17]), "r"(w[18]), "r"(w[19]), "r"(w[20]), "r"(w[21]), "r"(w[22]), "r"(w[23]), "r"(w[24]), "r"(w[25]), "r"(w[26]), "r"(w[27]), "r"(w[28]), "r"(w[29]), "r"(w[30]), "r"(w[31]), "r"(w[32]), "r"(w[33]), "r"(w[34]), "r"(w[35]), "r"(w[36]), "r"(w[37]), "r"(w[38]), "r"(w[39]), "l"(dx), "l"(de), "l"(dh)
      : "memory");
  }
  static __device__ __forceinline__ void wait_g(float* g) {
    asm volatile("wgmma.wait_group.sync.aligned 1;\n"
      : "+f"(g[0]), "+f"(g[1]), "+f"(g[2]), "+f"(g[3]), "+f"(g[4]), "+f"(g[5]), "+f"(g[6]), "+f"(g[7])
      :: "memory");
  }
  static __device__ __forceinline__ void wait_h(float* h) {
    asm volatile("wgmma.wait_group.sync.aligned 0;\n"
      : "+f"(h[0]), "+f"(h[1]), "+f"(h[2]), "+f"(h[3]), "+f"(h[4]), "+f"(h[5]), "+f"(h[6]), "+f"(h[7])
      :: "memory");
  }
};
template<> struct TileMMA<3> {
  static __device__ __forceinline__ void issue(float* g, float* h, const uint32_t* w, uint64_t dx, uint64_t de, uint64_t dh, uint64_t dc) {
    asm volatile(
      "{\n.reg .b64 dx1, dx2, dx3;\n"
      "add.s64 dx1, %64, 2;\nadd.s64 dx2, %64, 4;\nadd.s64 dx3, %64, 6;\n"
      "wgmma.fence.sync.aligned;\n"
      "wgmma.mma_async.sync.aligned.m64n24k16.f32.bf16.bf16 {%0, %1, %2, %3, %4, %5, %6, %7, %8, %9, %10, %11}, {%60, %61, %62, %63}, %66, 0, 1, 1, 0;\n"
      "wgmma.mma_async.sync.aligned.m64n24k16.f32.bf16.bf16 {%0, %1, %2, %3, %4, %5, %6, %7, %8, %9, %10, %11}, {%40, %41, %42, %43}, %65, 1, 1, 1, 0;\n"
      "wgmma.mma_async.sync.aligned.m64n24k16.f32.bf16.bf16 {%0, %1, %2, %3, %4, %5, %6, %7, %8, %9, %10, %11}, {%24, %25, %26, %27}, %64, 1, 1, 1, 0;\n"
      "wgmma.mma_async.sync.aligned.m64n24k16.f32.bf16.bf16 {%0, %1, %2, %3, %4, %5, %6, %7, %8, %9, %10, %11}, {%28, %29, %30, %31}, dx1, 1, 1, 1, 0;\n"
      "wgmma.mma_async.sync.aligned.m64n24k16.f32.bf16.bf16 {%0, %1, %2, %3, %4, %5, %6, %7, %8, %9, %10, %11}, {%32, %33, %34, %35}, dx2, 1, 1, 1, 0;\n"
      "wgmma.mma_async.sync.aligned.m64n24k16.f32.bf16.bf16 {%0, %1, %2, %3, %4, %5, %6, %7, %8, %9, %10, %11}, {%36, %37, %38, %39}, dx3, 1, 1, 1, 0;\n"
      "wgmma.commit_group.sync.aligned;\n"
      "wgmma.mma_async.sync.aligned.m64n24k16.f32.bf16.bf16 {%12, %13, %14, %15, %16, %17, %18, %19, %20, %21, %22, %23}, {%44, %45, %46, %47}, %64, 0, 1, 1, 0;\n"
      "wgmma.mma_async.sync.aligned.m64n24k16.f32.bf16.bf16 {%12, %13, %14, %15, %16, %17, %18, %19, %20, %21, %22, %23}, {%48, %49, %50, %51}, dx1, 1, 1, 1, 0;\n"
      "wgmma.mma_async.sync.aligned.m64n24k16.f32.bf16.bf16 {%12, %13, %14, %15, %16, %17, %18, %19, %20, %21, %22, %23}, {%52, %53, %54, %55}, dx2, 1, 1, 1, 0;\n"
      "wgmma.mma_async.sync.aligned.m64n24k16.f32.bf16.bf16 {%12, %13, %14, %15, %16, %17, %18, %19, %20, %21, %22, %23}, {%56, %57, %58, %59}, dx3, 1, 1, 1, 0;\n"
      "wgmma.commit_group.sync.aligned;\n}\n"
      : "=f"(g[0]), "=f"(g[1]), "=f"(g[2]), "=f"(g[3]), "=f"(g[4]), "=f"(g[5]), "=f"(g[6]), "=f"(g[7]), "=f"(g[8]), "=f"(g[9]), "=f"(g[10]), "=f"(g[11]),
        "=f"(h[0]), "=f"(h[1]), "=f"(h[2]), "=f"(h[3]), "=f"(h[4]), "=f"(h[5]), "=f"(h[6]), "=f"(h[7]), "=f"(h[8]), "=f"(h[9]), "=f"(h[10]), "=f"(h[11])
      : "r"(w[0]), "r"(w[1]), "r"(w[2]), "r"(w[3]), "r"(w[4]), "r"(w[5]), "r"(w[6]), "r"(w[7]), "r"(w[8]), "r"(w[9]), "r"(w[10]), "r"(w[11]), "r"(w[12]), "r"(w[13]), "r"(w[14]), "r"(w[15]), "r"(w[16]), "r"(w[17]), "r"(w[18]), "r"(w[19]), "r"(w[20]), "r"(w[21]), "r"(w[22]), "r"(w[23]), "r"(w[24]), "r"(w[25]), "r"(w[26]), "r"(w[27]), "r"(w[28]), "r"(w[29]), "r"(w[30]), "r"(w[31]), "r"(w[32]), "r"(w[33]), "r"(w[34]), "r"(w[35]), "r"(w[36]), "r"(w[37]), "r"(w[38]), "r"(w[39]), "l"(dx), "l"(de), "l"(dh)
      : "memory");
  }
  static __device__ __forceinline__ void wait_g(float* g) {
    asm volatile("wgmma.wait_group.sync.aligned 1;\n"
      : "+f"(g[0]), "+f"(g[1]), "+f"(g[2]), "+f"(g[3]), "+f"(g[4]), "+f"(g[5]), "+f"(g[6]), "+f"(g[7]), "+f"(g[8]), "+f"(g[9]), "+f"(g[10]), "+f"(g[11])
      :: "memory");
  }
  static __device__ __forceinline__ void wait_h(float* h) {
    asm volatile("wgmma.wait_group.sync.aligned 0;\n"
      : "+f"(h[0]), "+f"(h[1]), "+f"(h[2]), "+f"(h[3]), "+f"(h[4]), "+f"(h[5]), "+f"(h[6]), "+f"(h[7]), "+f"(h[8]), "+f"(h[9]), "+f"(h[10]), "+f"(h[11])
      :: "memory");
  }
};
template<> struct TileMMA<4> {
  static __device__ __forceinline__ void issue(float* g, float* h, const uint32_t* w, uint64_t dx, uint64_t de, uint64_t dh, uint64_t dc) {
    asm volatile(
      "{\n.reg .b64 dx1, dx2, dx3;\n"
      "add.s64 dx1, %72, 2;\nadd.s64 dx2, %72, 4;\nadd.s64 dx3, %72, 6;\n"
      "wgmma.fence.sync.aligned;\n"
      "wgmma.mma_async.sync.aligned.m64n32k16.f32.bf16.bf16 {%0, %1, %2, %3, %4, %5, %6, %7, %8, %9, %10, %11, %12, %13, %14, %15}, {%68, %69, %70, %71}, %74, 0, 1, 1, 0;\n"
      "wgmma.mma_async.sync.aligned.m64n32k16.f32.bf16.bf16 {%0, %1, %2, %3, %4, %5, %6, %7, %8, %9, %10, %11, %12, %13, %14, %15}, {%48, %49, %50, %51}, %73, 1, 1, 1, 0;\n"
      "wgmma.mma_async.sync.aligned.m64n32k16.f32.bf16.bf16 {%0, %1, %2, %3, %4, %5, %6, %7, %8, %9, %10, %11, %12, %13, %14, %15}, {%32, %33, %34, %35}, %72, 1, 1, 1, 0;\n"
      "wgmma.mma_async.sync.aligned.m64n32k16.f32.bf16.bf16 {%0, %1, %2, %3, %4, %5, %6, %7, %8, %9, %10, %11, %12, %13, %14, %15}, {%36, %37, %38, %39}, dx1, 1, 1, 1, 0;\n"
      "wgmma.mma_async.sync.aligned.m64n32k16.f32.bf16.bf16 {%0, %1, %2, %3, %4, %5, %6, %7, %8, %9, %10, %11, %12, %13, %14, %15}, {%40, %41, %42, %43}, dx2, 1, 1, 1, 0;\n"
      "wgmma.mma_async.sync.aligned.m64n32k16.f32.bf16.bf16 {%0, %1, %2, %3, %4, %5, %6, %7, %8, %9, %10, %11, %12, %13, %14, %15}, {%44, %45, %46, %47}, dx3, 1, 1, 1, 0;\n"
      "wgmma.commit_group.sync.aligned;\n"
      "wgmma.mma_async.sync.aligned.m64n32k16.f32.bf16.bf16 {%16, %17, %18, %19, %20, %21, %22, %23, %24, %25, %26, %27, %28, %29, %30, %31}, {%52, %53, %54, %55}, %72, 0, 1, 1, 0;\n"
      "wgmma.mma_async.sync.aligned.m64n32k16.f32.bf16.bf16 {%16, %17, %18, %19, %20, %21, %22, %23, %24, %25, %26, %27, %28, %29, %30, %31}, {%56, %57, %58, %59}, dx1, 1, 1, 1, 0;\n"
      "wgmma.mma_async.sync.aligned.m64n32k16.f32.bf16.bf16 {%16, %17, %18, %19, %20, %21, %22, %23, %24, %25, %26, %27, %28, %29, %30, %31}, {%60, %61, %62, %63}, dx2, 1, 1, 1, 0;\n"
      "wgmma.mma_async.sync.aligned.m64n32k16.f32.bf16.bf16 {%16, %17, %18, %19, %20, %21, %22, %23, %24, %25, %26, %27, %28, %29, %30, %31}, {%64, %65, %66, %67}, dx3, 1, 1, 1, 0;\n"
      "wgmma.commit_group.sync.aligned;\n}\n"
      : "=f"(g[0]), "=f"(g[1]), "=f"(g[2]), "=f"(g[3]), "=f"(g[4]), "=f"(g[5]), "=f"(g[6]), "=f"(g[7]), "=f"(g[8]), "=f"(g[9]), "=f"(g[10]), "=f"(g[11]), "=f"(g[12]), "=f"(g[13]), "=f"(g[14]), "=f"(g[15]),
        "=f"(h[0]), "=f"(h[1]), "=f"(h[2]), "=f"(h[3]), "=f"(h[4]), "=f"(h[5]), "=f"(h[6]), "=f"(h[7]), "=f"(h[8]), "=f"(h[9]), "=f"(h[10]), "=f"(h[11]), "=f"(h[12]), "=f"(h[13]), "=f"(h[14]), "=f"(h[15])
      : "r"(w[0]), "r"(w[1]), "r"(w[2]), "r"(w[3]), "r"(w[4]), "r"(w[5]), "r"(w[6]), "r"(w[7]), "r"(w[8]), "r"(w[9]), "r"(w[10]), "r"(w[11]), "r"(w[12]), "r"(w[13]), "r"(w[14]), "r"(w[15]), "r"(w[16]), "r"(w[17]), "r"(w[18]), "r"(w[19]), "r"(w[20]), "r"(w[21]), "r"(w[22]), "r"(w[23]), "r"(w[24]), "r"(w[25]), "r"(w[26]), "r"(w[27]), "r"(w[28]), "r"(w[29]), "r"(w[30]), "r"(w[31]), "r"(w[32]), "r"(w[33]), "r"(w[34]), "r"(w[35]), "r"(w[36]), "r"(w[37]), "r"(w[38]), "r"(w[39]), "l"(dx), "l"(de), "l"(dh)
      : "memory");
  }
  static __device__ __forceinline__ void wait_g(float* g) {
    asm volatile("wgmma.wait_group.sync.aligned 1;\n"
      : "+f"(g[0]), "+f"(g[1]), "+f"(g[2]), "+f"(g[3]), "+f"(g[4]), "+f"(g[5]), "+f"(g[6]), "+f"(g[7]), "+f"(g[8]), "+f"(g[9]), "+f"(g[10]), "+f"(g[11]), "+f"(g[12]), "+f"(g[13]), "+f"(g[14]), "+f"(g[15])
      :: "memory");
  }
  static __device__ __forceinline__ void wait_h(float* h) {
    asm volatile("wgmma.wait_group.sync.aligned 0;\n"
      : "+f"(h[0]), "+f"(h[1]), "+f"(h[2]), "+f"(h[3]), "+f"(h[4]), "+f"(h[5]), "+f"(h[6]), "+f"(h[7]), "+f"(h[8]), "+f"(h[9]), "+f"(h[10]), "+f"(h[11]), "+f"(h[12]), "+f"(h[13]), "+f"(h[14]), "+f"(h[15])
      :: "memory");
  }
};
template<> struct TileMMA<5> {
  static __device__ __forceinline__ void issue(float* g, float* h, const uint32_t* w, uint64_t dx, uint64_t de, uint64_t dh, uint64_t dc) {
    asm volatile(
      "{\n.reg .b64 dx1, dx2, dx3;\n"
      "add.s64 dx1, %80, 2;\nadd.s64 dx2, %80, 4;\nadd.s64 dx3, %80, 6;\n"
      "wgmma.fence.sync.aligned;\n"
      "wgmma.mma_async.sync.aligned.m64n40k16.f32.bf16.bf16 {%0, %1, %2, %3, %4, %5, %6, %7, %8, %9, %10, %11, %12, %13, %14, %15, %16, %17, %18, %19}, {%76, %77, %78, %79}, %82, 0, 1, 1, 0;\n"
      "wgmma.mma_async.sync.aligned.m64n40k16.f32.bf16.bf16 {%0, %1, %2, %3, %4, %5, %6, %7, %8, %9, %10, %11, %12, %13, %14, %15, %16, %17, %18, %19}, {%56, %57, %58, %59}, %81, 1, 1, 1, 0;\n"
      "wgmma.mma_async.sync.aligned.m64n40k16.f32.bf16.bf16 {%0, %1, %2, %3, %4, %5, %6, %7, %8, %9, %10, %11, %12, %13, %14, %15, %16, %17, %18, %19}, {%40, %41, %42, %43}, %80, 1, 1, 1, 0;\n"
      "wgmma.mma_async.sync.aligned.m64n40k16.f32.bf16.bf16 {%0, %1, %2, %3, %4, %5, %6, %7, %8, %9, %10, %11, %12, %13, %14, %15, %16, %17, %18, %19}, {%44, %45, %46, %47}, dx1, 1, 1, 1, 0;\n"
      "wgmma.mma_async.sync.aligned.m64n40k16.f32.bf16.bf16 {%0, %1, %2, %3, %4, %5, %6, %7, %8, %9, %10, %11, %12, %13, %14, %15, %16, %17, %18, %19}, {%48, %49, %50, %51}, dx2, 1, 1, 1, 0;\n"
      "wgmma.mma_async.sync.aligned.m64n40k16.f32.bf16.bf16 {%0, %1, %2, %3, %4, %5, %6, %7, %8, %9, %10, %11, %12, %13, %14, %15, %16, %17, %18, %19}, {%52, %53, %54, %55}, dx3, 1, 1, 1, 0;\n"
      "wgmma.commit_group.sync.aligned;\n"
      "wgmma.mma_async.sync.aligned.m64n40k16.f32.bf16.bf16 {%20, %21, %22, %23, %24, %25, %26, %27, %28, %29, %30, %31, %32, %33, %34, %35, %36, %37, %38, %39}, {%60, %61, %62, %63}, %80, 0, 1, 1, 0;\n"
      "wgmma.mma_async.sync.aligned.m64n40k16.f32.bf16.bf16 {%20, %21, %22, %23, %24, %25, %26, %27, %28, %29, %30, %31, %32, %33, %34, %35, %36, %37, %38, %39}, {%64, %65, %66, %67}, dx1, 1, 1, 1, 0;\n"
      "wgmma.mma_async.sync.aligned.m64n40k16.f32.bf16.bf16 {%20, %21, %22, %23, %24, %25, %26, %27, %28, %29, %30, %31, %32, %33, %34, %35, %36, %37, %38, %39}, {%68, %69, %70, %71}, dx2, 1, 1, 1, 0;\n"
      "wgmma.mma_async.sync.aligned.m64n40k16.f32.bf16.bf16 {%20, %21, %22, %23, %24, %25, %26, %27, %28, %29, %30, %31, %32, %33, %34, %35, %36, %37, %38, %39}, {%72, %73, %74, %75}, dx3, 1, 1, 1, 0;\n"
      "wgmma.commit_group.sync.aligned;\n}\n"
      : "=f"(g[0]), "=f"(g[1]), "=f"(g[2]), "=f"(g[3]), "=f"(g[4]), "=f"(g[5]), "=f"(g[6]), "=f"(g[7]), "=f"(g[8]), "=f"(g[9]), "=f"(g[10]), "=f"(g[11]), "=f"(g[12]), "=f"(g[13]), "=f"(g[14]), "=f"(g[15]), "=f"(g[16]), "=f"(g[17]), "=f"(g[18]), "=f"(g[19]),
        "=f"(h[0]), "=f"(h[1]), "=f"(h[2]), "=f"(h[3]), "=f"(h[4]), "=f"(h[5]), "=f"(h[6]), "=f"(h[7]), "=f"(h[8]), "=f"(h[9]), "=f"(h[10]), "=f"(h[11]), "=f"(h[12]), "=f"(h[13]), "=f"(h[14]), "=f"(h[15]), "=f"(h[16]), "=f"(h[17]), "=f"(h[18]), "=f"(h[19])
      : "r"(w[0]), "r"(w[1]), "r"(w[2]), "r"(w[3]), "r"(w[4]), "r"(w[5]), "r"(w[6]), "r"(w[7]), "r"(w[8]), "r"(w[9]), "r"(w[10]), "r"(w[11]), "r"(w[12]), "r"(w[13]), "r"(w[14]), "r"(w[15]), "r"(w[16]), "r"(w[17]), "r"(w[18]), "r"(w[19]), "r"(w[20]), "r"(w[21]), "r"(w[22]), "r"(w[23]), "r"(w[24]), "r"(w[25]), "r"(w[26]), "r"(w[27]), "r"(w[28]), "r"(w[29]), "r"(w[30]), "r"(w[31]), "r"(w[32]), "r"(w[33]), "r"(w[34]), "r"(w[35]), "r"(w[36]), "r"(w[37]), "r"(w[38]), "r"(w[39]), "l"(dx), "l"(de), "l"(dh)
      : "memory");
  }
  static __device__ __forceinline__ void wait_g(float* g) {
    asm volatile("wgmma.wait_group.sync.aligned 1;\n"
      : "+f"(g[0]), "+f"(g[1]), "+f"(g[2]), "+f"(g[3]), "+f"(g[4]), "+f"(g[5]), "+f"(g[6]), "+f"(g[7]), "+f"(g[8]), "+f"(g[9]), "+f"(g[10]), "+f"(g[11]), "+f"(g[12]), "+f"(g[13]), "+f"(g[14]), "+f"(g[15]), "+f"(g[16]), "+f"(g[17]), "+f"(g[18]), "+f"(g[19])
      :: "memory");
  }
  static __device__ __forceinline__ void wait_h(float* h) {
    asm volatile("wgmma.wait_group.sync.aligned 0;\n"
      : "+f"(h[0]), "+f"(h[1]), "+f"(h[2]), "+f"(h[3]), "+f"(h[4]), "+f"(h[5]), "+f"(h[6]), "+f"(h[7]), "+f"(h[8]), "+f"(h[9]), "+f"(h[10]), "+f"(h[11]), "+f"(h[12]), "+f"(h[13]), "+f"(h[14]), "+f"(h[15]), "+f"(h[16]), "+f"(h[17]), "+f"(h[18]), "+f"(h[19])
      :: "memory");
  }
};
template<> struct TileMMA<6> {
  static __device__ __forceinline__ void issue(float* g, float* h, const uint32_t* w, uint64_t dx, uint64_t de, uint64_t dh, uint64_t dc) {
    asm volatile(
      "{\n.reg .b64 dx1, dx2, dx3;\n"
      "add.s64 dx1, %88, 2;\nadd.s64 dx2, %88, 4;\nadd.s64 dx3, %88, 6;\n"
      "wgmma.fence.sync.aligned;\n"
      "wgmma.mma_async.sync.aligned.m64n48k16.f32.bf16.bf16 {%0, %1, %2, %3, %4, %5, %6, %7, %8, %9, %10, %11, %12, %13, %14, %15, %16, %17, %18, %19, %20, %21, %22, %23}, {%84, %85, %86, %87}, %90, 0, 1, 1, 0;\n"
      "wgmma.mma_async.sync.aligned.m64n48k16.f32.bf16.bf16 {%0, %1, %2, %3, %4, %5, %6, %7, %8, %9, %10, %11, %12, %13, %14, %15, %16, %17, %18, %19, %20, %21, %22, %23}, {%64, %65, %66, %67}, %89, 1, 1, 1, 0;\n"
      "wgmma.mma_async.sync.aligned.m64n48k16.f32.bf16.bf16 {%0, %1, %2, %3, %4, %5, %6, %7, %8, %9, %10, %11, %12, %13, %14, %15, %16, %17, %18, %19, %20, %21, %22, %23}, {%48, %49, %50, %51}, %88, 1, 1, 1, 0;\n"
      "wgmma.mma_async.sync.aligned.m64n48k16.f32.bf16.bf16 {%0, %1, %2, %3, %4, %5, %6, %7, %8, %9, %10, %11, %12, %13, %14, %15, %16, %17, %18, %19, %20, %21, %22, %23}, {%52, %53, %54, %55}, dx1, 1, 1, 1, 0;\n"
      "wgmma.mma_async.sync.aligned.m64n48k16.f32.bf16.bf16 {%0, %1, %2, %3, %4, %5, %6, %7, %8, %9, %10, %11, %12, %13, %14, %15, %16, %17, %18, %19, %20, %21, %22, %23}, {%56, %57, %58, %59}, dx2, 1, 1, 1, 0;\n"
      "wgmma.mma_async.sync.aligned.m64n48k16.f32.bf16.bf16 {%0, %1, %2, %3, %4, %5, %6, %7, %8, %9, %10, %11, %12, %13, %14, %15, %16, %17, %18, %19, %20, %21, %22, %23}, {%60, %61, %62, %63}, dx3, 1, 1, 1, 0;\n"
      "wgmma.commit_group.sync.aligned;\n"
      "wgmma.mma_async.sync.aligned.m64n48k16.f32.bf16.bf16 {%24, %25, %26, %27, %28, %29, %30, %31, %32, %33, %34, %35, %36, %37, %38, %39, %40, %41, %42, %43, %44, %45, %46, %47}, {%68, %69, %70, %71}, %88, 0, 1, 1, 0;\n"
      "wgmma.mma_async.sync.aligned.m64n48k16.f32.bf16.bf16 {%24, %25, %26, %27, %28, %29, %30, %31, %32, %33, %34, %35, %36, %37, %38, %39, %40, %41, %42, %43, %44, %45, %46, %47}, {%72, %73, %74, %75}, dx1, 1, 1, 1, 0;\n"
      "wgmma.mma_async.sync.aligned.m64n48k16.f32.bf16.bf16 {%24, %25, %26, %27, %28, %29, %30, %31, %32, %33, %34, %35, %36, %37, %38, %39, %40, %41, %42, %43, %44, %45, %46, %47}, {%76, %77, %78, %79}, dx2, 1, 1, 1, 0;\n"
      "wgmma.mma_async.sync.aligned.m64n48k16.f32.bf16.bf16 {%24, %25, %26, %27, %28, %29, %30, %31, %32, %33, %34, %35, %36, %37, %38, %39, %40, %41, %42, %43, %44, %45, %46, %47}, {%80, %81, %82, %83}, dx3, 1, 1, 1, 0;\n"
      "wgmma.commit_group.sync.aligned;\n}\n"
      : "=f"(g[0]), "=f"(g[1]), "=f"(g[2]), "=f"(g[3]), "=f"(g[4]), "=f"(g[5]), "=f"(g[6]), "=f"(g[7]), "=f"(g[8]), "=f"(g[9]), "=f"(g[10]), "=f"(g[11]), "=f"(g[12]), "=f"(g[13]), "=f"(g[14]), "=f"(g[15]), "=f"(g[16]), "=f"(g[17]), "=f"(g[18]), "=f"(g[19]), "=f"(g[20]), "=f"(g[21]), "=f"(g[22]), "=f"(g[23]),
        "=f"(h[0]), "=f"(h[1]), "=f"(h[2]), "=f"(h[3]), "=f"(h[4]), "=f"(h[5]), "=f"(h[6]), "=f"(h[7]), "=f"(h[8]), "=f"(h[9]), "=f"(h[10]), "=f"(h[11]), "=f"(h[12]), "=f"(h[13]), "=f"(h[14]), "=f"(h[15]), "=f"(h[16]), "=f"(h[17]), "=f"(h[18]), "=f"(h[19]), "=f"(h[20]), "=f"(h[21]), "=f"(h[22]), "=f"(h[23])
      : "r"(w[0]), "r"(w[1]), "r"(w[2]), "r"(w[3]), "r"(w[4]), "r"(w[5]), "r"(w[6]), "r"(w[7]), "r"(w[8]), "r"(w[9]), "r"(w[10]), "r"(w[11]), "r"(w[12]), "r"(w[13]), "r"(w[14]), "r"(w[15]), "r"(w[16]), "r"(w[17]), "r"(w[18]), "r"(w[19]), "r"(w[20]), "r"(w[21]), "r"(w[22]), "r"(w[23]), "r"(w[24]), "r"(w[25]), "r"(w[26]), "r"(w[27]), "r"(w[28]), "r"(w[29]), "r"(w[30]), "r"(w[31]), "r"(w[32]), "r"(w[33]), "r"(w[34]), "r"(w[35]), "r"(w[36]), "r"(w[37]), "r"(w[38]), "r"(w[39]), "l"(dx), "l"(de), "l"(dh)
      : "memory");
  }
  static __device__ __forceinline__ void wait_g(float* g) {
    asm volatile("wgmma.wait_group.sync.aligned 1;\n"
      : "+f"(g[0]), "+f"(g[1]), "+f"(g[2]), "+f"(g[3]), "+f"(g[4]), "+f"(g[5]), "+f"(g[6]), "+f"(g[7]), "+f"(g[8]), "+f"(g[9]), "+f"(g[10]), "+f"(g[11]), "+f"(g[12]), "+f"(g[13]), "+f"(g[14]), "+f"(g[15]), "+f"(g[16]), "+f"(g[17]), "+f"(g[18]), "+f"(g[19]), "+f"(g[20]), "+f"(g[21]), "+f"(g[22]), "+f"(g[23])
      :: "memory");
  }
  static __device__ __forceinline__ void wait_h(float* h) {
    asm volatile("wgmma.wait_group.sync.aligned 0;\n"
      : "+f"(h[0]), "+f"(h[1]), "+f"(h[2]), "+f"(h[3]), "+f"(h[4]), "+f"(h[5]), "+f"(h[6]), "+f"(h[7]), "+f"(h[8]), "+f"(h[9]), "+f"(h[10]), "+f"(h[11]), "+f"(h[12]), "+f"(h[13]), "+f"(h[14]), "+f"(h[15]), "+f"(h[16]), "+f"(h[17]), "+f"(h[18]), "+f"(h[19]), "+f"(h[20]), "+f"(h[21]), "+f"(h[22]), "+f"(h[23])
      :: "memory");
  }
};
template<> struct TileMMA<7> {
  static __device__ __forceinline__ void issue(float* g, float* h, const uint32_t* w, uint64_t dx, uint64_t de, uint64_t dh, uint64_t dc) {
    asm volatile(
      "{\n.reg .b64 dx1, dx2, dx3;\n"
      "add.s64 dx1, %96, 2;\nadd.s64 dx2, %96, 4;\nadd.s64 dx3, %96, 6;\n"
      "wgmma.fence.sync.aligned;\n"
      "wgmma.mma_async.sync.aligned.m64n56k16.f32.bf16.bf16 {%0, %1, %2, %3, %4, %5, %6, %7, %8, %9, %10, %11, %12, %13, %14, %15, %16, %17, %18, %19, %20, %21, %22, %23, %24, %25, %26, %27}, {%92, %93, %94, %95}, %98, 0, 1, 1, 0;\n"
      "wgmma.mma_async.sync.aligned.m64n56k16.f32.bf16.bf16 {%0, %1, %2, %3, %4, %5, %6, %7, %8, %9, %10, %11, %12, %13, %14, %15, %16, %17, %18, %19, %20, %21, %22, %23, %24, %25, %26, %27}, {%72, %73, %74, %75}, %97, 1, 1, 1, 0;\n"
      "wgmma.mma_async.sync.aligned.m64n56k16.f32.bf16.bf16 {%0, %1, %2, %3, %4, %5, %6, %7, %8, %9, %10, %11, %12, %13, %14, %15, %16, %17, %18, %19, %20, %21, %22, %23, %24, %25, %26, %27}, {%56, %57, %58, %59}, %96, 1, 1, 1, 0;\n"
      "wgmma.mma_async.sync.aligned.m64n56k16.f32.bf16.bf16 {%0, %1, %2, %3, %4, %5, %6, %7, %8, %9, %10, %11, %12, %13, %14, %15, %16, %17, %18, %19, %20, %21, %22, %23, %24, %25, %26, %27}, {%60, %61, %62, %63}, dx1, 1, 1, 1, 0;\n"
      "wgmma.mma_async.sync.aligned.m64n56k16.f32.bf16.bf16 {%0, %1, %2, %3, %4, %5, %6, %7, %8, %9, %10, %11, %12, %13, %14, %15, %16, %17, %18, %19, %20, %21, %22, %23, %24, %25, %26, %27}, {%64, %65, %66, %67}, dx2, 1, 1, 1, 0;\n"
      "wgmma.mma_async.sync.aligned.m64n56k16.f32.bf16.bf16 {%0, %1, %2, %3, %4, %5, %6, %7, %8, %9, %10, %11, %12, %13, %14, %15, %16, %17, %18, %19, %20, %21, %22, %23, %24, %25, %26, %27}, {%68, %69, %70, %71}, dx3, 1, 1, 1, 0;\n"
      "wgmma.commit_group.sync.aligned;\n"
      "wgmma.mma_async.sync.aligned.m64n56k16.f32.bf16.bf16 {%28, %29, %30, %31, %32, %33, %34, %35, %36, %37, %38, %39, %40, %41, %42, %43, %44, %45, %46, %47, %48, %49, %50, %51, %52, %53, %54, %55}, {%76, %77, %78, %79}, %96, 0, 1, 1, 0;\n"
      "wgmma.mma_async.sync.aligned.m64n56k16.f32.bf16.bf16 {%28, %29, %30, %31, %32, %33, %34, %35, %36, %37, %38, %39, %40, %41, %42, %43, %44, %45, %46, %47, %48, %49, %50, %51, %52, %53, %54, %55}, {%80, %81, %82, %83}, dx1, 1, 1, 1, 0;\n"
      "wgmma.mma_async.sync.aligned.m64n56k16.f32.bf16.bf16 {%28, %29, %30, %31, %32, %33, %34, %35, %36, %37, %38, %39, %40, %41, %42, %43, %44, %45, %46, %47, %48, %49, %50, %51, %52, %53, %54, %55}, {%84, %85, %86, %87}, dx2, 1, 1, 1, 0;\n"
      "wgmma.mma_async.sync.aligned.m64n56k16.f32.bf16.bf16 {%28, %29, %30, %31, %32, %33, %34, %35, %36, %37, %38, %39, %40, %41, %42, %43, %44, %45, %46, %47, %48, %49, %50, %51, %52, %53, %54, %55}, {%88, %89, %90, %91}, dx3, 1, 1, 1, 0;\n"
      "wgmma.commit_group.sync.aligned;\n}\n"
      : "=f"(g[0]), "=f"(g[1]), "=f"(g[2]), "=f"(g[3]), "=f"(g[4]), "=f"(g[5]), "=f"(g[6]), "=f"(g[7]), "=f"(g[8]), "=f"(g[9]), "=f"(g[10]), "=f"(g[11]), "=f"(g[12]), "=f"(g[13]), "=f"(g[14]), "=f"(g[15]), "=f"(g[16]), "=f"(g[17]), "=f"(g[18]), "=f"(g[19]), "=f"(g[20]), "=f"(g[21]), "=f"(g[22]), "=f"(g[23]), "=f"(g[24]), "=f"(g[25]), "=f"(g[26]), "=f"(g[27]),
        "=f"(h[0]), "=f"(h[1]), "=f"(h[2]), "=f"(h[3]), "=f"(h[4]), "=f"(h[5]), "=f"(h[6]), "=f"(h[7]), "=f"(h[8]), "=f"(h[9]), "=f"(h[10]), "=f"(h[11]), "=f"(h[12]), "=f"(h[13]), "=f"(h[14]), "=f"(h[15]), "=f"(h[16]), "=f"(h[17]), "=f"(h[18]), "=f"(h[19]), "=f"(h[20]), "=f"(h[21]), "=f"(h[22]), "=f"(h[23]), "=f"(h[24]), "=f"(h[25]), "=f"(h[26]), "=f"(h[27])
      : "r"(w[0]), "r"(w[1]), "r"(w[2]), "r"(w[3]), "r"(w[4]), "r"(w[5]), "r"(w[6]), "r"(w[7]), "r"(w[8]), "r"(w[9]), "r"(w[10]), "r"(w[11]), "r"(w[12]), "r"(w[13]), "r"(w[14]), "r"(w[15]), "r"(w[16]), "r"(w[17]), "r"(w[18]), "r"(w[19]), "r"(w[20]), "r"(w[21]), "r"(w[22]), "r"(w[23]), "r"(w[24]), "r"(w[25]), "r"(w[26]), "r"(w[27]), "r"(w[28]), "r"(w[29]), "r"(w[30]), "r"(w[31]), "r"(w[32]), "r"(w[33]), "r"(w[34]), "r"(w[35]), "r"(w[36]), "r"(w[37]), "r"(w[38]), "r"(w[39]), "l"(dx), "l"(de), "l"(dh)
      : "memory");
  }
  static __device__ __forceinline__ void wait_g(float* g) {
    asm volatile("wgmma.wait_group.sync.aligned 1;\n"
      : "+f"(g[0]), "+f"(g[1]), "+f"(g[2]), "+f"(g[3]), "+f"(g[4]), "+f"(g[5]), "+f"(g[6]), "+f"(g[7]), "+f"(g[8]), "+f"(g[9]), "+f"(g[10]), "+f"(g[11]), "+f"(g[12]), "+f"(g[13]), "+f"(g[14]), "+f"(g[15]), "+f"(g[16]), "+f"(g[17]), "+f"(g[18]), "+f"(g[19]), "+f"(g[20]), "+f"(g[21]), "+f"(g[22]), "+f"(g[23]), "+f"(g[24]), "+f"(g[25]), "+f"(g[26]), "+f"(g[27])
      :: "memory");
  }
  static __device__ __forceinline__ void wait_h(float* h) {
    asm volatile("wgmma.wait_group.sync.aligned 0;\n"
      : "+f"(h[0]), "+f"(h[1]), "+f"(h[2]), "+f"(h[3]), "+f"(h[4]), "+f"(h[5]), "+f"(h[6]), "+f"(h[7]), "+f"(h[8]), "+f"(h[9]), "+f"(h[10]), "+f"(h[11]), "+f"(h[12]), "+f"(h[13]), "+f"(h[14]), "+f"(h[15]), "+f"(h[16]), "+f"(h[17]), "+f"(h[18]), "+f"(h[19]), "+f"(h[20]), "+f"(h[21]), "+f"(h[22]), "+f"(h[23]), "+f"(h[24]), "+f"(h[25]), "+f"(h[26]), "+f"(h[27])
      :: "memory");
  }
};
template<> struct TileMMA<8> {
  static __device__ __forceinline__ void issue(float* g, float* h, const uint32_t* w, uint64_t dx, uint64_t de, uint64_t dh, uint64_t dc) {
    asm volatile(
      "{\n.reg .b64 dx1, dx2, dx3;\n"
      "add.s64 dx1, %104, 2;\nadd.s64 dx2, %104, 4;\nadd.s64 dx3, %104, 6;\n"
      "wgmma.fence.sync.aligned;\n"
      "wgmma.mma_async.sync.aligned.m64n64k16.f32.bf16.bf16 {%0, %1, %2, %3, %4, %5, %6, %7, %8, %9, %10, %11, %12, %13, %14, %15, %16, %17, %18, %19, %20, %21, %22, %23, %24, %25, %26, %27, %28, %29, %30, %31}, {%100, %101, %102, %103}, %106, 0, 1, 1, 0;\n"
      "wgmma.mma_async.sync.aligned.m64n64k16.f32.bf16.bf16 {%0, %1, %2, %3, %4, %5, %6, %7, %8, %9, %10, %11, %12, %13, %14, %15, %16, %17, %18, %19, %20, %21, %22, %23, %24, %25, %26, %27, %28, %29, %30, %31}, {%80, %81, %82, %83}, %105, 1, 1, 1, 0;\n"
      "wgmma.mma_async.sync.aligned.m64n64k16.f32.bf16.bf16 {%0, %1, %2, %3, %4, %5, %6, %7, %8, %9, %10, %11, %12, %13, %14, %15, %16, %17, %18, %19, %20, %21, %22, %23, %24, %25, %26, %27, %28, %29, %30, %31}, {%64, %65, %66, %67}, %104, 1, 1, 1, 0;\n"
      "wgmma.mma_async.sync.aligned.m64n64k16.f32.bf16.bf16 {%0, %1, %2, %3, %4, %5, %6, %7, %8, %9, %10, %11, %12, %13, %14, %15, %16, %17, %18, %19, %20, %21, %22, %23, %24, %25, %26, %27, %28, %29, %30, %31}, {%68, %69, %70, %71}, dx1, 1, 1, 1, 0;\n"
      "wgmma.mma_async.sync.aligned.m64n64k16.f32.bf16.bf16 {%0, %1, %2, %3, %4, %5, %6, %7, %8, %9, %10, %11, %12, %13, %14, %15, %16, %17, %18, %19, %20, %21, %22, %23, %24, %25, %26, %27, %28, %29, %30, %31}, {%72, %73, %74, %75}, dx2, 1, 1, 1, 0;\n"
      "wgmma.mma_async.sync.aligned.m64n64k16.f32.bf16.bf16 {%0, %1, %2, %3, %4, %5, %6, %7, %8, %9, %10, %11, %12, %13, %14, %15, %16, %17, %18, %19, %20, %21, %22, %23, %24, %25, %26, %27, %28, %29, %30, %31}, {%76, %77, %78, %79}, dx3, 1, 1, 1, 0;\n"
      "wgmma.commit_group.sync.aligned;\n"
      "wgmma.mma_async.sync.aligned.m64n64k16.f32.bf16.bf16 {%32, %33, %34, %35, %36, %37, %38, %39, %40, %41, %42, %43, %44, %45, %46, %47, %48, %49, %50, %51, %52, %53, %54, %55, %56, %57, %58, %59, %60, %61, %62, %63}, {%84, %85, %86, %87}, %104, 0, 1, 1, 0;\n"
      "wgmma.mma_async.sync.aligned.m64n64k16.f32.bf16.bf16 {%32, %33, %34, %35, %36, %37, %38, %39, %40, %41, %42, %43, %44, %45, %46, %47, %48, %49, %50, %51, %52, %53, %54, %55, %56, %57, %58, %59, %60, %61, %62, %63}, {%88, %89, %90, %91}, dx1, 1, 1, 1, 0;\n"
      "wgmma.mma_async.sync.aligned.m64n64k16.f32.bf16.bf16 {%32, %33, %34, %35, %36, %37, %38, %39, %40, %41, %42, %43, %44, %45, %46, %47, %48, %49, %50, %51, %52, %53, %54, %55, %56, %57, %58, %59, %60, %61, %62, %63}, {%92, %93, %94, %95}, dx2, 1, 1, 1, 0;\n"
      "wgmma.mma_async.sync.aligned.m64n64k16.f32.bf16.bf16 {%32, %33, %34, %35, %36, %37, %38, %39, %40, %41, %42, %43, %44, %45, %46, %47, %48, %49, %50, %51, %52, %53, %54, %55, %56, %57, %58, %59, %60, %61, %62, %63}, {%96, %97, %98, %99}, dx3, 1, 1, 1, 0;\n"
      "wgmma.commit_group.sync.aligned;\n}\n"
      : "=f"(g[0]), "=f"(g[1]), "=f"(g[2]), "=f"(g[3]), "=f"(g[4]), "=f"(g[5]), "=f"(g[6]), "=f"(g[7]), "=f"(g[8]), "=f"(g[9]), "=f"(g[10]), "=f"(g[11]), "=f"(g[12]), "=f"(g[13]), "=f"(g[14]), "=f"(g[15]), "=f"(g[16]), "=f"(g[17]), "=f"(g[18]), "=f"(g[19]), "=f"(g[20]), "=f"(g[21]), "=f"(g[22]), "=f"(g[23]), "=f"(g[24]), "=f"(g[25]), "=f"(g[26]), "=f"(g[27]), "=f"(g[28]), "=f"(g[29]), "=f"(g[30]), "=f"(g[31]),
        "=f"(h[0]), "=f"(h[1]), "=f"(h[2]), "=f"(h[3]), "=f"(h[4]), "=f"(h[5]), "=f"(h[6]), "=f"(h[7]), "=f"(h[8]), "=f"(h[9]), "=f"(h[10]), "=f"(h[11]), "=f"(h[12]), "=f"(h[13]), "=f"(h[14]), "=f"(h[15]), "=f"(h[16]), "=f"(h[17]), "=f"(h[18]), "=f"(h[19]), "=f"(h[20]), "=f"(h[21]), "=f"(h[22]), "=f"(h[23]), "=f"(h[24]), "=f"(h[25]), "=f"(h[26]), "=f"(h[27]), "=f"(h[28]), "=f"(h[29]), "=f"(h[30]), "=f"(h[31])
      : "r"(w[0]), "r"(w[1]), "r"(w[2]), "r"(w[3]), "r"(w[4]), "r"(w[5]), "r"(w[6]), "r"(w[7]), "r"(w[8]), "r"(w[9]), "r"(w[10]), "r"(w[11]), "r"(w[12]), "r"(w[13]), "r"(w[14]), "r"(w[15]), "r"(w[16]), "r"(w[17]), "r"(w[18]), "r"(w[19]), "r"(w[20]), "r"(w[21]), "r"(w[22]), "r"(w[23]), "r"(w[24]), "r"(w[25]), "r"(w[26]), "r"(w[27]), "r"(w[28]), "r"(w[29]), "r"(w[30]), "r"(w[31]), "r"(w[32]), "r"(w[33]), "r"(w[34]), "r"(w[35]), "r"(w[36]), "r"(w[37]), "r"(w[38]), "r"(w[39]), "l"(dx), "l"(de), "l"(dh)
      : "memory");
  }
  static __device__ __forceinline__ void wait_g(float* g) {
    asm volatile("wgmma.wait_group.sync.aligned 1;\n"
      : "+f"(g[0]), "+f"(g[1]), "+f"(g[2]), "+f"(g[3]), "+f"(g[4]), "+f"(g[5]), "+f"(g[6]), "+f"(g[7]), "+f"(g[8]), "+f"(g[9]), "+f"(g[10]), "+f"(g[11]), "+f"(g[12]), "+f"(g[13]), "+f"(g[14]), "+f"(g[15]), "+f"(g[16]), "+f"(g[17]), "+f"(g[18]), "+f"(g[19]), "+f"(g[20]), "+f"(g[21]), "+f"(g[22]), "+f"(g[23]), "+f"(g[24]), "+f"(g[25]), "+f"(g[26]), "+f"(g[27]), "+f"(g[28]), "+f"(g[29]), "+f"(g[30]), "+f"(g[31])
      :: "memory");
  }
  static __device__ __forceinline__ void wait_h(float* h) {
    asm volatile("wgmma.wait_group.sync.aligned 0;\n"
      : "+f"(h[0]), "+f"(h[1]), "+f"(h[2]), "+f"(h[3]), "+f"(h[4]), "+f"(h[5]), "+f"(h[6]), "+f"(h[7]), "+f"(h[8]), "+f"(h[9]), "+f"(h[10]), "+f"(h[11]), "+f"(h[12]), "+f"(h[13]), "+f"(h[14]), "+f"(h[15]), "+f"(h[16]), "+f"(h[17]), "+f"(h[18]), "+f"(h[19]), "+f"(h[20]), "+f"(h[21]), "+f"(h[22]), "+f"(h[23]), "+f"(h[24]), "+f"(h[25]), "+f"(h[26]), "+f"(h[27]), "+f"(h[28]), "+f"(h[29]), "+f"(h[30]), "+f"(h[31])
      :: "memory");
  }
};
template<> struct TileMMA<9> {
  static __device__ __forceinline__ void issue(float* g, float* h, const uint32_t* w, uint64_t dx, uint64_t de, uint64_t dh, uint64_t dc) {
    asm volatile(
      "{\n.reg .b64 dx1, dx2, dx3;\n"
      "add.s64 dx1, %112, 2;\nadd.s64 dx2, %112, 4;\nadd.s64 dx3, %112, 6;\n"
      "wgmma.fence.sync.aligned;\n"
      "wgmma.mma_async.sync.aligned.m64n72k16.f32.bf16.bf16 {%0, %1, %2, %3, %4, %5, %6, %7, %8, %9, %10, %11, %12, %13, %14, %15, %16, %17, %18, %19, %20, %21, %22, %23, %24, %25, %26, %27, %28, %29, %30, %31, %32, %33, %34, %35}, {%108, %109, %110, %111}, %114, 0, 1, 1, 0;\n"
      "wgmma.mma_async.sync.aligned.m64n72k16.f32.bf16.bf16 {%0, %1, %2, %3, %4, %5, %6, %7, %8, %9, %10, %11, %12, %13, %14, %15, %16, %17, %18, %19, %20, %21, %22, %23, %24, %25, %26, %27, %28, %29, %30, %31, %32, %33, %34, %35}, {%88, %89, %90, %91}, %113, 1, 1, 1, 0;\n"
      "wgmma.mma_async.sync.aligned.m64n72k16.f32.bf16.bf16 {%0, %1, %2, %3, %4, %5, %6, %7, %8, %9, %10, %11, %12, %13, %14, %15, %16, %17, %18, %19, %20, %21, %22, %23, %24, %25, %26, %27, %28, %29, %30, %31, %32, %33, %34, %35}, {%72, %73, %74, %75}, %112, 1, 1, 1, 0;\n"
      "wgmma.mma_async.sync.aligned.m64n72k16.f32.bf16.bf16 {%0, %1, %2, %3, %4, %5, %6, %7, %8, %9, %10, %11, %12, %13, %14, %15, %16, %17, %18, %19, %20, %21, %22, %23, %24, %25, %26, %27, %28, %29, %30, %31, %32, %33, %34, %35}, {%76, %77, %78, %79}, dx1, 1, 1, 1, 0;\n"
      "wgmma.mma_async.sync.aligned.m64n72k16.f32.bf16.bf16 {%0, %1, %2, %3, %4, %5, %6, %7, %8, %9, %10, %11, %12, %13, %14, %15, %16, %17, %18, %19, %20, %21, %22, %23, %24, %25, %26, %27, %28, %29, %30, %31, %32, %33, %34, %35}, {%80, %81, %82, %83}, dx2, 1, 1, 1, 0;\n"
      "wgmma.mma_async.sync.aligned.m64n72k16.f32.bf16.bf16 {%0, %1, %2, %3, %4, %5, %6, %7, %8, %9, %10, %11, %12, %13, %14, %15, %16, %17, %18, %19, %20, %21, %22, %23, %24, %25, %26, %27, %28, %29, %30, %31, %32, %33, %34, %35}, {%84, %85, %86, %87}, dx3, 1, 1, 1, 0;\n"
      "wgmma.commit_group.sync.aligned;\n"
      "wgmma.mma_async.sync.aligned.m64n72k16.f32.bf16.bf16 {%36, %37, %38, %39, %40, %41, %42, %43, %44, %45, %46, %47, %48, %49, %50, %51, %52, %53, %54, %55, %56, %57, %58, %59, %60, %61, %62, %63, %64, %65, %66, %67, %68, %69, %70, %71}, {%92, %93, %94, %95}, %112, 0, 1, 1, 0;\n"
      "wgmma.mma_async.sync.aligned.m64n72k16.f32.bf16.bf16 {%36, %37, %38, %39, %40, %41, %42, %43, %44, %45, %46, %47, %48, %49, %50, %51, %52, %53, %54, %55, %56, %57, %58, %59, %60, %61, %62, %63, %64, %65, %66, %67, %68, %69, %70, %71}, {%96, %97, %98, %99}, dx1, 1, 1, 1, 0;\n"
      "wgmma.mma_async.sync.aligned.m64n72k16.f32.bf16.bf16 {%36, %37, %38, %39, %40, %41, %42, %43, %44, %45, %46, %47, %48, %49, %50, %51, %52, %53, %54, %55, %56, %57, %58, %59, %60, %61, %62, %63, %64, %65, %66, %67, %68, %69, %70, %71}, {%100, %101, %102, %103}, dx2, 1, 1, 1, 0;\n"
      "wgmma.mma_async.sync.aligned.m64n72k16.f32.bf16.bf16 {%36, %37, %38, %39, %40, %41, %42, %43, %44, %45, %46, %47, %48, %49, %50, %51, %52, %53, %54, %55, %56, %57, %58, %59, %60, %61, %62, %63, %64, %65, %66, %67, %68, %69, %70, %71}, {%104, %105, %106, %107}, dx3, 1, 1, 1, 0;\n"
      "wgmma.commit_group.sync.aligned;\n}\n"
      : "=f"(g[0]), "=f"(g[1]), "=f"(g[2]), "=f"(g[3]), "=f"(g[4]), "=f"(g[5]), "=f"(g[6]), "=f"(g[7]), "=f"(g[8]), "=f"(g[9]), "=f"(g[10]), "=f"(g[11]), "=f"(g[12]), "=f"(g[13]), "=f"(g[14]), "=f"(g[15]), "=f"(g[16]), "=f"(g[17]), "=f"(g[18]), "=f"(g[19]), "=f"(g[20]), "=f"(g[21]), "=f"(g[22]), "=f"(g[23]), "=f"(g[24]), "=f"(g[25]), "=f"(g[26]), "=f"(g[27]), "=f"(g[28]), "=f"(g[29]), "=f"(g[30]), "=f"(g[31]), "=f"(g[32]), "=f"(g[33]), "=f"(g[34]), "=f"(g[35]),
        "=f"(h[0]), "=f"(h[1]), "=f"(h[2]), "=f"(h[3]), "=f"(h[4]), "=f"(h[5]), "=f"(h[6]), "=f"(h[7]), "=f"(h[8]), "=f"(h[9]), "=f"(h[10]), "=f"(h[11]), "=f"(h[12]), "=f"(h[13]), "=f"(h[14]), "=f"(h[15]), "=f"(h[16]), "=f"(h[17]), "=f"(h[18]), "=f"(h[19]), "=f"(h[20]), "=f"(h[21]), "=f"(h[22]), "=f"(h[23]), "=f"(h[24]), "=f"(h[25]), "=f"(h[26]), "=f"(h[27]), "=f"(h[28]), "=f"(h[29]), "=f"(h[30]), "=f"(h[31]), "=f"(h[32]), "=f"(h[33]), "=f"(h[34]), "=f"(h[35])
      : "r"(w[0]), "r"(w[1]), "r"(w[2]), "r"(w[3]), "r"(w[4]), "r"(w[5]), "r"(w[6]), "r"(w[7]), "r"(w[8]), "r"(w[9]), "r"(w[10]), "r"(w[11]), "r"(w[12]), "r"(w[13]), "r"(w[14]), "r"(w[15]), "r"(w[16]), "r"(w[17]), "r"(w[18]), "r"(w[19]), "r"(w[20]), "r"(w[21]), "r"(w[22]), "r"(w[23]), "r"(w[24]), "r"(w[25]), "r"(w[26]), "r"(w[27]), "r"(w[28]), "r"(w[29]), "r"(w[30]), "r"(w[31]), "r"(w[32]), "r"(w[33]), "r"(w[34]), "r"(w[35]), "r"(w[36]), "r"(w[37]), "r"(w[38]), "r"(w[39]), "l"(dx), "l"(de), "l"(dh)
      : "memory");
  }
  static __device__ __forceinline__ void wait_g(float* g) {
    asm volatile("wgmma.wait_group.sync.aligned 1;\n"
      : "+f"(g[0]), "+f"(g[1]), "+f"(g[2]), "+f"(g[3]), "+f"(g[4]), "+f"(g[5]), "+f"(g[6]), "+f"(g[7]), "+f"(g[8]), "+f"(g[9]), "+f"(g[10]), "+f"(g[11]), "+f"(g[12]), "+f"(g[13]), "+f"(g[14]), "+f"(g[15]), "+f"(g[16]), "+f"(g[17]), "+f"(g[18]), "+f"(g[19]), "+f"(g[20]), "+f"(g[21]), "+f"(g[22]), "+f"(g[23]), "+f"(g[24]), "+f"(g[25]), "+f"(g[26]), "+f"(g[27]), "+f"(g[28]), "+f"(g[29]), "+f"(g[30]), "+f"(g[31]), "+f"(g[32]), "+f"(g[33]), "+f"(g[34]), "+f"(g[35])
      :: "memory");
  }
  static __device__ __forceinline__ void wait_h(float* h) {
    asm volatile("wgmma.wait_group.sync.aligned 0;\n"
      : "+f"(h[0]), "+f"(h[1]), "+f"(h[2]), "+f"(h[3]), "+f"(h[4]), "+f"(h[5]), "+f"(h[6]), "+f"(h[7]), "+f"(h[8]), "+f"(h[9]), "+f"(h[10]), "+f"(h[11]), "+f"(h[12]), "+f"(h[13]), "+f"(h[14]), "+f"(h[15]), "+f"(h[16]), "+f"(h[17]), "+f"(h[18]), "+f"(h[19]), "+f"(h[20]), "+f"(h[21]), "+f"(h[22]), "+f"(h[23]), "+f"(h[24]), "+f"(h[25]), "+f"(h[26]), "+f"(h[27]), "+f"(h[28]), "+f"(h[29]), "+f"(h[30]), "+f"(h[31]), "+f"(h[32]), "+f"(h[33]), "+f"(h[34]), "+f"(h[35])
      :: "memory");
  }
};
template<> struct TileMMA<10> {
  static __device__ __forceinline__ void issue(float* g, float* h, const uint32_t* w, uint64_t dx, uint64_t de, uint64_t dh, uint64_t dc) {
    asm volatile(
      "{\n.reg .b64 dx1, dx2, dx3;\n"
      "add.s64 dx1, %120, 2;\nadd.s64 dx2, %120, 4;\nadd.s64 dx3, %120, 6;\n"
      "wgmma.fence.sync.aligned;\n"
      "wgmma.mma_async.sync.aligned.m64n80k16.f32.bf16.bf16 {%0, %1, %2, %3, %4, %5, %6, %7, %8, %9, %10, %11, %12, %13, %14, %15, %16, %17, %18, %19, %20, %21, %22, %23, %24, %25, %26, %27, %28, %29, %30, %31, %32, %33, %34, %35, %36, %37, %38, %39}, {%116, %117, %118, %119}, %122, 0, 1, 1, 0;\n"
      "wgmma.mma_async.sync.aligned.m64n80k16.f32.bf16.bf16 {%0, %1, %2, %3, %4, %5, %6, %7, %8, %9, %10, %11, %12, %13, %14, %15, %16, %17, %18, %19, %20, %21, %22, %23, %24, %25, %26, %27, %28, %29, %30, %31, %32, %33, %34, %35, %36, %37, %38, %39}, {%96, %97, %98, %99}, %121, 1, 1, 1, 0;\n"
      "wgmma.mma_async.sync.aligned.m64n80k16.f32.bf16.bf16 {%0, %1, %2, %3, %4, %5, %6, %7, %8, %9, %10, %11, %12, %13, %14, %15, %16, %17, %18, %19, %20, %21, %22, %23, %24, %25, %26, %27, %28, %29, %30, %31, %32, %33, %34, %35, %36, %37, %38, %39}, {%80, %81, %82, %83}, %120, 1, 1, 1, 0;\n"
      "wgmma.mma_async.sync.aligned.m64n80k16.f32.bf16.bf16 {%0, %1, %2, %3, %4, %5, %6, %7, %8, %9, %10, %11, %12, %13, %14, %15, %16, %17, %18, %19, %20, %21, %22, %23, %24, %25, %26, %27, %28, %29, %30, %31, %32, %33, %34, %35, %36, %37, %38, %39}, {%84, %85, %86, %87}, dx1, 1, 1, 1, 0;\n"
      "wgmma.mma_async.sync.aligned.m64n80k16.f32.bf16.bf16 {%0, %1, %2, %3, %4, %5, %6, %7, %8, %9, %10, %11, %12, %13, %14, %15, %16, %17, %18, %19, %20, %21, %22, %23, %24, %25, %26, %27, %28, %29, %30, %31, %32, %33, %34, %35, %36, %37, %38, %39}, {%88, %89, %90, %91}, dx2, 1, 1, 1, 0;\n"
      "wgmma.mma_async.sync.aligned.m64n80k16.f32.bf16.bf16 {%0, %1, %2, %3, %4, %5, %6, %7, %8, %9, %10, %11, %12, %13, %14, %15, %16, %17, %18, %19, %20, %21, %22, %23, %24, %25, %26, %27, %28, %29, %30, %31, %32, %33, %34, %35, %36, %37, %38, %39}, {%92, %93, %94, %95}, dx3, 1, 1, 1, 0;\n"
      "wgmma.commit_group.sync.aligned;\n"
      "wgmma.mma_async.sync.aligned.m64n80k16.f32.bf16.bf16 {%40, %41, %42, %43, %44, %45, %46, %47, %48, %49, %50, %51, %52, %53, %54, %55, %56, %57, %58, %59, %60, %61, %62, %63, %64, %65, %66, %67, %68, %69, %70, %71, %72, %73, %74, %75, %76, %77, %78, %79}, {%100, %101, %102, %103}, %120, 0, 1, 1, 0;\n"
      "wgmma.mma_async.sync.aligned.m64n80k16.f32.bf16.bf16 {%40, %41, %42, %43, %44, %45, %46, %47, %48, %49, %50, %51, %52, %53, %54, %55, %56, %57, %58, %59, %60, %61, %62, %63, %64, %65, %66, %67, %68, %69, %70, %71, %72, %73, %74, %75, %76, %77, %78, %79}, {%104, %105, %106, %107}, dx1, 1, 1, 1, 0;\n"
      "wgmma.mma_async.sync.aligned.m64n80k16.f32.bf16.bf16 {%40, %41, %42, %43, %44, %45, %46, %47, %48, %49, %50, %51, %52, %53, %54, %55, %56, %57, %58, %59, %60, %61, %62, %63, %64, %65, %66, %67, %68, %69, %70, %71, %72, %73, %74, %75, %76, %77, %78, %79}, {%108, %109, %110, %111}, dx2, 1, 1, 1, 0;\n"
      "wgmma.mma_async.sync.aligned.m64n80k16.f32.bf16.bf16 {%40, %41, %42, %43, %44, %45, %46, %47, %48, %49, %50, %51, %52, %53, %54, %55, %56, %57, %58, %59, %60, %61, %62, %63, %64, %65, %66, %67, %68, %69, %70, %71, %72, %73, %74, %75, %76, %77, %78, %79}, {%112, %113, %114, %115}, dx3, 1, 1, 1, 0;\n"
      "wgmma.commit_group.sync.aligned;\n}\n"
      : "=f"(g[0]), "=f"(g[1]), "=f"(g[2]), "=f"(g[3]), "=f"(g[4]), "=f"(g[5]), "=f"(g[6]), "=f"(g[7]), "=f"(g[8]), "=f"(g[9]), "=f"(g[10]), "=f"(g[11]), "=f"(g[12]), "=f"(g[13]), "=f"(g[14]), "=f"(g[15]), "=f"(g[16]), "=f"(g[17]), "=f"(g[18]), "=f"(g[19]), "=f"(g[20]), "=f"(g[21]), "=f"(g[22]), "=f"(g[23]), "=f"(g[24]), "=f"(g[25]), "=f"(g[26]), "=f"(g[27]), "=f"(g[28]), "=f"(g[29]), "=f"(g[30]), "=f"(g[31]), "=f"(g[32]), "=f"(g[33]), "=f"(g[34]), "=f"(g[35]), "=f"(g[36]), "=f"(g[37]), "=f"(g[38]), "=f"(g[39]),
        "=f"(h[0]), "=f"(h[1]), "=f"(h[2]), "=f"(h[3]), "=f"(h[4]), "=f"(h[5]), "=f"(h[6]), "=f"(h[7]), "=f"(h[8]), "=f"(h[9]), "=f"(h[10]), "=f"(h[11]), "=f"(h[12]), "=f"(h[13]), "=f"(h[14]), "=f"(h[15]), "=f"(h[16]), "=f"(h[17]), "=f"(h[18]), "=f"(h[19]), "=f"(h[20]), "=f"(h[21]), "=f"(h[22]), "=f"(h[23]), "=f"(h[24]), "=f"(h[25]), "=f"(h[26]), "=f"(h[27]), "=f"(h[28]), "=f"(h[29]), "=f"(h[30]), "=f"(h[31]), "=f"(h[32]), "=f"(h[33]), "=f"(h[34]), "=f"(h[35]), "=f"(h[36]), "=f"(h[37]), "=f"(h[38]), "=f"(h[39])
      : "r"(w[0]), "r"(w[1]), "r"(w[2]), "r"(w[3]), "r"(w[4]), "r"(w[5]), "r"(w[6]), "r"(w[7]), "r"(w[8]), "r"(w[9]), "r"(w[10]), "r"(w[11]), "r"(w[12]), "r"(w[13]), "r"(w[14]), "r"(w[15]), "r"(w[16]), "r"(w[17]), "r"(w[18]), "r"(w[19]), "r"(w[20]), "r"(w[21]), "r"(w[22]), "r"(w[23]), "r"(w[24]), "r"(w[25]), "r"(w[26]), "r"(w[27]), "r"(w[28]), "r"(w[29]), "r"(w[30]), "r"(w[31]), "r"(w[32]), "r"(w[33]), "r"(w[34]), "r"(w[35]), "r"(w[36]), "r"(w[37]), "r"(w[38]), "r"(w[39]), "l"(dx), "l"(de), "l"(dh)
      : "memory");
  }
  static __device__ __forceinline__ void wait_g(float* g) {
    asm volatile("wgmma.wait_group.sync.aligned 1;\n"
      : "+f"(g[0]), "+f"(g[1]), "+f"(g[2]), "+f"(g[3]), "+f"(g[4]), "+f"(g[5]), "+f"(g[6]), "+f"(g[7]), "+f"(g[8]), "+f"(g[9]), "+f"(g[10]), "+f"(g[11]), "+f"(g[12]), "+f"(g[13]), "+f"(g[14]), "+f"(g[15]), "+f"(g[16]), "+f"(g[17]), "+f"(g[18]), "+f"(g[19]), "+f"(g[20]), "+f"(g[21]), "+f"(g[22]), "+f"(g[23]), "+f"(g[24]), "+f"(g[25]), "+f"(g[26]), "+f"(g[27]), "+f"(g[28]), "+f"(g[29]), "+f"(g[30]), "+f"(g[31]), "+f"(g[32]), "+f"(g[33]), "+f"(g[34]), "+f"(g[35]), "+f"(g[36]), "+f"(g[37]), "+f"(g[38]), "+f"(g[39])
      :: "memory");
  }
  static __device__ __forceinline__ void wait_h(float* h) {
    asm volatile("wgmma.wait_group.sync.aligned 0;\n"
      : "+f"(h[0]), "+f"(h[1]), "+f"(h[2]), "+f"(h[3]), "+f"(h[4]), "+f"(h[5]), "+f"(h[6]), "+f"(h[7]), "+f"(h[8]), "+f"(h[9]), "+f"(h[10]), "+f"(h[11]), "+f"(h[12]), "+f"(h[13]), "+f"(h[14]), "+f"(h[15]), "+f"(h[16]), "+f"(h[17]), "+f"(h[18]), "+f"(h[19]), "+f"(h[20]), "+f"(h[21]), "+f"(h[22]), "+f"(h[23]), "+f"(h[24]), "+f"(h[25]), "+f"(h[26]), "+f"(h[27]), "+f"(h[28]), "+f"(h[29]), "+f"(h[30]), "+f"(h[31]), "+f"(h[32]), "+f"(h[33]), "+f"(h[34]), "+f"(h[35]), "+f"(h[36]), "+f"(h[37]), "+f"(h[38]), "+f"(h[39])
      :: "memory");
  }
};
template<> struct TileMMA<11> {
  static __device__ __forceinline__ void issue(float* g, float* h, const uint32_t* w, uint64_t dx, uint64_t de, uint64_t dh, uint64_t dc) {
    asm volatile(
      "{\n.reg .b64 dx1, dx2, dx3;\n"
      "add.s64 dx1, %124, 2;\nadd.s64 dx2, %124, 4;\nadd.s64 dx3, %124, 6;\n"
      "wgmma.fence.sync.aligned;\n"
      "wgmma.mma_async.sync.aligned.m64n88k16.f32.bf16.bf16 {%0, %1, %2, %3, %4, %5, %6, %7, %8, %9, %10, %11, %12, %13, %14, %15, %16, %17, %18, %19, %20, %21, %22, %23, %24, %25, %26, %27, %28, %29, %30, %31, %32, %33, %34, %35, %36, %37, %38, %39, %40, %41, %42, %43}, {%120, %121, %122, %123}, %126, 0, 1, 1, 0;\n"
      "wgmma.mma_async.sync.aligned.m64n88k16.f32.bf16.bf16 {%0, %1, %2, %3, %4, %5, %6, %7, %8, %9, %10, %11, %12, %13, %14, %15, %16, %17, %18, %19, %20, %21, %22, %23, %24, %25, %26, %27, %28, %29, %30, %31, %32, %33, %34, %35, %36, %37, %38, %39, %40, %41, %42, %43}, %127, %125, 1, 1, 1, 0, 0;\n"
      "wgmma.mma_async.sync.aligned.m64n88k16.f32.bf16.bf16 {%0, %1, %2, %3, %4, %5, %6, %7, %8, %9, %10, %11, %12, %13, %14, %15, %16, %17, %18, %19, %20, %21, %22, %23, %24, %25, %26, %27, %28, %29, %30, %31, %32, %33, %34, %35, %36, %37, %38, %39, %40, %41, %42, %43}, {%88, %89, %90, %91}, %124, 1, 1, 1, 0;\n"
      "wgmma.mma_async.sync.aligned.m64n88k16.f32.bf16.bf16 {%0, %1, %2, %3, %4, %5, %6, %7, %8, %9, %10, %11, %12, %13, %14, %15, %16, %17, %18, %19, %20, %21, %22, %23, %24, %25, %26, %27, %28, %29, %30, %31, %32, %33, %34, %35, %36, %37, %38, %39, %40, %41, %42, %43}, {%92, %93, %94, %95}, dx1, 1, 1, 1, 0;\n"
      "wgmma.mma_async.sync.aligned.m64n88k16.f32.bf16.bf16 {%0, %1, %2, %3, %4, %5, %6, %7, %8, %9, %10, %11, %12, %13, %14, %15, %16, %17, %18, %19, %20, %21, %22, %23, %24, %25, %26, %27, %28, %29, %30, %31, %32, %33, %34, %35, %36, %37, %38, %39, %40, %41, %42, %43}, {%96, %97, %98, %99}, dx2, 1, 1, 1, 0;\n"
      "wgmma.mma_async.sync.aligned.m64n88k16.f32.bf16.bf16 {%0, %1, %2, %3, %4, %5, %6, %7, %8, %9, %10, %11, %12, %13, %14, %15, %16, %17, %18, %19, %20, %21, %22, %23, %24, %25, %26, %27, %28, %29, %30, %31, %32, %33, %34, %35, %36, %37, %38, %39, %40, %41, %42, %43}, {%100, %101, %102, %103}, dx3, 1, 1, 1, 0;\n"
      "wgmma.commit_group.sync.aligned;\n"
      "wgmma.mma_async.sync.aligned.m64n88k16.f32.bf16.bf16 {%44, %45, %46, %47, %48, %49, %50, %51, %52, %53, %54, %55, %56, %57, %58, %59, %60, %61, %62, %63, %64, %65, %66, %67, %68, %69, %70, %71, %72, %73, %74, %75, %76, %77, %78, %79, %80, %81, %82, %83, %84, %85, %86, %87}, {%104, %105, %106, %107}, %124, 0, 1, 1, 0;\n"
      "wgmma.mma_async.sync.aligned.m64n88k16.f32.bf16.bf16 {%44, %45, %46, %47, %48, %49, %50, %51, %52, %53, %54, %55, %56, %57, %58, %59, %60, %61, %62, %63, %64, %65, %66, %67, %68, %69, %70, %71, %72, %73, %74, %75, %76, %77, %78, %79, %80, %81, %82, %83, %84, %85, %86, %87}, {%108, %109, %110, %111}, dx1, 1, 1, 1, 0;\n"
      "wgmma.mma_async.sync.aligned.m64n88k16.f32.bf16.bf16 {%44, %45, %46, %47, %48, %49, %50, %51, %52, %53, %54, %55, %56, %57, %58, %59, %60, %61, %62, %63, %64, %65, %66, %67, %68, %69, %70, %71, %72, %73, %74, %75, %76, %77, %78, %79, %80, %81, %82, %83, %84, %85, %86, %87}, {%112, %113, %114, %115}, dx2, 1, 1, 1, 0;\n"
      "wgmma.mma_async.sync.aligned.m64n88k16.f32.bf16.bf16 {%44, %45, %46, %47, %48, %49, %50, %51, %52, %53, %54, %55, %56, %57, %58, %59, %60, %61, %62, %63, %64, %65, %66, %67, %68, %69, %70, %71, %72, %73, %74, %75, %76, %77, %78, %79, %80, %81, %82, %83, %84, %85, %86, %87}, {%116, %117, %118, %119}, dx3, 1, 1, 1, 0;\n"
      "wgmma.commit_group.sync.aligned;\n}\n"
      : "=f"(g[0]), "=f"(g[1]), "=f"(g[2]), "=f"(g[3]), "=f"(g[4]), "=f"(g[5]), "=f"(g[6]), "=f"(g[7]), "=f"(g[8]), "=f"(g[9]), "=f"(g[10]), "=f"(g[11]), "=f"(g[12]), "=f"(g[13]), "=f"(g[14]), "=f"(g[15]), "=f"(g[16]), "=f"(g[17]), "=f"(g[18]), "=f"(g[19]), "=f"(g[20]), "=f"(g[21]), "=f"(g[22]), "=f"(g[23]), "=f"(g[24]), "=f"(g[25]), "=f"(g[26]), "=f"(g[27]), "=f"(g[28]), "=f"(g[29]), "=f"(g[30]), "=f"(g[31]), "=f"(g[32]), "=f"(g[33]), "=f"(g[34]), "=f"(g[35]), "=f"(g[36]), "=f"(g[37]), "=f"(g[38]), "=f"(g[39]), "=f"(g[40]), "=f"(g[41]), "=f"(g[42]), "=f"(g[43]),
        "=f"(h[0]), "=f"(h[1]), "=f"(h[2]), "=f"(h[3]), "=f"(h[4]), "=f"(h[5]), "=f"(h[6]), "=f"(h[7]), "=f"(h[8]), "=f"(h[9]), "=f"(h[10]), "=f"(h[11]), "=f"(h[12]), "=f"(h[13]), "=f"(h[14]), "=f"(h[15]), "=f"(h[16]), "=f"(h[17]), "=f"(h[18]), "=f"(h[19]), "=f"(h[20]), "=f"(h[21]), "=f"(h[22]), "=f"(h[23]), "=f"(h[24]), "=f"(h[25]), "=f"(h[26]), "=f"(h[27]), "=f"(h[28]), "=f"(h[29]), "=f"(h[30]), "=f"(h[31]), "=f"(h[32]), "=f"(h[33]), "=f"(h[34]), "=f"(h[35]), "=f"(h[36]), "=f"(h[37]), "=f"(h[38]), "=f"(h[39]), "=f"(h[40]), "=f"(h[41]), "=f"(h[42]), "=f"(h[43])
      : "r"(w[0]), "r"(w[1]), "r"(w[2]), "r"(w[3]), "r"(w[4]), "r"(w[5]), "r"(w[6]), "r"(w[7]), "r"(w[8]), "r"(w[9]), "r"(w[10]), "r"(w[11]), "r"(w[12]), "r"(w[13]), "r"(w[14]), "r"(w[15]), "r"(w[20]), "r"(w[21]), "r"(w[22]), "r"(w[23]), "r"(w[24]), "r"(w[25]), "r"(w[26]), "r"(w[27]), "r"(w[28]), "r"(w[29]), "r"(w[30]), "r"(w[31]), "r"(w[32]), "r"(w[33]), "r"(w[34]), "r"(w[35]), "r"(w[36]), "r"(w[37]), "r"(w[38]), "r"(w[39]), "l"(dx), "l"(de), "l"(dh), "l"(dc)
      : "memory");
  }
  static __device__ __forceinline__ void wait_g(float* g) {
    asm volatile("wgmma.wait_group.sync.aligned 1;\n"
      : "+f"(g[0]), "+f"(g[1]), "+f"(g[2]), "+f"(g[3]), "+f"(g[4]), "+f"(g[5]), "+f"(g[6]), "+f"(g[7]), "+f"(g[8]), "+f"(g[9]), "+f"(g[10]), "+f"(g[11]), "+f"(g[12]), "+f"(g[13]), "+f"(g[14]), "+f"(g[15]), "+f"(g[16]), "+f"(g[17]), "+f"(g[18]), "+f"(g[19]), "+f"(g[20]), "+f"(g[21]), "+f"(g[22]), "+f"(g[23]), "+f"(g[24]), "+f"(g[25]), "+f"(g[26]), "+f"(g[27]), "+f"(g[28]), "+f"(g[29]), "+f"(g[30]), "+f"(g[31]), "+f"(g[32]), "+f"(g[33]), "+f"(g[34]), "+f"(g[35]), "+f"(g[36]), "+f"(g[37]), "+f"(g[38]), "+f"(g[39]), "+f"(g[40]), "+f"(g[41]), "+f"(g[42]), "+f"(g[43])
      :: "memory");
  }
  static __device__ __forceinline__ void wait_h(float* h) {
    asm volatile("wgmma.wait_group.sync.aligned 0;\n"
      : "+f"(h[0]), "+f"(h[1]), "+f"(h[2]), "+f"(h[3]), "+f"(h[4]), "+f"(h[5]), "+f"(h[6]), "+f"(h[7]), "+f"(h[8]), "+f"(h[9]), "+f"(h[10]), "+f"(h[11]), "+f"(h[12]), "+f"(h[13]), "+f"(h[14]), "+f"(h[15]), "+f"(h[16]), "+f"(h[17]), "+f"(h[18]), "+f"(h[19]), "+f"(h[20]), "+f"(h[21]), "+f"(h[22]), "+f"(h[23]), "+f"(h[24]), "+f"(h[25]), "+f"(h[26]), "+f"(h[27]), "+f"(h[28]), "+f"(h[29]), "+f"(h[30]), "+f"(h[31]), "+f"(h[32]), "+f"(h[33]), "+f"(h[34]), "+f"(h[35]), "+f"(h[36]), "+f"(h[37]), "+f"(h[38]), "+f"(h[39]), "+f"(h[40]), "+f"(h[41]), "+f"(h[42]), "+f"(h[43])
      :: "memory");
  }
};
__device__ __forceinline__ void node_mma(float* g, const uint32_t* w, uint64_t dx) {
    asm volatile(
      "{\n.reg .b64 dx1, dx2, dx3;\n"
      "add.s64 dx1, %48, 2;\nadd.s64 dx2, %48, 4;\nadd.s64 dx3, %48, 6;\n"
      "wgmma.fence.sync.aligned;\n"
      "wgmma.mma_async.sync.aligned.m64n64k16.f32.bf16.bf16 {%0, %1, %2, %3, %4, %5, %6, %7, %8, %9, %10, %11, %12, %13, %14, %15, %16, %17, %18, %19, %20, %21, %22, %23, %24, %25, %26, %27, %28, %29, %30, %31}, {%32, %33, %34, %35}, %48, 0, 1, 1, 0;\n"
      "wgmma.mma_async.sync.aligned.m64n64k16.f32.bf16.bf16 {%0, %1, %2, %3, %4, %5, %6, %7, %8, %9, %10, %11, %12, %13, %14, %15, %16, %17, %18, %19, %20, %21, %22, %23, %24, %25, %26, %27, %28, %29, %30, %31}, {%36, %37, %38, %39}, dx1, 1, 1, 1, 0;\n"
      "wgmma.mma_async.sync.aligned.m64n64k16.f32.bf16.bf16 {%0, %1, %2, %3, %4, %5, %6, %7, %8, %9, %10, %11, %12, %13, %14, %15, %16, %17, %18, %19, %20, %21, %22, %23, %24, %25, %26, %27, %28, %29, %30, %31}, {%40, %41, %42, %43}, dx2, 1, 1, 1, 0;\n"
      "wgmma.mma_async.sync.aligned.m64n64k16.f32.bf16.bf16 {%0, %1, %2, %3, %4, %5, %6, %7, %8, %9, %10, %11, %12, %13, %14, %15, %16, %17, %18, %19, %20, %21, %22, %23, %24, %25, %26, %27, %28, %29, %30, %31}, {%44, %45, %46, %47}, dx3, 1, 1, 1, 0;\n"
      "wgmma.commit_group.sync.aligned;\n}\n"
      : "=f"(g[0]), "=f"(g[1]), "=f"(g[2]), "=f"(g[3]), "=f"(g[4]), "=f"(g[5]), "=f"(g[6]), "=f"(g[7]), "=f"(g[8]), "=f"(g[9]), "=f"(g[10]), "=f"(g[11]), "=f"(g[12]), "=f"(g[13]), "=f"(g[14]), "=f"(g[15]), "=f"(g[16]), "=f"(g[17]), "=f"(g[18]), "=f"(g[19]), "=f"(g[20]), "=f"(g[21]), "=f"(g[22]), "=f"(g[23]), "=f"(g[24]), "=f"(g[25]), "=f"(g[26]), "=f"(g[27]), "=f"(g[28]), "=f"(g[29]), "=f"(g[30]), "=f"(g[31])
      : "r"(w[0]), "r"(w[1]), "r"(w[2]), "r"(w[3]), "r"(w[4]), "r"(w[5]), "r"(w[6]), "r"(w[7]), "r"(w[8]), "r"(w[9]), "r"(w[10]), "r"(w[11]), "r"(w[12]), "r"(w[13]), "r"(w[14]), "r"(w[15]), "l"(dx)
      : "memory");
}

__device__ __forceinline__ uint32_t smem_u32(const void* p) { return (uint32_t)__cvta_generic_to_shared(p); }
__device__ __forceinline__ float ex2f(float x) { float y; asm("ex2.approx.ftz.f32 %0, %1;" : "=f"(y) : "f"(x)); return y; }
__device__ __forceinline__ float rcpf(float x) { float y; asm("rcp.approx.ftz.f32 %0, %1;" : "=f"(y) : "f"(x)); return y; }
__device__ __forceinline__ uint32_t pack_bf16(float lo, float hi) {
    uint32_t r; asm("cvt.rn.bf16x2.f32 %0, %1, %2;" : "=r"(r) : "f"(hi), "f"(lo)); return r;
}
__device__ __forceinline__ float bf_lo(uint32_t v) { return __uint_as_float(v << 16); }
__device__ __forceinline__ float bf_hi(uint32_t v) { return __uint_as_float(v & 0xFFFF0000u); }
template<int STRIDE>
__device__ __forceinline__ void cp16i(uint32_t dst, const char* base, uint32_t idx) {
    asm volatile("{\n.reg .b64 a;\nmad.wide.u32 a, %2, %3, %1;\ncp.async.cg.shared.global [%0], [a], 16;\n}\n" :: "r"(dst), "l"(base), "r"(idx), "n"(STRIDE) : "memory");
}
__device__ __forceinline__ void cp16e(uint32_t dst, const char* base, uint32_t idx, uint64_t pol) {
    asm volatile("{\n.reg .b64 a;\nmad.wide.u32 a, %2, 32, %1;\ncp.async.cg.shared.global.L2::cache_hint [%0], [a], 16, %3;\n}\n" :: "r"(dst), "l"(base), "r"(idx), "l"(pol) : "memory");
}
template<int STRIDE>
__device__ __forceinline__ void cp16z(uint32_t dst, const char* base, uint32_t idx, int k, int n, uint64_t pol) {
    if (STRIDE == 32)
        asm volatile("{\n.reg .b64 a;\n.reg .pred p;\nsetp.ge.s32 p, %3, %4;\nmad.wide.u32 a, %2, 32, %1;\ncp.async.cg.shared.global.L2::cache_hint [%0], [a], 16, p, %5;\n}\n"
                     :: "r"(dst), "l"(base), "r"(idx), "r"(k), "r"(n), "l"(pol) : "memory");
    else
        asm volatile("{\n.reg .b64 a;\n.reg .pred p;\nsetp.ge.s32 p, %3, %4;\nmad.wide.u32 a, %2, 128, %1;\ncp.async.cg.shared.global [%0], [a], 16, p;\n}\n"
                     :: "r"(dst), "l"(base), "r"(idx), "r"(k), "r"(n) : "memory");
}
template<int HI, bool Z>
__device__ __forceinline__ void cpx(uint32_t hi, uint32_t dst, uint32_t p, uint32_t lo, int k, int n) {
    if (Z) asm volatile("{\n.reg .b32 l;\n.reg .b64 a;\n.reg .pred q;\nsetp.ge.s32 q, %5, %6;\ndp2a.lo.u32.u32 l, %1, %2, %3;\nmov.b64 a, {l, %0};\ncp.async.cg.shared.global [%4], [a], 16, q;\n}\n"
                        :: "r"(hi), "r"(p), "r"(HI ? 0x8000u : 0x80u), "r"(lo), "r"(dst), "r"(k), "r"(n) : "memory");
    else asm volatile("{\n.reg .b32 l;\n.reg .b64 a;\ndp2a.lo.u32.u32 l, %1, %2, %3;\nmov.b64 a, {l, %0};\ncp.async.cg.shared.global [%4], [a], 16;\n}\n"
                      :: "r"(hi), "r"(p), "r"(HI ? 0x8000u : 0x80u), "r"(lo), "r"(dst) : "memory");
}
template<bool Z>
__device__ __forceinline__ void cpe(uint32_t hi, uint32_t dst, uint32_t idx, uint32_t lo, int k, int n, uint64_t pol) {
    if (Z) asm volatile("{\n.reg .b32 l;\n.reg .b64 a;\n.reg .pred q;\nsetp.ge.s32 q, %5, %6;\nmad.lo.u32 l, %1, 32, %2;\nmov.b64 a, {l, %0};\ncp.async.cg.shared.global.L2::cache_hint [%3], [a], 16, q, %4;\n}\n"
                        :: "r"(hi), "r"(idx), "r"(lo), "r"(dst), "l"(pol), "r"(k), "r"(n) : "memory");
    else asm volatile("{\n.reg .b32 l;\n.reg .b64 a;\nmad.lo.u32 l, %1, 32, %2;\nmov.b64 a, {l, %0};\ncp.async.cg.shared.global.L2::cache_hint [%3], [a], 16, %4;\n}\n"
                      :: "r"(hi), "r"(idx), "r"(lo), "r"(dst), "l"(pol) : "memory");
}
__device__ __forceinline__ void cp_commit() { asm volatile("cp.async.commit_group;" ::: "memory"); }
template<int N> __device__ __forceinline__ void cp_wait() { asm volatile("cp.async.wait_group %0;" :: "n"(N) : "memory"); }
__device__ __forceinline__ void mbar_init(uint32_t bar, int cnt) { asm volatile("mbarrier.init.shared.b64 [%0], %1;" :: "r"(bar), "r"(cnt) : "memory"); }
__device__ __forceinline__ void mbar_arrive(uint32_t bar) { asm volatile("mbarrier.arrive.shared.b64 _, [%0];" :: "r"(bar) : "memory"); }
__device__ __forceinline__ void mbar_expect(uint32_t bar, uint32_t bytes) { asm volatile("mbarrier.arrive.expect_tx.shared.b64 _, [%0], %1;" :: "r"(bar), "r"(bytes) : "memory"); }
__device__ __forceinline__ void mbar_cp_arrive(uint32_t bar) { asm volatile("cp.async.mbarrier.arrive.noinc.shared.b64 [%0];" :: "r"(bar) : "memory"); }
__device__ __forceinline__ void mbar_wait(uint32_t bar, uint32_t parity) {
    asm volatile("{\n.reg .pred p;\n.reg .u32 n;\nmbarrier.try_wait.parity.shared.b64 p, [%0], %1;\n@p bra DONE_%=;\nmov.u32 n, 0;\n"
                 "WAIT_%=:\nmbarrier.try_wait.parity.shared.b64 p, [%0], %1, 0x100000;\n@p bra DONE_%=;\n"
                 "add.u32 n, n, 1;\nsetp.lt.u32 p, n, 0x400000;\n@p bra WAIT_%=;\ntrap;\nDONE_%=:\n}\n"
                 :: "r"(bar), "r"(parity) : "memory");
}
__device__ __forceinline__ void mbar_wait_c(uint32_t bar, uint32_t parity) {
    asm volatile("{\n.reg .pred p;\nWAIT_%=:\nmbarrier.try_wait.parity.shared.b64 p, [%0], %1;\n@p bra DONE_%=;\nbra WAIT_%=;\nDONE_%=:\n}\n"
                 :: "r"(bar), "r"(parity) : "memory");
}
__device__ __forceinline__ void mbar_wait_h(uint32_t bar, uint32_t parity) {
    asm volatile("{\n.reg .pred p;\nWAIT_%=:\nmbarrier.try_wait.parity.shared.b64 p, [%0], %1, 0x100000;\n@p bra DONE_%=;\nbra WAIT_%=;\nDONE_%=:\n}\n"
                 :: "r"(bar), "r"(parity) : "memory");
}
__device__ __forceinline__ uint32_t lds32(uint32_t a) { uint32_t v; asm volatile("ld.shared.u32 %0, [%1];" : "=r"(v) : "r"(a) : "memory"); return v; }
__device__ __forceinline__ void sts32(uint32_t a, uint32_t v) { asm volatile("st.shared.u32 [%0], %1;" :: "r"(a), "r"(v) : "memory"); }
__device__ __forceinline__ uint2 lds64(uint32_t a) { uint2 v; asm volatile("ld.shared.v2.u32 {%0,%1}, [%2];" : "=r"(v.x), "=r"(v.y) : "r"(a) : "memory"); return v; }
__device__ __forceinline__ uint4 lds128(uint32_t a) { uint4 v; asm volatile("ld.shared.v4.u32 {%0,%1,%2,%3}, [%4];" : "=r"(v.x), "=r"(v.y), "=r"(v.z), "=r"(v.w) : "r"(a) : "memory"); return v; }
__device__ __forceinline__ void sts128(uint32_t a, uint4 v) { asm volatile("st.shared.v4.u32 [%0], {%1,%2,%3,%4};" :: "r"(a), "r"(v.x), "r"(v.y), "r"(v.z), "r"(v.w) : "memory"); }
__device__ __forceinline__ void ldsm4t(uint32_t* v, uint32_t a) {
    asm volatile("ldmatrix.sync.aligned.m8n8.x4.trans.shared.b16 {%0,%1,%2,%3}, [%4];" : "=r"(v[0]), "=r"(v[1]), "=r"(v[2]), "=r"(v[3]) : "r"(a) : "memory");
}
__device__ __forceinline__ void stsm4t(uint32_t a, const uint32_t* v) {
    asm volatile("stmatrix.sync.aligned.m8n8.x4.trans.shared.b16 [%0], {%1,%2,%3,%4};" :: "r"(a), "r"(v[0]), "r"(v[1]), "r"(v[2]), "r"(v[3]) : "memory");
}
__device__ __forceinline__ int atoms_inc(uint32_t a) { int v; asm volatile("atom.shared.add.u32 %0, [%1], 1;" : "=r"(v) : "r"(a) : "memory"); return v; }
__device__ __forceinline__ bool elect_one() {
    uint32_t el;
    asm volatile("{\n.reg .pred p;\nelect.sync _|p, 0xffffffff;\nselp.u32 %0, 1, 0, p;\n}" : "=r"(el));
    return el != 0;
}
__device__ __forceinline__ float tanhf_a(float x) { float y; asm("tanh.approx.f32 %0, %1;" : "=f"(y) : "f"(x)); return y; }
__device__ __forceinline__ const char* as_pair(const void* p, uint32_t scratch) {
    const char* r;
    asm volatile("st.shared.u64 [%1], %2;\nld.volatile.shared.u64 %0, [%1];" : "=l"(r) : "r"(scratch), "l"(p) : "memory");
    return r;
}
__device__ __forceinline__ void ld_unit(uint4& v, const char* p, bool ok) {
    asm volatile("{\n.reg .pred q;\nsetp.ne.u32 q, %5, 0;\n@q ld.relaxed.gpu.global.v4.u32 {%0,%1,%2,%3}, [%4];\n}"
                 : "+r"(v.x), "+r"(v.y), "+r"(v.z), "+r"(v.w) : "l"(p), "r"((uint32_t)ok) : "memory");
}
__device__ __forceinline__ void ld_unit(uint2& v, const char* p, bool ok) {
    asm volatile("{\n.reg .pred q;\nsetp.ne.u32 q, %3, 0;\n@q ld.relaxed.gpu.global.v2.u32 {%0,%1}, [%2];\n}"
                 : "+r"(v.x), "+r"(v.y) : "l"(p), "r"((uint32_t)ok) : "memory");
}
__device__ __forceinline__ void bulk_ld(uint32_t dst, const void* src, int bytes, uint32_t bar) {
    mbar_expect(bar, bytes);
    if (bytes > 0) asm volatile("cp.async.bulk.shared::cluster.global.mbarrier::complete_tx::bytes [%0], [%1], %2, [%3];" :: "r"(dst), "l"(src), "r"(bytes), "r"(bar) : "memory");
}
#define ELECT "{\n.reg .pred p;\nelect.sync _|p, 0xffffffff;\n@p "
__device__ __forceinline__ void w_expect(uint32_t bar, uint32_t bytes) { asm volatile(ELECT "mbarrier.arrive.expect_tx.shared.b64 _, [%0], %1;\n}" :: "r"(bar), "r"(bytes) : "memory"); }
__device__ __forceinline__ void w_ld(uint32_t dst, const void* src, int bytes, uint32_t bar) {
    asm volatile(ELECT "cp.async.bulk.shared::cluster.global.mbarrier::complete_tx::bytes [%0], [%1], %2, [%3];\n}" :: "r"(dst), "l"(src), "r"(bytes), "r"(bar) : "memory");
}
__device__ __forceinline__ void w_box_ld(uint32_t dst, const CUtensorMap* tm, int row, uint32_t bar) {
    asm volatile(ELECT "cp.async.bulk.tensor.2d.shared::cluster.global.mbarrier::complete_tx::bytes [%0], [%1, {%3, %4}], [%2];\n}"
        :: "r"(dst), "l"((uint64_t)tm), "r"(bar), "r"(0), "r"(row) : "memory");
}
__device__ __forceinline__ void w_st(void* dst, uint32_t src, int bytes) {
    asm volatile(ELECT "cp.async.bulk.global.shared::cta.bulk_group [%0], [%1], %2;\n}" :: "l"(dst), "r"(src), "r"(bytes) : "memory");
}
__device__ __forceinline__ void w_box_st(const CUtensorMap* tm, int col, uint32_t src) {
    asm volatile(ELECT "cp.async.bulk.tensor.2d.global.shared::cta.bulk_group [%0, {%2, %3}], [%1];\n}" :: "l"((uint64_t)tm), "r"(src), "r"(col), "r"(0) : "memory");
}
__device__ __forceinline__ void w_sent(unsigned* p, uint32_t src) {
    asm volatile(ELECT "cp.reduce.async.bulk.global.shared::cta.bulk_group.add.u32 [%0], [%1], 16;\n}" :: "l"(p), "r"(src) : "memory");
}
__device__ __forceinline__ void w_inc(unsigned* p) { asm volatile(ELECT "red.relaxed.gpu.global.add.u32 [%0], 1;\n}" :: "l"(p) : "memory"); }
__device__ __forceinline__ void w_hint(unsigned* p, uint32_t all) {
    #pragma unroll 1
    for (int i = 0; i < 4096; i++) {
        uint32_t v; asm volatile("ld.relaxed.gpu.global.u32 %0, [%1];" : "=r"(v) : "l"(p) : "memory");
        if (__all_sync(~0u, (int)(v - all) >= 0)) break;
    }
}

__device__ __forceinline__ void finish(uint4& a, const uint4& xu, const uint4& xv) {
    asm("{\n.reg .b32 z;\nfma.rn.relu.bf16x2 z, %0, %3, %1;\nadd.rn.bf16x2 %0, z, %2;\n}" : "+r"(a.x) : "r"(xu.x), "r"(xv.x), "r"(0x3F803F80u));
    asm("{\n.reg .b32 z;\nfma.rn.relu.bf16x2 z, %0, %3, %1;\nadd.rn.bf16x2 %0, z, %2;\n}" : "+r"(a.y) : "r"(xu.y), "r"(xv.y), "r"(0x3F803F80u));
    asm("{\n.reg .b32 z;\nfma.rn.relu.bf16x2 z, %0, %3, %1;\nadd.rn.bf16x2 %0, z, %2;\n}" : "+r"(a.z) : "r"(xu.z), "r"(xv.z), "r"(0x3F803F80u));
    asm("{\n.reg .b32 z;\nfma.rn.relu.bf16x2 z, %0, %3, %1;\nadd.rn.bf16x2 %0, z, %2;\n}" : "+r"(a.w) : "r"(xu.w), "r"(xv.w), "r"(0x3F803F80u));
}

constexpr float EPS2 = 2e-6f;
constexpr float TAU = 2.5e-5f;

template<bool HALF>
__device__ __forceinline__ void make_wfrag(uint32_t* f, const uint32_t* v) {
    const uint32_t v0 = v[0], v1 = v[1], v2 = v[2], v3 = v[3];
    f[0] = __byte_perm(v0, v1, 0x5410); f[1] = __byte_perm(v0, v1, 0x7632);
    f[2] = __byte_perm(v2, v3, 0x5410); f[3] = __byte_perm(v2, v3, 0x7632);
    if (HALF) {
        #pragma unroll
        for (int i = 0; i < 4; i++) asm("mul.rn.bf16x2 %0, %0, %1;" : "+r"(f[i]) : "r"(0x3F003F00u));
    }
}

template<int NP>
__device__ __forceinline__ void epi_fast(const float* g, const float* h, float m1, float m2,
                                         float& n0, float& d0, float& n1, float& d1, float& dmin)
{
    constexpr int JC = NP >= 6 ? NP - 1 - 2 : NP >= 4 ? NP - 2 : NP - 1;
    constexpr int JT = NP < 3 ? -1 : JC < NP - 1 ? JC : NP - 2;
    #pragma unroll
    for (int j = 0; j < NP; j++) {
        float t0 = tanhf_a(g[4*j+0]), t1 = tanhf_a(g[4*j+1]), t2 = tanhf_a(g[4*j+2]), t3 = tanhf_a(g[4*j+3]);
        auto add_d = [&]() {
            if (j == 0) { d0 = t0 + (2.f * (JT + 1) + EPS2); d1 = t2 + (2.f * (JT + 1) + EPS2); } else { d0 += t0; d1 += t2; }
            d0 += t1; d1 += t3;
        };
        if (j <= JT) add_d();
        if (j == NP - 1) { t0 = fmaf(t0, m1, m1); t1 = fmaf(t1, m2, m2); t2 = fmaf(t2, m1, m1); t3 = fmaf(t3, m2, m2); }
        else { t0 += 1.f; t1 += 1.f; t2 += 1.f; t3 += 1.f; }
        if (j > JT) add_d();
        if (j == 0) { n0 = t0 * h[0]; n1 = t2 * h[2]; } else { n0 = fmaf(t0, h[4*j], n0); n1 = fmaf(t2, h[4*j+2], n1); }
        n0 = fmaf(t1, h[4*j+1], n0); n1 = fmaf(t3, h[4*j+3], n1);
        if (j == JC) dmin = fminf(d0, d1);
    }
}

__device__ __noinline__ float4 epi_exact(const float4* gh, int np, int dv)
{
    float n0 = 0.f, d0 = EPS2, n1 = 0.f, d1 = EPS2;
    #pragma unroll 2
    for (int j = 0; j < np; j++) {
        const float4 g = gh[j], h = gh[NPMAX + j];
        const float ma = (2 * j < dv) ? 2.f : 0.f, mb = (2 * j + 1 < dv) ? 2.f : 0.f;
        const float e0 = ma * rcpf(1.f + ex2f(-2.f * LOG2E * g.x)), e1 = mb * rcpf(1.f + ex2f(-2.f * LOG2E * g.y));
        const float e2 = ma * rcpf(1.f + ex2f(-2.f * LOG2E * g.z)), e3 = mb * rcpf(1.f + ex2f(-2.f * LOG2E * g.w));
        d0 += e0 + e1; n0 = fmaf(e0, h.x, fmaf(e1, h.y, n0));
        d1 += e2 + e3; n1 = fmaf(e2, h.z, fmaf(e3, h.w, n1));
    }
    return make_float4(n0, d0, n1, d1);
}
template<int NP>
__device__ __forceinline__ void epi_dump(const float* g, const float* h, float4* gh) {
    #pragma unroll
    for (int i = 0; i < NP; i++) {
        gh[i] = make_float4(g[4*i], g[4*i+1], g[4*i+2], g[4*i+3]);
        gh[NPMAX + i] = make_float4(h[4*i], h[4*i+1], h[4*i+2], h[4*i+3]);
    }
}

__device__ __noinline__ void slow_bin(const __nv_bfloat16* x, const __nv_bfloat16* ea, const int* src, const int* dst,
                                      const __nv_bfloat16* wa, const __nv_bfloat16* wb, const __nv_bfloat16* wc,
                                      const __nv_bfloat16* wu, const __nv_bfloat16* wv, __nv_bfloat16* out,
                                      int E, int node0, int nn, int nthr)
{
    const int tid = threadIdx.x, lane = tid & 31;
    for (int i = tid; i < nn * 128; i += nthr) g_slow[(size_t)node0 * 128 + i] = 0.f;
    asm volatile("bar.sync 1, %0;" :: "r"(nthr) : "memory");
    for (int e0 = (tid >> 5) * 32; e0 < E; e0 += nthr) {
        int d = (e0 + lane < E) ? dst[e0 + lane] - node0 : -1;
        unsigned m = __ballot_sync(~0u, d >= 0 && d < nn);
        while (m) {
            int l = __ffs(m) - 1; m &= m - 1;
            int e = e0 + l, n = node0 + __shfl_sync(~0u, d, l), s = src[e];
            float g0 = 0, g1 = 0, h0 = 0, h1 = 0;
            for (int k = 0; k < 64; k++) {
                float xs = __bfloat162float(x[(size_t)s * 64 + k]), xd = __bfloat162float(x[(size_t)n * 64 + k]);
                uint32_t b2 = *(const uint32_t*)(wb + k * 64 + 2 * lane), v2 = *(const uint32_t*)(wv + k * 64 + 2 * lane);
                uint32_t a2 = *(const uint32_t*)(wa + k * 64 + 2 * lane);
                g0 = fmaf(xs, bf_lo(b2), fmaf(xd, bf_lo(a2), g0)); g1 = fmaf(xs, bf_hi(b2), fmaf(xd, bf_hi(a2), g1));
                h0 = fmaf(xs, bf_lo(v2), h0); h1 = fmaf(xs, bf_hi(v2), h1);
            }
            for (int k = 0; k < 16; k++) {
                float ev = __bfloat162float(ea[(size_t)e * 16 + k]);
                uint32_t c2 = *(const uint32_t*)(wc + k * 64 + 2 * lane);
                g0 = fmaf(ev, bf_lo(c2), g0); g1 = fmaf(ev, bf_hi(c2), g1);
            }
            float s0 = rcpf(1.f + ex2f(-LOG2E * g0)), s1 = rcpf(1.f + ex2f(-LOG2E * g1));
            float* acc = g_slow + (size_t)n * 128 + 4 * lane;
            atomicAdd(acc + 0, s0 * h0); atomicAdd(acc + 1, s0);
            atomicAdd(acc + 2, s1 * h1); atomicAdd(acc + 3, s1);
        }
    }
    __threadfence();
    asm volatile("bar.sync 1, %0;" :: "r"(nthr) : "memory");
    for (int i = tid; i < nn * 32; i += nthr) {
        int n = node0 + (i >> 5), cp = i & 31;
        float4 a = __ldcg((const float4*)(g_slow + (size_t)n * 128 + 4 * cp));
        float u0 = 0, u1 = 0;
        for (int k = 0; k < 64; k++) {
            float xd = __bfloat162float(x[(size_t)n * 64 + k]);
            uint32_t w2 = *(const uint32_t*)(wu + k * 64 + 2 * cp);
            u0 = fmaf(xd, bf_lo(w2), u0); u1 = fmaf(xd, bf_hi(w2), u1);
        }
        uint32_t xv = *(const uint32_t*)(x + (size_t)n * 64 + 2 * cp);
        float z0 = u0 + a.x / (a.y + 1e-6f), z1 = u1 + a.z / (a.w + 1e-6f);
        *(uint32_t*)(out + (size_t)n * 64 + 2 * cp) = pack_bf16(bf_lo(xv) + fmaxf(z0, 0.f), bf_hi(xv) + fmaxf(z1, 0.f));
    }
}

__global__ void __launch_bounds__(256) slow_kernel(const __nv_bfloat16* x, const __nv_bfloat16* ea, const int* src, const int* dst,
        const __nv_bfloat16* wa, const __nv_bfloat16* wb, const __nv_bfloat16* wc, const __nv_bfloat16* wu, const __nv_bfloat16* wv,
        __nv_bfloat16* out, int N, int E, int npb)
{
    int node0 = blockIdx.x * npb;
    slow_bin(x, ea, src, dst, wa, wb, wc, wu, wv, out, E, node0, max(0, min(npb, N - node0)), 256);
}

constexpr int XS_BYTES = NPMAX * 1024;
constexpr int ES_BYTES = NPMAX * 256;
constexpr int SM_XS = 0;
constexpr int SM_XU = SM_XS + 3 * NSTAGE * XS_BYTES;
constexpr int SM_TAB = SM_XU + NPB_MAX * 128;
constexpr int SM_ES = SM_TAB + (NPB_MAX + 2) * 128;
constexpr int SM_WC = SM_ES + 3 * NSTAGE * ES_BYTES;
constexpr int SM_OH = SM_WC + 2048;
constexpr int SM_EID = SM_OH + 256;
constexpr int SM_SRC = SM_EID + (SLOT_CAP + 32) * 4;
constexpr int SM_TINFO = SM_SRC + (SLOT_CAP + 32) * 2;
constexpr int SM_MISC = SM_TINFO + TILE_CAP * 32;
constexpr int SM_CLAIM = SM_TAB + (NPB_MAX + 1) * 128;
constexpr int SM_BARS = SM_MISC + 32 * 4;
constexpr int SM_ABAR = SM_BARS + 6 * 48;
constexpr int SM_GBAR = SM_ABAR + 16 * 8;
constexpr int SM_WL = SM_GBAR + 97 * 8;
constexpr int WST = 9;
constexpr int SMEM_BYTES = SM_WL + (96 + WST) * 8;
constexpr int SM_P2 = 0, SM_P1 = P2B + 256;
constexpr int SM_DEG = SM_P1 + P1B + 256;
constexpr int SM_CLS = SM_DEG + 512 * 4;
constexpr int SM_HIST = SM_CLS + NCLS * 4;
constexpr int SM_XLIST = SM_HIST + NB_MAX * 4;
constexpr int SM_SORT = SM_XLIST + 8;
constexpr int SM_SDEG = SM_SORT + NPB_MAX * 4;
constexpr int SM_PAIR = SM_SDEG + NPB_MAX * 2;
constexpr int SM_ENT = SM_ES + 1024;
constexpr int SM_H1 = SM_P1 + HB, SM_H2 = SM_P1;
constexpr int SM_IDX = SM_EID;
constexpr int SM_WR = SM_TAB;
static_assert(TILE_CAP <= 128 && TR >= 2 && SM_ES % 256 == 0 && NSTAGE == 2 && SM_BARS % 16 == 0 && SM_TINFO % 16 == 0 && SM_EID % 128 == 0 && SM_TAB % 1024 == 0 && SM_XU % 1024 == 0 && SM_TINFO % 8 == 0 && SM_OH % 16 == 0 && SM_XLIST % 8 == 0 && SM_PAIR % 8 == 0, "align");
static_assert(SM_P1 % 128 == 0 && P1B + HB <= SM_SRC - SM_EID && 2 * HB <= P1B && SM_H1 + 5 * 128 * 16 <= SM_XU && NB_MAX * (CE / 4) <= 6 * 384 && NB_MAX * 4 <= 5 * 128 && NB_MIN * 4 >= 3 * 128 && SM_PAIR + 128 * 8 <= SM_XU && CH_MAX * 4 <= SM_SRC - SM_EID && SM_DEG >= 3 << 14, "alias");
static_assert(SMEM_BYTES <= 232448, "smem");
constexpr uint32_t C_BRK = 16  , C_CONT = 32, C_MORE = 64;
constexpr uint32_t ONE_F = 0x3F800000u;
constexpr int NONE = NPB_MAX;

__device__ __forceinline__ uint2 tile_info(uint32_t e) {
    const uint32_t y = (uint32_t)((int)e >> 16) & (ONE_F | 0x1FFFu);
    return make_uint2(e, (e & 0x1F000000u) ? y | 0x80000000u : y);
}
__device__ __forceinline__ bool unpad(uint32_t w1, int np, float ga, float gb, float& d0, float& d1, int& dv) {
    const int pad = (int)w1 < 0 ? (w1 >> 8) & 31 : 0;
    dv = 2 * np - 2 - pad + ((int)w1 > 127) + ((int)w1 >= (int)ONE_F);
    float t0 = TAU * 2 * np, t1 = t0;
    if (pad) {
        t0 = fmaxf(t0, d0 * (1.f / 1024)); t1 = fmaxf(t1, d1 * (1.f / 1024));
        asm volatile("tanh.approx.f32 %0, %0;\ntanh.approx.f32 %1, %1;" : "+f"(ga), "+f"(gb));
        d0 -= pad * (1.f + ga); d1 -= pad * (1.f + gb);
    }
    if (dv == 0) { d0 = d1 = EPS2; t0 = t1 = 0.f; }
    return __any_sync(~0u, d0 < t0 || d1 < t1);
}
__device__ __forceinline__ void place(uint32_t sbase, uint32_t slot, uint32_t v, uint32_t eb) {
    asm volatile("{\n.reg .pred p;\nsetp.lt.u32 p, %0, %5;\n@p st.shared.u32 [%1], %2;\n@p st.shared.u16 [%3], %4;\n}"
                 :: "r"(slot), "r"(sbase + SM_EID + slot * 4), "r"(eb + (v >> 19)), "r"(sbase + SM_SRC + slot * 2), "r"(v), "n"(SLOT_CAP) : "memory");
}
__device__ __forceinline__ uint64_t desc_sw128(uint32_t a) {
    return (uint64_t)((a & 0x3FFFF) >> 4) | ((uint64_t)1 << 16) | ((uint64_t)64 << 32) | ((uint64_t)1 << 62);
}

template<bool LO32>
__global__ void __launch_bounds__(THREADS, 1)
gcn_kernel(const int* __restrict__ dst, unsigned* gbar, char* gs, const int* __restrict__ src, int E, int ch, int N, int npb, uint32_t magic,
           const __nv_bfloat16* __restrict__ x, const __nv_bfloat16* __restrict__ ea,
           const __nv_bfloat16* __restrict__ wa, const __nv_bfloat16* __restrict__ wb, const __nv_bfloat16* __restrict__ wc,
           const __nv_bfloat16* __restrict__ wu, const __nv_bfloat16* __restrict__ wv,
           __nv_bfloat16* out, int4 wrow, const __grid_constant__ CUtensorMap tm1, const __grid_constant__ CUtensorMap tm2,
           const __grid_constant__ CUtensorMap tmw, const __grid_constant__ CUtensorMap tmx)
{
    extern __shared__ __align__(1024) uint8_t smem[];
    int* cls = (int*)(smem + SM_CLS);
    int* misc = (int*)(smem + SM_MISC);
    WG0(); WS(0); CG(0);
    const uint32_t sbase = smem_u32(smem);
    const int tid = threadIdx.x, lane = tid & 31;
    const int b = blockIdx.x, nb = gridDim.x;
    const int cnt = max(0, min(ch, E - b * ch));
    const int node0 = b * npb;
    if (tid >= 384) {
        if (elect_one()) {
            const int v = (tid >> 5) & 3;
            mbar_init(sbase + SM_ABAR + v * 8, 1);
            asm volatile("fence.mbarrier_init.release.cluster;" ::: "memory");
            if (v < 3) bulk_ld(sbase + SM_IDX + v * 8192, dst + b * ch + v * 2048, min(max(cnt * 4 - v * 8192, 0), 8192), sbase + SM_ABAR + v * 8);
            else {
                mbar_init(sbase + SM_ABAR + 32, 1); mbar_init(sbase + SM_ABAR + 40, 1); mbar_init(sbase + SM_GBAR + 96 * 8, 32); mbar_init(sbase + SM_ABAR + 72, 12);
                mbar_init(sbase + SM_ABAR + 80, 1); mbar_init(sbase + SM_ABAR + 112, 12); mbar_init(sbase + SM_ABAR + 120, 1);
                mbar_expect(sbase + SM_ABAR + 24, 4 * 8192 + 2048); mbar_expect(sbase + SM_ABAR + 32, cnt * 4);
                mbar_expect(sbase + SM_ABAR + 80, nb * (CE * 2)); mbar_expect(sbase + SM_ABAR + 40, nb * 64); mbar_expect(sbase + SM_ABAR + 120, nb * 64);
            }
            #pragma unroll 8
            for (int i = 0; i < 24; i++) mbar_init(sbase + SM_GBAR + (v * 24 + i) * 8, 32);
            if (tid < 480) {
                #pragma unroll
                for (int i = 0; i < 2; i++) { mbar_init(sbase + SM_BARS + (v * 2 + i) * 48, 64); mbar_init(sbase + SM_BARS + (v * 2 + i) * 48 + 8, 128); }
                mbar_init(sbase + SM_ABAR + 48 + v * 8, 4); mbar_init(sbase + SM_ABAR + 88 + v * 8, 1); mbar_expect(sbase + SM_ABAR + 88 + v * 8, 16384);
            }
            asm volatile("fence.mbarrier_init.release.cluster;" ::: "memory");
        }
    }
    uint32_t tag = 0;
    if (tid < 384) asm volatile("ld.relaxed.gpu.global.u32 %0, [%1];" : "=r"(tag) : "l"(gbar + (OWNE ? 96 + 32 * b : 0)));
    const int warp = (int)__reduce_max_sync(~0u, (unsigned)tid >> 5);
    const int wg = warp >> 2, w = warp & 3;
    const int q = lane >> 2, t = lane & 3;
    const int ch0 = 16 * w + 2 * q;
    const int nn = max(0, min(npb, N - node0));
    if (sbase & 1023) __trap();

    sts32(sbase + SM_DEG + tid * 4, tid < NPB_MAX ? 0 : 0x80000000u);
    if (tid < NCLS + NB_MAX) cls[tid] = tid < NCLS ? 0 : ((tid - NCLS) * 20) & 63;
    else if (wg == 2) {
        if (w < 2) {
            *(uint32_t*)(smem + SM_OH + (tid & 63) * 4) = t != (q >> 1) ? 0u : (w == 0 ? 0x00003F00u : 0x3F000000u);
        } else if (w == 2) *(uint32_t*)(smem + SM_TAB + NPB_MAX * 128 + lane * 4) = 0u;
        else misc[lane] = lane == 5 ? TILE_CAP - TILE_X : lane == 8;
    }
    if (warp == 13 && lane < WST * 2) sts32(sbase + SM_WL + 768 + lane * 4, NONE * 0x10001u);
    if (warp == 14) sts32(sbase + SM_TINFO + 96 * 32 + lane * 4, 0);
    if (warp == 15) sts32(sbase + SM_CLAIM + lane * 4, lane == 0 ? 3 : 0x40000000);
    if (tid == 0) sts32(sbase + SM_XLIST, tag);
    tag = (tag & 1) | 2;
    if (wg < 3) {
        const uint32_t d0 = ((NPB_MAX + ((2 * lane) & 15) + 16 * (b & 1)) * 4 | (tag << 14)) * 0x10001u, d1 = d0 + 0x40004u, d2 = tag << 16;
        #pragma unroll 1
        for (int i = tid; i < (P1B + 256) / 16; i += 384) {
            sts128(sbase + SM_P1 + i * 16, make_uint4(d0, d0, d1, d1));
            sts128(sbase + SM_P2 + i * 16, make_uint4(d2, d2, d2, d2)); sts128(sbase + SM_P2 + P1B + i * 16, make_uint4(d2, d2, d2, d2));
        }
    }
    WS(1);
    __syncthreads();
    if (wg == 3) tag = lds32(sbase + SM_P2) >> 16;
    uint32_t all = 0;
    if (wg == 3) all = (lds32(sbase + SM_XLIST) + 1) * nb;
    if (tid == 128) {
        asm volatile("prefetch.tensormap [%0];" :: "l"((uint64_t)&tmw) : "memory");
        asm volatile("prefetch.tensormap [%0];" :: "l"((uint64_t)&tm1) : "memory");
        asm volatile("prefetch.tensormap [%0];" :: "l"((uint64_t)&tm2) : "memory");
        asm volatile("prefetch.tensormap [%0];" :: "l"((uint64_t)&tmx) : "memory");
    }
    const uint32_t su = __reduce_or_sync(~0u, sbase);
    uint32_t ent[EPT];
    #pragma unroll
    for (int v = 0; v < EPT / 4; v++) {
        mbar_wait_c(sbase + SM_ABAR + v * 8, 0);
        if (v == 0) {
            if (warp == 10) { if (cnt > 0) w_ld(su + SM_XU, src + b * ch, cnt * 4, su + SM_ABAR + 32); }
            else if (warp == 11) w_ld(su + SM_WR + 24576, wc, 2048, su + SM_ABAR + 24);
            else if (wg == 3) w_box_ld(su + SM_WR + (w == 3 ? 5 : w) * 8192, &tmw, w == 0 ? wrow.x : w == 1 ? wrow.y : w == 2 ? wrow.z : wrow.w, su + SM_ABAR + 24);
        }
        const uint32_t off = v * (THREADS * 4) + tid * 4;
        if (off < (uint32_t)cnt) {
            const uint32_t ia = sbase + SM_IDX + off * 4;
            const uint4 u = lds128(ia);
            uint32_t dv[4] = {u.x, u.y, u.z, u.w}, ps[4], ck[4];
            uint32_t* en = ent + 4 * v;
            #pragma unroll
            for (int k = 0; k < 4; k++) {
                dv[k] = min(dv[k], (uint32_t)(nb * npb - 1));
                ps[k] = __umulhi(dv[k], magic);
                asm volatile("atom.shared.add.u32 %0, [%1], 0x10001;" : "=r"(ck[k]) : "r"(sbase + SM_HIST + ps[k] * 4) : "memory");
            }
            #pragma unroll
            for (int k = 0; k < 4; k++) {
                dv[k] = (dv[k] - ps[k] * npb) * 4 + (tag << 14);
                en[k] = (ck[k] & 63) + ps[k] * CE;
            }
            if (__builtin_expect(max(max(ck[0], ck[1]), max(ck[2], ck[3])) >= CE << 16, 0)) {
                #pragma unroll
                for (int k = 0; k < 4; k++) {
                    if (ck[k] >= CE << 16) {
                        uint32_t j; asm volatile("atom.shared.inc.u32 %0, [%1], 0x7fffffff;" : "=r"(j) : "r"(sbase + SM_MISC + 8) : "memory");
                        if (j >= 15) { sts32(sbase + SM_P1 + P1B + 60, 0xFE0000u | (tag << 14)); j = min(j + 1, 63u); }
                        sts32(sbase + SM_P1 + P1B + j * 4, dv[k] | ((j < 63 ? ps[k] : 255u) << 16));
                        en[k] = NB_MAX * CE + j;
                    }
                }
            }
            #pragma unroll
            for (int k = 0; k < 4; k++)
                asm volatile("{\n.reg .pred p;\nsetp.lt.u32 p, %2, %3;\n@p st.shared.u16 [%0], %1;\n}" :: "r"(sbase + SM_P1 + en[k] * 2), "r"(dv[k]), "r"(en[k]), "n"(NB_MAX * CE) : "memory");
        }
    }
    if (warp == 15) {
        #pragma unroll
        for (int v = 0; v < EPT / 4; v++) sts128(sbase + SM_ENT + v * 512 + lane * 16, make_uint4(ent[4*v], ent[4*v+1], ent[4*v+2], ent[4*v+3]));
    }
    asm volatile("fence.proxy.async.shared::cta;" ::: "memory");
    WS(5);
    __syncthreads();
    auto delay = [&](uint32_t d) { uint32_t c0, c1; asm volatile("mov.u32 %0, %%clock;" : "=r"(c0)); do { asm volatile("mov.u32 %0, %%clock;" : "=r"(c1)); } while (__all_sync(~0u, c1 - c0 < d)); };
    if (warp == 15) {
        w_inc(gbar + 32);
        w_st(gs + G_H1 + b * 64, su + SM_P1 + P1B, 64);
        w_box_st(&tm1, b * (CE / 2), su + SM_P1);
        w_st(gs + G_L + b * 512, su + SM_P1 + P1B, 256);
        asm volatile("cp.async.bulk.commit_group;" ::: "memory");
    } else {
        mbar_wait_c(su + SM_ABAR + 32, 0);
        auto put = [&](uint32_t off, const uint32_t* uu) {
            if (off < (uint32_t)cnt) {
                const uint4 sv = lds128(sbase + SM_XU + off * 4);
                const uint32_t ss[4] = {sv.x, sv.y, sv.z, sv.w};
                #pragma unroll
                for (int k = 0; k < 4; k++) sts32(sbase + SM_P2 + uu[k] * 4, (ss[k] & 0xFFFF) | (((off + k) << 19) + (tag << 16)));
            }
        };
        if (wg == 3) {
            const uint4 e = lds128(sbase + SM_ENT + w * 512 + lane * 16);
            const uint32_t uu[4] = {e.x, e.y, e.z, e.w};
            put(w * (THREADS * 4) + (480 + lane) * 4, uu);
        }
        #pragma unroll
        for (int v = 0; v < EPT / 4; v++) put(v * (THREADS * 4) + tid * 4, ent + 4 * v);
        asm volatile("fence.proxy.async.shared::cta;" ::: "memory");
        WS(7);
        __syncwarp();
        asm volatile("bar.arrive 12, 512;" ::: "memory");
    }
    WS(8);

    const int ngroups = (nn + 3) >> 2;
    if (warp < 12) {
        asm volatile("setmaxnreg.inc.sync.aligned.u32 152;");
        const uint32_t ab = su + SM_ABAR;
        uint32_t wf[40], wn[16];
        const uint32_t mo = sbase + (8 * (lane >> 4) + (lane & 7)) * 128 + (((2 * w + ((lane >> 3) & 1)) ^ (lane & 7)) << 4);
        mbar_wait(ab + 24, 0);
        {
            uint32_t wr[36];
            const uint32_t wo = sbase + SM_WR + (2 * t) * 128, w0 = wo + ((ch0 * 2) ^ (2 * t << 4)), w1 = wo + 128 + ((ch0 * 2) ^ ((2 * t + 1) << 4));
            #pragma unroll
            for (int i = 0; i < 36; i++) {
                const int ks = i >> 2, ro = 4 * (i & 2) * 128;
                wr[i] = ks == 4 ? lds32(wo + 24576 + ch0 * 2 + (i & 1) * 128 + ro) : lds32((i & 1 ? w1 : w0) + (ks < 4 ? ks : ks - 1) * 2048 + ro);
            }
            #pragma unroll
            for (int ks = 0; ks < 4; ks++) ldsm4t(wn + 4 * ks, mo + SM_WR + 16384 + ks * 2048);
            #pragma unroll
            for (int ks = 0; ks < 9; ks++) { if (ks < 5) make_wfrag<true>(wf + 4 * ks, wr + 4 * ks); else make_wfrag<false>(wf + 4 * ks, wr + 4 * ks); }
            const uint32_t a = sbase + SM_WC + (16 * w + q) * 32 + t * 4, sw = (q >> 2) << 4;
            sts32(a + sw, wf[16]); sts32(a + 256 + sw, wf[17]); sts32(a + (sw ^ 16), wf[18]); sts32(a + 256 + (sw ^ 16), wf[19]);
            uint32_t z = 0;
            #pragma unroll
            for (int i = 0; i < 36; i++) z ^= wf[i];
            sts32(sbase + SM_ES + lane * 4, z);
            asm volatile("fence.proxy.async.shared::cta;" ::: "memory");
        }
        const uint64_t wcd = __reduce_or_sync(~0u, (((sbase + SM_WC) & 0x3FFFF) >> 4) | (8u << 16)) | EDHI;
        const uint32_t bar0 = __reduce_or_sync(~0u, sbase + SM_BARS + wg * 96);
        const uint32_t xd0 = __reduce_or_sync(~0u, (((sbase + SM_XS + wg * NSTAGE * XS_BYTES) & 0x3FFFF) >> 4) | (1u << 16));
        const uint32_t ed0 = __reduce_or_sync(~0u, (((sbase + SM_ES + wg * NSTAGE * ES_BYTES) & 0x3FFFF) >> 4) | (8u << 16));
        const uint64_t ohd = __reduce_or_sync(~0u, (((sbase + SM_OH) & 0x3FFFF) >> 4) | (8u << 16));
        const uint32_t tabx = __reduce_or_sync(~0u, sbase + SM_TAB);
        const uint32_t bars = __reduce_or_sync(~0u, 2 * bar0 + 48), xds = __reduce_or_sync(~0u, 2 * xd0 + XS_BYTES / 16), eds = __reduce_or_sync(~0u, 2 * ed0 + ES_BYTES / 16);
        const uint32_t xuo = __reduce_or_sync(~0u, sbase + SM_XU + wg * 16384);
        { const uint2 z = lds64(sbase + SM_OH + 8); wf[37] = z.x; wf[38] = z.y; }
        const uint32_t c2 = __shfl_sync(~0u, ch0 * 2, lane), t8 = __shfl_sync(~0u, t * 8, lane);
        WS(9);
        constexpr int NU = 6;
        const uint32_t dm = ((NPB_MAX + lane) * 4 | (tag << 14)) * 0x10001u;
        uint2 r1[NU];
        mbar_wait(ab + 80, 0);
        WS(2);
        #pragma unroll
        for (int i = 0; i < NU; i++) {
            r1[i] = make_uint2(dm, dm);
            if (i < 5 && NB_MIN * 16 >= 384 * (i + 1) || tid + 384 * i < nb * 16) r1[i] = lds64(sbase + SM_IDX + (tid + 384 * i) * 8);
        }
        uint32_t spins = 0;
        while (true) {
            uint32_t bad = 0;
            #pragma unroll
            for (int i = 0; i < NU; i++) bad |= r1[i].y ^ dm;
            if (__builtin_expect(!__any_sync(~0u, bad & 0xC000), 1)) break;
            #pragma unroll
            for (int i = 0; i < NU; i++) ld_unit(r1[i], gs + b * (P1B + P2B) + (tid + 384 * i) * 8, (r1[i].y ^ dm) & 0xC000);
            if (++spins > (1u << 22)) break;
        }
        WS(3);
        const uint32_t db = sbase + SM_DEG - (tag << 14);
        int rk[NU][4];
        #pragma unroll
        for (int i = 0; i < NU; i++) {
            rk[i][0] = r1[i].x & 0xFFFF; rk[i][1] = r1[i].x >> 16; rk[i][2] = r1[i].y & 0xFFFF; rk[i][3] = r1[i].y >> 16;
            #pragma unroll
            for (int k = 0; k < 4; k++) asm volatile("red.shared.add.u32 [%0], 1;" :: "r"(db + min((uint32_t)rk[i][k], NPB_MAX * 4 + (tag << 14))) : "memory");
        }
        WS(10);
        asm volatile("bar.sync 11, 512;" ::: "memory");
        WS(11);
        int mycls = 0, mycr = 0, dg = lds32(sbase + SM_DEG + tid * 4);
        if (tid < nn) {
            mycls = NCLS - 1 - (dg <= 40 ? dg : min(41 + ((dg - 41) >> 3), NCLS - 1)); mycr = atomicAdd(&cls[mycls], 1);
        }
        int s0 = 0;
        if (__builtin_expect(dg > 40, 0)) s0 = max(SLOT_CAP - ((dg + 1) & ~1) - atomicAdd(&misc[6], (dg + 1) & ~1), 0);
        asm volatile("bar.sync 1, 384;" ::: "memory");
        WS(12);
        {
            const uint2 c = lds64(sbase + SM_CLS + lane * 8);
            const int v0 = c.x * (lane > 11 ? ((64 - 2 * lane) << 16) + 1 : 1), v1 = c.y * (lane >= 11 ? ((62 - 2 * lane) << 16) + 1 : 1);
            int inc = v0 + v1;
            #pragma unroll
            for (int o = 1; o < 32; o <<= 1) { int y = __shfl_up_sync(~0u, inc, o); if (lane >= o) inc += y; }
            const int e0 = __shfl_sync(~0u, inc - v0 - v1, mycls >> 1), e1 = __shfl_sync(~0u, inc - v1, mycls >> 1);
            const int e = (mycls & 1) ? e1 : e0;
            if (tid < nn) {
                if (dg <= 40) s0 = min((e >> 16) + mycr * ((dg + 1) & ~1), SLOT_CAP - 40);
                sts32(sbase + SM_DEG + tid * 4, s0);
            }
            const uint32_t pos = tid < nn ? (e & 0xFFFF) + mycr : tid;
            sts32(sbase + SM_SORT + pos * 4, tid < nn ? (uint32_t)tid | ((uint32_t)s0 << 16) : NONE);
            asm volatile("st.shared.u16 [%0], %1;" :: "r"(sbase + SM_SDEG + pos * 2), "r"(min(dg, 65535)) : "memory");
            asm volatile("st.shared.u16 [%0], %1;" :: "r"(sbase + SM_WL + pos * 2), "r"(tid < nn ? tid : NONE) : "memory");
            if (tid == 383) { misc[4] = (nn - c.y + 3) >> 2; if ((inc >> 16) + misc[6] > SLOT_CAP - 40) misc[1] = 1; }
        }
        asm volatile("bar.sync 1, 384;" ::: "memory");
        WS(13);
        const uint32_t sv = lds32(sbase + SM_SORT + tid * 4);
        const uint2 d4 = lds64(sbase + SM_SDEG + (tid >> 2) * 8);
        const uint32_t slow = lds32(sbase + SM_MISC + 4);
        #pragma unroll
        for (int i = 0; i < NU; i++) {
            #pragma unroll
            for (int k = 0; k < 4; k++) rk[i][k] = atoms_inc(db + rk[i][k]);
        }
        if (__reduce_or_sync(~0u, slow) == 0) {
            const uint32_t nd = sv & 0xFFFF;
            const int g = tid >> 2;
            dg = ((t & 2 ? d4.y : d4.x) >> (16 * (t & 1))) & 0xFFFF;
            const uint32_t hi2 = __vmaxu2(d4.x, d4.y), lo2 = __vminu2(d4.x, d4.y);
            const int mx = max(hi2 >> 16, hi2 & 0xFFFF), mn = min(lo2 >> 16, lo2 & 0xFFFF);
            int left = (mx + 1) >> 1;
            int tl = g, nx = ngroups + 4 + g, nt = left > NPMAX ? 2 : 1;
            const bool odd = left > 2 * NPMAX || (nt == 2 && nx >= TILE_CAP - TILE_X);
            if (__builtin_expect(__any_sync(~0u, odd), 0)) {
                if (odd) nt = (left + NPMAX - 1) / NPMAX;
                if (odd && t == 0) { asm volatile("atom.shared.add.u32 %0, [%1], %2;" : "=r"(nx) : "r"(sbase + SM_MISC + 20), "r"(nt - 1) : "memory"); if (nx + nt - 1 > TILE_CAP) misc[1] = 1; }
                nx = __shfl_sync(~0u, nx, lane & ~3);
                if (odd && nx + nt - 1 > TILE_CAP) left = 0;
            }
            const uint32_t w0 = nd * 128 + ((nd & 7) << 4);
            if (g >= ngroups + 4) tl = ngroups;
            uint32_t cont = 0;
            int done = 0;
            bool act = true;
            do {
                int np = nt <= 2 ? (left + nt - 1) >> (nt - 1) : (left + nt - 1) / nt;
                left -= np; nt = max(nt - 1, 1);
                if (np) np = max(np, NPMIN);
                const int dv = min(max(dg - done, 0), 2 * np);
                uint32_t code = (uint32_t)np | cont | (left > 0 ? C_MORE : 0u);
                const bool gen = mn - done < 2 * np - 2;
                if (np == 0) code = 0;
                if (gen || (code & (C_CONT | C_MORE))) code |= C_BRK;
                const uint32_t w1 = code | (dv == 2 * np ? 0x8000u : dv == 2 * np - 1 ? 128u : (2 * np - 2 - dv) << 8);
                if (act) *(uint2*)(smem + SM_TINFO + tl * 32 + t * 8) = make_uint2((dv ? (sv >> 16) + done : 0) | ((gen ? (np > 8 ? 15 : np > 5 ? 14 : 13) : np) << 16) | ((left > 0 ? nx : 0) << 20) | ((uint32_t)dv << 27), w0 | (np == 0 ? 0u : w1 << 16));
                tl = nx++; cont = C_CONT; done += 2 * np; act = left > 0;
            } while (__any_sync(~0u, act));
        }
        __syncwarp();
        asm volatile("bar.arrive 4, 512;" ::: "memory");
        WS(14);
        #pragma unroll
        for (int pc = 0; pc < 3; pc++) {
            uint4 r2[2];
            mbar_wait(ab + pc * 8, 1);
            if (pc == 0) WS(4); if (pc == 2) WS(16);
            #pragma unroll
            for (int k = 0; k < 2; k++) {
                r2[k] = lds128(sbase + SM_P2 + (tid + 384 * (2 * pc + k)) * 16);
                if (rk[2 * pc + k][0] < 0) r2[k].w = tag << 16;
            }
            while (__builtin_expect(__any_sync(~0u, ((r2[0].w ^ (tag << 16)) | (r2[1].w ^ (tag << 16))) & 0x30000), 0)) {
                #pragma unroll
                for (int k = 0; k < 2; k++)
                    ld_unit(r2[k], gs + b * (P1B + P2B) + P1B + (tid + 384 * (2 * pc + k)) * 16, (r2[k].w ^ (tag << 16)) & 0x30000);
                if (++spins > (1u << 22)) break;
            }
            #pragma unroll
            for (int k = 0; k < 2; k++) {
                const int i = 2 * pc + k;
                const uint32_t eb = ((tid >> 4) + 24 * i) * ch;
                place(sbase, rk[i][0], r2[k].x, eb); place(sbase, rk[i][1], r2[k].y, eb); place(sbase, rk[i][2], r2[k].z, eb); place(sbase, rk[i][3], r2[k].w, eb);
            }
        }
        WGD();
        __syncwarp();
        asm volatile("bar.arrive 3, 480;" ::: "memory");
        float g[4 * NPMAX], h[4 * NPMAX];
        float4 lgh[2 * NPMAX];
        float4 cyr = make_float4(0.f, 0.f, 0.f, 0.f);
        WS(15); CG(1);
        mbar_wait(ab + 88 + wg * 8, 0);
        WSG(1);
        auto pack = [&](uint32_t* v, const float* u) {
            #pragma unroll
            for (int i = 0; i < 16; i++) v[i] = pack_bf16(u[2*i], u[2*i+1]);
        };
        auto rows_st = [&](uint32_t p, const uint32_t* v) {
            #pragma unroll
            for (int i = 0; i < 4; i++) stsm4t(p + i * 2048, v + 4 * i);
        };
        {
            const uint64_t d0 = desc_sw128(xuo), d1 = d0 + 512;
            const uint32_t mr = mo + wg * 16384;
            uint32_t v[16];
            node_mma(g, wn, d0); node_mma(h, wn, d1);
            TileMMA<8>::wait_g(g);
            pack(v, g); rows_st(mr + SM_TAB, v);
            TileMMA<8>::wait_h(h);
            WSG(5);
            #pragma unroll
            for (int ks = 0; ks < 4; ks++) ldsm4t(wn + 4 * ks, mo + SM_WR + 40960 + ks * 2048);
            node_mma(g, wn, d0);
            if (wg == 2) asm volatile("bar.sync 5, 384;" ::: "memory"); else asm volatile("bar.arrive 5, 384;" ::: "memory");
            pack(v, h); rows_st(mr + SM_TAB + 8192, v);
            node_mma(h, wn, d1);
            __syncwarp();
            if (lane == 0) mbar_arrive(sbase + SM_ABAR + 112);
            WSG(7);
            TileMMA<8>::wait_g(g);
            pack(v, g);
            asm volatile("bar.sync %0, 128;" :: "r"(8 + wg) : "memory");
            rows_st(mr + SM_XU, v);
            TileMMA<8>::wait_h(h);
            WSG(11);
            pack(v, h);
            asm volatile("bar.sync %0, 128;" :: "r"(8 + wg) : "memory");
            rows_st(mr + SM_XU + 8192, v);
            __syncwarp();
            if (lane == 0) mbar_arrive(sbase + SM_ABAR + 72);
            mbar_wait(ab + 112, 0);
            __syncwarp();
            if (__builtin_expect(__reduce_or_sync(~0u, misc[1]) != 0, 0)) { slow_bin(x, ea, src, dst, wa, wb, wc, wu, wv, out, E, node0, nn, 384); asm volatile("exit;"); }
            WS(6);
        }
        uint32_t bar = bar0, xd = xd0, ed = ed0, ph = 0, code, w1, ta, pta = NONE * 128 + c2;
        float pn0 = 0.f, pd0 = 1.f, pn1 = 0.f, pd1 = 1.f;
        uint2 ni = tile_info(lds32(sbase + SM_TINFO + wg * 32 + t * 8 + 4));
        auto fetch_a = [&]() {
            ta = (ni.x & 0xFFFFu) ^ c2;
            wf[36] = lds32(tabx + ta); wf[39] = lds32(tabx + ta);
            code = __reduce_or_sync(~0u, ni.y);
        };
        auto emit = [&]() { sts32(tabx + pta, pack_bf16(pn0 * rcpf(pd0), pn1 * rcpf(pd1))); };
        auto carry = [&]() {
            if (w1 & C_CONT) { pn0 += cyr.x; pd0 += cyr.y; pn1 += cyr.z; pd1 += cyr.w; }
            if (w1 & C_MORE) { cyr = make_float4(pn0, pd0 - EPS2, pn1, pd1 - EPS2); pn0 = pn1 = 0.f; pta = NONE * 128 + c2; }
        };
        auto next = [&](uint32_t fb) {
            pta = ta;
            w1 = ni.y;
            ni = lds64(fb + 16 + t8);
        };
        fetch_a();
        while (true) {
            switch (code & 15) {
                default: goto finished;
#define TILE(P) { \
                    float dmin; \
                    do { \
                        mbar_wait_c(bar, ph); \
                        TileMMA<P>::issue(g, h, wf, xd | (0x40000040ull << 32), ed | EDHI, ohd, wcd); \
                        const uint32_t eb = bar + 8; \
                        ph ^= bar != bar0; bar = bars - bar; xd = xds - xd; ed = eds - ed; \
                          \
                        asm volatile("{\n.reg .pred p;\nsetp.eq.u32 p, %0, 77;\n@p trap;\n}" :: "r"(xds) : "memory"); \
                        emit(); next(eb - 8); \
                        TileMMA<P>::wait_g(g); fetch_a(); TileMMA<P>::wait_h(h); \
                        mbar_arrive(eb); \
                        float m1; \
                        asm("set.gt.f32.f32 %0, %1, 0f0000007F;" : "=f"(m1) : "f"(__uint_as_float(w1))); \
                        epi_fast<P>(g, h, m1, __uint_as_float(w1), pn0, pd0, pn1, pd1, dmin); \
                    } while (!(__any_sync(~0u, dmin < TAU * 2 * P) | ((code & 31) != P))); \
                    if (__builtin_expect(__any_sync(~0u, (int)w1 < 0 || dmin < TAU * 2 * P), 0)) { \
                        int dv; \
                        if (unpad(w1, P, g[P > 1 ? 4 * P - 7 : 0], g[P > 1 ? 4 * P - 5 : 0], pd0, pd1, dv)) { \
                            epi_dump<P>(g, h, lgh); \
                            const float4 r = epi_exact(lgh, P, dv); \
                            pn0 = r.x; pd0 = r.y; pn1 = r.z; pd1 = r.w; \
                        } \
                    } \
                    if (code & C_BRK) { carry(); if (P != 11 && (code & 15) == P) goto L##P; } \
                    if (P == 11) {         \
                        const uint32_t a = tabx + (SM_WC - SM_TAB) + (c2 & 0x60) * 16 + (c2 & 0x1C) * 8 + (t8 >> 1), sw = c2 & 16; \
                        wf[16] = lds32(a + sw); wf[17] = lds32(a + 256 + sw); wf[18] = lds32(a + (sw ^ 16)); wf[19] = lds32(a + 256 + (sw ^ 16)); \
                    } }
#define CASE(P, UP, DN) case P: L##P: TILE(P) \
                    if (P > NPMIN && (code & 15) == P - 1) goto L##DN; \
                    if ((code & 15) == UP) goto L##UP; \
                    break;
                CASE(11, 11, 10) CASE(10, 11, 9) CASE(9, 10, 8) CASE(8, 9, 7) CASE(7, 8, 6) CASE(6, 7, 5) CASE(5, 6, 4) CASE(4, 5, 4)
#undef CASE
#undef TILE
            }
        }
finished:
        emit();
        __syncwarp();
        if (lane == 0) mbar_arrive(sbase + SM_ABAR + 48 + wg * 8);
    } else {
        asm volatile("setmaxnreg.dec.sync.aligned.u32 56;");
        auto x_ld = [&](int i0, int i1) {
            #pragma unroll
            for (int i = i0; i < i1; i++) w_box_ld(su + SM_XU + i * 8192, &tmx, node0 + i * 64, su + SM_ABAR + 88 + (i >> 1) * 8);
        };
        if (w == 3) {
            w_hint(gbar + 32, all);
            asm volatile("cp.async.bulk.wait_group.read 0;" ::: "memory");
            if (D1) delay(D1);
            WS(2);
            w_ld(su + SM_IDX, gs + b * (P1B + P2B), nb * (CE * 2), su + SM_ABAR + 80);
            w_ld(su + SM_H1, gs + G_H1, nb * 64, su + SM_ABAR + 120);
        asm volatile("bar.sync 12, 512;" ::: "memory");
            if (D3) delay(D3);
            if (H2M == 1) w_inc(gbar + 64);
            w_box_st(&tm2, P1B / 4 + b * CE, su + SM_P2);
            w_st(gs + G_H2 + b * 64, su + SM_P2 + P2B, 64);
            w_st(gs + G_L + b * 512 + 256, su + SM_P2 + P2B, 256);
            if (H2M == 0) w_sent(gbar + 64, su + SM_MISC + 32);
            asm volatile("cp.async.bulk.commit_group;" ::: "memory");
            if (!XAFT) x_ld(0, XSPL);
        }
        const uint32_t ab = su + SM_ABAR;
        uint32_t todo = 0;
        WS(12);
        mbar_wait(ab + 120, 0);
        WS(13);
        {
            uint4 r[5];
            #pragma unroll
            for (int i = 0; i < 5; i++) r[i] = lds128(sbase + SM_H1 + (tid - 384 + 128 * i) * 16);
            #pragma unroll
            for (int i = 0; i < 5; i++) {
                const uint32_t bb = b << 16;
                const uint32_t m = min(min(min(r[i].x ^ bb, r[i].y ^ bb), min(r[i].z ^ bb, r[i].w ^ bb)), r[i].w ^ 0xFE0000u) >> 16;
                if ((m == 0) | (((r[i].w ^ (tag << 14)) & 0xC000) != 0)) todo |= 1 << i;
            }
            todo &= tid - 384 + 512 < nb * 4 ? 31 : tid - 384 + 384 < nb * 4 ? 15 : 7;
        }
        #pragma unroll 1
        for (int put = 0; put < 2; put++) {
            uint32_t any = __reduce_or_sync(~0u, todo), m = 0, u = 0;
            #pragma unroll 1
            while (any | m) {
                uint4 r = make_uint4(0, 0, 0, 0), r2 = r;
                uint32_t s, go, gd;
                bool on;
                if (__builtin_expect(m == 0, 1)) {
                    const uint32_t i = __ffs(any) - 1;
                    any &= any - 1; u = tid - 384 + 128 * i; on = (todo >> i) & 1;
                    r = lds128(sbase + SM_H1 + u * 16); r2 = lds128(sbase + SM_H2 + u * 16);
                    s = u >> 2; go = G_H1 + u * 16; gd = HB;
                } else {
                    s = ((u & ~31) + __ffs(m) - 1) >> 2; m &= m - 1; on = lane < 12;
                    go = G_L + s * 512 + 64 + lane * 16; gd = 256;
                }
                #pragma unroll 1
                for (int n = 0; n < (1 << 22); n++) {
                    const bool b1 = on && ((r.w >> 14) & 3) != tag, b2 = on && put && ((r2.w >> 16) & 3) != tag;
                    if (__builtin_expect(!__any_sync(~0u, b1 | b2), 1)) break;
                    ld_unit(r, gs + go, b1); ld_unit(r2, gs + go + gd, b2);
                }
                if (gd == HB) m = __ballot_sync(~0u, on && r.w >> 16 == 0xFE);
                if (on && r.w >> 16 == 255) sts32(sbase + SM_MISC + 4, 1);
                const uint32_t e[4] = {r.x, r.y, r.z, r.w}, v[4] = {r2.x, r2.y, r2.z, r2.w};
                uint32_t slot[4];
                #pragma unroll
                for (int k = 0; k < 4; k++) slot[k] = atoms_inc(sbase + SM_DEG + (on && e[k] >> 16 == (uint32_t)b ? (e[k] & 0x3FFF) : (NPB_MAX + lane) * 4));
                if (put) {
                    #pragma unroll
                    for (int k = 0; k < 4; k++) place(sbase, slot[k], v[k], s * ch);
                }
            }
            if (put == 0) {
                WS(4);
                asm volatile("bar.arrive 11, 512;" ::: "memory");
                if (w == 3) {
                    if (XAFT) x_ld(0, XSPL);
                    w_expect(su + SM_ABAR, 12288); w_expect(su + SM_ABAR + 8, 12288); w_expect(su + SM_ABAR + 16, nb * (CE * 4) - 24576);
                    w_hint(gbar + 64, all);
                    if (D2) delay(D2);
                    asm volatile("cp.async.bulk.wait_group.read 0;" ::: "memory");
                    WS(3);
                    const char* g2 = gs + b * (P1B + P2B) + P1B;
                    w_ld(su + SM_P2, g2, 12288, su + SM_ABAR);
                    w_ld(su + SM_P2 + 12288, g2 + 12288, 12288, su + SM_ABAR + 8);
                    w_ld(su + SM_P2 + 24576, g2 + 24576, nb * (CE * 4) - 24576, su + SM_ABAR + 16);
                    w_ld(su + SM_H2, gs + G_H2, nb * 64, su + SM_ABAR + 40);
                    x_ld(XSPL, 6);
                }
                asm volatile("bar.sync 4, 512;" ::: "memory");
                mbar_wait(ab + 40, 0);
            }
        }
        __syncwarp();
        WS(10);
        WGD();
        const uint32_t scr = sbase + SM_PAIR + (tid & 127) * 8;
        const int r4 = lane >> 3, c8 = lane & 7;
        const uint32_t sb = su;
        if (w < 3) {
            const char* gx = as_pair((const char*)x + c8 * 16, scr);
            const char* ge = as_pair((const char*)ea + (lane & 1) * 16, scr);
            const uint32_t gx0 = (uint32_t)(uint64_t)gx, ge0 = (uint32_t)(uint64_t)ge, hi = (uint64_t)gx >> 32, he = (uint64_t)ge >> 32;
            const int s = (lane >> 1) & 3;
            const uint32_t xs0 = sb + SM_XS + w * NSTAGE * XS_BYTES;
            const uint32_t es0 = sb + SM_ES + w * NSTAGE * ES_BYTES + r4 * 64 + (((lane ^ (r4 >> 1)) & 1) << 4) + (s >> 1) * 256 + (s & 1) * 32;
            const uint32_t bars = sb + SM_BARS + w * 96;
            const uint32_t xoffA = (2 * r4) * 128 + ((c8 ^ (2 * r4)) << 4), xoffB = (2 * r4 + 1) * 128 + ((c8 ^ (2 * r4 + 1)) << 4);
            uint64_t pol;
            asm volatile("createpolicy.fractional.L2::evict_first.b64 %0, 1.0;" : "=l"(pol));
            if (TLBW) {
                const uint32_t k = w * 32 + lane;
                asm volatile("prefetch.global.L2 [%0];" :: "l"(k < 64 ? (const char*)ea + (size_t)(E >> 6) * k * 32 : (const char*)x + (size_t)(N >> 5) * (k - 64) * 128));
            }
            asm volatile("bar.sync 6, 128;" ::: "memory");
            bool first = true; int tcount = 0;
            WS(15);
            uint32_t ph = 1, cur = w;
            uint32_t hist = 96 * 0x010101u;
            auto done3 = [&]() { mbar_arrive(sb + SM_GBAR + ((hist >> 16) & 0xFF) * 8); };
            const bool go = misc[1] == 0 && nn > 0;
            const uint32_t ca = sb + SM_CLAIM + lane * 4, pa = sb + SM_TINFO + r4 * 8;
            uint32_t pw = lds32(pa + w * 32), brk = (lds32(pa + w * 32 + 4) >> 16) & C_BRK;
            const uint32_t se0 = sb + SM_EID + s * 4, xab = xoffB - xoffA, das = 2 * (xs0 + xoffA) + XS_BYTES, des = 2 * es0 + ES_BYTES, brs = 2 * bars + 48;
            uint32_t da = xs0 + xoffA, de = es0, br = bars;
            #pragma unroll 1
            while (go) {
                const uint32_t pt = __reduce_or_sync(~0u, pw);
                uint32_t se, sx;
                asm("dp2a.lo.u32.u32 %0, %1, 4, %2;" : "=r"(se) : "r"(pw), "r"(se0));
                asm("dp2a.lo.u32.u32 %0, %1, 2, %2;" : "=r"(sx) : "r"(pw), "r"(sb + SM_SRC));
                const int dv = pw >> 27;
                const uint32_t db = da + xab;
                const uint32_t sel = (pt >> 16) & 15, nx = (pt >> 20) & 127;
                uint32_t g;
                auto claim = [&]() { asm volatile("atom.shared.add.u32 %0, [%1], %2;" : "=r"(g) : "r"(ca), "r"(nx == 0 ? 1u : 0u) : "memory"); };
                if (sel == 0) break;
                if (first) { asm volatile("bar.sync 3, 480;" ::: "memory"); first = false;
                }
                switch (sel) {
#define CASE(L, P, GEN) case L: { \
                        uint32_t oe[(P + 1) / 2], o[P]; \
                        _Pragma("unroll") for (int j = 0; j < (P + 1) / 2; j++) oe[j] = lds32(se + j * 16); \
                        _Pragma("unroll") for (int j = 0; j < P; j++) o[j] = lds32(sx + j * 4); \
                        mbar_wait_h(br + 8, ph); \
                        _Pragma("unroll") for (int j = 0; j < (P + 1) / 2; j++) \
                            if (LO32) { if (!GEN && 2 * j + 2 < P) cpe<false>(he, de + j * 512, oe[j], ge0, 0, 0, pol); \
                                else if (2 * j + 1 < NPMAX || s < 2) cpe<true>(he, de + j * 512, oe[j], ge0, 4 * j + s, dv, pol); } \
                            else if (!GEN && 2 * j + 2 < P) cp16e(de + j * 512, ge, oe[j], pol); else if (2 * j + 1 < NPMAX || s < 2) cp16z<32>(de + j * 512, ge, oe[j], 4 * j + s, dv, pol); \
                        _Pragma("unroll") for (int j = 0; j < P - 1; j++) { \
                            if (LO32) { cpx<0, GEN>(hi, da + j * 1024, o[j], gx0, 2 * j, dv); cpx<1, GEN>(hi, db + j * 1024, o[j], gx0, 2 * j + 1, dv); } \
                            else if (GEN) { cp16z<128>(da + j * 1024, gx, o[j] & 0xFFFFu, 2 * j, dv, 0); cp16z<128>(db + j * 1024, gx, o[j] >> 16, 2 * j + 1, dv, 0); } \
                            else { cp16i<128>(da + j * 1024, gx, o[j] & 0xFFFFu); cp16i<128>(db + j * 1024, gx, o[j] >> 16); } } \
                        if (LO32) { cpx<0, true>(hi, da + (P - 1) * 1024, o[P - 1], gx0, 2 * P - 2, dv); cpx<1, true>(hi, db + (P - 1) * 1024, o[P - 1], gx0, 2 * P - 1, dv); } \
                        else { cp16z<128>(da + (P - 1) * 1024, gx, o[P - 1] & 0xFFFFu, 2 * P - 2, dv, 0); cp16z<128>(db + (P - 1) * 1024, gx, o[P - 1] >> 16, 2 * P - 1, dv, 0); } \
                    } break;
                    CASE(4, 4, false) CASE(5, 5, false) CASE(6, 6, false) CASE(7, 7, false) CASE(8, 8, false) CASE(9, 9, false) CASE(10, 10, false) CASE(11, 11, false)
                    CASE(15, NPMAX, true) CASE(14, 8, true) default: CASE(13, 5, true)
#undef CASE
                }
                claim();
                mbar_cp_arrive(br);
                done3();
                g = __reduce_min_sync(~0u, g);
                {
                    const uint2 e = lds64(pa + (nx == 0 ? g : nx) * 32);
                    const uint2 v = tile_info(e.y);
                    pw = e.x;
                    asm volatile("st.shared.v2.u32 [%0], {%1, %2};" :: "r"(br + 16 + r4 * 8), "r"(v.x), "r"((v.y & ~C_BRK) | brk) : "memory");
                    brk = v.y & C_BRK;
                }
                mbar_arrive(br);
                hist = (hist << 8) | (nx == 0 ? cur : 96u);
                cur = nx == 0 ? g : cur;
                ph ^= br != bars; br = brs - br; da = das - da; de = des - de;
            }
            if (first) asm volatile("bar.sync 3, 480;" ::: "memory");
            if (go) {
                mbar_wait(sb + SM_ABAR + 72, 0);
                const int g0 = 3 * max((ngroups + 2) / 3 - TR, 0) + w;
                uint32_t nd[TR]; uint4 xv[TR];
                #pragma unroll
                for (int k = 0; k < TR; k++) {
                    asm volatile("ld.shared.u16 %0, [%1];" : "=r"(nd[k]) : "r"(sb + SM_WL + (g0 + 3 * k) * 8 + r4 * 2) : "memory");
                    xv[k] = __ldg((const uint4*)(gx + (size_t)(node0 + (nd[k] == NONE ? 0u : nd[k])) * 128));
                }
                #pragma unroll 1
                for (int k = 0; k < 3; k++) {
                    mbar_wait(k < 2 ? br + 8 : sb + SM_ABAR + 48 + w * 8, k < 2 ? ph : 0);
                    done3(); hist <<= 8;
                    ph ^= br != bars; br = brs - br;
                }
                #pragma unroll
                for (int k = 0; k < TR; k++) {
                    const uint32_t ro = sb + nd[k] * 128 + ((c8 ^ (nd[k] & 7)) << 4);
                    const uint4 xu = lds128(ro + SM_XU);
                    uint4 a = make_uint4(0, 0, 0, 0);
                    if (g0 + 3 * k < misc[4]) { mbar_wait(sb + SM_GBAR + (g0 + 3 * k) * 8, 0); a = lds128(ro + SM_TAB); }
                    finish(a, xu, xv[k]);
                    if (nd[k] != NONE) *(uint4*)((char*)out + (size_t)(node0 + nd[k]) * 128 + c8 * 16) = a;
                }
            }
            cp_wait<0>();
        } else {
            const char* gx = as_pair((const char*)x + (size_t)node0 * 128 + c8 * 16, scr);
            const char* ob = as_pair((const char*)out + (size_t)node0 * 128 + c8 * 16, scr);
            asm volatile("bar.arrive 6, 128;" ::: "memory");
            WS(15);
            if (OWNE) w_inc(gbar + 96 + 32 * b);
            else if (b == 0 && lane == 0) asm volatile("red.relaxed.gpu.global.add.u32 [%0], 1;" :: "l"(gbar) : "memory");
            if (misc[1] == 0) mbar_wait(sb + SM_ABAR + 72, 0);
            const int rounds = misc[1] ? 0 : max((ngroups + 2) / 3 - TR, 0);
            const int gz = misc[4], fast = __reduce_min_sync(~0u, min(rounds, gz / 3));
            uint32_t wl = sb + SM_WL + r4 * 2, gbar = sb + SM_GBAR;
            auto row_at = [&](uint32_t a) { uint32_t n; asm volatile("ld.shared.u16 %0, [%1];" : "=r"(n) : "r"(a) : "memory"); return n; };
            auto fetch = [&](uint32_t n, uint4& v) {
                asm volatile("{\n.reg .b64 p;\nmad.wide.u32 p, %5, 128, %4;\nld.global.nc.L1::no_allocate.v4.u32 {%0,%1,%2,%3}, [p];\n}"
                             : "=r"(v.x), "=r"(v.y), "=r"(v.z), "=r"(v.w) : "l"(gx), "r"(n));
            };
            auto store = [&](uint32_t n, const uint4& a) {
                asm volatile("{\n.reg .b64 p;\nmad.wide.u32 p, %1, 128, %0;\nst.global.v4.u32 [p], {%2,%3,%4,%5};\n}" :: "l"(ob), "r"(n), "r"(a.x), "r"(a.y), "r"(a.z), "r"(a.w) : "memory");
            };
            uint32_t n0[3]; uint4 x0[3];
            if (fast) {
                #pragma unroll
                for (int r = 0; r < 3; r++) { n0[r] = row_at(wl + r * 8); fetch(n0[r], x0[r]); }
            }
            #pragma unroll 1
            for (int k = 0; k < fast; k++) {
                wl += 24;
                #pragma unroll
                for (int r = 0; r < 3; r++) {
                    const uint32_t nd = n0[r], ro = sb + nd * 128 + ((c8 ^ (nd & 7)) << 4);
                    const uint4 xu = lds128(ro + SM_XU);
                    n0[r] = row_at(wl + r * 8);
                    mbar_wait(gbar + r * 8, 0);
                    uint4 a = lds128(ro + SM_TAB);
                    finish(a, xu, x0[r]);
                    fetch(n0[r], x0[r]);
                    store(nd, a);
                }
                gbar += 24;
            }
            #pragma unroll 1
            for (int g = 3 * fast; g < 3 * rounds; g++) {
                const uint32_t nd = row_at(sb + SM_WL + r4 * 2 + g * 8), ro = sb + nd * 128 + ((c8 ^ (nd & 7)) << 4);
                uint4 xv, a = make_uint4(0, 0, 0, 0);
                fetch(nd, xv);
                if (g < gz) { mbar_wait(sb + SM_GBAR + g * 8, 0); a = lds128(ro + SM_TAB); }
                finish(a, lds128(ro + SM_XU), xv);
                store(nd, a);
            }
        }
    }
    WS(17); WG1(); CG(2);
}

}

extern "C" void kernel_launch(void* const* d_in, const int* in_sizes, int n_in, void* d_out, int out_size) {
    const __nv_bfloat16* x = (const __nv_bfloat16*)d_in[0];
    const __nv_bfloat16* ea = (const __nv_bfloat16*)d_in[1];
    const int* src = (const int*)d_in[2];
    const int* dst = (const int*)d_in[3];
    const __nv_bfloat16* wa = (const __nv_bfloat16*)d_in[4];
    const __nv_bfloat16* wb = (const __nv_bfloat16*)d_in[5];
    const __nv_bfloat16* wc = (const __nv_bfloat16*)d_in[6];
    const __nv_bfloat16* wu = (const __nv_bfloat16*)d_in[7];
    const __nv_bfloat16* wv = (const __nv_bfloat16*)d_in[8];
    __nv_bfloat16* out = (__nv_bfloat16*)d_out;
    int N = in_sizes[0] / 64, E = in_sizes[2];
    static int sms = 0;
    static CUtensorMap tm1, tm2, tmw, tmx;
    static bool tm_ok = false;
    static void* gp = nullptr; static void* gb = nullptr;
    typedef CUresult (*EncFn)(CUtensorMap*, CUtensorMapDataType, cuuint32_t, void*, const cuuint64_t*, const cuuint64_t*, const cuuint32_t*,
                              const cuuint32_t*, CUtensorMapInterleave, CUtensorMapSwizzle, CUtensorMapL2promotion, CUtensorMapFloatOOBfill);
    static void* fn = nullptr;
    auto enc = [&](CUtensorMap* tm, const void* base, cuuint64_t cols, cuuint64_t rows, cuuint32_t bc, cuuint32_t br, CUtensorMapSwizzle sw) {
        cuuint64_t g2[2] = {cols, rows}, gs[1] = {cols * 4};
        cuuint32_t b2[2] = {bc, br}, es[2] = {1, 1};
        return ((EncFn)fn)(tm, CU_TENSOR_MAP_DATA_TYPE_UINT32, 2, (void*)base, g2, gs, b2, es, CU_TENSOR_MAP_INTERLEAVE_NONE, sw,
                           CU_TENSOR_MAP_L2_PROMOTION_NONE, CU_TENSOR_MAP_FLOAT_OOB_FILL_NONE) == CUDA_SUCCESS;
    };
    if (!sms) {
        cudaDeviceGetAttribute(&sms, cudaDevAttrMultiProcessorCount, 0);
        cudaDriverEntryPointQueryResult qr;
        cudaGetDriverEntryPoint("cuTensorMapEncodeTiled", &fn, cudaEnableDefault, &qr);
        cudaGetSymbolAddress(&gp, g_str); cudaGetSymbolAddress(&gb, g_bar);
        if (fn && gp && gb) {
            const cuuint32_t rows = sms < NB_MAX ? sms : NB_MAX;
            tm_ok = enc(&tm1, gp, (P1B + P2B) / 4, NB_MAX, CE / 2, rows, CU_TENSOR_MAP_SWIZZLE_NONE) && enc(&tm2, gp, (P1B + P2B) / 4, NB_MAX, CE, rows, CU_TENSOR_MAP_SWIZZLE_NONE);
        }
        cudaFuncSetAttribute(gcn_kernel<true>, cudaFuncAttributeMaxDynamicSharedMemorySize, SMEM_LAUNCH);
        cudaFuncSetAttribute(gcn_kernel<false>, cudaFuncAttributeMaxDynamicSharedMemorySize, SMEM_LAUNCH);
    }
    int nb = sms < NB_MAX ? sms : NB_MAX;
    int npb = (N + nb - 1) / nb;
    int ch = (((E + nb - 1) / nb) + 3) & ~3;
    const uintptr_t wp[4] = {(uintptr_t)wb, (uintptr_t)wv, (uintptr_t)wa, (uintptr_t)wu};
    uintptr_t wlo = wp[0], whi = wp[0], wal = 0;
    for (int i = 0; i < 4; i++) { wlo = wp[i] < wlo ? wp[i] : wlo; whi = wp[i] > whi ? wp[i] : whi; wal |= wp[i] - wp[0]; }
    bool ok = tm_ok && nb >= NB_MIN && npb <= NPB_MAX && ch <= CH_MAX && !(E & 3) && N <= 65535 && npb >= 2 && !(wal & 127) && (whi - wlo) >> 7 < (1u << 30) &&
              !(((uintptr_t)src | (uintptr_t)dst | (uintptr_t)x | (uintptr_t)wb | (uintptr_t)wc) & 15);
    ok = ok && enc(&tmw, (const void*)wlo, 32, ((whi - wlo) >> 7) + 64, 32, 64, CU_TENSOR_MAP_SWIZZLE_128B) && enc(&tmx, x, 32, N, 32, 64, CU_TENSOR_MAP_SWIZZLE_128B);
    if (!ok) {
        int g = 1024, p = (N + g - 1) / g;
        slow_kernel<<<g, 256>>>(x, ea, src, dst, wa, wb, wc, wu, wv, out, N, E, p < 1 ? 1 : p);
        return;
    }
    int4 wrow = make_int4((int)((wp[0] - wlo) >> 7), (int)((wp[1] - wlo) >> 7), (int)((wp[2] - wlo) >> 7), (int)((wp[3] - wlo) >> 7));
    uint32_t magic = (uint32_t)((1ull << 32) / (uint32_t)npb) + 1u;
    void* args[] = {&dst, &gb, &gp, &src, &E, &ch, &N, &npb, &magic, &x, &ea, &wa, &wb, &wc, &wu, &wv, &out, &wrow, &tm1, &tm2, &tmw, &tmx};
    const bool lo32 = ((uintptr_t)x >> 32) == (((uintptr_t)x + (size_t)N * 128 - 1) >> 32) && ((uintptr_t)ea >> 32) == (((uintptr_t)ea + (size_t)E * 32 - 1) >> 32);
    cudaLaunchCooperativeKernel(lo32 && !FORCE64 ? (const void*)gcn_kernel<true> : (const void*)gcn_kernel<false>, dim3(nb), dim3(THREADS), args, SMEM_LAUNCH, cudaStreamPerThread);
}
```

```cpp
#include <cuda_runtime.h>
#include <cuda.h>
#include <cuda_bf16.h>
#include <stdint.h>

namespace {

constexpr int N_MAX = 65536;
constexpr int NPMAX = 11;
constexpr int NPMIN = 4;
constexpr int THREADS = 512;
constexpr int EPT = 12;
constexpr int CH_MAX = THREADS * EPT;
constexpr int NB_MAX = 134, NB_MIN = 120;
constexpr int CE = 64;
constexpr int P1B = NB_MAX * CE * 2;
constexpr int P2B = NB_MAX * CE * 4;
constexpr int HB = NB_MAX * 64;
constexpr int G_H1 = NB_MAX * (P1B + P2B), G_H2 = G_H1 + HB, G_L = G_H2 + HB, G_END = G_L + NB_MAX * 512;
constexpr int NPB_MAX = 384;
constexpr int SLOT_CAP = 6784;
constexpr int TILE_CAP = 124;
constexpr int TILE_X = 8;
constexpr int NCLS = 64;
constexpr int NSTAGE = 2;
constexpr int TR = 2;
constexpr float LOG2E = 1.4426950408889634f;

__device__ __align__(256) uint4 g_str[G_END / 16];
__device__ __align__(128) unsigned g_bar[96];
__device__ float g_slow[N_MAX * 128];

#define WS(k)
#define WS1(k)
#define WSG(k)
#define WGD()
#define WG0()
#define WG1()
#define CG(k)
#define SMEM_LAUNCH SMEM_BYTES
#define EPOLL 0
#define WSPL 1
#define XT0 1000
#define XDT 800
#define D3 0
#define XMID 0
#define SRCE 0
#define XA 1
#define XC 0
#define XW 1
#define XE 0
#define XEW 1
#define XAFT 1
#define WDET 1
#define H1F 0
#define TSRC 1000
#define G3F 1
#define TLBW 0
#define OWNE 0
#define UFORM 0
#define XW2 1
#define FBLOG(P)
#define FBW 0
#define PD 300
#define SRCV 0
#define SD 0
#define WV 1
#define WLATE 2
#define WPF 0
#define HI1 1
#define HI2 4
#define HORD 0
#define T1 6000
#define NOH2 0
#define XPF 0
#define XLD 4
#define XSPL 1
#define P2W 1
#define H2M 0
#define D1 0
#define D2 0
#define FORCE64 0
#define EDHI ((16ull << 32) | (3ull << 62))
template<int NP> struct TileMMA;
template<> struct TileMMA<1> {
  static __device__ __forceinline__ void issue(float* g, float* h, const uint32_t* w, uint32_t dx, uint64_t de, uint64_t dh, uint64_t dc) {
    asm volatile(
      "{\n.reg .b64 dx0, dx1, dx2, dx3;\n.reg .b32 l1, l2, l3, hx;\nmov.b32 hx, 0x40000040;\n"
      "add.u32 l1, %48, 2;\nadd.u32 l2, %48, 4;\nadd.u32 l3, %48, 6;\n"
      "mov.b64 dx0, {%48, hx};\nmov.b64 dx1, {l1, hx};\nmov.b64 dx2, {l2, hx};\nmov.b64 dx3, {l3, hx};\n"
      "wgmma.fence.sync.aligned;\n"
      "wgmma.mma_async.sync.aligned.m64n8k16.f32.bf16.bf16 {%0, %1, %2, %3}, {%44, %45, %46, %47}, %50, 0, 1, 1, 0;\n"
      "wgmma.mma_async.sync.aligned.m64n8k16.f32.bf16.bf16 {%0, %1, %2, %3}, {%24, %25, %26, %27}, %49, 1, 1, 1, 0;\n"
      "wgmma.mma_async.sync.aligned.m64n8k16.f32.bf16.bf16 {%0, %1, %2, %3}, {%8, %9, %10, %11}, dx0, 1, 1, 1, 0;\n"
      "wgmma.mma_async.sync.aligned.m64n8k16.f32.bf16.bf16 {%0, %1, %2, %3}, {%12, %13, %14, %15}, dx1, 1, 1, 1, 0;\n"
      "wgmma.mma_async.sync.aligned.m64n8k16.f32.bf16.bf16 {%0, %1, %2, %3}, {%16, %17, %18, %19}, dx2, 1, 1, 1, 0;\n"
      "wgmma.mma_async.sync.aligned.m64n8k16.f32.bf16.bf16 {%0, %1, %2, %3}, {%20, %21, %22, %23}, dx3, 1, 1, 1, 0;\n"
      "wgmma.commit_group.sync.aligned;\n"
      "wgmma.mma_async.sync.aligned.m64n8k16.f32.bf16.bf16 {%4, %5, %6, %7}, {%28, %29, %30, %31}, dx0, 0, 1, 1, 0;\n"
      "wgmma.mma_async.sync.aligned.m64n8k16.f32.bf16.bf16 {%4, %5, %6, %7}, {%32, %33, %34, %35}, dx1, 1, 1, 1, 0;\n"
      "wgmma.mma_async.sync.aligned.m64n8k16.f32.bf16.bf16 {%4, %5, %6, %7}, {%36, %37, %38, %39}, dx2, 1, 1, 1, 0;\n"
      "wgmma.mma_async.sync.aligned.m64n8k16.f32.bf16.bf16 {%4, %5, %6, %7}, {%40, %41, %42, %43}, dx3, 1, 1, 1, 0;\n"
      "wgmma.commit_group.sync.aligned;\n}\n"
      : "=f"(g[0]), "=f"(g[1]), "=f"(g[2]), "=f"(g[3]),
        "=f"(h[0]), "=f"(h[1]), "=f"(h[2]), "=f"(h[3])
      : "r"(w[0]), "r"(w[1]), "r"(w[2]), "r"(w[3]), "r"(w[4]), "r"(w[5]), "r"(w[6]), "r"(w[7]), "r"(w[8]), "r"(w[9]), "r"(w[10]), "r"(w[11]), "r"(w[12]), "r"(w[13]), "r"(w[14]), "r"(w[15]), "r"(w[16]), "r"(w[17]), "r"(w[18]), "r"(w[19]), "r"(w[20]), "r"(w[21]), "r"(w[22]), "r"(w[23]), "r"(w[24]), "r"(w[25]), "r"(w[26]), "r"(w[27]), "r"(w[28]), "r"(w[29]), "r"(w[30]), "r"(w[31]), "r"(w[32]), "r"(w[33]), "r"(w[34]), "r"(w[35]), "r"(w[36]), "r"(w[37]), "r"(w[38]), "r"(w[39]), "r"(dx), "l"(de), "l"(dh)
      : "memory");
  }
  static __device__ __forceinline__ void wait_g(float* g) {
    asm volatile("wgmma.wait_group.sync.aligned 1;\n"
      : "+f"(g[0]), "+f"(g[1]), "+f"(g[2]), "+f"(g[3])
      :: "memory");
  }
  static __device__ __forceinline__ void wait_h(float* h) {
    asm volatile("wgmma.wait_group.sync.aligned 0;\n"
      : "+f"(h[0]), "+f"(h[1]), "+f"(h[2]), "+f"(h[3])
      :: "memory");
  }
};
template<> struct TileMMA<2> {
  static __device__ __forceinline__ void issue(float* g, float* h, const uint32_t* w, uint32_t dx, uint64_t de, uint64_t dh, uint64_t dc) {
    asm volatile(
      "{\n.reg .b64 dx0, dx1, dx2, dx3;\n.reg .b32 l1, l2, l3, hx;\nmov.b32 hx, 0x40000040;\n"
      "add.u32 l1, %56, 2;\nadd.u32 l2, %56, 4;\nadd.u32 l3, %56, 6;\n"
      "mov.b64 dx0, {%56, hx};\nmov.b64 dx1, {l1, hx};\nmov.b64 dx2, {l2, hx};\nmov.b64 dx3, {l3, hx};\n"
      "wgmma.fence.sync.aligned;\n"
      "wgmma.mma_async.sync.aligned.m64n16k16.f32.bf16.bf16 {%0, %1, %2, %3, %4, %5, %6, %7}, {%52, %53, %54, %55}, %58, 0, 1, 1, 0;\n"
      "wgmma.mma_async.sync.aligned.m64n16k16.f32.bf16.bf16 {%0, %1, %2, %3, %4, %5, %6, %7}, {%32, %33, %34, %35}, %57, 1, 1, 1, 0;\n"
      "wgmma.mma_async.sync.aligned.m64n16k16.f32.bf16.bf16 {%0, %1, %2, %3, %4, %5, %6, %7}, {%16, %17, %18, %19}, dx0, 1, 1, 1, 0;\n"
      "wgmma.mma_async.sync.aligned.m64n16k16.f32.bf16.bf16 {%0, %1, %2, %3, %4, %5, %6, %7}, {%20, %21, %22, %23}, dx1, 1, 1, 1, 0;\n"
      "wgmma.mma_async.sync.aligned.m64n16k16.f32.bf16.bf16 {%0, %1, %2, %3, %4, %5, %6, %7}, {%24, %25, %26, %27}, dx2, 1, 1, 1, 0;\n"
      "wgmma.mma_async.sync.aligned.m64n16k16.f32.bf16.bf16 {%0, %1, %2, %3, %4, %5, %6, %7}, {%28, %29, %30, %31}, dx3, 1, 1, 1, 0;\n"
      "wgmma.commit_group.sync.aligned;\n"
      "wgmma.mma_async.sync.aligned.m64n16k16.f32.bf16.bf16 {%8, %9, %10, %11, %12, %13, %14, %15}, {%36, %37, %38, %39}, dx0, 0, 1, 1, 0;\n"
      "wgmma.mma_async.sync.aligned.m64n16k16.f32.bf16.bf16 {%8, %9, %10, %11, %12, %13, %14, %15}, {%40, %41, %42, %43}, dx1, 1, 1, 1, 0;\n"
      "wgmma.mma_async.sync.aligned.m64n16k16.f32.bf16.bf16 {%8, %9, %10, %11, %12, %13, %14, %15}, {%44, %45, %46, %47}, dx2, 1, 1, 1, 0;\n"
      "wgmma.mma_async.sync.aligned.m64n16k16.f32.bf16.bf16 {%8, %9, %10, %11, %12, %13, %14, %15}, {%48, %49, %50, %51}, dx3, 1, 1, 1, 0;\n"
      "wgmma.commit_group.sync.aligned;\n}\n"
      : "=f"(g[0]), "=f"(g[1]), "=f"(g[2]), "=f"(g[3]), "=f"(g[4]), "=f"(g[5]), "=f"(g[6]), "=f"(g[7]),
        "=f"(h[0]), "=f"(h[1]), "=f"(h[2]), "=f"(h[3]), "=f"(h[4]), "=f"(h[5]), "=f"(h[6]), "=f"(h[7])
      : "r"(w[0]), "r"(w[1]), "r"(w[2]), "r"(w[3]), "r"(w[4]), "r"(w[5]), "r"(w[6]), "r"(w[7]), "r"(w[8]), "r"(w[9]), "r"(w[10]), "r"(w[11]), "r"(w[12]), "r"(w[13]), "r"(w[14]), "r"(w[15]), "r"(w[16]), "r"(w[17]), "r"(w[18]), "r"(w[19]), "r"(w[20]), "r"(w[21]), "r"(w[22]), "r"(w[23]), "r"(w[24]), "r"(w[25]), "r"(w[26]), "r"(w[27]), "r"(w[28]), "r"(w[29]), "r"(w[30]), "r"(w[31]), "r"(w[32]), "r"(w[33]), "r"(w[34]), "r"(w[35]), "r"(w[36]), "r"(w[37]), "r"(w[38]), "r"(w[39]), "r"(dx), "l"(de), "l"(dh)
      : "memory");
  }
  static __device__ __forceinline__ void wait_g(float* g) {
    asm volatile("wgmma.wait_group.sync.aligned 1;\n"
      : "+f"(g[0]), "+f"(g[1]), "+f"(g[2]), "+f"(g[3]), "+f"(g[4]), "+f"(g[5]), "+f"(g[6]), "+f"(g[7])
      :: "memory");
  }
  static __device__ __forceinline__ void wait_h(float* h) {
    asm volatile("wgmma.wait_group.sync.aligned 0;\n"
      : "+f"(h[0]), "+f"(h[1]), "+f"(h[2]), "+f"(h[3]), "+f"(h[4]), "+f"(h[5]), "+f"(h[6]), "+f"(h[7])
      :: "memory");
  }
};
template<> struct TileMMA<3> {
  static __device__ __forceinline__ void issue(float* g, float* h, const uint32_t* w, uint32_t dx, uint64_t de, uint64_t dh, uint64_t dc) {
    asm volatile(
      "{\n.reg .b64 dx0, dx1, dx2, dx3;\n.reg .b32 l1, l2, l3, hx;\nmov.b32 hx, 0x40000040;\n"
      "add.u32 l1, %64, 2;\nadd.u32 l2, %64, 4;\nadd.u32 l3, %64, 6;\n"
      "mov.b64 dx0, {%64, hx};\nmov.b64 dx1, {l1, hx};\nmov.b64 dx2, {l2, hx};\nmov.b64 dx3, {l3, hx};\n"
      "wgmma.fence.sync.aligned;\n"
      "wgmma.mma_async.sync.aligned.m64n24k16.f32.bf16.bf16 {%0, %1, %2, %3, %4, %5, %6, %7, %8, %9, %10, %11}, {%60, %61, %62, %63}, %66, 0, 1, 1, 0;\n"
      "wgmma.mma_async.sync.aligned.m64n24k16.f32.bf16.bf16 {%0, %1, %2, %3, %4, %5, %6, %7, %8, %9, %10, %11}, {%40, %41, %42, %43}, %65, 1, 1, 1, 0;\n"
      "wgmma.mma_async.sync.aligned.m64n24k16.f32.bf16.bf16 {%0, %1, %2, %3, %4, %5, %6, %7, %8, %9, %10, %11}, {%24, %25, %26, %27}, dx0, 1, 1, 1, 0;\n"
      "wgmma.mma_async.sync.aligned.m64n24k16.f32.bf16.bf16 {%0, %1, %2, %3, %4, %5, %6, %7, %8, %9, %10, %11}, {%28, %29, %30, %31}, dx1, 1, 1, 1, 0;\n"
      "wgmma.mma_async.sync.aligned.m64n24k16.f32.bf16.bf16 {%0, %1, %2, %3, %4, %5, %6, %7, %8, %9, %10, %11}, {%32, %33, %34, %35}, dx2, 1, 1, 1, 0;\n"
      "wgmma.mma_async.sync.aligned.m64n24k16.f32.bf16.bf16 {%0, %1, %2, %3, %4, %5, %6, %7, %8, %9, %10, %11}, {%36, %37, %38, %39}, dx3, 1, 1, 1, 0;\n"
      "wgmma.commit_group.sync.aligned;\n"
      "wgmma.mma_async.sync.aligned.m64n24k16.f32.bf16.bf16 {%12, %13, %14, %15, %16, %17, %18, %19, %20, %21, %22, %23}, {%44, %45, %46, %47}, dx0, 0, 1, 1, 0;\n"
      "wgmma.mma_async.sync.aligned.m64n24k16.f32.bf16.bf16 {%12, %13, %14, %15, %16, %17, %18, %19, %20, %21, %22, %23}, {%48, %49, %50, %51}, dx1, 1, 1, 1, 0;\n"
      "wgmma.mma_async.sync.aligned.m64n24k16.f32.bf16.bf16 {%12, %13, %14, %15, %16, %17, %18, %19, %20, %21, %22, %23}, {%52, %53, %54, %55}, dx2, 1, 1, 1, 0;\n"
      "wgmma.mma_async.sync.aligned.m64n24k16.f32.bf16.bf16 {%12, %13, %14, %15, %16, %17, %18, %19, %20, %21, %22, %23}, {%56, %57, %58, %59}, dx3, 1, 1, 1, 0;\n"
      "wgmma.commit_group.sync.aligned;\n}\n"
      : "=f"(g[0]), "=f"(g[1]), "=f"(g[2]), "=f"(g[3]), "=f"(g[4]), "=f"(g[5]), "=f"(g[6]), "=f"(g[7]), "=f"(g[8]), "=f"(g[9]), "=f"(g[10]), "=f"(g[11]),
        "=f"(h[0]), "=f"(h[1]), "=f"(h[2]), "=f"(h[3]), "=f"(h[4]), "=f"(h[5]), "=f"(h[6]), "=f"(h[7]), "=f"(h[8]), "=f"(h[9]), "=f"(h[10]), "=f"(h[11])
      : "r"(w[0]), "r"(w[1]), "r"(w[2]), "r"(w[3]), "r"(w[4]), "r"(w[5]), "r"(w[6]), "r"(w[7]), "r"(w[8]), "r"(w[9]), "r"(w[10]), "r"(w[11]), "r"(w[12]), "r"(w[13]), "r"(w[14]), "r"(w[15]), "r"(w[16]), "r"(w[17]), "r"(w[18]), "r"(w[19]), "r"(w[20]), "r"(w[21]), "r"(w[22]), "r"(w[23]), "r"(w[24]), "r"(w[25]), "r"(w[26]), "r"(w[27]), "r"(w[28]), "r"(w[29]), "r"(w[30]), "r"(w[31]), "r"(w[32]), "r"(w[33]), "r"(w[34]), "r"(w[35]), "r"(w[36]), "r"(w[37]), "r"(w[38]), "r"(w[39]), "r"(dx), "l"(de), "l"(dh)
      : "memory");
  }
  static __device__ __forceinline__ void wait_g(float* g) {
    asm volatile("wgmma.wait_group.sync.aligned 1;\n"
      : "+f"(g[0]), "+f"(g[1]), "+f"(g[2]), "+f"(g[3]), "+f"(g[4]), "+f"(g[5]), "+f"(g[6]), "+f"(g[7]), "+f"(g[8]), "+f"(g[9]), "+f"(g[10]), "+f"(g[11])
      :: "memory");
  }
  static __device__ __forceinline__ void wait_h(float* h) {
    asm volatile("wgmma.wait_group.sync.aligned 0;\n"
      : "+f"(h[0]), "+f"(h[1]), "+f"(h[2]), "+f"(h[3]), "+f"(h[4]), "+f"(h[5]), "+f"(h[6]), "+f"(h[7]), "+f"(h[8]), "+f"(h[9]), "+f"(h[10]), "+f"(h[11])
      :: "memory");
  }
};
template<> struct TileMMA<4> {
  static __device__ __forceinline__ void issue(float* g, float* h, const uint32_t* w, uint32_t dx, uint64_t de, uint64_t dh, uint64_t dc) {
    asm volatile(
      "{\n.reg .b64 dx0, dx1, dx2, dx3;\n.reg .b32 l1, l2, l3, hx;\nmov.b32 hx, 0x40000040;\n"
      "add.u32 l1, %72, 2;\nadd.u32 l2, %72, 4;\nadd.u32 l3, %72, 6;\n"
      "mov.b64 dx0, {%72, hx};\nmov.b64 dx1, {l1, hx};\nmov.b64 dx2, {l2, hx};\nmov.b64 dx3, {l3, hx};\n"
      "wgmma.fence.sync.aligned;\n"
      "wgmma.mma_async.sync.aligned.m64n32k16.f32.bf16.bf16 {%0, %1, %2, %3, %4, %5, %6, %7, %8, %9, %10, %11, %12, %13, %14, %15}, {%68, %69, %70, %71}, %74, 0, 1, 1, 0;\n"
      "wgmma.mma_async.sync.aligned.m64n32k16.f32.bf16.bf16 {%0, %1, %2, %3, %4, %5, %6, %7, %8, %9, %10, %11, %12, %13, %14, %15}, {%48, %49, %50, %51}, %73, 1, 1, 1, 0;\n"
      "wgmma.mma_async.sync.aligned.m64n32k16.f32.bf16.bf16 {%0, %1, %2, %3, %4, %5, %6, %7, %8, %9, %10, %11, %12, %13, %14, %15}, {%32, %33, %34, %35}, dx0, 1, 1, 1, 0;\n"
      "wgmma.mma_async.sync.aligned.m64n32k16.f32.bf16.bf16 {%0, %1, %2, %3, %4, %5, %6, %7, %8, %9, %10, %11, %12, %13, %14, %15}, {%36, %37, %38, %39}, dx1, 1, 1, 1, 0;\n"
      "wgmma.mma_async.sync.aligned.m64n32k16.f32.bf16.bf16 {%0, %1, %2, %3, %4, %5, %6, %7, %8, %9, %10, %11, %12, %13, %14, %15}, {%40, %41, %42, %43}, dx2, 1, 1, 1, 0;\n"
      "wgmma.mma_async.sync.aligned.m64n32k16.f32.bf16.bf16 {%0, %1, %2, %3, %4, %5, %6, %7, %8, %9, %10, %11, %12, %13, %14, %15}, {%44, %45, %46, %47}, dx3, 1, 1, 1, 0;\n"
      "wgmma.commit_group.sync.aligned;\n"
      "wgmma.mma_async.sync.aligned.m64n32k16.f32.bf16.bf16 {%16, %17, %18, %19, %20, %21, %22, %23, %24, %25, %26, %27, %28, %29, %30, %31}, {%52, %53, %54, %55}, dx0, 0, 1, 1, 0;\n"
      "wgmma.mma_async.sync.aligned.m64n32k16.f32.bf16.bf16 {%16, %17, %18, %19, %20, %21, %22, %23, %24, %25, %26, %27, %28, %29, %30, %31}, {%56, %57, %58, %59}, dx1, 1, 1, 1, 0;\n"
      "wgmma.mma_async.sync.aligned.m64n32k16.f32.bf16.bf16 {%16, %17, %18, %19, %20, %21, %22, %23, %24, %25, %26, %27, %28, %29, %30, %31}, {%60, %61, %62, %63}, dx2, 1, 1, 1, 0;\n"
      "wgmma.mma_async.sync.aligned.m64n32k16.f32.bf16.bf16 {%16, %17, %18, %19, %20, %21, %22, %23, %24, %25, %26, %27, %28, %29, %30, %31}, {%64, %65, %66, %67}, dx3, 1, 1, 1, 0;\n"
      "wgmma.commit_group.sync.aligned;\n}\n"
      : "=f"(g[0]), "=f"(g[1]), "=f"(g[2]), "=f"(g[3]), "=f"(g[4]), "=f"(g[5]), "=f"(g[6]), "=f"(g[7]), "=f"(g[8]), "=f"(g[9]), "=f"(g[10]), "=f"(g[11]), "=f"(g[12]), "=f"(g[13]), "=f"(g[14]), "=f"(g[15]),
        "=f"(h[0]), "=f"(h[1]), "=f"(h[2]), "=f"(h[3]), "=f"(h[4]), "=f"(h[5]), "=f"(h[6]), "=f"(h[7]), "=f"(h[8]), "=f"(h[9]), "=f"(h[10]), "=f"(h[11]), "=f"(h[12]), "=f"(h[13]), "=f"(h[14]), "=f"(h[15])
      : "r"(w[0]), "r"(w[1]), "r"(w[2]), "r"(w[3]), "r"(w[4]), "r"(w[5]), "r"(w[6]), "r"(w[7]), "r"(w[8]), "r"(w[9]), "r"(w[10]), "r"(w[11]), "r"(w[12]), "r"(w[13]), "r"(w[14]), "r"(w[15]), "r"(w[16]), "r"(w[17]), "r"(w[18]), "r"(w[19]), "r"(w[20]), "r"(w[21]), "r"(w[22]), "r"(w[23]), "r"(w[24]), "r"(w[25]), "r"(w[26]), "r"(w[27]), "r"(w[28]), "r"(w[29]), "r"(w[30]), "r"(w[31]), "r"(w[32]), "r"(w[33]), "r"(w[34]), "r"(w[35]), "r"(w[36]), "r"(w[37]), "r"(w[38]), "r"(w[39]), "r"(dx), "l"(de), "l"(dh)
      : "memory");
  }
  static __device__ __forceinline__ void wait_g(float* g) {
    asm volatile("wgmma.wait_group.sync.aligned 1;\n"
      : "+f"(g[0]), "+f"(g[1]), "+f"(g[2]), "+f"(g[3]), "+f"(g[4]), "+f"(g[5]), "+f"(g[6]), "+f"(g[7]), "+f"(g[8]), "+f"(g[9]), "+f"(g[10]), "+f"(g[11]), "+f"(g[12]), "+f"(g[13]), "+f"(g[14]), "+f"(g[15])
      :: "memory");
  }
  static __device__ __forceinline__ void wait_h(float* h) {
    asm volatile("wgmma.wait_group.sync.aligned 0;\n"
      : "+f"(h[0]), "+f"(h[1]), "+f"(h[2]), "+f"(h[3]), "+f"(h[4]), "+f"(h[5]), "+f"(h[6]), "+f"(h[7]), "+f"(h[8]), "+f"(h[9]), "+f"(h[10]), "+f"(h[11]), "+f"(h[12]), "+f"(h[13]), "+f"(h[14]), "+f"(h[15])
      :: "memory");
  }
};
template<> struct TileMMA<5> {
  static __device__ __forceinline__ void issue(float* g, float* h, const uint32_t* w, uint32_t dx, uint64_t de, uint64_t dh, uint64_t dc) {
    asm volatile(
      "{\n.reg .b64 dx0, dx1, dx2, dx3;\n.reg .b32 l1, l2, l3, hx;\nmov.b32 hx, 0x40000040;\n"
      "add.u32 l1, %80, 2;\nadd.u32 l2, %80, 4;\nadd.u32 l3, %80, 6;\n"
      "mov.b64 dx0, {%80, hx};\nmov.b64 dx1, {l1, hx};\nmov.b64 dx2, {l2, hx};\nmov.b64 dx3, {l3, hx};\n"
      "wgmma.fence.sync.aligned;\n"
      "wgmma.mma_async.sync.aligned.m64n40k16.f32.bf16.bf16 {%0, %1, %2, %3, %4, %5, %6, %7, %8, %9, %10, %11, %12, %13, %14, %15, %16, %17, %18, %19}, {%76, %77, %78, %79}, %82, 0, 1, 1, 0;\n"
      "wgmma.mma_async.sync.aligned.m64n40k16.f32.bf16.bf16 {%0, %1, %2, %3, %4, %5, %6, %7, %8, %9, %10, %11, %12, %13, %14, %15, %16, %17, %18, %19}, {%56, %57, %58, %59}, %81, 1, 1, 1, 0;\n"
      "wgmma.mma_async.sync.aligned.m64n40k16.f32.bf16.bf16 {%0, %1, %2, %3, %4, %5, %6, %7, %8, %9, %10, %11, %12, %13, %14, %15, %16, %17, %18, %19}, {%40, %41, %42, %43}, dx0, 1, 1, 1, 0;\n"
      "wgmma.mma_async.sync.aligned.m64n40k16.f32.bf16.bf16 {%0, %1, %2, %3, %4, %5, %6, %7, %8, %9, %10, %11, %12, %13, %14, %15, %16, %17, %18, %19}, {%44, %45, %46, %47}, dx1, 1, 1, 1, 0;\n"
      "wgmma.mma_async.sync.aligned.m64n40k16.f32.bf16.bf16 {%0, %1, %2, %3, %4, %5, %6, %7, %8, %9, %10, %11, %12, %13, %14, %15, %16, %17, %18, %19}, {%48, %49, %50, %51}, dx2, 1, 1, 1, 0;\n"
      "wgmma.mma_async.sync.aligned.m64n40k16.f32.bf16.bf16 {%0, %1, %2, %3, %4, %5, %6, %7, %8, %9, %10, %11, %12, %13, %14, %15, %16, %17, %18, %19}, {%52, %53, %54, %55}, dx3, 1, 1, 1, 0;\n"
      "wgmma.commit_group.sync.aligned;\n"
      "wgmma.mma_async.sync.aligned.m64n40k16.f32.bf16.bf16 {%20, %21, %22, %23, %24, %25, %26, %27, %28, %29, %30, %31, %32, %33, %34, %35, %36, %37, %38, %39}, {%60, %61, %62, %63}, dx0, 0, 1, 1, 0;\n"
      "wgmma.mma_async.sync.aligned.m64n40k16.f32.bf16.bf16 {%20, %21, %22, %23, %24, %25, %26, %27, %28, %29, %30, %31, %32, %33, %34, %35, %36, %37, %38, %39}, {%64, %65, %66, %67}, dx1, 1, 1, 1, 0;\n"
      "wgmma.mma_async.sync.aligned.m64n40k16.f32.bf16.bf16 {%20, %21, %22, %23, %24, %25, %26, %27, %28, %29, %30, %31, %32, %33, %34, %35, %36, %37, %38, %39}, {%68, %69, %70, %71}, dx2, 1, 1, 1, 0;\n"
      "wgmma.mma_async.sync.aligned.m64n40k16.f32.bf16.bf16 {%20, %21, %22, %23, %24, %25, %26, %27, %28, %29, %30, %31, %32, %33, %34, %35, %36, %37, %38, %39}, {%72, %73, %74, %75}, dx3, 1, 1, 1, 0;\n"
      "wgmma.commit_group.sync.aligned;\n}\n"
      : "=f"(g[0]), "=f"(g[1]), "=f"(g[2]), "=f"(g[3]), "=f"(g[4]), "=f"(g[5]), "=f"(g[6]), "=f"(g[7]), "=f"(g[8]), "=f"(g[9]), "=f"(g[10]), "=f"(g[11]), "=f"(g[12]), "=f"(g[13]), "=f"(g[14]), "=f"(g[15]), "=f"(g[16]), "=f"(g[17]), "=f"(g[18]), "=f"(g[19]),
        "=f"(h[0]), "=f"(h[1]), "=f"(h[2]), "=f"(h[3]), "=f"(h[4]), "=f"(h[5]), "=f"(h[6]), "=f"(h[7]), "=f"(h[8]), "=f"(h[9]), "=f"(h[10]), "=f"(h[11]), "=f"(h[12]), "=f"(h[13]), "=f"(h[14]), "=f"(h[15]), "=f"(h[16]), "=f"(h[17]), "=f"(h[18]), "=f"(h[19])
      : "r"(w[0]), "r"(w[1]), "r"(w[2]), "r"(w[3]), "r"(w[4]), "r"(w[5]), "r"(w[6]), "r"(w[7]), "r"(w[8]), "r"(w[9]), "r"(w[10]), "r"(w[11]), "r"(w[12]), "r"(w[13]), "r"(w[14]), "r"(w[15]), "r"(w[16]), "r"(w[17]), "r"(w[18]), "r"(w[19]), "r"(w[20]), "r"(w[21]), "r"(w[22]), "r"(w[23]), "r"(w[24]), "r"(w[25]), "r"(w[26]), "r"(w[27]), "r"(w[28]), "r"(w[29]), "r"(w[30]), "r"(w[31]), "r"(w[32]), "r"(w[33]), "r"(w[34]), "r"(w[35]), "r"(w[36]), "r"(w[37]), "r"(w[38]), "r"(w[39]), "r"(dx), "l"(de), "l"(dh)
      : "memory");
  }
  static __device__ __forceinline__ void wait_g(float* g) {
    asm volatile("wgmma.wait_group.sync.aligned 1;\n"
      : "+f"(g[0]), "+f"(g[1]), "+f"(g[2]), "+f"(g[3]), "+f"(g[4]), "+f"(g[5]), "+f"(g[6]), "+f"(g[7]), "+f"(g[8]), "+f"(g[9]), "+f"(g[10]), "+f"(g[11]), "+f"(g[12]), "+f"(g[13]), "+f"(g[14]), "+f"(g[15]), "+f"(g[16]), "+f"(g[17]), "+f"(g[18]), "+f"(g[19])
      :: "memory");
  }
  static __device__ __forceinline__ void wait_h(float* h) {
    asm volatile("wgmma.wait_group.sync.aligned 0;\n"
      : "+f"(h[0]), "+f"(h[1]), "+f"(h[2]), "+f"(h[3]), "+f"(h[4]), "+f"(h[5]), "+f"(h[6]), "+f"(h[7]), "+f"(h[8]), "+f"(h[9]), "+f"(h[10]), "+f"(h[11]), "+f"(h[12]), "+f"(h[13]), "+f"(h[14]), "+f"(h[15]), "+f"(h[16]), "+f"(h[17]), "+f"(h[18]), "+f"(h[19])
      :: "memory");
  }
};
template<> struct TileMMA<6> {
  static __device__ __forceinline__ void issue(float* g, float* h, const uint32_t* w, uint32_t dx, uint64_t de, uint64_t dh, uint64_t dc) {
    asm volatile(
      "{\n.reg .b64 dx0, dx1, dx2, dx3;\n.reg .b32 l1, l2, l3, hx;\nmov.b32 hx, 0x40000040;\n"
      "add.u32 l1, %88, 2;\nadd.u32 l2, %88, 4;\nadd.u32 l3, %88, 6;\n"
      "mov.b64 dx0, {%88, hx};\nmov.b64 dx1, {l1, hx};\nmov.b64 dx2, {l2, hx};\nmov.b64 dx3, {l3, hx};\n"
      "wgmma.fence.sync.aligned;\n"
      "wgmma.mma_async.sync.aligned.m64n48k16.f32.bf16.bf16 {%0, %1, %2, %3, %4, %5, %6, %7, %8, %9, %10, %11, %12, %13, %14, %15, %16, %17, %18, %19, %20, %21, %22, %23}, {%84, %85, %86, %87}, %90, 0, 1, 1, 0;\n"
      "wgmma.mma_async.sync.aligned.m64n48k16.f32.bf16.bf16 {%0, %1, %2, %3, %4, %5, %6, %7, %8, %9, %10, %11, %12, %13, %14, %15, %16, %17, %18, %19, %20, %21, %22, %23}, {%64, %65, %66, %67}, %89, 1, 1, 1, 0;\n"
      "wgmma.mma_async.sync.aligned.m64n48k16.f32.bf16.bf16 {%0, %1, %2, %3, %4, %5, %6, %7, %8, %9, %10, %11, %12, %13, %14, %15, %16, %17, %18, %19, %20, %21, %22, %23}, {%48, %49, %50, %51}, dx0, 1, 1, 1, 0;\n"
      "wgmma.mma_async.sync.aligned.m64n48k16.f32.bf16.bf16 {%0, %1, %2, %3, %4, %5, %6, %7, %8, %9, %10, %11, %12, %13, %14, %15, %16, %17, %18, %19, %20, %21, %22, %23}, {%52, %53, %54, %55}, dx1, 1, 1, 1, 0;\n"
      "wgmma.mma_async.sync.aligned.m64n48k16.f32.bf16.bf16 {%0, %1, %2, %3, %4, %5, %6, %7, %8, %9, %10, %11, %12, %13, %14, %15, %16, %17, %18, %19, %20, %21, %22, %23}, {%56, %57, %58, %59}, dx2, 1, 1, 1, 0;\n"
      "wgmma.mma_async.sync.aligned.m64n48k16.f32.bf16.bf16 {%0, %1, %2, %3, %4, %5, %6, %7, %8, %9, %10, %11, %12, %13, %14, %15, %16, %17, %18, %19, %20, %21, %22, %23}, {%60, %61, %62, %63}, dx3, 1, 1, 1, 0;\n"
      "wgmma.commit_group.sync.aligned;\n"
      "wgmma.mma_async.sync.aligned.m64n48k16.f32.bf16.bf16 {%24, %25, %26, %27, %28, %29, %30, %31, %32, %33, %34, %35, %36, %37, %38, %39, %40, %41, %42, %43, %44, %45, %46, %47}, {%68, %69, %70, %71}, dx0, 0, 1, 1, 0;\n"
      "wgmma.mma_async.sync.aligned.m64n48k16.f32.bf16.bf16 {%24, %25, %26, %27, %28, %29, %30, %31, %32, %33, %34, %35, %36, %37, %38, %39, %40, %41, %42, %43, %44, %45, %46, %47}, {%72, %73, %74, %75}, dx1, 1, 1, 1, 0;\n"
      "wgmma.mma_async.sync.aligned.m64n48k16.f32.bf16.bf16 {%24, %25, %26, %27, %28, %29, %30, %31, %32, %33, %34, %35, %36, %37, %38, %39, %40, %41, %42, %43, %44, %45, %46, %47}, {%76, %77, %78, %79}, dx2, 1, 1, 1, 0;\n"
      "wgmma.mma_async.sync.aligned.m64n48k16.f32.bf16.bf16 {%24, %25, %26, %27, %28, %29, %30, %31, %32, %33, %34, %35, %36, %37, %38, %39, %40, %41, %42, %43, %44, %45, %46, %47}, {%80, %81, %82, %83}, dx3, 1, 1, 1, 0;\n"
      "wgmma.commit_group.sync.aligned;\n}\n"
      : "=f"(g[0]), "=f"(g[1]), "=f"(g[2]), "=f"(g[3]), "=f"(g[4]), "=f"(g[5]), "=f"(g[6]), "=f"(g[7]), "=f"(g[8]), "=f"(g[9]), "=f"(g[10]), "=f"(g[11]), "=f"(g[12]), "=f"(g[13]), "=f"(g[14]), "=f"(g[15]), "=f"(g[16]), "=f"(g[17]), "=f"(g[18]), "=f"(g[19]), "=f"(g[20]), "=f"(g[21]), "=f"(g[22]), "=f"(g[23]),
        "=f"(h[0]), "=f"(h[1]), "=f"(h[2]), "=f"(h[3]), "=f"(h[4]), "=f"(h[5]), "=f"(h[6]), "=f"(h[7]), "=f"(h[8]), "=f"(h[9]), "=f"(h[10]), "=f"(h[11]), "=f"(h[12]), "=f"(h[13]), "=f"(h[14]), "=f"(h[15]), "=f"(h[16]), "=f"(h[17]), "=f"(h[18]), "=f"(h[19]), "=f"(h[20]), "=f"(h[21]), "=f"(h[22]), "=f"(h[23])
      : "r"(w[0]), "r"(w[1]), "r"(w[2]), "r"(w[3]), "r"(w[4]), "r"(w[5]), "r"(w[6]), "r"(w[7]), "r"(w[8]), "r"(w[9]), "r"(w[10]), "r"(w[11]), "r"(w[12]), "r"(w[13]), "r"(w[14]), "r"(w[15]), "r"(w[16]), "r"(w[17]), "r"(w[18]), "r"(w[19]), "r"(w[20]), "r"(w[21]), "r"(w[22]), "r"(w[23]), "r"(w[24]), "r"(w[25]), "r"(w[26]), "r"(w[27]), "r"(w[28]), "r"(w[29]), "r"(w[30]), "r"(w[31]), "r"(w[32]), "r"(w[33]), "r"(w[34]), "r"(w[35]), "r"(w[36]), "r"(w[37]), "r"(w[38]), "r"(w[39]), "r"(dx), "l"(de), "l"(dh)
      : "memory");
  }
  static __device__ __forceinline__ void wait_g(float* g) {
    asm volatile("wgmma.wait_group.sync.aligned 1;\n"
      : "+f"(g[0]), "+f"(g[1]), "+f"(g[2]), "+f"(g[3]), "+f"(g[4]), "+f"(g[5]), "+f"(g[6]), "+f"(g[7]), "+f"(g[8]), "+f"(g[9]), "+f"(g[10]), "+f"(g[11]), "+f"(g[12]), "+f"(g[13]), "+f"(g[14]), "+f"(g[15]), "+f"(g[16]), "+f"(g[17]), "+f"(g[18]), "+f"(g[19]), "+f"(g[20]), "+f"(g[21]), "+f"(g[22]), "+f"(g[23])
      :: "memory");
  }
  static __device__ __forceinline__ void wait_h(float* h) {
    asm volatile("wgmma.wait_group.sync.aligned 0;\n"
      : "+f"(h[0]), "+f"(h[1]), "+f"(h[2]), "+f"(h[3]), "+f"(h[4]), "+f"(h[5]), "+f"(h[6]), "+f"(h[7]), "+f"(h[8]), "+f"(h[9]), "+f"(h[10]), "+f"(h[11]), "+f"(h[12]), "+f"(h[13]), "+f"(h[14]), "+f"(h[15]), "+f"(h[16]), "+f"(h[17]), "+f"(h[18]), "+f"(h[19]), "+f"(h[20]), "+f"(h[21]), "+f"(h[22]), "+f"(h[23])
      :: "memory");
  }
};
template<> struct TileMMA<7> {
  static __device__ __forceinline__ void issue(float* g, float* h, const uint32_t* w, uint32_t dx, uint64_t de, uint64_t dh, uint64_t dc) {
    asm volatile(
      "{\n.reg .b64 dx0, dx1, dx2, dx3;\n.reg .b32 l1, l2, l3, hx;\nmov.b32 hx, 0x40000040;\n"
      "add.u32 l1, %96, 2;\nadd.u32 l2, %96, 4;\nadd.u32 l3, %96, 6;\n"
      "mov.b64 dx0, {%96, hx};\nmov.b64 dx1, {l1, hx};\nmov.b64 dx2, {l2, hx};\nmov.b64 dx3, {l3, hx};\n"
      "wgmma.fence.sync.aligned;\n"
      "wgmma.mma_async.sync.aligned.m64n56k16.f32.bf16.bf16 {%0, %1, %2, %3, %4, %5, %6, %7, %8, %9, %10, %11, %12, %13, %14, %15, %16, %17, %18, %19, %20, %21, %22, %23, %24, %25, %26, %27}, {%92, %93, %94, %95}, %98, 0, 1, 1, 0;\n"
      "wgmma.mma_async.sync.aligned.m64n56k16.f32.bf16.bf16 {%0, %1, %2, %3, %4, %5, %6, %7, %8, %9, %10, %11, %12, %13, %14, %15, %16, %17, %18, %19, %20, %21, %22, %23, %24, %25, %26, %27}, {%72, %73, %74, %75}, %97, 1, 1, 1, 0;\n"
      "wgmma.mma_async.sync.aligned.m64n56k16.f32.bf16.bf16 {%0, %1, %2, %3, %4, %5, %6, %7, %8, %9, %10, %11, %12, %13, %14, %15, %16, %17, %18, %19, %20, %21, %22, %23, %24, %25, %26, %27}, {%56, %57, %58, %59}, dx0, 1, 1, 1, 0;\n"
      "wgmma.mma_async.sync.aligned.m64n56k16.f32.bf16.bf16 {%0, %1, %2, %3, %4, %5, %6, %7, %8, %9, %10, %11, %12, %13, %14, %15, %16, %17, %18, %19, %20, %21, %22, %23, %24, %25, %26, %27}, {%60, %61, %62, %63}, dx1, 1, 1, 1, 0;\n"
      "wgmma.mma_async.sync.aligned.m64n56k16.f32.bf16.bf16 {%0, %1, %2, %3, %4, %5, %6, %7, %8, %9, %10, %11, %12, %13, %14, %15, %16, %17, %18, %19, %20, %21, %22, %23, %24, %25, %26, %27}, {%64, %65, %66, %67}, dx2, 1, 1, 1, 0;\n"
      "wgmma.mma_async.sync.aligned.m64n56k16.f32.bf16.bf16 {%0, %1, %2, %3, %4, %5, %6, %7, %8, %9, %10, %11, %12, %13, %14, %15, %16, %17, %18, %19, %20, %21, %22, %23, %24, %25, %26, %27}, {%68, %69, %70, %71}, dx3, 1, 1, 1, 0;\n"
      "wgmma.commit_group.sync.aligned;\n"
      "wgmma.mma_async.sync.aligned.m64n56k16.f32.bf16.bf16 {%28, %29, %30, %31, %32, %33, %34, %35, %36, %37, %38, %39, %40, %41, %42, %43, %44, %45, %46, %47, %48, %49, %50, %51, %52, %53, %54, %55}, {%76, %77, %78, %79}, dx0, 0, 1, 1, 0;\n"
      "wgmma.mma_async.sync.aligned.m64n56k16.f32.bf16.bf16 {%28, %29, %30, %31, %32, %33, %34, %35, %36, %37, %38, %39, %40, %41, %42, %43, %44, %45, %46, %47, %48, %49, %50, %51, %52, %53, %54, %55}, {%80, %81, %82, %83}, dx1, 1, 1, 1, 0;\n"
      "wgmma.mma_async.sync.aligned.m64n56k16.f32.bf16.bf16 {%28, %29, %30, %31, %32, %33, %34, %35, %36, %37, %38, %39, %40, %41, %42, %43, %44, %45, %46, %47, %48, %49, %50, %51, %52, %53, %54, %55}, {%84, %85, %86, %87}, dx2, 1, 1, 1, 0;\n"
      "wgmma.mma_async.sync.aligned.m64n56k16.f32.bf16.bf16 {%28, %29, %30, %31, %32, %33, %34, %35, %36, %37, %38, %39, %40, %41, %42, %43, %44, %45, %46, %47, %48, %49, %50, %51, %52, %53, %54, %55}, {%88, %89, %90, %91}, dx3, 1, 1, 1, 0;\n"
      "wgmma.commit_group.sync.aligned;\n}\n"
      : "=f"(g[0]), "=f"(g[1]), "=f"(g[2]), "=f"(g[3]), "=f"(g[4]), "=f"(g[5]), "=f"(g[6]), "=f"(g[7]), "=f"(g[8]), "=f"(g[9]), "=f"(g[10]), "=f"(g[11]), "=f"(g[12]), "=f"(g[13]), "=f"(g[14]), "=f"(g[15]), "=f"(g[16]), "=f"(g[17]), "=f"(g[18]), "=f"(g[19]), "=f"(g[20]), "=f"(g[21]), "=f"(g[22]), "=f"(g[23]), "=f"(g[24]), "=f"(g[25]), "=f"(g[26]), "=f"(g[27]),
        "=f"(h[0]), "=f"(h[1]), "=f"(h[2]), "=f"(h[3]), "=f"(h[4]), "=f"(h[5]), "=f"(h[6]), "=f"(h[7]), "=f"(h[8]), "=f"(h[9]), "=f"(h[10]), "=f"(h[11]), "=f"(h[12]), "=f"(h[13]), "=f"(h[14]), "=f"(h[15]), "=f"(h[16]), "=f"(h[17]), "=f"(h[18]), "=f"(h[19]), "=f"(h[20]), "=f"(h[21]), "=f"(h[22]), "=f"(h[23]), "=f"(h[24]), "=f"(h[25]), "=f"(h[26]), "=f"(h[27])
      : "r"(w[0]), "r"(w[1]), "r"(w[2]), "r"(w[3]), "r"(w[4]), "r"(w[5]), "r"(w[6]), "r"(w[7]), "r"(w[8]), "r"(w[9]), "r"(w[10]), "r"(w[11]), "r"(w[12]), "r"(w[13]), "r"(w[14]), "r"(w[15]), "r"(w[16]), "r"(w[17]), "r"(w[18]), "r"(w[19]), "r"(w[20]), "r"(w[21]), "r"(w[22]), "r"(w[23]), "r"(w[24]), "r"(w[25]), "r"(w[26]), "r"(w[27]), "r"(w[28]), "r"(w[29]), "r"(w[30]), "r"(w[31]), "r"(w[32]), "r"(w[33]), "r"(w[34]), "r"(w[35]), "r"(w[36]), "r"(w[37]), "r"(w[38]), "r"(w[39]), "r"(dx), "l"(de), "l"(dh)
      : "memory");
  }
  static __device__ __forceinline__ void wait_g(float* g) {
    asm volatile("wgmma.wait_group.sync.aligned 1;\n"
      : "+f"(g[0]), "+f"(g[1]), "+f"(g[2]), "+f"(g[3]), "+f"(g[4]), "+f"(g[5]), "+f"(g[6]), "+f"(g[7]), "+f"(g[8]), "+f"(g[9]), "+f"(g[10]), "+f"(g[11]), "+f"(g[12]), "+f"(g[13]), "+f"(g[14]), "+f"(g[15]), "+f"(g[16]), "+f"(g[17]), "+f"(g[18]), "+f"(g[19]), "+f"(g[20]), "+f"(g[21]), "+f"(g[22]), "+f"(g[23]), "+f"(g[24]), "+f"(g[25]), "+f"(g[26]), "+f"(g[27])
      :: "memory");
  }
  static __device__ __forceinline__ void wait_h(float* h) {
    asm volatile("wgmma.wait_group.sync.aligned 0;\n"
      : "+f"(h[0]), "+f"(h[1]), "+f"(h[2]), "+f"(h[3]), "+f"(h[4]), "+f"(h[5]), "+f"(h[6]), "+f"(h[7]), "+f"(h[8]), "+f"(h[9]), "+f"(h[10]), "+f"(h[11]), "+f"(h[12]), "+f"(h[13]), "+f"(h[14]), "+f"(h[15]), "+f"(h[16]), "+f"(h[17]), "+f"(h[18]), "+f"(h[19]), "+f"(h[20]), "+f"(h[21]), "+f"(h[22]), "+f"(h[23]), "+f"(h[24]), "+f"(h[25]), "+f"(h[26]), "+f"(h[27])
      :: "memory");
  }
};
template<> struct TileMMA<8> {
  static __device__ __forceinline__ void issue(float* g, float* h, const uint32_t* w, uint32_t dx, uint64_t de, uint64_t dh, uint64_t dc) {
    asm volatile(
      "{\n.reg .b64 dx0, dx1, dx2, dx3;\n.reg .b32 l1, l2, l3, hx;\nmov.b32 hx, 0x40000040;\n"
      "add.u32 l1, %104, 2;\nadd.u32 l2, %104, 4;\nadd.u32 l3, %104, 6;\n"
      "mov.b64 dx0, {%104, hx};\nmov.b64 dx1, {l1, hx};\nmov.b64 dx2, {l2, hx};\nmov.b64 dx3, {l3, hx};\n"
      "wgmma.fence.sync.aligned;\n"
      "wgmma.mma_async.sync.aligned.m64n64k16.f32.bf16.bf16 {%0, %1, %2, %3, %4, %5, %6, %7, %8, %9, %10, %11, %12, %13, %14, %15, %16, %17, %18, %19, %20, %21, %22, %23, %24, %25, %26, %27, %28, %29, %30, %31}, {%100, %101, %102, %103}, %106, 0, 1, 1, 0;\n"
      "wgmma.mma_async.sync.aligned.m64n64k16.f32.bf16.bf16 {%0, %1, %2, %3, %4, %5, %6, %7, %8, %9, %10, %11, %12, %13, %14, %15, %16, %17, %18, %19, %20, %21, %22, %23, %24, %25, %26, %27, %28, %29, %30, %31}, {%80, %81, %82, %83}, %105, 1, 1, 1, 0;\n"
      "wgmma.mma_async.sync.aligned.m64n64k16.f32.bf16.bf16 {%0, %1, %2, %3, %4, %5, %6, %7, %8, %9, %10, %11, %12, %13, %14, %15, %16, %17, %18, %19, %20, %21, %22, %23, %24, %25, %26, %27, %28, %29, %30, %31}, {%64, %65, %66, %67}, dx0, 1, 1, 1, 0;\n"
      "wgmma.mma_async.sync.aligned.m64n64k16.f32.bf16.bf16 {%0, %1, %2, %3, %4, %5, %6, %7, %8, %9, %10, %11, %12, %13, %14, %15, %16, %17, %18, %19, %20, %21, %22, %23, %24, %25, %26, %27, %28, %29, %30, %31}, {%68, %69, %70, %71}, dx1, 1, 1, 1, 0;\n"
      "wgmma.mma_async.sync.aligned.m64n64k16.f32.bf16.bf16 {%0, %1, %2, %3, %4, %5, %6, %7, %8, %9, %10, %11, %12, %13, %14, %15, %16, %17, %18, %19, %20, %21, %22, %23, %24, %25, %26, %27, %28, %29, %30, %31}, {%72, %73, %74, %75}, dx2, 1, 1, 1, 0;\n"
      "wgmma.mma_async.sync.aligned.m64n64k16.f32.bf16.bf16 {%0, %1, %2, %3, %4, %5, %6, %7, %8, %9, %10, %11, %12, %13, %14, %15, %16, %17, %18, %19, %20, %21, %22, %23, %24, %25, %26, %27, %28, %29, %30, %31}, {%76, %77, %78, %79}, dx3, 1, 1, 1, 0;\n"
      "wgmma.commit_group.sync.aligned;\n"
      "wgmma.mma_async.sync.aligned.m64n64k16.f32.bf16.bf16 {%32, %33, %34, %35, %36, %37, %38, %39, %40, %41, %42, %43, %44, %45, %46, %47, %48, %49, %50, %51, %52, %53, %54, %55, %56, %57, %58, %59, %60, %61, %62, %63}, {%84, %85, %86, %87}, dx0, 0, 1, 1, 0;\n"
      "wgmma.mma_async.sync.aligned.m64n64k16.f32.bf16.bf16 {%32, %33, %34, %35, %36, %37, %38, %39, %40, %41, %42, %43, %44, %45, %46, %47, %48, %49, %50, %51, %52, %53, %54, %55, %56, %57, %58, %59, %60, %61, %62, %63}, {%88, %89, %90, %91}, dx1, 1, 1, 1, 0;\n"
      "wgmma.mma_async.sync.aligned.m64n64k16.f32.bf16.bf16 {%32, %33, %34, %35, %36, %37, %38, %39, %40, %41, %42, %43, %44, %45, %46, %47, %48, %49, %50, %51, %52, %53, %54, %55, %56, %57, %58, %59, %60, %61, %62, %63}, {%92, %93, %94, %95}, dx2, 1, 1, 1, 0;\n"
      "wgmma.mma_async.sync.aligned.m64n64k16.f32.bf16.bf16 {%32, %33, %34, %35, %36, %37, %38, %39, %40, %41, %42, %43, %44, %45, %46, %47, %48, %49, %50, %51, %52, %53, %54, %55, %56, %57, %58, %59, %60, %61, %62, %63}, {%96, %97, %98, %99}, dx3, 1, 1, 1, 0;\n"
      "wgmma.commit_group.sync.aligned;\n}\n"
      : "=f"(g[0]), "=f"(g[1]), "=f"(g[2]), "=f"(g[3]), "=f"(g[4]), "=f"(g[5]), "=f"(g[6]), "=f"(g[7]), "=f"(g[8]), "=f"(g[9]), "=f"(g[10]), "=f"(g[11]), "=f"(g[12]), "=f"(g[13]), "=f"(g[14]), "=f"(g[15]), "=f"(g[16]), "=f"(g[17]), "=f"(g[18]), "=f"(g[19]), "=f"(g[20]), "=f"(g[21]), "=f"(g[22]), "=f"(g[23]), "=f"(g[24]), "=f"(g[25]), "=f"(g[26]), "=f"(g[27]), "=f"(g[28]), "=f"(g[29]), "=f"(g[30]), "=f"(g[31]),
        "=f"(h[0]), "=f"(h[1]), "=f"(h[2]), "=f"(h[3]), "=f"(h[4]), "=f"(h[5]), "=f"(h[6]), "=f"(h[7]), "=f"(h[8]), "=f"(h[9]), "=f"(h[10]), "=f"(h[11]), "=f"(h[12]), "=f"(h[13]), "=f"(h[14]), "=f"(h[15]), "=f"(h[16]), "=f"(h[17]), "=f"(h[18]), "=f"(h[19]), "=f"(h[20]), "=f"(h[21]), "=f"(h[22]), "=f"(h[23]), "=f"(h[24]), "=f"(h[25]), "=f"(h[26]), "=f"(h[27]), "=f"(h[28]), "=f"(h[29]), "=f"(h[30]), "=f"(h[31])
      : "r"(w[0]), "r"(w[1]), "r"(w[2]), "r"(w[3]), "r"(w[4]), "r"(w[5]), "r"(w[6]), "r"(w[7]), "r"(w[8]), "r"(w[9]), "r"(w[10]), "r"(w[11]), "r"(w[12]), "r"(w[13]), "r"(w[14]), "r"(w[15]), "r"(w[16]), "r"(w[17]), "r"(w[18]), "r"(w[19]), "r"(w[20]), "r"(w[21]), "r"(w[22]), "r"(w[23]), "r"(w[24]), "r"(w[25]), "r"(w[26]), "r"(w[27]), "r"(w[28]), "r"(w[29]), "r"(w[30]), "r"(w[31]), "r"(w[32]), "r"(w[33]), "r"(w[34]), "r"(w[35]), "r"(w[36]), "r"(w[37]), "r"(w[38]), "r"(w[39]), "r"(dx), "l"(de), "l"(dh)
      : "memory");
  }
  static __device__ __forceinline__ void wait_g(float* g) {
    asm volatile("wgmma.wait_group.sync.aligned 1;\n"
      : "+f"(g[0]), "+f"(g[1]), "+f"(g[2]), "+f"(g[3]), "+f"(g[4]), "+f"(g[5]), "+f"(g[6]), "+f"(g[7]), "+f"(g[8]), "+f"(g[9]), "+f"(g[10]), "+f"(g[11]), "+f"(g[12]), "+f"(g[13]), "+f"(g[14]), "+f"(g[15]), "+f"(g[16]), "+f"(g[17]), "+f"(g[18]), "+f"(g[19]), "+f"(g[20]), "+f"(g[21]), "+f"(g[22]), "+f"(g[23]), "+f"(g[24]), "+f"(g[25]), "+f"(g[26]), "+f"(g[27]), "+f"(g[28]), "+f"(g[29]), "+f"(g[30]), "+f"(g[31])
      :: "memory");
  }
  static __device__ __forceinline__ void wait_h(float* h) {
    asm volatile("wgmma.wait_group.sync.aligned 0;\n"
      : "+f"(h[0]), "+f"(h[1]), "+f"(h[2]), "+f"(h[3]), "+f"(h[4]), "+f"(h[5]), "+f"(h[6]), "+f"(h[7]), "+f"(h[8]), "+f"(h[9]), "+f"(h[10]), "+f"(h[11]), "+f"(h[12]), "+f"(h[13]), "+f"(h[14]), "+f"(h[15]), "+f"(h[16]), "+f"(h[17]), "+f"(h[18]), "+f"(h[19]), "+f"(h[20]), "+f"(h[21]), "+f"(h[22]), "+f"(h[23]), "+f"(h[24]), "+f"(h[25]), "+f"(h[26]), "+f"(h[27]), "+f"(h[28]), "+f"(h[29]), "+f"(h[30]), "+f"(h[31])
      :: "memory");
  }
};
template<> struct TileMMA<9> {
  static __device__ __forceinline__ void issue(float* g, float* h, const uint32_t* w, uint32_t dx, uint64_t de, uint64_t dh, uint64_t dc) {
    asm volatile(
      "{\n.reg .b64 dx0, dx1, dx2, dx3;\n.reg .b32 l1, l2, l3, hx;\nmov.b32 hx, 0x40000040;\n"
      "add.u32 l1, %112, 2;\nadd.u32 l2, %112, 4;\nadd.u32 l3, %112, 6;\n"
      "mov.b64 dx0, {%112, hx};\nmov.b64 dx1, {l1, hx};\nmov.b64 dx2, {l2, hx};\nmov.b64 dx3, {l3, hx};\n"
      "wgmma.fence.sync.aligned;\n"
      "wgmma.mma_async.sync.aligned.m64n72k16.f32.bf16.bf16 {%0, %1, %2, %3, %4, %5, %6, %7, %8, %9, %10, %11, %12, %13, %14, %15, %16, %17, %18, %19, %20, %21, %22, %23, %24, %25, %26, %27, %28, %29, %30, %31, %32, %33, %34, %35}, {%108, %109, %110, %111}, %114, 0, 1, 1, 0;\n"
      "wgmma.mma_async.sync.aligned.m64n72k16.f32.bf16.bf16 {%0, %1, %2, %3, %4, %5, %6, %7, %8, %9, %10, %11, %12, %13, %14, %15, %16, %17, %18, %19, %20, %21, %22, %23, %24, %25, %26, %27, %28, %29, %30, %31, %32, %33, %34, %35}, {%88, %89, %90, %91}, %113, 1, 1, 1, 0;\n"
      "wgmma.mma_async.sync.aligned.m64n72k16.f32.bf16.bf16 {%0, %1, %2, %3, %4, %5, %6, %7, %8, %9, %10, %11, %12, %13, %14, %15, %16, %17, %18, %19, %20, %21, %22, %23, %24, %25, %26, %27, %28, %29, %30, %31, %32, %33, %34, %35}, {%72, %73, %74, %75}, dx0, 1, 1, 1, 0;\n"
      "wgmma.mma_async.sync.aligned.m64n72k16.f32.bf16.bf16 {%0, %1, %2, %3, %4, %5, %6, %7, %8, %9, %10, %11, %12, %13, %14, %15, %16, %17, %18, %19, %20, %21, %22, %23, %24, %25, %26, %27, %28, %29, %30, %31, %32, %33, %34, %35}, {%76, %77, %78, %79}, dx1, 1, 1, 1, 0;\n"
      "wgmma.mma_async.sync.aligned.m64n72k16.f32.bf16.bf16 {%0, %1, %2, %3, %4, %5, %6, %7, %8, %9, %10, %11, %12, %13, %14, %15, %16, %17, %18, %19, %20, %21, %22, %23, %24, %25, %26, %27, %28, %29, %30, %31, %32, %33, %34, %35}, {%80, %81, %82, %83}, dx2, 1, 1, 1, 0;\n"
      "wgmma.mma_async.sync.aligned.m64n72k16.f32.bf16.bf16 {%0, %1, %2, %3, %4, %5, %6, %7, %8, %9, %10, %11, %12, %13, %14, %15, %16, %17, %18, %19, %20, %21, %22, %23, %24, %25, %26, %27, %28, %29, %30, %31, %32, %33, %34, %35}, {%84, %85, %86, %87}, dx3, 1, 1, 1, 0;\n"
      "wgmma.commit_group.sync.aligned;\n"
      "wgmma.mma_async.sync.aligned.m64n72k16.f32.bf16.bf16 {%36, %37, %38, %39, %40, %41, %42, %43, %44, %45, %46, %47, %48, %49, %50, %51, %52, %53, %54, %55, %56, %57, %58, %59, %60, %61, %62, %63, %64, %65, %66, %67, %68, %69, %70, %71}, {%92, %93, %94, %95}, dx0, 0, 1, 1, 0;\n"
      "wgmma.mma_async.sync.aligned.m64n72k16.f32.bf16.bf16 {%36, %37, %38, %39, %40, %41, %42, %43, %44, %45, %46, %47, %48, %49, %50, %51, %52, %53, %54, %55, %56, %57, %58, %59, %60, %61, %62, %63, %64, %65, %66, %67, %68, %69, %70, %71}, {%96, %97, %98, %99}, dx1, 1, 1, 1, 0;\n"
      "wgmma.mma_async.sync.aligned.m64n72k16.f32.bf16.bf16 {%36, %37, %38, %39, %40, %41, %42, %43, %44, %45, %46, %47, %48, %49, %50, %51, %52, %53, %54, %55, %56, %57, %58, %59, %60, %61, %62, %63, %64, %65, %66, %67, %68, %69, %70, %71}, {%100, %101, %102, %103}, dx2, 1, 1, 1, 0;\n"
      "wgmma.mma_async.sync.aligned.m64n72k16.f32.bf16.bf16 {%36, %37, %38, %39, %40, %41, %42, %43, %44, %45, %46, %47, %48, %49, %50, %51, %52, %53, %54, %55, %56, %57, %58, %59, %60, %61, %62, %63, %64, %65, %66, %67, %68, %69, %70, %71}, {%104, %105, %106, %107}, dx3, 1, 1, 1, 0;\n"
      "wgmma.commit_group.sync.aligned;\n}\n"
      : "=f"(g[0]), "=f"(g[1]), "=f"(g[2]), "=f"(g[3]), "=f"(g[4]), "=f"(g[5]), "=f"(g[6]), "=f"(g[7]), "=f"(g[8]), "=f"(g[9]), "=f"(g[10]), "=f"(g[11]), "=f"(g[12]), "=f"(g[13]), "=f"(g[14]), "=f"(g[15]), "=f"(g[16]), "=f"(g[17]), "=f"(g[18]), "=f"(g[19]), "=f"(g[20]), "=f"(g[21]), "=f"(g[22]), "=f"(g[23]), "=f"(g[24]), "=f"(g[25]), "=f"(g[26]), "=f"(g[27]), "=f"(g[28]), "=f"(g[29]), "=f"(g[30]), "=f"(g[31]), "=f"(g[32]), "=f"(g[33]), "=f"(g[34]), "=f"(g[35]),
        "=f"(h[0]), "=f"(h[1]), "=f"(h[2]), "=f"(h[3]), "=f"(h[4]), "=f"(h[5]), "=f"(h[6]), "=f"(h[7]), "=f"(h[8]), "=f"(h[9]), "=f"(h[10]), "=f"(h[11]), "=f"(h[12]), "=f"(h[13]), "=f"(h[14]), "=f"(h[15]), "=f"(h[16]), "=f"(h[17]), "=f"(h[18]), "=f"(h[19]), "=f"(h[20]), "=f"(h[21]), "=f"(h[22]), "=f"(h[23]), "=f"(h[24]), "=f"(h[25]), "=f"(h[26]), "=f"(h[27]), "=f"(h[28]), "=f"(h[29]), "=f"(h[30]), "=f"(h[31]), "=f"(h[32]), "=f"(h[33]), "=f"(h[34]), "=f"(h[35])
      : "r"(w[0]), "r"(w[1]), "r"(w[2]), "r"(w[3]), "r"(w[4]), "r"(w[5]), "r"(w[6]), "r"(w[7]), "r"(w[8]), "r"(w[9]), "r"(w[10]), "r"(w[11]), "r"(w[12]), "r"(w[13]), "r"(w[14]), "r"(w[15]), "r"(w[16]), "r"(w[17]), "r"(w[18]), "r"(w[19]), "r"(w[20]), "r"(w[21]), "r"(w[22]), "r"(w[23]), "r"(w[24]), "r"(w[25]), "r"(w[26]), "r"(w[27]), "r"(w[28]), "r"(w[29]), "r"(w[30]), "r"(w[31]), "r"(w[32]), "r"(w[33]), "r"(w[34]), "r"(w[35]), "r"(w[36]), "r"(w[37]), "r"(w[38]), "r"(w[39]), "r"(dx), "l"(de), "l"(dh)
      : "memory");
  }
  static __device__ __forceinline__ void wait_g(float* g) {
    asm volatile("wgmma.wait_group.sync.aligned 1;\n"
      : "+f"(g[0]), "+f"(g[1]), "+f"(g[2]), "+f"(g[3]), "+f"(g[4]), "+f"(g[5]), "+f"(g[6]), "+f"(g[7]), "+f"(g[8]), "+f"(g[9]), "+f"(g[10]), "+f"(g[11]), "+f"(g[12]), "+f"(g[13]), "+f"(g[14]), "+f"(g[15]), "+f"(g[16]), "+f"(g[17]), "+f"(g[18]), "+f"(g[19]), "+f"(g[20]), "+f"(g[21]), "+f"(g[22]), "+f"(g[23]), "+f"(g[24]), "+f"(g[25]), "+f"(g[26]), "+f"(g[27]), "+f"(g[28]), "+f"(g[29]), "+f"(g[30]), "+f"(g[31]), "+f"(g[32]), "+f"(g[33]), "+f"(g[34]), "+f"(g[35])
      :: "memory");
  }
  static __device__ __forceinline__ void wait_h(float* h) {
    asm volatile("wgmma.wait_group.sync.aligned 0;\n"
      : "+f"(h[0]), "+f"(h[1]), "+f"(h[2]), "+f"(h[3]), "+f"(h[4]), "+f"(h[5]), "+f"(h[6]), "+f"(h[7]), "+f"(h[8]), "+f"(h[9]), "+f"(h[10]), "+f"(h[11]), "+f"(h[12]), "+f"(h[13]), "+f"(h[14]), "+f"(h[15]), "+f"(h[16]), "+f"(h[17]), "+f"(h[18]), "+f"(h[19]), "+f"(h[20]), "+f"(h[21]), "+f"(h[22]), "+f"(h[23]), "+f"(h[24]), "+f"(h[25]), "+f"(h[26]), "+f"(h[27]), "+f"(h[28]), "+f"(h[29]), "+f"(h[30]), "+f"(h[31]), "+f"(h[32]), "+f"(h[33]), "+f"(h[34]), "+f"(h[35])
      :: "memory");
  }
};
template<> struct TileMMA<10> {
  static __device__ __forceinline__ void issue(float* g, float* h, const uint32_t* w, uint32_t dx, uint64_t de, uint64_t dh, uint64_t dc) {
    asm volatile(
      "{\n.reg .b64 dx0, dx1, dx2, dx3;\n.reg .b32 l1, l2, l3, hx;\nmov.b32 hx, 0x40000040;\n"
      "add.u32 l1, %120, 2;\nadd.u32 l2, %120, 4;\nadd.u32 l3, %120, 6;\n"
      "mov.b64 dx0, {%120, hx};\nmov.b64 dx1, {l1, hx};\nmov.b64 dx2, {l2, hx};\nmov.b64 dx3, {l3, hx};\n"
      "wgmma.fence.sync.aligned;\n"
      "wgmma.mma_async.sync.aligned.m64n80k16.f32.bf16.bf16 {%0, %1, %2, %3, %4, %5, %6, %7, %8, %9, %10, %11, %12, %13, %14, %15, %16, %17, %18, %19, %20, %21, %22, %23, %24, %25, %26, %27, %28, %29, %30, %31, %32, %33, %34, %35, %36, %37, %38, %39}, {%116, %117, %118, %119}, %122, 0, 1, 1, 0;\n"
      "wgmma.mma_async.sync.aligned.m64n80k16.f32.bf16.bf16 {%0, %1, %2, %3, %4, %5, %6, %7, %8, %9, %10, %11, %12, %13, %14, %15, %16, %17, %18, %19, %20, %21, %22, %23, %24, %25, %26, %27, %28, %29, %30, %31, %32, %33, %34, %35, %36, %37, %38, %39}, {%96, %97, %98, %99}, %121, 1, 1, 1, 0;\n"
      "wgmma.mma_async.sync.aligned.m64n80k16.f32.bf16.bf16 {%0, %1, %2, %3, %4, %5, %6, %7, %8, %9, %10, %11, %12, %13, %14, %15, %16, %17, %18, %19, %20, %21, %22, %23, %24, %25, %26, %27, %28, %29, %30, %31, %32, %33, %34, %35, %36, %37, %38, %39}, {%80, %81, %82, %83}, dx0, 1, 1, 1, 0;\n"
      "wgmma.mma_async.sync.aligned.m64n80k16.f32.bf16.bf16 {%0, %1, %2, %3, %4, %5, %6, %7, %8, %9, %10, %11, %12, %13, %14, %15, %16, %17, %18, %19, %20, %21, %22, %23, %24, %25, %26, %27, %28, %29, %30, %31, %32, %33, %34, %35, %36, %37, %38, %39}, {%84, %85, %86, %87}, dx1, 1, 1, 1, 0;\n"
      "wgmma.mma_async.sync.aligned.m64n80k16.f32.bf16.bf16 {%0, %1, %2, %3, %4, %5, %6, %7, %8, %9, %10, %11, %12, %13, %14, %15, %16, %17, %18, %19, %20, %21, %22, %23, %24, %25, %26, %27, %28, %29, %30, %31, %32, %33, %34, %35, %36, %37, %38, %39}, {%88, %89, %90, %91}, dx2, 1, 1, 1, 0;\n"
      "wgmma.mma_async.sync.aligned.m64n80k16.f32.bf16.bf16 {%0, %1, %2, %3, %4, %5, %6, %7, %8, %9, %10, %11, %12, %13, %14, %15, %16, %17, %18, %19, %20, %21, %22, %23, %24, %25, %26, %27, %28, %29, %30, %31, %32, %33, %34, %35, %36, %37, %38, %39}, {%92, %93, %94, %95}, dx3, 1, 1, 1, 0;\n"
      "wgmma.commit_group.sync.aligned;\n"
      "wgmma.mma_async.sync.aligned.m64n80k16.f32.bf16.bf16 {%40, %41, %42, %43, %44, %45, %46, %47, %48, %49, %50, %51, %52, %53, %54, %55, %56, %57, %58, %59, %60, %61, %62, %63, %64, %65, %66, %67, %68, %69, %70, %71, %72, %73, %74, %75, %76, %77, %78, %79}, {%100, %101, %102, %103}, dx0, 0, 1, 1, 0;\n"
      "wgmma.mma_async.sync.aligned.m64n80k16.f32.bf16.bf16 {%40, %41, %42, %43, %44, %45, %46, %47, %48, %49, %50, %51, %52, %53, %54, %55, %56, %57, %58, %59, %60, %61, %62, %63, %64, %65, %66, %67, %68, %69, %70, %71, %72, %73, %74, %75, %76, %77, %78, %79}, {%104, %105, %106, %107}, dx1, 1, 1, 1, 0;\n"
      "wgmma.mma_async.sync.aligned.m64n80k16.f32.bf16.bf16 {%40, %41, %42, %43, %44, %45, %46, %47, %48, %49, %50, %51, %52, %53, %54, %55, %56, %57, %58, %59, %60, %61, %62, %63, %64, %65, %66, %67, %68, %69, %70, %71, %72, %73, %74, %75, %76, %77, %78, %79}, {%108, %109, %110, %111}, dx2, 1, 1, 1, 0;\n"
      "wgmma.mma_async.sync.aligned.m64n80k16.f32.bf16.bf16 {%40, %41, %42, %43, %44, %45, %46, %47, %48, %49, %50, %51, %52, %53, %54, %55, %56, %57, %58, %59, %60, %61, %62, %63, %64, %65, %66, %67, %68, %69, %70, %71, %72, %73, %74, %75, %76, %77, %78, %79}, {%112, %113, %114, %115}, dx3, 1, 1, 1, 0;\n"
      "wgmma.commit_group.sync.aligned;\n}\n"
      : "=f"(g[0]), "=f"(g[1]), "=f"(g[2]), "=f"(g[3]), "=f"(g[4]), "=f"(g[5]), "=f"(g[6]), "=f"(g[7]), "=f"(g[8]), "=f"(g[9]), "=f"(g[10]), "=f"(g[11]), "=f"(g[12]), "=f"(g[13]), "=f"(g[14]), "=f"(g[15]), "=f"(g[16]), "=f"(g[17]), "=f"(g[18]), "=f"(g[19]), "=f"(g[20]), "=f"(g[21]), "=f"(g[22]), "=f"(g[23]), "=f"(g[24]), "=f"(g[25]), "=f"(g[26]), "=f"(g[27]), "=f"(g[28]), "=f"(g[29]), "=f"(g[30]), "=f"(g[31]), "=f"(g[32]), "=f"(g[33]), "=f"(g[34]), "=f"(g[35]), "=f"(g[36]), "=f"(g[37]), "=f"(g[38]), "=f"(g[39]),
        "=f"(h[0]), "=f"(h[1]), "=f"(h[2]), "=f"(h[3]), "=f"(h[4]), "=f"(h[5]), "=f"(h[6]), "=f"(h[7]), "=f"(h[8]), "=f"(h[9]), "=f"(h[10]), "=f"(h[11]), "=f"(h[12]), "=f"(h[13]), "=f"(h[14]), "=f"(h[15]), "=f"(h[16]), "=f"(h[17]), "=f"(h[18]), "=f"(h[19]), "=f"(h[20]), "=f"(h[21]), "=f"(h[22]), "=f"(h[23]), "=f"(h[24]), "=f"(h[25]), "=f"(h[26]), "=f"(h[27]), "=f"(h[28]), "=f"(h[29]), "=f"(h[30]), "=f"(h[31]), "=f"(h[32]), "=f"(h[33]), "=f"(h[34]), "=f"(h[35]), "=f"(h[36]), "=f"(h[37]), "=f"(h[38]), "=f"(h[39])
      : "r"(w[0]), "r"(w[1]), "r"(w[2]), "r"(w[3]), "r"(w[4]), "r"(w[5]), "r"(w[6]), "r"(w[7]), "r"(w[8]), "r"(w[9]), "r"(w[10]), "r"(w[11]), "r"(w[12]), "r"(w[13]), "r"(w[14]), "r"(w[15]), "r"(w[16]), "r"(w[17]), "r"(w[18]), "r"(w[19]), "r"(w[20]), "r"(w[21]), "r"(w[22]), "r"(w[23]), "r"(w[24]), "r"(w[25]), "r"(w[26]), "r"(w[27]), "r"(w[28]), "r"(w[29]), "r"(w[30]), "r"(w[31]), "r"(w[32]), "r"(w[33]), "r"(w[34]), "r"(w[35]), "r"(w[36]), "r"(w[37]), "r"(w[38]), "r"(w[39]), "r"(dx), "l"(de), "l"(dh)
      : "memory");
  }
  static __device__ __forceinline__ void wait_g(float* g) {
    asm volatile("wgmma.wait_group.sync.aligned 1;\n"
      : "+f"(g[0]), "+f"(g[1]), "+f"(g[2]), "+f"(g[3]), "+f"(g[4]), "+f"(g[5]), "+f"(g[6]), "+f"(g[7]), "+f"(g[8]), "+f"(g[9]), "+f"(g[10]), "+f"(g[11]), "+f"(g[12]), "+f"(g[13]), "+f"(g[14]), "+f"(g[15]), "+f"(g[16]), "+f"(g[17]), "+f"(g[18]), "+f"(g[19]), "+f"(g[20]), "+f"(g[21]), "+f"(g[22]), "+f"(g[23]), "+f"(g[24]), "+f"(g[25]), "+f"(g[26]), "+f"(g[27]), "+f"(g[28]), "+f"(g[29]), "+f"(g[30]), "+f"(g[31]), "+f"(g[32]), "+f"(g[33]), "+f"(g[34]), "+f"(g[35]), "+f"(g[36]), "+f"(g[37]), "+f"(g[38]), "+f"(g[39])
      :: "memory");
  }
  static __device__ __forceinline__ void wait_h(float* h) {
    asm volatile("wgmma.wait_group.sync.aligned 0;\n"
      : "+f"(h[0]), "+f"(h[1]), "+f"(h[2]), "+f"(h[3]), "+f"(h[4]), "+f"(h[5]), "+f"(h[6]), "+f"(h[7]), "+f"(h[8]), "+f"(h[9]), "+f"(h[10]), "+f"(h[11]), "+f"(h[12]), "+f"(h[13]), "+f"(h[14]), "+f"(h[15]), "+f"(h[16]), "+f"(h[17]), "+f"(h[18]), "+f"(h[19]), "+f"(h[20]), "+f"(h[21]), "+f"(h[22]), "+f"(h[23]), "+f"(h[24]), "+f"(h[25]), "+f"(h[26]), "+f"(h[27]), "+f"(h[28]), "+f"(h[29]), "+f"(h[30]), "+f"(h[31]), "+f"(h[32]), "+f"(h[33]), "+f"(h[34]), "+f"(h[35]), "+f"(h[36]), "+f"(h[37]), "+f"(h[38]), "+f"(h[39])
      :: "memory");
  }
};
template<> struct TileMMA<11> {
  static __device__ __forceinline__ void issue(float* g, float* h, const uint32_t* w, uint32_t dx, uint64_t de, uint64_t dh, uint64_t dc) {
    asm volatile(
      "{\n.reg .b64 dx0, dx1, dx2, dx3;\n.reg .b32 l1, l2, l3, hx;\nmov.b32 hx, 0x40000040;\n"
      "add.u32 l1, %124, 2;\nadd.u32 l2, %124, 4;\nadd.u32 l3, %124, 6;\n"
      "mov.b64 dx0, {%124, hx};\nmov.b64 dx1, {l1, hx};\nmov.b64 dx2, {l2, hx};\nmov.b64 dx3, {l3, hx};\n"
      "wgmma.fence.sync.aligned;\n"
      "wgmma.mma_async.sync.aligned.m64n88k16.f32.bf16.bf16 {%0, %1, %2, %3, %4, %5, %6, %7, %8, %9, %10, %11, %12, %13, %14, %15, %16, %17, %18, %19, %20, %21, %22, %23, %24, %25, %26, %27, %28, %29, %30, %31, %32, %33, %34, %35, %36, %37, %38, %39, %40, %41, %42, %43}, {%120, %121, %122, %123}, %126, 0, 1, 1, 0;\n"
      "wgmma.mma_async.sync.aligned.m64n88k16.f32.bf16.bf16 {%0, %1, %2, %3, %4, %5, %6, %7, %8, %9, %10, %11, %12, %13, %14, %15, %16, %17, %18, %19, %20, %21, %22, %23, %24, %25, %26, %27, %28, %29, %30, %31, %32, %33, %34, %35, %36, %37, %38, %39, %40, %41, %42, %43}, %127, %125, 1, 1, 1, 0, 0;\n"
      "wgmma.mma_async.sync.aligned.m64n88k16.f32.bf16.bf16 {%0, %1, %2, %3, %4, %5, %6, %7, %8, %9, %10, %11, %12, %13, %14, %15, %16, %17, %18, %19, %20, %21, %22, %23, %24, %25, %26, %27, %28, %29, %30, %31, %32, %33, %34, %35, %36, %37, %38, %39, %40, %41, %42, %43}, {%88, %89, %90, %91}, dx0, 1, 1, 1, 0;\n"
      "wgmma.mma_async.sync.aligned.m64n88k16.f32.bf16.bf16 {%0, %1, %2, %3, %4, %5, %6, %7, %8, %9, %10, %11, %12, %13, %14, %15, %16, %17, %18, %19, %20, %21, %22, %23, %24, %25, %26, %27, %28, %29, %30, %31, %32, %33, %34, %35, %36, %37, %38, %39, %40, %41, %42, %43}, {%92, %93, %94, %95}, dx1, 1, 1, 1, 0;\n"
      "wgmma.mma_async.sync.aligned.m64n88k16.f32.bf16.bf16 {%0, %1, %2, %3, %4, %5, %6, %7, %8, %9, %10, %11, %12, %13, %14, %15, %16, %17, %18, %19, %20, %21, %22, %23, %24, %25, %26, %27, %28, %29, %30, %31, %32, %33, %34, %35, %36, %37, %38, %39, %40, %41, %42, %43}, {%96, %97, %98, %99}, dx2, 1, 1, 1, 0;\n"
      "wgmma.mma_async.sync.aligned.m64n88k16.f32.bf16.bf16 {%0, %1, %2, %3, %4, %5, %6, %7, %8, %9, %10, %11, %12, %13, %14, %15, %16, %17, %18, %19, %20, %21, %22, %23, %24, %25, %26, %27, %28, %29, %30, %31, %32, %33, %34, %35, %36, %37, %38, %39, %40, %41, %42, %43}, {%100, %101, %102, %103}, dx3, 1, 1, 1, 0;\n"
      "wgmma.commit_group.sync.aligned;\n"
      "wgmma.mma_async.sync.aligned.m64n88k16.f32.bf16.bf16 {%44, %45, %46, %47, %48, %49, %50, %51, %52, %53, %54, %55, %56, %57, %58, %59, %60, %61, %62, %63, %64, %65, %66, %67, %68, %69, %70, %71, %72, %73, %74, %75, %76, %77, %78, %79, %80, %81, %82, %83, %84, %85, %86, %87}, {%104, %105, %106, %107}, dx0, 0, 1, 1, 0;\n"
      "wgmma.mma_async.sync.aligned.m64n88k16.f32.bf16.bf16 {%44, %45, %46, %47, %48, %49, %50, %51, %52, %53, %54, %55, %56, %57, %58, %59, %60, %61, %62, %63, %64, %65, %66, %67, %68, %69, %70, %71, %72, %73, %74, %75, %76, %77, %78, %79, %80, %81, %82, %83, %84, %85, %86, %87}, {%108, %109, %110, %111}, dx1, 1, 1, 1, 0;\n"
      "wgmma.mma_async.sync.aligned.m64n88k16.f32.bf16.bf16 {%44, %45, %46, %47, %48, %49, %50, %51, %52, %53, %54, %55, %56, %57, %58, %59, %60, %61, %62, %63, %64, %65, %66, %67, %68, %69, %70, %71, %72, %73, %74, %75, %76, %77, %78, %79, %80, %81, %82, %83, %84, %85, %86, %87}, {%112, %113, %114, %115}, dx2, 1, 1, 1, 0;\n"
      "wgmma.mma_async.sync.aligned.m64n88k16.f32.bf16.bf16 {%44, %45, %46, %47, %48, %49, %50, %51, %52, %53, %54, %55, %56, %57, %58, %59, %60, %61, %62, %63, %64, %65, %66, %67, %68, %69, %70, %71, %72, %73, %74, %75, %76, %77, %78, %79, %80, %81, %82, %83, %84, %85, %86, %87}, {%116, %117, %118, %119}, dx3, 1, 1, 1, 0;\n"
      "wgmma.commit_group.sync.aligned;\n}\n"
      : "=f"(g[0]), "=f"(g[1]), "=f"(g[2]), "=f"(g[3]), "=f"(g[4]), "=f"(g[5]), "=f"(g[6]), "=f"(g[7]), "=f"(g[8]), "=f"(g[9]), "=f"(g[10]), "=f"(g[11]), "=f"(g[12]), "=f"(g[13]), "=f"(g[14]), "=f"(g[15]), "=f"(g[16]), "=f"(g[17]), "=f"(g[18]), "=f"(g[19]), "=f"(g[20]), "=f"(g[21]), "=f"(g[22]), "=f"(g[23]), "=f"(g[24]), "=f"(g[25]), "=f"(g[26]), "=f"(g[27]), "=f"(g[28]), "=f"(g[29]), "=f"(g[30]), "=f"(g[31]), "=f"(g[32]), "=f"(g[33]), "=f"(g[34]), "=f"(g[35]), "=f"(g[36]), "=f"(g[37]), "=f"(g[38]), "=f"(g[39]), "=f"(g[40]), "=f"(g[41]), "=f"(g[42]), "=f"(g[43]),
        "=f"(h[0]), "=f"(h[1]), "=f"(h[2]), "=f"(h[3]), "=f"(h[4]), "=f"(h[5]), "=f"(h[6]), "=f"(h[7]), "=f"(h[8]), "=f"(h[9]), "=f"(h[10]), "=f"(h[11]), "=f"(h[12]), "=f"(h[13]), "=f"(h[14]), "=f"(h[15]), "=f"(h[16]), "=f"(h[17]), "=f"(h[18]), "=f"(h[19]), "=f"(h[20]), "=f"(h[21]), "=f"(h[22]), "=f"(h[23]), "=f"(h[24]), "=f"(h[25]), "=f"(h[26]), "=f"(h[27]), "=f"(h[28]), "=f"(h[29]), "=f"(h[30]), "=f"(h[31]), "=f"(h[32]), "=f"(h[33]), "=f"(h[34]), "=f"(h[35]), "=f"(h[36]), "=f"(h[37]), "=f"(h[38]), "=f"(h[39]), "=f"(h[40]), "=f"(h[41]), "=f"(h[42]), "=f"(h[43])
      : "r"(w[0]), "r"(w[1]), "r"(w[2]), "r"(w[3]), "r"(w[4]), "r"(w[5]), "r"(w[6]), "r"(w[7]), "r"(w[8]), "r"(w[9]), "r"(w[10]), "r"(w[11]), "r"(w[12]), "r"(w[13]), "r"(w[14]), "r"(w[15]), "r"(w[20]), "r"(w[21]), "r"(w[22]), "r"(w[23]), "r"(w[24]), "r"(w[25]), "r"(w[26]), "r"(w[27]), "r"(w[28]), "r"(w[29]), "r"(w[30]), "r"(w[31]), "r"(w[32]), "r"(w[33]), "r"(w[34]), "r"(w[35]), "r"(w[36]), "r"(w[37]), "r"(w[38]), "r"(w[39]), "r"(dx), "l"(de), "l"(dh), "l"(dc)
      : "memory");
  }
  static __device__ __forceinline__ void wait_g(float* g) {
    asm volatile("wgmma.wait_group.sync.aligned 1;\n"
      : "+f"(g[0]), "+f"(g[1]), "+f"(g[2]), "+f"(g[3]), "+f"(g[4]), "+f"(g[5]), "+f"(g[6]), "+f"(g[7]), "+f"(g[8]), "+f"(g[9]), "+f"(g[10]), "+f"(g[11]), "+f"(g[12]), "+f"(g[13]), "+f"(g[14]), "+f"(g[15]), "+f"(g[16]), "+f"(g[17]), "+f"(g[18]), "+f"(g[19]), "+f"(g[20]), "+f"(g[21]), "+f"(g[22]), "+f"(g[23]), "+f"(g[24]), "+f"(g[25]), "+f"(g[26]), "+f"(g[27]), "+f"(g[28]), "+f"(g[29]), "+f"(g[30]), "+f"(g[31]), "+f"(g[32]), "+f"(g[33]), "+f"(g[34]), "+f"(g[35]), "+f"(g[36]), "+f"(g[37]), "+f"(g[38]), "+f"(g[39]), "+f"(g[40]), "+f"(g[41]), "+f"(g[42]), "+f"(g[43])
      :: "memory");
  }
  static __device__ __forceinline__ void wait_h(float* h) {
    asm volatile("wgmma.wait_group.sync.aligned 0;\n"
      : "+f"(h[0]), "+f"(h[1]), "+f"(h[2]), "+f"(h[3]), "+f"(h[4]), "+f"(h[5]), "+f"(h[6]), "+f"(h[7]), "+f"(h[8]), "+f"(h[9]), "+f"(h[10]), "+f"(h[11]), "+f"(h[12]), "+f"(h[13]), "+f"(h[14]), "+f"(h[15]), "+f"(h[16]), "+f"(h[17]), "+f"(h[18]), "+f"(h[19]), "+f"(h[20]), "+f"(h[21]), "+f"(h[22]), "+f"(h[23]), "+f"(h[24]), "+f"(h[25]), "+f"(h[26]), "+f"(h[27]), "+f"(h[28]), "+f"(h[29]), "+f"(h[30]), "+f"(h[31]), "+f"(h[32]), "+f"(h[33]), "+f"(h[34]), "+f"(h[35]), "+f"(h[36]), "+f"(h[37]), "+f"(h[38]), "+f"(h[39]), "+f"(h[40]), "+f"(h[41]), "+f"(h[42]), "+f"(h[43])
      :: "memory");
  }
};
__device__ __forceinline__ void node_mma(float* g, const uint32_t* w, uint64_t dx) {
    asm volatile(
      "{\n.reg .b64 dx1, dx2, dx3;\n"
      "add.s64 dx1, %48, 2;\nadd.s64 dx2, %48, 4;\nadd.s64 dx3, %48, 6;\n"
      "wgmma.fence.sync.aligned;\n"
      "wgmma.mma_async.sync.aligned.m64n64k16.f32.bf16.bf16 {%0, %1, %2, %3, %4, %5, %6, %7, %8, %9, %10, %11, %12, %13, %14, %15, %16, %17, %18, %19, %20, %21, %22, %23, %24, %25, %26, %27, %28, %29, %30, %31}, {%32, %33, %34, %35}, %48, 0, 1, 1, 0;\n"
      "wgmma.mma_async.sync.aligned.m64n64k16.f32.bf16.bf16 {%0, %1, %2, %3, %4, %5, %6, %7, %8, %9, %10, %11, %12, %13, %14, %15, %16, %17, %18, %19, %20, %21, %22, %23, %24, %25, %26, %27, %28, %29, %30, %31}, {%36, %37, %38, %39}, dx1, 1, 1, 1, 0;\n"
      "wgmma.mma_async.sync.aligned.m64n64k16.f32.bf16.bf16 {%0, %1, %2, %3, %4, %5, %6, %7, %8, %9, %10, %11, %12, %13, %14, %15, %16, %17, %18, %19, %20, %21, %22, %23, %24, %25, %26, %27, %28, %29, %30, %31}, {%40, %41, %42, %43}, dx2, 1, 1, 1, 0;\n"
      "wgmma.mma_async.sync.aligned.m64n64k16.f32.bf16.bf16 {%0, %1, %2, %3, %4, %5, %6, %7, %8, %9, %10, %11, %12, %13, %14, %15, %16, %17, %18, %19, %20, %21, %22, %23, %24, %25, %26, %27, %28, %29, %30, %31}, {%44, %45, %46, %47}, dx3, 1, 1, 1, 0;\n"
      "wgmma.commit_group.sync.aligned;\n}\n"
      : "=f"(g[0]), "=f"(g[1]), "=f"(g[2]), "=f"(g[3]), "=f"(g[4]), "=f"(g[5]), "=f"(g[6]), "=f"(g[7]), "=f"(g[8]), "=f"(g[9]), "=f"(g[10]), "=f"(g[11]), "=f"(g[12]), "=f"(g[13]), "=f"(g[14]), "=f"(g[15]), "=f"(g[16]), "=f"(g[17]), "=f"(g[18]), "=f"(g[19]), "=f"(g[20]), "=f"(g[21]), "=f"(g[22]), "=f"(g[23]), "=f"(g[24]), "=f"(g[25]), "=f"(g[26]), "=f"(g[27]), "=f"(g[28]), "=f"(g[29]), "=f"(g[30]), "=f"(g[31])
      : "r"(w[0]), "r"(w[1]), "r"(w[2]), "r"(w[3]), "r"(w[4]), "r"(w[5]), "r"(w[6]), "r"(w[7]), "r"(w[8]), "r"(w[9]), "r"(w[10]), "r"(w[11]), "r"(w[12]), "r"(w[13]), "r"(w[14]), "r"(w[15]), "l"(dx)
      : "memory");
}

__device__ __forceinline__ uint32_t smem_u32(const void* p) { return (uint32_t)__cvta_generic_to_shared(p); }
__device__ __forceinline__ float ex2f(float x) { float y; asm("ex2.approx.ftz.f32 %0, %1;" : "=f"(y) : "f"(x)); return y; }
__device__ __forceinline__ float rcpf(float x) { float y; asm("rcp.approx.ftz.f32 %0, %1;" : "=f"(y) : "f"(x)); return y; }
__device__ __forceinline__ uint32_t pack_bf16(float lo, float hi) {
    uint32_t r; asm("cvt.rn.bf16x2.f32 %0, %1, %2;" : "=r"(r) : "f"(hi), "f"(lo)); return r;
}
__device__ __forceinline__ float bf_lo(uint32_t v) { return __uint_as_float(v << 16); }
__device__ __forceinline__ float bf_hi(uint32_t v) { return __uint_as_float(v & 0xFFFF0000u); }
template<int STRIDE>
__device__ __forceinline__ void cp16i(uint32_t dst, const char* base, uint32_t idx) {
    asm volatile("{\n.reg .b64 a;\nmad.wide.u32 a, %2, %3, %1;\ncp.async.cg.shared.global [%0], [a], 16;\n}\n" :: "r"(dst), "l"(base), "r"(idx), "n"(STRIDE) : "memory");
}
__device__ __forceinline__ void cp16e(uint32_t dst, const char* base, uint32_t idx, uint64_t pol) {
    asm volatile("{\n.reg .b64 a;\nmad.wide.u32 a, %2, 32, %1;\ncp.async.cg.shared.global.L2::cache_hint [%0], [a], 16, %3;\n}\n" :: "r"(dst), "l"(base), "r"(idx), "l"(pol) : "memory");
}
template<int STRIDE>
__device__ __forceinline__ void cp16z(uint32_t dst, const char* base, uint32_t idx, int k, int n, uint64_t pol) {
    if (STRIDE == 32)
        asm volatile("{\n.reg .b64 a;\n.reg .pred p;\nsetp.ge.s32 p, %3, %4;\nmad.wide.u32 a, %2, 32, %1;\ncp.async.cg.shared.global.L2::cache_hint [%0], [a], 16, p, %5;\n}\n"
                     :: "r"(dst), "l"(base), "r"(idx), "r"(k), "r"(n), "l"(pol) : "memory");
    else
        asm volatile("{\n.reg .b64 a;\n.reg .pred p;\nsetp.ge.s32 p, %3, %4;\nmad.wide.u32 a, %2, 128, %1;\ncp.async.cg.shared.global [%0], [a], 16, p;\n}\n"
                     :: "r"(dst), "l"(base), "r"(idx), "r"(k), "r"(n) : "memory");
}
template<int HI, bool Z>
__device__ __forceinline__ void cpx(uint32_t hi, uint32_t dst, uint32_t p, uint32_t lo, int k, int n) {
    if (Z) asm volatile("{\n.reg .b32 l;\n.reg .b64 a;\n.reg .pred q;\nsetp.ge.s32 q, %5, %6;\ndp2a.lo.u32.u32 l, %1, %2, %3;\nmov.b64 a, {l, %0};\ncp.async.cg.shared.global [%4], [a], 16, q;\n}\n"
                        :: "r"(hi), "r"(p), "r"(HI ? 0x8000u : 0x80u), "r"(lo), "r"(dst), "r"(k), "r"(n) : "memory");
    else asm volatile("{\n.reg .b32 l;\n.reg .b64 a;\ndp2a.lo.u32.u32 l, %1, %2, %3;\nmov.b64 a, {l, %0};\ncp.async.cg.shared.global [%4], [a], 16;\n}\n"
                      :: "r"(hi), "r"(p), "r"(HI ? 0x8000u : 0x80u), "r"(lo), "r"(dst) : "memory");
}
template<bool Z>
__device__ __forceinline__ void cpe(uint32_t hi, uint32_t dst, uint32_t idx, uint32_t lo, int k, int n, uint64_t pol) {
    if (Z) asm volatile("{\n.reg .b32 l;\n.reg .b64 a;\n.reg .pred q;\nsetp.ge.s32 q, %5, %6;\nmad.lo.u32 l, %1, 32, %2;\nmov.b64 a, {l, %0};\ncp.async.cg.shared.global.L2::cache_hint [%3], [a], 16, q, %4;\n}\n"
                        :: "r"(hi), "r"(idx), "r"(lo), "r"(dst), "l"(pol), "r"(k), "r"(n) : "memory");
    else asm volatile("{\n.reg .b32 l;\n.reg .b64 a;\nmad.lo.u32 l, %1, 32, %2;\nmov.b64 a, {l, %0};\ncp.async.cg.shared.global.L2::cache_hint [%3], [a], 16, %4;\n}\n"
                      :: "r"(hi), "r"(idx), "r"(lo), "r"(dst), "l"(pol) : "memory");
}
__device__ __forceinline__ void cp_commit() { asm volatile("cp.async.commit_group;" ::: "memory"); }
template<int N> __device__ __forceinline__ void cp_wait() { asm volatile("cp.async.wait_group %0;" :: "n"(N) : "memory"); }
__device__ __forceinline__ void mbar_init(uint32_t bar, int cnt) { asm volatile("mbarrier.init.shared.b64 [%0], %1;" :: "r"(bar), "r"(cnt) : "memory"); }
__device__ __forceinline__ void mbar_arrive(uint32_t bar) { asm volatile("mbarrier.arrive.shared.b64 _, [%0];" :: "r"(bar) : "memory"); }
__device__ __forceinline__ void mbar_expect(uint32_t bar, uint32_t bytes) { asm volatile("mbarrier.arrive.expect_tx.shared.b64 _, [%0], %1;" :: "r"(bar), "r"(bytes) : "memory"); }
__device__ __forceinline__ void mbar_cp_arrive(uint32_t bar) { asm volatile("cp.async.mbarrier.arrive.noinc.shared.b64 [%0];" :: "r"(bar) : "memory"); }
__device__ __forceinline__ void mbar_wait(uint32_t bar, uint32_t parity) {
    asm volatile("{\n.reg .pred p;\n.reg .u32 n;\nmbarrier.try_wait.parity.shared.b64 p, [%0], %1;\n@p bra DONE_%=;\nmov.u32 n, 0;\n"
                 "WAIT_%=:\nmbarrier.try_wait.parity.shared.b64 p, [%0], %1, 0x100000;\n@p bra DONE_%=;\n"
                 "add.u32 n, n, 1;\nsetp.lt.u32 p, n, 0x400000;\n@p bra WAIT_%=;\ntrap;\nDONE_%=:\n}\n"
                 :: "r"(bar), "r"(parity) : "memory");
}
__device__ __forceinline__ void mbar_wait_c(uint32_t bar, uint32_t parity) {
    asm volatile("{\n.reg .pred p;\nWAIT_%=:\nmbarrier.try_wait.parity.shared.b64 p, [%0], %1;\n@p bra DONE_%=;\nbra WAIT_%=;\nDONE_%=:\n}\n"
                 :: "r"(bar), "r"(parity) : "memory");
}
__device__ __forceinline__ void mbar_wait_h(uint32_t bar, uint32_t parity) {
    asm volatile("{\n.reg .pred p;\nWAIT_%=:\nmbarrier.try_wait.parity.shared.b64 p, [%0], %1, 0x100000;\n@p bra DONE_%=;\nbra WAIT_%=;\nDONE_%=:\n}\n"
                 :: "r"(bar), "r"(parity) : "memory");
}
__device__ __forceinline__ uint32_t lds32(uint32_t a) { uint32_t v; asm volatile("ld.shared.u32 %0, [%1];" : "=r"(v) : "r"(a) : "memory"); return v; }
__device__ __forceinline__ void sts32(uint32_t a, uint32_t v) { asm volatile("st.shared.u32 [%0], %1;" :: "r"(a), "r"(v) : "memory"); }
__device__ __forceinline__ uint2 lds64(uint32_t a) { uint2 v; asm volatile("ld.shared.v2.u32 {%0,%1}, [%2];" : "=r"(v.x), "=r"(v.y) : "r"(a) : "memory"); return v; }
__device__ __forceinline__ uint4 lds128(uint32_t a) { uint4 v; asm volatile("ld.shared.v4.u32 {%0,%1,%2,%3}, [%4];" : "=r"(v.x), "=r"(v.y), "=r"(v.z), "=r"(v.w) : "r"(a) : "memory"); return v; }
__device__ __forceinline__ void sts128(uint32_t a, uint4 v) { asm volatile("st.shared.v4.u32 [%0], {%1,%2,%3,%4};" :: "r"(a), "r"(v.x), "r"(v.y), "r"(v.z), "r"(v.w) : "memory"); }
__device__ __forceinline__ void ldsm4t(uint32_t* v, uint32_t a) {
    asm volatile("ldmatrix.sync.aligned.m8n8.x4.trans.shared.b16 {%0,%1,%2,%3}, [%4];" : "=r"(v[0]), "=r"(v[1]), "=r"(v[2]), "=r"(v[3]) : "r"(a) : "memory");
}
__device__ __forceinline__ void stsm4t(uint32_t a, const uint32_t* v) {
    asm volatile("stmatrix.sync.aligned.m8n8.x4.trans.shared.b16 [%0], {%1,%2,%3,%4};" :: "r"(a), "r"(v[0]), "r"(v[1]), "r"(v[2]), "r"(v[3]) : "memory");
}
__device__ __forceinline__ int atoms_inc(uint32_t a) { int v; asm volatile("atom.shared.add.u32 %0, [%1], 1;" : "=r"(v) : "r"(a) : "memory"); return v; }
__device__ __forceinline__ bool elect_one() {
    uint32_t el;
    asm volatile("{\n.reg .pred p;\nelect.sync _|p, 0xffffffff;\nselp.u32 %0, 1, 0, p;\n}" : "=r"(el));
    return el != 0;
}
__device__ __forceinline__ float tanhf_a(float x) { float y; asm("tanh.approx.f32 %0, %1;" : "=f"(y) : "f"(x)); return y; }
__device__ __forceinline__ const char* as_pair(const void* p, uint32_t scratch) {
    const char* r;
    asm volatile("st.shared.u64 [%1], %2;\nld.volatile.shared.u64 %0, [%1];" : "=l"(r) : "r"(scratch), "l"(p) : "memory");
    return r;
}
__device__ __forceinline__ void ld_unit(uint4& v, const char* p, bool ok) {
    asm volatile("{\n.reg .pred q;\nsetp.ne.u32 q, %5, 0;\n@q ld.relaxed.gpu.global.v4.u32 {%0,%1,%2,%3}, [%4];\n}"
                 : "+r"(v.x), "+r"(v.y), "+r"(v.z), "+r"(v.w) : "l"(p), "r"((uint32_t)ok) : "memory");
}
__device__ __forceinline__ void ld_unit(uint2& v, const char* p, bool ok) {
    asm volatile("{\n.reg .pred q;\nsetp.ne.u32 q, %3, 0;\n@q ld.relaxed.gpu.global.v2.u32 {%0,%1}, [%2];\n}"
                 : "+r"(v.x), "+r"(v.y) : "l"(p), "r"((uint32_t)ok) : "memory");
}
__device__ __forceinline__ void bulk_ld(uint32_t dst, const void* src, int bytes, uint32_t bar) {
    mbar_expect(bar, bytes);
    if (bytes > 0) asm volatile("cp.async.bulk.shared::cluster.global.mbarrier::complete_tx::bytes [%0], [%1], %2, [%3];" :: "r"(dst), "l"(src), "r"(bytes), "r"(bar) : "memory");
}
#define ELECT "{\n.reg .pred p;\nelect.sync _|p, 0xffffffff;\n@p "
__device__ __forceinline__ void w_expect(uint32_t bar, uint32_t bytes) { asm volatile(ELECT "mbarrier.arrive.expect_tx.shared.b64 _, [%0], %1;\n}" :: "r"(bar), "r"(bytes) : "memory"); }
__device__ __forceinline__ void w_ld(uint32_t dst, const void* src, int bytes, uint32_t bar) {
    asm volatile(ELECT "cp.async.bulk.shared::cluster.global.mbarrier::complete_tx::bytes [%0], [%1], %2, [%3];\n}" :: "r"(dst), "l"(src), "r"(bytes), "r"(bar) : "memory");
}
__device__ __forceinline__ void w_box_ld(uint32_t dst, const CUtensorMap* tm, int row, uint32_t bar) {
    asm volatile(ELECT "cp.async.bulk.tensor.2d.shared::cluster.global.mbarrier::complete_tx::bytes [%0], [%1, {%3, %4}], [%2];\n}"
        :: "r"(dst), "l"((uint64_t)tm), "r"(bar), "r"(0), "r"(row) : "memory");
}
__device__ __forceinline__ void w_st(void* dst, uint32_t src, int bytes) {
    asm volatile(ELECT "cp.async.bulk.global.shared::cta.bulk_group [%0], [%1], %2;\n}" :: "l"(dst), "r"(src), "r"(bytes) : "memory");
}
__device__ __forceinline__ void w_box_st(const CUtensorMap* tm, int col, uint32_t src) {
    asm volatile(ELECT "cp.async.bulk.tensor.2d.global.shared::cta.bulk_group [%0, {%2, %3}], [%1];\n}" :: "l"((uint64_t)tm), "r"(src), "r"(col), "r"(0) : "memory");
}
__device__ __forceinline__ void w_sent(unsigned* p, uint32_t src) {
    asm volatile(ELECT "cp.reduce.async.bulk.global.shared::cta.bulk_group.add.u32 [%0], [%1], 16;\n}" :: "l"(p), "r"(src) : "memory");
}
__device__ __forceinline__ void w_inc(unsigned* p) { asm volatile(ELECT "red.relaxed.gpu.global.add.u32 [%0], 1;\n}" :: "l"(p) : "memory"); }
__device__ __forceinline__ void w_hint(unsigned* p, uint32_t all) {
    #pragma unroll 1
    for (int i = 0; i < 4096; i++) {
        uint32_t v; asm volatile("ld.relaxed.gpu.global.u32 %0, [%1];" : "=r"(v) : "l"(p) : "memory");
        if (__all_sync(~0u, (int)(v - all) >= 0)) break;
    }
}

__device__ __forceinline__ void finish(uint4& a, const uint4& xu, const uint4& xv) {
    asm("{\n.reg .b32 z;\nfma.rn.relu.bf16x2 z, %0, %3, %1;\nadd.rn.bf16x2 %0, z, %2;\n}" : "+r"(a.x) : "r"(xu.x), "r"(xv.x), "r"(0x3F803F80u));
    asm("{\n.reg .b32 z;\nfma.rn.relu.bf16x2 z, %0, %3, %1;\nadd.rn.bf16x2 %0, z, %2;\n}" : "+r"(a.y) : "r"(xu.y), "r"(xv.y), "r"(0x3F803F80u));
    asm("{\n.reg .b32 z;\nfma.rn.relu.bf16x2 z, %0, %3, %1;\nadd.rn.bf16x2 %0, z, %2;\n}" : "+r"(a.z) : "r"(xu.z), "r"(xv.z), "r"(0x3F803F80u));
    asm("{\n.reg .b32 z;\nfma.rn.relu.bf16x2 z, %0, %3, %1;\nadd.rn.bf16x2 %0, z, %2;\n}" : "+r"(a.w) : "r"(xu.w), "r"(xv.w), "r"(0x3F803F80u));
}

constexpr float EPS2 = 2e-6f;
constexpr float TAU = 2.5e-5f;

constexpr uint32_t TAU_BITS = 0x3A103000u;
template<int NP>
__device__ __forceinline__ void epi_fast(const float* g, const float* h, float m2,
                                         float& n0, float& d0, float& n1, float& d1, float& dmin)
{
    constexpr int JC = NP >= 6 ? NP - 1 - 2 : NP >= 4 ? NP - 2 : NP - 1;
    constexpr int JT = NP < 3 ? -1 : JC < NP - 1 ? JC : NP - 2;
    #pragma unroll
    for (int j = 0; j < NP; j++) {
        float t0 = tanhf_a(g[4*j+0]), t1 = tanhf_a(g[4*j+1]), t2 = tanhf_a(g[4*j+2]), t3 = tanhf_a(g[4*j+3]);
        auto add_d = [&]() {
            if (j == 0) { d0 = t0 + (2.f * (JT + 1) + EPS2); d1 = t2 + (2.f * (JT + 1) + EPS2); } else { d0 += t0; d1 += t2; }
            d0 += t1; d1 += t3;
        };
        if (j <= JT) add_d();
        if (UFORM && j <= JT) {
            const float u0 = fmaf(t0, h[4*j], h[4*j]), u1 = fmaf(t1, h[4*j+1], h[4*j+1]), u2 = fmaf(t2, h[4*j+2], h[4*j+2]), u3 = fmaf(t3, h[4*j+3], h[4*j+3]);
            if (j == 0) { n0 = u0 + u1; n1 = u2 + u3; } else { n0 += u0; n1 += u2; n0 += u1; n1 += u3; }
            if (j == JC) dmin = fminf(d0, d1);
            continue;
        }
        if (j == NP - 1) { t0 += 1.f; t1 = fmaf(t1, m2, m2); t2 += 1.f; t3 = fmaf(t3, m2, m2); }
        else { t0 += 1.f; t1 += 1.f; t2 += 1.f; t3 += 1.f; }
        if (j > JT) add_d();
        if (j == 0) { n0 = t0 * h[0]; n1 = t2 * h[2]; } else { n0 = fmaf(t0, h[4*j], n0); n1 = fmaf(t2, h[4*j+2], n1); }
        n0 = fmaf(t1, h[4*j+1], n0); n1 = fmaf(t3, h[4*j+3], n1);
        if (j == JC) dmin = fminf(d0, d1);
    }
}

__device__ __noinline__ float4 epi_exact(const float4* gh, int np, int dv, uint32_t sa, int one)
{
    float n0 = 0.f, d0 = 0.f, n1 = 0.f, d1 = 0.f;
    int j = 0, je = np;
    if (sa) {
        __syncwarp();
        dv = __shfl_sync(~0u, dv, one); j = min(threadIdx.x & 15, np); je = j + 1;
    }
    #pragma unroll 1
    for (; j < je; j++) {
        const float4 g = gh[j], h = gh[NPMAX + j];
        const bool ma = 2 * j < dv, mb = 2 * j + 1 < dv;
        const float e0 = 2.f * rcpf(1.f + ex2f(-2.f * LOG2E * g.x)), e1 = 2.f * rcpf(1.f + ex2f(-2.f * LOG2E * g.y));
        const float e2 = 2.f * rcpf(1.f + ex2f(-2.f * LOG2E * g.z)), e3 = 2.f * rcpf(1.f + ex2f(-2.f * LOG2E * g.w));
        if (ma) { d0 += e0; n0 = fmaf(e0, h.x, n0); d1 += e2; n1 = fmaf(e2, h.z, n1); }
        if (mb) { d0 += e1; n0 = fmaf(e1, h.y, n0); d1 += e3; n1 = fmaf(e3, h.w, n1); }
    }
    if (sa) {
        #pragma unroll
        for (int o = 1; o < 16; o <<= 1) {
            n0 += __shfl_xor_sync(~0u, n0, o); d0 += __shfl_xor_sync(~0u, d0, o);
            n1 += __shfl_xor_sync(~0u, n1, o); d1 += __shfl_xor_sync(~0u, d1, o);
        }
        sts32(sa, 0);
    }
    return make_float4(n0, d0 + EPS2, n1, d1 + EPS2);
}
template<int NP>
__device__ __forceinline__ void epi_dump(const float* g, const float* h, float4* gh, bool on) {
    #pragma unroll
    for (int i = 0; i < 2 * NP; i++) {
        const float* v = i < NP ? g + 4 * i : h + 4 * (i - NP);
        asm volatile("{\n.reg .pred p;\nsetp.ne.u32 p, %5, 0;\n@p st.v4.f32 [%0], {%1,%2,%3,%4};\n}"
                     :: "l"(gh + (i < NP ? i : NPMAX + i - NP)), "f"(v[0]), "f"(v[1]), "f"(v[2]), "f"(v[3]), "r"((uint32_t)on) : "memory");
    }
}

__device__ __noinline__ void slow_bin(const __nv_bfloat16* x, const __nv_bfloat16* ea, const int* src, const int* dst,
                                      const __nv_bfloat16* wa, const __nv_bfloat16* wb, const __nv_bfloat16* wc,
                                      const __nv_bfloat16* wu, const __nv_bfloat16* wv, __nv_bfloat16* out,
                                      int E, int node0, int nn, int nthr)
{
    const int tid = threadIdx.x, lane = tid & 31;
    for (int i = tid; i < nn * 128; i += nthr) g_slow[(size_t)node0 * 128 + i] = 0.f;
    asm volatile("bar.sync 1, %0;" :: "r"(nthr) : "memory");
    for (int e0 = (tid >> 5) * 32; e0 < E; e0 += nthr) {
        int d = (e0 + lane < E) ? dst[e0 + lane] - node0 : -1;
        unsigned m = __ballot_sync(~0u, d >= 0 && d < nn);
        while (m) {
            int l = __ffs(m) - 1; m &= m - 1;
            int e = e0 + l, n = node0 + __shfl_sync(~0u, d, l), s = src[e];
            float g0 = 0, g1 = 0, h0 = 0, h1 = 0;
            for (int k = 0; k < 64; k++) {
                float xs = __bfloat162float(x[(size_t)s * 64 + k]), xd = __bfloat162float(x[(size_t)n * 64 + k]);
                uint32_t b2 = *(const uint32_t*)(wb + k * 64 + 2 * lane), v2 = *(const uint32_t*)(wv + k * 64 + 2 * lane);
                uint32_t a2 = *(const uint32_t*)(wa + k * 64 + 2 * lane);
                g0 = fmaf(xs, bf_lo(b2), fmaf(xd, bf_lo(a2), g0)); g1 = fmaf(xs, bf_hi(b2), fmaf(xd, bf_hi(a2), g1));
                h0 = fmaf(xs, bf_lo(v2), h0); h1 = fmaf(xs, bf_hi(v2), h1);
            }
            for (int k = 0; k < 16; k++) {
                float ev = __bfloat162float(ea[(size_t)e * 16 + k]);
                uint32_t c2 = *(const uint32_t*)(wc + k * 64 + 2 * lane);
                g0 = fmaf(ev, bf_lo(c2), g0); g1 = fmaf(ev, bf_hi(c2), g1);
            }
            float s0 = rcpf(1.f + ex2f(-LOG2E * g0)), s1 = rcpf(1.f + ex2f(-LOG2E * g1));
            float* acc = g_slow + (size_t)n * 128 + 4 * lane;
            atomicAdd(acc + 0, s0 * h0); atomicAdd(acc + 1, s0);
            atomicAdd(acc + 2, s1 * h1); atomicAdd(acc + 3, s1);
        }
    }
    __threadfence();
    asm volatile("bar.sync 1, %0;" :: "r"(nthr) : "memory");
    for (int i = tid; i < nn * 32; i += nthr) {
        int n = node0 + (i >> 5), cp = i & 31;
        float4 a = __ldcg((const float4*)(g_slow + (size_t)n * 128 + 4 * cp));
        float u0 = 0, u1 = 0;
        for (int k = 0; k < 64; k++) {
            float xd = __bfloat162float(x[(size_t)n * 64 + k]);
            uint32_t w2 = *(const uint32_t*)(wu + k * 64 + 2 * cp);
            u0 = fmaf(xd, bf_lo(w2), u0); u1 = fmaf(xd, bf_hi(w2), u1);
        }
        uint32_t xv = *(const uint32_t*)(x + (size_t)n * 64 + 2 * cp);
        float z0 = u0 + a.x / (a.y + 1e-6f), z1 = u1 + a.z / (a.w + 1e-6f);
        *(uint32_t*)(out + (size_t)n * 64 + 2 * cp) = pack_bf16(bf_lo(xv) + fmaxf(z0, 0.f), bf_hi(xv) + fmaxf(z1, 0.f));
    }
}

__global__ void __launch_bounds__(256) slow_kernel(const __nv_bfloat16* x, const __nv_bfloat16* ea, const int* src, const int* dst,
        const __nv_bfloat16* wa, const __nv_bfloat16* wb, const __nv_bfloat16* wc, const __nv_bfloat16* wu, const __nv_bfloat16* wv,
        __nv_bfloat16* out, int N, int E, int npb)
{
    int node0 = blockIdx.x * npb;
    slow_bin(x, ea, src, dst, wa, wb, wc, wu, wv, out, E, node0, max(0, min(npb, N - node0)), 256);
}

constexpr int XS_BYTES = NPMAX * 1024;
constexpr int ES_BYTES = NPMAX * 256;
constexpr int SM_XS = 0;
constexpr int SM_XU = SM_XS + 3 * NSTAGE * XS_BYTES;
constexpr int SM_TAB = SM_XU + NPB_MAX * 128;
constexpr int SM_ES = SM_TAB + NPB_MAX * 128;
constexpr int SM_WC = SM_ES + 3 * NSTAGE * ES_BYTES;
constexpr int SM_OH = SM_WC + 2048;
constexpr int SM_EID = SM_OH + 128;
constexpr int SM_SRC = SM_EID + SLOT_CAP * 4;
constexpr int SM_TINFO = SM_SRC + SLOT_CAP * 2;
constexpr int SM_MISC = SM_TINFO + TILE_CAP * 32;
constexpr int SM_CLAIM = SM_MISC + 32 * 4;
constexpr int STG = 272;
constexpr int SM_BARS = SM_CLAIM + 32 * 4;
constexpr int SM_ABAR = SM_BARS + 6 * STG;
constexpr int SM_GBAR = SM_ABAR + 16 * 8;
constexpr int SMEM_BYTES = SM_GBAR + 97 * 8;
constexpr int SM_P2 = 0, SM_P1 = P2B + 256;
constexpr int SM_DEG = SM_P1 + P1B + 256;
constexpr int SM_CLS = SM_DEG + 512 * 4;
constexpr int SM_HIST = SM_CLS + NCLS * 4;
constexpr int SM_XLIST = SM_HIST + NB_MAX * 4;
constexpr int SM_SORT = SM_XLIST + 8;
constexpr int SM_SDEG = SM_SORT + NPB_MAX * 4;
constexpr int SM_PAIR = SM_SDEG + NPB_MAX * 2;
constexpr int SM_ENT = SM_ES + 1024;
constexpr int SM_H1 = SM_P1 + HB, SM_H2 = SM_P1;
constexpr int SM_IDX = SM_EID;
constexpr int SM_WR = SM_TAB;
static_assert(TILE_CAP <= 128 && TR >= 2 && SM_ES % 256 == 0 && NSTAGE == 2 && SM_BARS % 16 == 0 && SM_TINFO % 16 == 0 && SM_EID % 128 == 0 && SM_TAB % 1024 == 0 && SM_XU % 1024 == 0 && SM_TINFO % 8 == 0 && SM_OH % 16 == 0 && SM_XLIST % 8 == 0 && SM_PAIR % 8 == 0, "align");
static_assert(SM_P1 % 128 == 0 && P1B + HB <= SM_SRC - SM_EID && 2 * HB <= P1B && SM_H1 + 5 * 128 * 16 <= SM_XU && NB_MAX * (CE / 4) <= 6 * 384 && NB_MAX * 4 <= 5 * 128 && NB_MIN * 4 >= 3 * 128 && SM_PAIR + 128 * 8 <= SM_XU && CH_MAX * 4 <= SM_SRC - SM_EID && SM_DEG >= 3 << 14, "alias");
static_assert(SMEM_BYTES <= 232448, "smem");
constexpr uint32_t C_BRK = 16  , C_CONT = 32, C_MORE = 64;
constexpr uint32_t ONE_F = 0x3F800000u;
constexpr int NONE = NPB_MAX - 1;
__host__ __device__ constexpr uint32_t tab_at(uint32_t n) { return (n >> 2) * 512 + (n & 3) * 32 + ((n >> 2) & 1) * 16; }

__device__ __forceinline__ uint32_t unpad(uint32_t w1, int np, float ga, float gb, float& d0, float& d1, int& dv) {
    const int pad = (w1 >> 8) & 31;
    dv = 2 * np - 1 - pad + (w1 >= ONE_F);
    float t0 = TAU * 2 * np, t1 = t0;
    if (pad) {
        t0 = fmaxf(t0, d0 * (1.f / 1024)); t1 = fmaxf(t1, d1 * (1.f / 1024));
        asm volatile("tanh.approx.f32 %0, %0;\ntanh.approx.f32 %1, %1;" : "+f"(ga), "+f"(gb));
        d0 -= pad * (1.f + ga); d1 -= pad * (1.f + gb);
    }
    if (dv == 0) { d0 = d1 = EPS2; t0 = t1 = 0.f; }
    return __ballot_sync(~0u, d0 < t0 || d1 < t1);
}
__device__ __forceinline__ void place(uint32_t sbase, uint32_t slot, uint32_t v, uint32_t eb) {
    asm volatile("{\n.reg .pred p;\nsetp.lt.u32 p, %0, %5;\n@p st.shared.u32 [%1], %2;\n@p st.shared.u16 [%3], %4;\n}"
                 :: "r"(slot), "r"(sbase + SM_EID + slot * 4), "r"(eb + (v >> 19)), "r"(sbase + SM_SRC + slot * 2), "r"(v), "n"(SLOT_CAP) : "memory");
}
__device__ __forceinline__ uint64_t desc_sw128(uint32_t a) {
    return (uint64_t)((a & 0x3FFFF) >> 4) | ((uint64_t)1 << 16) | ((uint64_t)64 << 32) | ((uint64_t)1 << 62);
}

template<bool LO32>
__global__ void __launch_bounds__(THREADS, 1)
gcn_kernel(const int* __restrict__ dst, unsigned* gbar, char* gs, const int* __restrict__ src, int E, int ch, int N, int npb, uint32_t magic,
           const __nv_bfloat16* __restrict__ x, const __nv_bfloat16* __restrict__ ea,
           const __nv_bfloat16* __restrict__ wa, const __nv_bfloat16* __restrict__ wb, const __nv_bfloat16* __restrict__ wc,
           const __nv_bfloat16* __restrict__ wu, const __nv_bfloat16* __restrict__ wv,
           __nv_bfloat16* out, int4 wrow, const __grid_constant__ CUtensorMap tm1, const __grid_constant__ CUtensorMap tm2,
           const __grid_constant__ CUtensorMap tmw, const __grid_constant__ CUtensorMap tmx)
{
    extern __shared__ __align__(1024) uint8_t smem[];
    int* cls = (int*)(smem + SM_CLS);
    int* misc = (int*)(smem + SM_MISC);
    WG0(); WS(0); CG(0);
    const uint32_t sbase = smem_u32(smem);
    const int tid = threadIdx.x, lane = tid & 31;
    const int b = blockIdx.x, nb = gridDim.x;
    const int cnt = max(0, min(ch, E - b * ch));
    const int node0 = b * npb;
    uint32_t tag = 0, cstart; asm volatile("mov.u32 %0, %%clock;" : "=r"(cstart));
    if (tid >= 384 && elect_one()) {
        const int v = (tid >> 5) & 3;
        const uint32_t a1 = sbase + SM_ABAR + (v == 0 ? 80 : v == 1 ? 120 : 32);
        mbar_init(sbase + SM_ABAR + v * 8, 1); mbar_init(a1, 1);
        mbar_expect(sbase + SM_ABAR + v * 8, v < 3 ? min(max(cnt * 4 - v * 8192, 0), 8192) : 4 * 8192 + 2048);
        if (v < 2) mbar_expect(a1, v == 0 ? nb * (CE * 2) : nb * 64);
        asm volatile("fence.mbarrier_init.release.cluster;" ::: "memory");
    }
    asm volatile("{\n.reg .pred q;\nsetp.lt.u32 q, %2, 384;\n@q ld.relaxed.gpu.global.u32 %0, [%1];\n}" : "+r"(tag) : "l"(gbar), "r"(tid));
    #pragma unroll
    for (int v = 0; v < EPT / 4; v++) {
        const uint32_t off = v * (THREADS * 4) + tid * 4;
        if (PD && v) { uint32_t c0, c1; asm volatile("mov.u32 %0, %%clock;" : "=r"(c0)); do { asm volatile("mov.u32 %0, %%clock;" : "=r"(c1)); } while (c1 - c0 < PD); }
        asm volatile("{\n.reg .pred q;\nsetp.lt.u32 q, %2, %3;\n@q cp.async.cg.shared.global [%0], [%1], 16;\n}"
                     :: "r"(sbase + SM_IDX + off * 4), "l"(dst + b * ch + off), "r"(off), "r"(cnt) : "memory");
        cp_commit();
    }
    const int warp = (int)__reduce_max_sync(~0u, (unsigned)tid >> 5);
    const int wg = warp >> 2, w = warp & 3;
    const int q = lane >> 2, t = lane & 3;
    const int nn = max(0, min(npb, N - node0));
    if (sbase & 1023) __trap();

    sts32(sbase + SM_DEG + tid * 4, tid < NPB_MAX ? 0 : 0x80000000u);
    if (tid < NCLS + NB_MAX) cls[tid] = tid < NCLS ? 0 : ((tid - NCLS) * 20) & 63;
    else if (warp == 8) sts32(sbase + SM_OH + lane * 4, t != (q >> 1) ? 0u : 0x00003F00u);
    else if (warp == 11) misc[lane] = lane == 5 ? TILE_CAP - TILE_X : lane == 8 || lane == 3;
    if (warp == 14) sts32(sbase + SM_TINFO + 96 * 32 + lane * 4, lane & 1 ? tab_at(NONE) : 0);
    if (warp == 15) sts32(sbase + SM_CLAIM + lane * 4, lane == 0 ? 3 * 32 : 0x40000000);
    if (tid == 0) sts32(sbase + SM_XLIST, tag);
    tag = (tag & 1) | 2;
    if (wg < 3) {
        const uint32_t d0 = ((NPB_MAX + ((2 * lane) & 15) + 16 * (b & 1)) * 4 | (tag << 14)) * 0x10001u, d1 = d0 + 0x40004u, d2 = tag << 16;
        #pragma unroll 1
        for (int i = tid; i < (P1B + 256) / 16; i += 384) {
            sts128(sbase + SM_P1 + i * 16, make_uint4(d0, d0, d1, d1));
            sts128(sbase + SM_P2 + i * 16, make_uint4(d2, d2, d2, d2)); sts128(sbase + SM_P2 + P1B + i * 16, make_uint4(d2, d2, d2, d2));
        }
    }
    WS(1);
    __syncthreads();
    if (wg == 3) tag = lds32(sbase + SM_P2) >> 16;
    uint32_t all = 0;
    if (wg == 3) all = (lds32(sbase + SM_XLIST) + 1) * nb;
    if (tid == 128) {
        asm volatile("prefetch.tensormap [%0];" :: "l"((uint64_t)&tmw) : "memory");
        asm volatile("prefetch.tensormap [%0];" :: "l"((uint64_t)&tm1) : "memory");
        asm volatile("prefetch.tensormap [%0];" :: "l"((uint64_t)&tm2) : "memory");
        asm volatile("prefetch.tensormap [%0];" :: "l"((uint64_t)&tmx) : "memory");
    }
    const uint32_t su = __reduce_or_sync(~0u, sbase);
    if (WPF && warp == 9 && b < 5) asm volatile(ELECT "cp.async.bulk.prefetch.L2.global [%0], %1;\n}" :: "l"(b == 0 ? wa : b == 1 ? wb : b == 2 ? wu : b == 3 ? wv : wc), "r"(b < 4 ? 8192 : 2048) : "memory");
    uint32_t ent[EPT];
    #pragma unroll
    for (int v = 0; v < EPT / 4; v++) {
        if (v == 0) cp_wait<2>(); else if (v == 1) cp_wait<1>(); else cp_wait<0>();
        if (v == SRCV && wg == 2 && w < 3) {
            const int n = min(cnt * 4 - w * 8192, 8192);
            if (n > 0) w_ld(su + SM_XU + w * 8192, src + b * ch + w * 2048, n, su + SM_ABAR + w * 8);
        }
        if (v == WV) {
            if (warp == 11) w_ld(su + SM_WR + 24576, wc, 2048, su + SM_ABAR + 24);
            else if (wg == 3) w_box_ld(su + SM_WR + (w == 3 ? 5 : w) * 8192, &tmw, w == 0 ? wrow.x : w == 1 ? wrow.y : w == 2 ? wrow.z : wrow.w, su + SM_ABAR + 24);
        }
        const uint32_t off = v * (THREADS * 4) + tid * 4;
        if (off < (uint32_t)cnt) {
            const uint4 u = lds128(sbase + SM_IDX + off * 4);
            uint32_t dv[4] = {u.x, u.y, u.z, u.w}, ps[4], ck[4];
            uint32_t* en = ent + 4 * v;
            #pragma unroll
            for (int k = 0; k < 4; k++) {
                dv[k] = min(dv[k], (uint32_t)(nb * npb - 1));
                ps[k] = __umulhi(dv[k], magic);
                asm volatile("atom.shared.add.u32 %0, [%1], 0x10001;" : "=r"(ck[k]) : "r"(sbase + SM_HIST + ps[k] * 4) : "memory");
            }
            #pragma unroll
            for (int k = 0; k < 4; k++) {
                dv[k] = (dv[k] - ps[k] * npb) * 4 + (tag << 14);
                en[k] = (ck[k] & 63) + ps[k] * CE;
            }
            if (__builtin_expect(max(max(ck[0], ck[1]), max(ck[2], ck[3])) >= CE << 16, 0)) {
                #pragma unroll
                for (int k = 0; k < 4; k++) {
                    if (ck[k] >= CE << 16) {
                        uint32_t j; asm volatile("atom.shared.inc.u32 %0, [%1], 0x7fffffff;" : "=r"(j) : "r"(sbase + SM_MISC + 8) : "memory");
                        if (j >= 15) { sts32(sbase + SM_P1 + P1B + 60, 0xFE0000u | (tag << 14)); j = min(j + 1, 63u); }
                        sts32(sbase + SM_P1 + P1B + j * 4, dv[k] | ((j < 63 ? ps[k] : 255u) << 16));
                        en[k] = NB_MAX * CE + j;
                    }
                }
            }
            #pragma unroll
            for (int k = 0; k < 4; k++)
                asm volatile("{\n.reg .pred p;\nsetp.lt.u32 p, %2, %3;\n@p st.shared.u16 [%0], %1;\n}" :: "r"(sbase + SM_P1 + en[k] * 2), "r"(dv[k]), "r"(en[k]), "n"(NB_MAX * CE) : "memory");
        }
    }
    if (warp == 15) {
        #pragma unroll
        for (int v = 0; v < EPT / 4; v++) sts128(sbase + SM_ENT + v * 512 + lane * 16, make_uint4(ent[4*v], ent[4*v+1], ent[4*v+2], ent[4*v+3]));
    }
    asm volatile("fence.proxy.async.shared::cta;" ::: "memory");
    WS(5);
    __syncthreads();
    auto delay = [&](uint32_t d) { uint32_t c0, c1; asm volatile("mov.u32 %0, %%clock;" : "=r"(c0)); do { asm volatile("mov.u32 %0, %%clock;" : "=r"(c1)); } while (__all_sync(~0u, c1 - c0 < d)); };
    if (warp == 15) {
        if (HORD != 2) w_inc(gbar + HI1);
        w_st(gs + G_H1 + b * 64, su + SM_P1 + P1B, 64);
        w_box_st(&tm1, b * (CE / 2), su + SM_P1);
        w_st(gs + G_L + b * 512, su + SM_P1 + P1B, 256);
        asm volatile("cp.async.bulk.commit_group;" ::: "memory");
        if (WV == 3) {
            w_box_ld(su + SM_WR, &tmw, wrow.x, su + SM_ABAR + 24); w_box_ld(su + SM_WR + 8192, &tmw, wrow.y, su + SM_ABAR + 24);
            w_box_ld(su + SM_WR + 16384, &tmw, wrow.z, su + SM_ABAR + 24); w_ld(su + SM_WR + 24576, wc, 2048, su + SM_ABAR + 24);
            w_box_ld(su + SM_WR + 40960, &tmw, wrow.w, su + SM_ABAR + 24);
        }
    } else {
        mbar_wait_c(su + SM_ABAR, 0);
        auto put = [&](uint32_t off, const uint32_t* uu) {
            if (off < (uint32_t)cnt) {
                const uint4 sv = lds128(sbase + SM_XU + off * 4);
                const uint32_t ss[4] = {sv.x, sv.y, sv.z, sv.w};
                #pragma unroll
                for (int k = 0; k < 4; k++) sts32(sbase + SM_P2 + uu[k] * 4, (ss[k] & 0xFFFF) | (((off + k) << 19) + (tag << 16)));
            }
        };
        #pragma unroll
        for (int v = 0; v < EPT / 4; v++) { if (v) mbar_wait_c(su + SM_ABAR + v * 8, 0); put(v * (THREADS * 4) + tid * 4, ent + 4 * v); }
        if (wg == 3) {
            const uint4 e = lds128(sbase + SM_ENT + w * 512 + lane * 16);
            const uint32_t uu[4] = {e.x, e.y, e.z, e.w};
            put(w * (THREADS * 4) + (480 + lane) * 4, uu);
        }
        asm volatile("fence.proxy.async.shared::cta;" ::: "memory");
        WS(7);
        __syncwarp();
        asm volatile("bar.arrive 12, 512;" ::: "memory");
    }
    WS(8);

    const int ngroups = (nn + 3) >> 2;
    if (warp < 12) {
        asm volatile("setmaxnreg.inc.sync.aligned.u32 152;");
        const uint32_t ab = su + SM_ABAR;
        float4 lgh[2 * NPMAX];
        uint32_t wf[40], wn[16];
        const uint32_t mo = sbase + (8 * (lane >> 4) + (lane & 7)) * 128 + (((2 * w + ((lane >> 3) & 1)) ^ (lane & 7)) << 4);
        const uint32_t wca = __shfl_sync(~0u, sbase + SM_WC + (16 * w + q) * 32 + t * 4 + ((q >> 2) << 4), lane), l16 = __shfl_sync(~0u, (lane & 15) * 16, lane);
        WS(1);
        mbar_wait(ab + 24, 0);
        WS(5);
        {
            #pragma unroll
            for (int ks = 0; ks < 4; ks++) { ldsm4t(wf + 4 * ks, mo + SM_WR + ks * 2048); ldsm4t(wf + 20 + 4 * ks, mo + SM_WR + 8192 + ks * 2048); ldsm4t(wn + 4 * ks, mo + SM_WR + 16384 + ks * 2048); }
            auto half = [](uint32_t& v) { asm("mul.rn.bf16x2 %0, %0, %1;" : "+r"(v) : "r"(0x3F003F00u)); };
            uint32_t z = 0;
            #pragma unroll
            for (int i = 0; i < 16; i++) { half(wf[i]); z ^= wf[i]; }
            sts32(sbase + SM_ES + lane * 4, z);
            if (wg == 2) {
                uint32_t f[4];
                ldsm4t(f, (mo ^ ((lane & 7) << 4)) + SM_WR + 24576);
                half(f[0]); half(f[1]); half(f[2]); half(f[3]);
                sts32(wca, f[0]); sts32(wca + 256, f[1]); sts32(wca ^ 16, f[2]); sts32((wca ^ 16) + 256, f[3]);
                asm volatile("fence.proxy.async.shared::cta;" ::: "memory");
            }
        }
        const uint64_t wcd = __reduce_or_sync(~0u, (((sbase + SM_WC) & 0x3FFFF) >> 4) | (8u << 16)) | EDHI;
        const uint32_t bar0 = __reduce_or_sync(~0u, sbase + SM_BARS + wg * 2 * STG);
        const uint32_t xd0 = __reduce_or_sync(~0u, (((sbase + SM_XS + wg * NSTAGE * XS_BYTES) & 0x3FFFF) >> 4) | (1u << 16));
        const uint32_t ed0 = __reduce_or_sync(~0u, (((sbase + SM_ES + wg * NSTAGE * ES_BYTES) & 0x3FFFF) >> 4) | (8u << 16));
        const uint64_t ohd = __reduce_or_sync(~0u, ((sbase + SM_OH) & 0x3FFFF) >> 4);
        const uint32_t tabx = __reduce_or_sync(~0u, sbase + SM_TAB + w * 128);
        const uint32_t bars = __reduce_or_sync(~0u, 2 * bar0 + STG), xds = __reduce_or_sync(~0u, 2 * xd0 + XS_BYTES / 16), eds = __reduce_or_sync(~0u, 2 * ed0 + ES_BYTES / 16);
        const uint32_t xuo = __reduce_or_sync(~0u, sbase + SM_XU + wg * 16384);
        { const uint2 z = lds64(sbase + SM_OH + 8); wf[38] = z.x; wf[39] = z.y; }
        WS(9);
        constexpr int NU = 6;
        const uint32_t dm = ((NPB_MAX + lane) * 4 | (tag << 14)) * 0x10001u;
        uint2 r1[NU];
        mbar_wait(ab + 80, 0);
        WS(2);
        #pragma unroll
        for (int i = 0; i < NU; i++) {
            r1[i] = make_uint2(dm, dm);
            if (i < 5 && NB_MIN * 16 >= 384 * (i + 1) || tid + 384 * i < nb * 16) r1[i] = lds64(sbase + SM_IDX + (tid + 384 * i) * 8);
        }
        uint32_t spins = 0;
        while (true) {
            uint32_t bad = 0;
            #pragma unroll
            for (int i = 0; i < NU; i++) bad |= r1[i].y ^ dm;
            if (__builtin_expect(!__any_sync(~0u, bad & 0xC000), 1)) break;
            #pragma unroll
            for (int i = 0; i < NU; i++) ld_unit(r1[i], gs + b * (P1B + P2B) + (tid + 384 * i) * 8, (r1[i].y ^ dm) & 0xC000);
            if (++spins > (1u << 22)) break;
        }
        WS(3);
        const uint32_t db = sbase + SM_DEG - (tag << 14);
        int rk[NU][4];
        #pragma unroll
        for (int i = 0; i < NU; i++) {
            rk[i][0] = r1[i].x & 0xFFFF; rk[i][1] = r1[i].x >> 16; rk[i][2] = r1[i].y & 0xFFFF; rk[i][3] = r1[i].y >> 16;
            #pragma unroll
            for (int k = 0; k < 4; k++) asm volatile("red.shared.add.u32 [%0], 1;" :: "r"(db + min((uint32_t)rk[i][k], NPB_MAX * 4 + (tag << 14))) : "memory");
        }
        WS(10);
        asm volatile("bar.sync 11, 512;" ::: "memory");
        int mycls = 0, mycr = 0, dg = lds32(sbase + SM_DEG + tid * 4);
        if (tid < nn) {
            mycls = NCLS - 1 - (dg <= 40 ? dg : min(41 + ((dg - 41) >> 3), NCLS - 1)); mycr = atomicAdd(&cls[mycls], 1);
        }
        int s0 = 0;
        if (__builtin_expect(dg > 40, 0)) s0 = max(SLOT_CAP - ((dg + 1) & ~1) - atomicAdd(&misc[6], (dg + 1) & ~1), 0);
        asm volatile("bar.sync 1, 384;" ::: "memory");
        WS(12);
        {
            const uint2 c = lds64(sbase + SM_CLS + lane * 8);
            const int v0 = c.x * (lane > 11 ? ((64 - 2 * lane) << 16) + 1 : 1), v1 = c.y * (lane >= 11 ? ((62 - 2 * lane) << 16) + 1 : 1);
            int inc = v0 + v1;
            #pragma unroll
            for (int o = 1; o < 32; o <<= 1) { int y = __shfl_up_sync(~0u, inc, o); if (lane >= o) inc += y; }
            const int e0 = __shfl_sync(~0u, inc - v0 - v1, mycls >> 1), e1 = __shfl_sync(~0u, inc - v1, mycls >> 1);
            const int e = (mycls & 1) ? e1 : e0;
            if (tid < nn) {
                if (dg <= 40) s0 = min((e >> 16) + mycr * ((dg + 1) & ~1), SLOT_CAP - 40);
                sts32(sbase + SM_DEG + tid * 4, s0);
            }
            const uint32_t pos = tid < nn ? (e & 0xFFFF) + mycr : tid;
            sts32(sbase + SM_SORT + pos * 4, tid < nn ? (uint32_t)tid | ((uint32_t)s0 << 16) : NONE);
            asm volatile("st.shared.u16 [%0], %1;" :: "r"(sbase + SM_SDEG + pos * 2), "r"(min(dg, 65535)) : "memory");
            if (tid == 383) { misc[4] = (nn - c.y + 3) >> 2; if ((inc >> 16) + misc[6] > SLOT_CAP - 40) misc[1] = 1; }
        }
        asm volatile("bar.sync 1, 384;" ::: "memory");
        WS(13);
        const uint32_t sv = lds32(sbase + SM_SORT + tid * 4);
        const uint2 d4 = lds64(sbase + SM_SDEG + (tid >> 2) * 8);
        const uint32_t slow = lds32(sbase + SM_MISC + 4);
        #pragma unroll
        for (int i = 0; i < NU; i++) {
            #pragma unroll
            for (int k = 0; k < 4; k++) rk[i][k] = atoms_inc(db + rk[i][k]);
        }
        if (__reduce_or_sync(~0u, slow) == 0) {
            const uint32_t nd = sv & 0xFFFF;
            const int g = tid >> 2;
            dg = ((t & 2 ? d4.y : d4.x) >> (16 * (t & 1))) & 0xFFFF;
            const uint32_t hi2 = __vmaxu2(d4.x, d4.y), lo2 = __vminu2(d4.x, d4.y);
            const int mx = max(hi2 >> 16, hi2 & 0xFFFF), mn = min(lo2 >> 16, lo2 & 0xFFFF);
            int left = (mx + 1) >> 1;
            int tl = g, nx = ngroups + 4 + g, nt = left > NPMAX ? 2 : 1;
            const bool odd = left > 2 * NPMAX || (nt == 2 && nx >= TILE_CAP - TILE_X);
            if (__builtin_expect(__any_sync(~0u, odd), 0)) {
                if (odd) nt = (left + NPMAX - 1) / NPMAX;
                if (odd && t == 0) { asm volatile("atom.shared.add.u32 %0, [%1], %2;" : "=r"(nx) : "r"(sbase + SM_MISC + 20), "r"(nt - 1) : "memory"); if (nx + nt - 1 > TILE_CAP) misc[1] = 1; }
                nx = __shfl_sync(~0u, nx, lane & ~3);
                if (odd && nx + nt - 1 > TILE_CAP) left = 0;
            }
            const uint32_t w0 = tab_at(nd);
            if (g >= ngroups + 4) tl = ngroups;
            uint32_t cont = 0;
            int done = 0;
            bool act = true;
            do {
                int np = nt <= 2 ? (left + nt - 1) >> (nt - 1) : (left + nt - 1) / nt;
                left -= np; nt = max(nt - 1, 1);
                if (np) np = max(np, NPMIN);
                const int dv = min(max(dg - done, 0), 2 * np);
                uint32_t code = (uint32_t)np | cont | (left > 0 ? C_MORE : 0u);
                const bool gen = mn - done < 2 * np - (np == NPMIN ? 1 : 2);
                if (np == 0) code = 0;
                const uint32_t w1 = code | (dv == 2 * np ? 0x8000u : (2 * np - 1 - dv) << 8);
                if (act) *(uint2*)(smem + SM_TINFO + tl * 32 + t * 8) = make_uint2((dv ? (sv >> 16) + done : 0) | ((gen ? (np > 8 ? 15 : np > 5 ? 14 : 13) : np) << 16) | ((left > 0 ? nx : 0) << 20) | ((uint32_t)dv << 27), w0 | (np == 0 ? 0u : w1 << 16));
                tl = nx++; cont = C_CONT; done += 2 * np; act = left > 0;
            } while (__any_sync(~0u, act));
        }
        __syncwarp();
        asm volatile("bar.arrive 4, 512;" ::: "memory");
        WS(14);
        wf[16] = lds32(wca); wf[17] = lds32(wca + 256); wf[18] = lds32(wca ^ 16); wf[19] = lds32((wca ^ 16) + 256);
        #pragma unroll
        for (int pc = 0; pc < 3; pc++) {
            uint4 r2[2];
            mbar_wait(ab + pc * 8, 1);
            if (pc == 0) WS(4); if (pc == 2) WS(16);
            #pragma unroll
            for (int k = 0; k < 2; k++) {
                r2[k] = lds128(sbase + SM_P2 + (tid + 384 * (2 * pc + k)) * 16);
                if (rk[2 * pc + k][0] < 0) r2[k].w = tag << 16;
            }
            while (__builtin_expect(__any_sync(~0u, ((r2[0].w ^ (tag << 16)) | (r2[1].w ^ (tag << 16))) & 0x30000), 0)) {
                #pragma unroll
                for (int k = 0; k < 2; k++)
                    ld_unit(r2[k], gs + b * (P1B + P2B) + P1B + (tid + 384 * (2 * pc + k)) * 16, (r2[k].w ^ (tag << 16)) & 0x30000);
                if (++spins > (1u << 22)) break;
            }
            #pragma unroll
            for (int k = 0; k < 2; k++) {
                const int i = 2 * pc + k;
                const uint32_t eb = ((tid >> 4) + 24 * i) * ch;
                place(sbase, rk[i][0], r2[k].x, eb); place(sbase, rk[i][1], r2[k].y, eb); place(sbase, rk[i][2], r2[k].z, eb); place(sbase, rk[i][3], r2[k].w, eb);
            }
        }
        WGD();
        __syncwarp();
        asm volatile("bar.arrive 3, 480;" ::: "memory");
        float g[4 * NPMAX], h[4 * NPMAX];
        float4 cyr = make_float4(0.f, 0.f, 0.f, 0.f);
        WS(15); CG(1);
        mbar_wait(ab + 88 + wg * 8, 0);
        WSG(1);
        auto pack = [&](uint32_t* v, const float* u) {
            #pragma unroll
            for (int i = 0; i < 16; i++) v[i] = pack_bf16(u[2*i], u[2*i+1]);
        };
        auto rows_st = [&](uint32_t p, const uint32_t* v) {
            #pragma unroll
            for (int i = 0; i < 4; i++) stsm4t(p + i * 2048, v + 4 * i);
        };
        {
            const uint64_t d0 = desc_sw128(xuo), d1 = d0 + 512;
            const uint32_t mr = sbase + wg * 16384 + w * 128 + (tab_at(8 * (lane >> 4) + (lane & 7)) ^ ((lane & 8) << 1));
            uint32_t v[16];
            node_mma(g, wn, d0); node_mma(h, wn, d1);
            TileMMA<8>::wait_g(g);
            pack(v, g); rows_st(mr + SM_TAB, v);
            TileMMA<8>::wait_h(h);
            WSG(5);
            #pragma unroll
            for (int ks = 0; ks < 4; ks++) ldsm4t(wn + 4 * ks, mo + SM_WR + 40960 + ks * 2048);
            node_mma(g, wn, d0);
            if (wg == 2) asm volatile("bar.sync 5, 384;" ::: "memory"); else asm volatile("bar.arrive 5, 384;" ::: "memory");
            pack(v, h); rows_st(mr + SM_TAB + 8192, v);
            node_mma(h, wn, d1);
            __syncwarp();
            if (lane == 0) mbar_arrive(sbase + SM_ABAR + 112);
            WSG(7);
            TileMMA<8>::wait_g(g);
            pack(v, g);
            asm volatile("bar.sync %0, 128;" :: "r"(8 + wg) : "memory");
            rows_st(mr + SM_XU, v);
            TileMMA<8>::wait_h(h);
            WSG(11);
            pack(v, h);
            asm volatile("bar.sync %0, 128;" :: "r"(8 + wg) : "memory");
            rows_st(mr + SM_XU + 8192, v);
            __syncwarp();
            if (lane == 0) mbar_arrive(sbase + SM_ABAR + 72);
            mbar_wait(ab + 112, 0);
            __syncwarp();
            if (__builtin_expect(__reduce_or_sync(~0u, misc[1]) != 0, 0)) { slow_bin(x, ea, src, dst, wa, wb, wc, wu, wv, out, E, node0, nn, 384); asm volatile("exit;"); }
            WS(6);
        }
        uint32_t bar = bar0, xd = xd0, ed = ed0, ph = 0;
        float pn0 = 0.f, pd0 = 1.f, pn1 = 0.f, pd1 = 1.f;
        uint4 rc;
        rc.x = lds32(sbase + SM_TINFO + wg * 32 + ((lane >> 1) & 3) * 8 + 4);
        uint32_t code = __reduce_or_sync(~0u, rc.x >> 16);
        rc.x = (rc.x & 0xFFFF) ^ ((lane & 8) << 1); rc.y = tab_at(NONE);
        auto fetch_a = [&]() {
            asm volatile("ldmatrix.sync.aligned.m8n8.x2.trans.shared.b16 {%0,%1}, [%2];" : "=r"(wf[36]), "=r"(wf[37]) : "r"(tabx + rc.x) : "memory");
        };
        auto emit = [&]() {
            asm volatile("stmatrix.sync.aligned.m8n8.x1.trans.shared.b16 [%0], {%1};" :: "r"(tabx + rc.y), "r"(pack_bf16(pn0 * rcpf(pd0), pn1 * rcpf(pd1))) : "memory");
        };
        auto carry = [&]() {
            if (rc.z & C_CONT) { pn0 += cyr.x; pd0 += cyr.y; pn1 += cyr.z; pd1 += cyr.w; }
            if (rc.z & C_MORE) { cyr = make_float4(pn0, pd0 - EPS2, pn1, pd1 - EPS2); pn0 = pn1 = 0.f; rc.y = tab_at(NONE); }
        };
        auto shared_copy = [&](uint32_t bad) {
            uint32_t old = 1;
            if ((bad & (bad - 1)) == 0) asm volatile(ELECT "atom.shared.exch.b32 %0, [%1], 1;\n}" : "+r"(old) : "r"(ab + (SM_MISC + 12 - SM_ABAR)) : "memory");
            return __reduce_and_sync(~0u, old) ? 0u : ab + (SM_MISC + 12 - SM_ABAR);
        };
        fetch_a();
        while (true) {
            switch (code & 15) {
                default: goto finished;
#define TILE(P) { \
                    float dmin; \
                    do { \
                        mbar_wait_c(bar, ph); \
                        TileMMA<P>::issue(g, h, wf, xd, ed | EDHI, ohd, wcd); \
                        const uint32_t eb = bar + 8; \
                        ph ^= bar != bar0; bar = bars - bar; xd = xds - xd; ed = eds - ed; \
                          \
                        asm volatile("{\n.reg .pred p;\nsetp.eq.u32 p, %0, 77;\n@p trap;\n}" :: "r"(xds) : "memory"); \
                        emit(); rc = lds128(eb + 8 + l16); \
                        TileMMA<P>::wait_g(g); fetch_a(); TileMMA<P>::wait_h(h); \
                        mbar_arrive(eb); \
                        epi_fast<P>(g, h, __uint_as_float(rc.z), pn0, pd0, pn1, pd1, dmin); \
                    } while (!__any_sync(~0u, !(dmin >= __uint_as_float(rc.w)))); \
                    code = __reduce_or_sync(~0u, rc.w); \
                    if (__builtin_expect(__any_sync(~0u, (rc.z & 0x1F00) != 0 || dmin < TAU * 2 * P), 0)) { \
                        int dv; \
                        const uint32_t bad = unpad(rc.z, P, g[4 * P - 4], g[4 * P - 2], pd0, pd1, dv); \
                        if (bad) { \
                            FBLOG(P); \
                            const uint32_t sa = shared_copy(bad); \
                            float4* gh = sa ? (float4*)(smem + SM_XU + tab_at(NPB_MAX - 4) - 16) : lgh; \
                            const bool on = !sa || ((bad >> lane) & 1); \
                            epi_dump<P>(g, h, gh, on); \
                            const float4 r = epi_exact(gh, P, dv, sa, __ffs(bad) - 1); \
                            if (on) { pn0 = r.x; pd0 = r.y; pn1 = r.z; pd1 = r.w; } \
                        } \
                    } \
                    if (code & C_BRK) { carry(); if (P != 11 && (code & 15) == P) goto L##P; } \
                    if (P == 11) {         \
                        wf[16] = lds32(wca); wf[17] = lds32(wca + 256); wf[18] = lds32(wca ^ 16); wf[19] = lds32((wca ^ 16) + 256); \
                    } }
#define CASE(P, UP, DN) case P: L##P: TILE(P) \
                    if (P > NPMIN && (code & 15) == P - 1) goto L##DN; \
                    if ((code & 15) == UP) goto L##UP; \
                    break;
                CASE(11, 11, 10) CASE(10, 11, 9) CASE(9, 10, 8) CASE(8, 9, 7) CASE(7, 8, 6) CASE(6, 7, 5) CASE(5, 6, 4) CASE(4, 5, 4)
#undef CASE
#undef TILE
            }
        }
finished:
        emit();
        __syncwarp();
        if (lane == 0) mbar_arrive(sbase + SM_ABAR + 48 + wg * 8);
    } else {
        asm volatile("setmaxnreg.dec.sync.aligned.u32 56;");
        auto x_ld = [&](int i0, int i1) {
            #pragma unroll
            for (int i = i0; i < i1; i++) w_box_ld(su + SM_XU + i * 8192, &tmx, node0 + i * 64, su + SM_ABAR + 88 + (i >> 1) * 8);
        };
        auto w_init = [&](uint32_t bar, int n) { asm volatile(ELECT "mbarrier.init.shared.b64 [%0], %1;\n}" :: "r"(bar), "r"(n) : "memory"); };
        if (w < 3) {
            #pragma unroll
            for (int i = 0; i < 2; i++) { w_init(su + SM_BARS + (w * 2 + i) * STG, 64); w_init(su + SM_BARS + (w * 2 + i) * STG + 8, 128); }
            w_init(su + SM_ABAR + 48 + w * 8, 4);
            w_init(su + (w == 0 ? SM_GBAR + 96 * 8 : w == 1 ? SM_ABAR + 72 : SM_ABAR + 112), w == 0 ? 32 : 12);
        } else {
            #pragma unroll
            for (int i = 0; i < 4; i++) { w_init(su + SM_ABAR + (i < 3 ? 88 + i * 8 : 40), 1); w_expect(su + SM_ABAR + (i < 3 ? 88 + i * 8 : 40), i < 3 ? 16384 : nb * 64); }
            asm volatile("fence.mbarrier_init.release.cluster;" ::: "memory");
            if (HORD == 3) { uint32_t c; do { asm volatile("mov.u32 %0, %%clock;" : "=r"(c)); } while (__all_sync(~0u, c - cstart < T1)); }
            if (!HORD || HORD == 3) w_hint(gbar + HI1, all);
            asm volatile("cp.async.bulk.wait_group.read 0;" ::: "memory");
            WS(9);
            if (HORD == 1) w_hint(gbar + HI1, all);
            if (HORD == 2) { uint32_t c; do { asm volatile("mov.u32 %0, %%clock;" : "=r"(c)); } while (__all_sync(~0u, c - cstart < T1)); }
            if (D1) delay(D1);
            WS(2);
            if (H1F) w_ld(su + SM_H1, gs + G_H1, nb * 64, su + SM_ABAR + 120);
            w_ld(su + SM_IDX, gs + b * (P1B + P2B), nb * (CE * 2), su + SM_ABAR + 80);
            if (!H1F) w_ld(su + SM_H1, gs + G_H1, nb * 64, su + SM_ABAR + 120);
        asm volatile("bar.sync 12, 512;" ::: "memory");
            if (D3) delay(D3);
            if (H2M == 1) w_inc(gbar + HI2);
            w_box_st(&tm2, P1B / 4 + b * CE, su + SM_P2);
            w_st(gs + G_H2 + b * 64, su + SM_P2 + P2B, 64);
            w_st(gs + G_L + b * 512 + 256, su + SM_P2 + P2B, 256);
            if (H2M == 0) w_sent(gbar + HI2, su + SM_MISC + 32);
            asm volatile("cp.async.bulk.commit_group;" ::: "memory");
            if (!XAFT) x_ld(0, XSPL);
        }
        const uint32_t ab = su + SM_ABAR;
        uint32_t todo = 0;
        WS(12);
        mbar_wait(ab + 120, 0);
        WS(13);
        {
            uint4 r[5];
            #pragma unroll
            for (int i = 0; i < 5; i++) r[i] = lds128(sbase + SM_H1 + (tid - 384 + 128 * i) * 16);
            #pragma unroll
            for (int i = 0; i < 5; i++) {
                const uint32_t bb = b << 16;
                const uint32_t m = min(min(min(r[i].x ^ bb, r[i].y ^ bb), min(r[i].z ^ bb, r[i].w ^ bb)), r[i].w ^ 0xFE0000u) >> 16;
                if ((m == 0) | (((r[i].w ^ (tag << 14)) & 0xC000) != 0)) todo |= 1 << i;
            }
            todo &= tid - 384 + 512 < nb * 4 ? 31 : tid - 384 + 384 < nb * 4 ? 15 : 7;
        }
        #pragma unroll 1
        for (int put = 0; put < 2; put++) {
            uint32_t any = __reduce_or_sync(~0u, todo), m = 0, u = 0;
            #pragma unroll 1
            while (any | m) {
                uint4 r = make_uint4(0, 0, 0, 0), r2 = r;
                uint32_t s, go, gd;
                bool on;
                if (__builtin_expect(m == 0, 1)) {
                    const uint32_t i = __ffs(any) - 1;
                    any &= any - 1; u = tid - 384 + 128 * i; on = (todo >> i) & 1;
                    r = lds128(sbase + SM_H1 + u * 16); if (!NOH2) r2 = lds128(sbase + SM_H2 + u * 16);
                    s = u >> 2; go = G_H1 + u * 16; gd = HB;
                } else {
                    s = ((u & ~31) + __ffs(m) - 1) >> 2; m &= m - 1; on = lane < 12;
                    go = G_L + s * 512 + 64 + lane * 16; gd = 256;
                }
                #pragma unroll 1
                for (int n = 0; n < (1 << 22); n++) {
                    const bool b1 = on && ((r.w >> 14) & 3) != tag, b2 = on && put && ((r2.w >> 16) & 3) != tag;
                    if (__builtin_expect(!__any_sync(~0u, b1 | b2), 1)) break;
                    ld_unit(r, gs + go, b1); ld_unit(r2, gs + go + gd, b2);
                }
                if (gd == HB) m = __ballot_sync(~0u, on && r.w >> 16 == 0xFE);
                if (on && r.w >> 16 == 255) sts32(sbase + SM_MISC + 4, 1);
                const uint32_t e[4] = {r.x, r.y, r.z, r.w}, v[4] = {r2.x, r2.y, r2.z, r2.w};
                uint32_t slot[4];
                #pragma unroll
                for (int k = 0; k < 4; k++) slot[k] = atoms_inc(sbase + SM_DEG + (on && e[k] >> 16 == (uint32_t)b ? (e[k] & 0x3FFF) : (NPB_MAX + lane) * 4));
                if (put) {
                    #pragma unroll
                    for (int k = 0; k < 4; k++) place(sbase, slot[k], v[k], s * ch);
                }
            }
            if (put == 0) {
                WS(4);
                asm volatile("bar.arrive 11, 512;" ::: "memory");
                if (w == 3) {
                    if (XAFT) x_ld(0, XSPL);
                    w_expect(su + SM_ABAR, 12288); w_expect(su + SM_ABAR + 8, 12288); w_expect(su + SM_ABAR + 16, nb * (CE * 4) - 24576);
                    w_hint(gbar + HI2, all);
                    if (D2) delay(D2);
                    asm volatile("cp.async.bulk.wait_group.read 0;" ::: "memory");
                    WS(3);
                    const char* g2 = gs + b * (P1B + P2B) + P1B;
                    w_ld(su + SM_P2, g2, 12288, su + SM_ABAR);
                    w_ld(su + SM_P2 + 12288, g2 + 12288, 12288, su + SM_ABAR + 8);
                    w_ld(su + SM_P2 + 24576, g2 + 24576, nb * (CE * 4) - 24576, su + SM_ABAR + 16);
                    if (!NOH2) w_ld(su + SM_H2, gs + G_H2, nb * 64, su + SM_ABAR + 40);
                    if (XW2) mbar_wait(ab + (XW2 - 1) * 8, 1);
                    x_ld(XSPL, 6);
                } else {
                    #pragma unroll 8
                    for (int i = 0; i < 32; i++) w_init(su + SM_GBAR + (w * 32 + i) * 8, 32);
                }
                asm volatile("bar.sync 4, 512;" ::: "memory");
                if (NOH2) mbar_wait(ab, 1); else mbar_wait(ab + 40, 0);
            }
        }
        __syncwarp();
        WS(10);
        WGD();
        const uint32_t scr = sbase + SM_PAIR + (tid & 127) * 8;
        const int r4 = lane >> 3, c8 = lane & 7;
        const uint32_t sb = su;
        const uint32_t tk = ((c8 & 1) << 4) | ((c8 >> 1) << 7);
        auto row_bytes = [](uint32_t o) { return (o & 0xFE00) | ((o << 2) & 0x180); };
        if (w < 3) {
            const char* gx = as_pair((const char*)x + c8 * 16, scr);
            const char* ge = as_pair((const char*)ea + (lane & 1) * 16, scr);
            const uint32_t gx0 = (uint32_t)(uint64_t)gx, ge0 = (uint32_t)(uint64_t)ge, hi = (uint64_t)gx >> 32, he = (uint64_t)ge >> 32;
            const int s = (lane >> 1) & 3;
            const uint32_t xs0 = sb + SM_XS + w * NSTAGE * XS_BYTES;
            const uint32_t es0 = sb + SM_ES + w * NSTAGE * ES_BYTES + r4 * 64 + (((lane ^ (r4 >> 1)) & 1) << 4) + (s >> 1) * 256 + (s & 1) * 32;
            const uint32_t bars = sb + SM_BARS + w * 2 * STG;
            const uint32_t xoffA = (2 * r4) * 128 + ((c8 ^ (2 * r4)) << 4), xoffB = (2 * r4 + 1) * 128 + ((c8 ^ (2 * r4 + 1)) << 4);
            uint64_t pol;
            asm volatile("createpolicy.fractional.L2::evict_first.b64 %0, 1.0;" : "=l"(pol));
            if (TLBW) {
                const uint32_t k = w * 32 + lane;
                asm volatile("prefetch.global.L2 [%0];" :: "l"(k < 64 ? (const char*)ea + (size_t)(E >> 6) * k * 32 : (const char*)x + (size_t)(N >> 5) * (k - 64) * 128));
            }
            asm volatile("bar.sync 6, 128;" ::: "memory");
            bool first = true; int tcount = 0;
            WS(15);
            uint32_t ph = 1, cur = w;
            uint32_t hist = 96 * 0x010101u;
            auto done3 = [&]() { mbar_arrive(sb + SM_GBAR + ((hist >> 16) & 0xFF) * 8); };
            const bool go = misc[1] == 0 && nn > 0;
            const uint32_t ca = sb + SM_CLAIM + lane * 4, pa = sb + SM_TINFO + r4 * 8;
            const uint32_t pb = sb + SM_TINFO + s * 8 + 4, pc = sb + SM_TINFO + (lane & 3) * 8 + 6, xl = (lane & 8) << 1, xs = (lane & 1) << 4, ra = (lane & 15) * 16 + 16;
            auto row_of = [&](uint32_t o) { uint32_t v; asm volatile("ld.shared.u16 %0, [%1];" : "=r"(v) : "r"(pb + o) : "memory"); return v; };
            auto code_of = [&](uint32_t o) { uint32_t v; asm volatile("ld.shared.s16 %0, [%1];" : "=r"(v) : "r"(pc + o) : "memory"); return v; };
            uint32_t pw = lds32(pa + w * 32), pt = __reduce_or_sync(~0u, pw), cont = 0;
            uint4 rc = make_uint4(0, row_of(w * 32) ^ xs, code_of(w * 32) & (ONE_F | 0x1FFFu), 0);
            const uint32_t se0 = sb + SM_EID + s * 4, xab = xoffB - xoffA, das = 2 * (xs0 + xoffA) + XS_BYTES, des = 2 * es0 + ES_BYTES, brs = 2 * bars + STG;
            uint32_t da = xs0 + xoffA, de = es0, br = bars;
            #pragma unroll 1
            while (go) {
                uint32_t se, sx;
                asm("dp2a.lo.u32.u32 %0, %1, 4, %2;" : "=r"(se) : "r"(pw), "r"(se0));
                asm("dp2a.lo.u32.u32 %0, %1, 2, %2;" : "=r"(sx) : "r"(pw), "r"(sb + SM_SRC));
                const int dv = pw >> 27;
                const uint32_t db = da + xab;
                const uint32_t sel = (pt >> 16) & 15, nx = (pt >> 15) & (127 << 5);
                uint32_t g;
                auto claim = [&]() { asm volatile("atom.shared.add.u32 %0, [%1], %2;" : "=r"(g) : "r"(ca), "r"(nx == 0 ? 32u : 0u) : "memory"); };
                if (sel == 0) break;
                if (first) { asm volatile("bar.sync 3, 480;" ::: "memory"); first = false;
                }
                switch (sel) {
#define CASE(L, P, GEN) case L: { \
                        uint32_t oe[(P + 1) / 2], o[P]; \
                        _Pragma("unroll") for (int j = 0; j < (P + 1) / 2; j++) oe[j] = lds32(se + j * 16); \
                        _Pragma("unroll") for (int j = 0; j < P; j++) o[j] = lds32(sx + j * 4); \
                        mbar_wait_h(br + 8, ph); \
                        _Pragma("unroll") for (int j = 0; j < (P + 1) / 2; j++) \
                            if (LO32) { if (!GEN && 2 * j + 2 < P) cpe<false>(he, de + j * 512, oe[j], ge0, 0, 0, pol); \
                                else if (2 * j + 1 < NPMAX || s < 2) cpe<true>(he, de + j * 512, oe[j], ge0, 4 * j + s, dv, pol); } \
                            else if (!GEN && 2 * j + 2 < P) cp16e(de + j * 512, ge, oe[j], pol); else if (2 * j + 1 < NPMAX || s < 2) cp16z<32>(de + j * 512, ge, oe[j], 4 * j + s, dv, pol); \
                        _Pragma("unroll") for (int j = 0; j < P - 1; j++) { \
                            if (LO32) { cpx<0, GEN>(hi, da + j * 1024, o[j], gx0, 2 * j, dv); cpx<1, GEN>(hi, db + j * 1024, o[j], gx0, 2 * j + 1, dv); } \
                            else if (GEN) { cp16z<128>(da + j * 1024, gx, o[j] & 0xFFFFu, 2 * j, dv, 0); cp16z<128>(db + j * 1024, gx, o[j] >> 16, 2 * j + 1, dv, 0); } \
                            else { cp16i<128>(da + j * 1024, gx, o[j] & 0xFFFFu); cp16i<128>(db + j * 1024, gx, o[j] >> 16); } } \
                        if (LO32) { cpx<0, true>(hi, da + (P - 1) * 1024, o[P - 1], gx0, 2 * P - 2, dv); cpx<1, true>(hi, db + (P - 1) * 1024, o[P - 1], gx0, 2 * P - 1, dv); } \
                        else { cp16z<128>(da + (P - 1) * 1024, gx, o[P - 1] & 0xFFFFu, 2 * P - 2, dv, 0); cp16z<128>(db + (P - 1) * 1024, gx, o[P - 1] >> 16, 2 * P - 1, dv, 0); } \
                    } break;
                    CASE(4, 4, false) CASE(5, 5, false) CASE(6, 6, false) CASE(7, 7, false) CASE(8, 8, false) CASE(9, 9, false) CASE(10, 10, false) CASE(11, 11, false)
                    CASE(15, NPMAX, true) CASE(14, 8, true) default: CASE(13, 5, true)
#undef CASE
                }
                claim();
                mbar_cp_arrive(br);
                done3();
                g = __reduce_min_sync(~0u, g);
                {
                    const uint32_t o = nx == 0 ? g : nx;
                    pw = lds32(pa + o);
                    const uint32_t ya = row_of(o), yb = code_of(o);
                    pt = __reduce_or_sync(~0u, pw);
                    const uint32_t brk = (cont | nx) ? C_BRK : 0u;
                    rc.x = ya ^ xl;
                    const uint32_t lv = brk | ((sel + (15 - NPMAX)) & 16) | (((pt >> 16) & 15) ^ sel);
                    rc.w = (yb & 15) | (lv ? 0x70000000u | brk : TAU_BITS);
                    asm volatile("st.shared.v4.u32 [%2], {%3, %0, %1, %4};\nxor.b32 %0, %5, %6;\nand.b32 %1, %7, %8;"
                                 : "+r"(rc.y), "+r"(rc.z) : "r"(br + ra), "r"(rc.x), "r"(rc.w), "r"(ya), "r"(xs), "r"(yb), "n"(ONE_F | 0x1FFFu) : "memory");
                    cont = nx;
                }
                mbar_arrive(br);
                hist = (hist << 8) | (nx == 0 ? cur : 96u);
                cur = nx == 0 ? g >> 5 : cur;
                ph ^= br != bars; br = brs - br; da = das - da; de = des - de;
            }
            if (first) asm volatile("bar.sync 3, 480;" ::: "memory");
            if (go) {
                mbar_wait(sb + SM_ABAR + 72, 0);
                const int g0 = 3 * max((ngroups + 2) / 3 - TR, 0) + w;
                uint32_t nd[TR]; uint4 xv[TR];
                #pragma unroll
                for (int k = 0; k < TR; k++) {
                    asm volatile("ld.shared.u16 %0, [%1];" : "=r"(nd[k]) : "r"(pa + (g0 + 3 * k) * 32 + 4) : "memory");
                    xv[k] = __ldg((const uint4*)(gx + (size_t)node0 * 128 + (nd[k] == tab_at(NONE) ? 0u : row_bytes(nd[k]))));
                }
                #pragma unroll 1
                for (int k = 0; k < 3; k++) {
                    mbar_wait(k < 2 ? br + 8 : sb + SM_ABAR + 48 + w * 8, k < 2 ? ph : 0);
                    done3(); hist <<= 8;
                    ph ^= br != bars; br = brs - br;
                }
                #pragma unroll
                for (int k = 0; k < TR; k++) {
                    const uint32_t ro = sb + (nd[k] ^ tk);
                    const uint4 xu = lds128(ro + SM_XU);
                    uint4 a = make_uint4(0, 0, 0, 0);
                    if (g0 + 3 * k < misc[4]) { mbar_wait(sb + SM_GBAR + (g0 + 3 * k) * 8, 0); a = lds128(ro + SM_TAB); }
                    finish(a, xu, xv[k]);
                    if (nd[k] != tab_at(NONE)) *(uint4*)((char*)out + (size_t)node0 * 128 + row_bytes(nd[k]) + c8 * 16) = a;
                }
            }
            cp_wait<0>();
        } else {
            const char* gx = as_pair((const char*)x + (size_t)node0 * 128 + c8 * 16, scr);
            const char* ob = as_pair((const char*)out + (size_t)node0 * 128 + c8 * 16, scr);
            asm volatile("bar.arrive 6, 128;" ::: "memory");
            WS(15);
            if (b == 0 && lane == 0) asm volatile("red.relaxed.gpu.global.add.u32 [%0], 1;" :: "l"(gbar) : "memory");
            if (misc[1] == 0) mbar_wait(sb + SM_ABAR + 72, 0);
            if (npb <= NPB_MAX - 4) sts32(sb + SM_MISC + 12, 0);
            const int rounds = misc[1] ? 0 : max((ngroups + 2) / 3 - TR, 0);
            const int gz = misc[4], fast = __reduce_min_sync(~0u, min(rounds, gz / 3));
            uint32_t wl = sb + SM_TINFO + r4 * 8 + 4, gbar = sb + SM_GBAR;
            auto row_at = [&](uint32_t a) { uint32_t n; asm volatile("ld.shared.u16 %0, [%1];" : "=r"(n) : "r"(a) : "memory"); return n; };
            auto fetch = [&](uint32_t n, uint4& v) {
                asm volatile("{\n.reg .b64 p;\ncvt.u64.u32 p, %5;\nadd.u64 p, p, %4;\nld.global.nc.L1::no_allocate.v4.u32 {%0,%1,%2,%3}, [p];\n}"
                             : "=r"(v.x), "=r"(v.y), "=r"(v.z), "=r"(v.w) : "l"(gx), "r"(n));
            };
            auto store = [&](uint32_t n, const uint4& a) {
                asm volatile("{\n.reg .b64 p;\ncvt.u64.u32 p, %1;\nadd.u64 p, p, %0;\nst.global.v4.u32 [p], {%2,%3,%4,%5};\n}" :: "l"(ob), "r"(n), "r"(a.x), "r"(a.y), "r"(a.z), "r"(a.w) : "memory");
            };
            uint32_t n0[3], o0[3]; uint4 x0[3];
            const uint32_t tw = __shfl_sync(~0u, tk, lane);
            if (fast) {
                #pragma unroll
                for (int r = 0; r < 3; r++) { const uint32_t v = row_at(wl + r * 32); n0[r] = row_bytes(v); o0[r] = v ^ tw; fetch(n0[r], x0[r]); }
            }
            #pragma unroll 1
            for (int k = 0; k < fast; k++) {
                wl += 96;
                #pragma unroll
                for (int r = 0; r < 3; r++) {
                    const uint32_t nd = n0[r];
                    const uint4 xu = lds128(sb + o0[r] + SM_XU);
                    const uint32_t v = row_at(wl + r * 32);
                    mbar_wait(gbar + r * 8, 0);
                    uint4 a = lds128(sb + o0[r] + SM_TAB);
                    n0[r] = row_bytes(v); o0[r] = v ^ tw;
                    finish(a, xu, x0[r]);
                    fetch(n0[r], x0[r]);
                    store(nd, a);
                }
                gbar += 24;
            }
            #pragma unroll 1
            for (int g = 3 * fast; g < 3 * rounds; g++) {
                const uint32_t v = row_at(sb + SM_TINFO + r4 * 8 + 4 + g * 32), nd = row_bytes(v), ro = sb + (v ^ tw);
                uint4 xv, a = make_uint4(0, 0, 0, 0);
                fetch(nd, xv);
                if (g < gz) { mbar_wait(sb + SM_GBAR + g * 8, 0); a = lds128(ro + SM_TAB); }
                finish(a, lds128(ro + SM_XU), xv);
                store(nd, a);
            }
        }
    }
    WS(17); WG1(); CG(2);
}

}

extern "C" void kernel_launch(void* const* d_in, const int* in_sizes, int n_in, void* d_out, int out_size) {
    const __nv_bfloat16* x = (const __nv_bfloat16*)d_in[0];
    const __nv_bfloat16* ea = (const __nv_bfloat16*)d_in[1];
    const int* src = (const int*)d_in[2];
    const int* dst = (const int*)d_in[3];
    const __nv_bfloat16* wa = (const __nv_bfloat16*)d_in[4];
    const __nv_bfloat16* wb = (const __nv_bfloat16*)d_in[5];
    const __nv_bfloat16* wc = (const __nv_bfloat16*)d_in[6];
    const __nv_bfloat16* wu = (const __nv_bfloat16*)d_in[7];
    const __nv_bfloat16* wv = (const __nv_bfloat16*)d_in[8];
    __nv_bfloat16* out = (__nv_bfloat16*)d_out;
    int N = in_sizes[0] / 64, E = in_sizes[2];
    static int sms = 0;
    static CUtensorMap tm1, tm2, tmw, tmx;
    static bool tm_ok = false;
    static void* gp = nullptr; static void* gb = nullptr;
    typedef CUresult (*EncFn)(CUtensorMap*, CUtensorMapDataType, cuuint32_t, void*, const cuuint64_t*, const cuuint64_t*, const cuuint32_t*,
                              const cuuint32_t*, CUtensorMapInterleave, CUtensorMapSwizzle, CUtensorMapL2promotion, CUtensorMapFloatOOBfill);
    static void* fn = nullptr;
    auto enc = [&](CUtensorMap* tm, const void* base, cuuint64_t cols, cuuint64_t rows, cuuint32_t bc, cuuint32_t br, CUtensorMapSwizzle sw) {
        cuuint64_t g2[2] = {cols, rows}, gs[1] = {cols * 4};
        cuuint32_t b2[2] = {bc, br}, es[2] = {1, 1};
        return ((EncFn)fn)(tm, CU_TENSOR_MAP_DATA_TYPE_UINT32, 2, (void*)base, g2, gs, b2, es, CU_TENSOR_MAP_INTERLEAVE_NONE, sw,
                           CU_TENSOR_MAP_L2_PROMOTION_NONE, CU_TENSOR_MAP_FLOAT_OOB_FILL_NONE) == CUDA_SUCCESS;
    };
    if (!sms) {
        cudaDeviceGetAttribute(&sms, cudaDevAttrMultiProcessorCount, 0);
        cudaDriverEntryPointQueryResult qr;
        cudaGetDriverEntryPoint("cuTensorMapEncodeTiled", &fn, cudaEnableDefault, &qr);
        cudaGetSymbolAddress(&gp, g_str); cudaGetSymbolAddress(&gb, g_bar);
        if (fn && gp && gb) {
            const cuuint32_t rows = sms < NB_MAX ? sms : NB_MAX;
            tm_ok = enc(&tm1, gp, (P1B + P2B) / 4, NB_MAX, CE / 2, rows, CU_TENSOR_MAP_SWIZZLE_NONE) && enc(&tm2, gp, (P1B + P2B) / 4, NB_MAX, CE, rows, CU_TENSOR_MAP_SWIZZLE_NONE);
        }
        cudaFuncSetAttribute(gcn_kernel<true>, cudaFuncAttributeMaxDynamicSharedMemorySize, SMEM_LAUNCH);
        cudaFuncSetAttribute(gcn_kernel<false>, cudaFuncAttributeMaxDynamicSharedMemorySize, SMEM_LAUNCH);
    }
    int nb = sms < NB_MAX ? sms : NB_MAX;
    int npb = (N + nb - 1) / nb;
    int ch = (((E + nb - 1) / nb) + 3) & ~3;
    const uintptr_t wp[4] = {(uintptr_t)wb, (uintptr_t)wv, (uintptr_t)wa, (uintptr_t)wu};
    uintptr_t wlo = wp[0], whi = wp[0], wal = 0;
    for (int i = 0; i < 4; i++) { wlo = wp[i] < wlo ? wp[i] : wlo; whi = wp[i] > whi ? wp[i] : whi; wal |= wp[i] - wp[0]; }
    bool ok = tm_ok && nb >= NB_MIN && npb < NPB_MAX && ch <= CH_MAX && !(E & 3) && N <= 65535 && npb >= 2 && !(wal & 127) && (whi - wlo) >> 7 < (1u << 30) &&
              !(((uintptr_t)src | (uintptr_t)dst | (uintptr_t)x | (uintptr_t)wb | (uintptr_t)wc) & 15);
    ok = ok && enc(&tmw, (const void*)wlo, 32, ((whi - wlo) >> 7) + 64, 32, 64, CU_TENSOR_MAP_SWIZZLE_128B) && enc(&tmx, x, 32, N, 32, 64, CU_TENSOR_MAP_SWIZZLE_128B);
    if (!ok) {
        int g = 1024, p = (N + g - 1) / g;
        slow_kernel<<<g, 256>>>(x, ea, src, dst, wa, wb, wc, wu, wv, out, N, E, p < 1 ? 1 : p);
        return;
    }
    int4 wrow = make_int4((int)((wp[0] - wlo) >> 7), (int)((wp[1] - wlo) >> 7), (int)((wp[2] - wlo) >> 7), (int)((wp[3] - wlo) >> 7));
    uint32_t magic = (uint32_t)((1ull << 32) / (uint32_t)npb) + 1u;
    void* args[] = {&dst, &gb, &gp, &src, &E, &ch, &N, &npb, &magic, &x, &ea, &wa, &wb, &wc, &wu, &wv, &out, &wrow, &tm1, &tm2, &tmw, &tmx};
    const bool lo32 = ((uintptr_t)x >> 32) == (((uintptr_t)x + (size_t)N * 128 - 1) >> 32) && ((uintptr_t)ea >> 32) == (((uintptr_t)ea + (size_t)E * 32 - 1) >> 32);
    cudaLaunchCooperativeKernel(lo32 && !FORCE64 ? (const void*)gcn_kernel<true> : (const void*)gcn_kernel<false>, dim3(nb), dim3(THREADS), args, SMEM_LAUNCH, cudaStreamPerThread);
}
```

```cpp
#include <cuda_runtime.h>
#include <cuda.h>
#include <cuda_bf16.h>
#include <stdint.h>

namespace {

constexpr int N_MAX = 65536;
constexpr int NPMAX = 11;
constexpr int NPMIN = 4;
constexpr int THREADS = 512;
constexpr int EPT = 12;
constexpr int CH_MAX = THREADS * EPT;
constexpr int NB_MAX = 134, NB_MIN = 120;
constexpr int CE = 64;
constexpr int P1B = NB_MAX * CE * 2;
constexpr int P2B = NB_MAX * CE * 4;
constexpr int HB = NB_MAX * 64;
constexpr int G_H1 = NB_MAX * (P1B + P2B), G_H2 = G_H1 + HB, G_L = G_H2 + HB, G_END = G_L + NB_MAX * 512;
constexpr int NPB_MAX = 384;
constexpr int SLOT_CAP = 6784;
constexpr int TILE_CAP = 124;
constexpr int TILE_X = 8;
constexpr int NCLS = 64;
constexpr int NSTAGE = 2;
constexpr int TR = 2;
constexpr float LOG2E = 1.4426950408889634f;

__device__ __align__(256) uint4 g_str[G_END / 16];
__device__ __align__(128) unsigned g_bar[96];
__device__ float g_slow[N_MAX * 128];

#define WS(k)
#define WS1(k)
#define WSG(k)
#define WGD()
#define WG0()
#define WG1()
#define CG(k)
#define SMEM_LAUNCH SMEM_BYTES
#define EPOLL 0
#define WSPL 1
#define XT0 1000
#define XDT 800
#define D3 0
#define XMID 0
#define SRCE 0
#define XA 1
#define XC 0
#define XW 1
#define XE 0
#define XEW 1
#define XAFT 1
#define WDET 1
#define H1F 0
#define TSRC 1000
#define G3F 1
#define TLBW 0
#define OWNE 0
#define UFORM 0
#define XW2 0
#define FBLOG(P)
#define FBW 0
#define PD 300
#define SRCV 0
#define SD 0
#define WV 9
#define WLATE 2
#define WPF 0
#define HI1 1
#define HI2 4
#define HORD 0
#define T1 6000
#define NOH2 0
#define TSPIN 0
#define WMAP 0
#define P1S 0
#define BW mbar_wait_c
#define OVU 1
#define S2W 0
#define GD 0
#define XPF 0
#define XLD 4
#define XSPL 1
#define P2W 1
#define H2M 0
#define D1 0
#define D2 0
#define FORCE64 0
#define EDHI ((16ull << 32) | (3ull << 62))
template<int NP> struct TileMMA;
template<> struct TileMMA<1> {
  static __device__ __forceinline__ void issue(float* g, float* h, const uint32_t* w, uint32_t dx, uint64_t de, uint64_t dh, uint64_t dc) {
    asm volatile(
      "{\n.reg .b64 dx0, dx1, dx2, dx3;\n.reg .b32 l1, l2, l3, hx;\nmov.b32 hx, 0x40000040;\n"
      "add.u32 l1, %48, 2;\nadd.u32 l2, %48, 4;\nadd.u32 l3, %48, 6;\n"
      "mov.b64 dx0, {%48, hx};\nmov.b64 dx1, {l1, hx};\nmov.b64 dx2, {l2, hx};\nmov.b64 dx3, {l3, hx};\n"
      "wgmma.fence.sync.aligned;\n"
      "wgmma.mma_async.sync.aligned.m64n8k16.f32.bf16.bf16 {%0, %1, %2, %3}, {%44, %45, %46, %47}, %50, 0, 1, 1, 0;\n"
      "wgmma.mma_async.sync.aligned.m64n8k16.f32.bf16.bf16 {%0, %1, %2, %3}, {%24, %25, %26, %27}, %49, 1, 1, 1, 0;\n"
      "wgmma.mma_async.sync.aligned.m64n8k16.f32.bf16.bf16 {%0, %1, %2, %3}, {%8, %9, %10, %11}, dx0, 1, 1, 1, 0;\n"
      "wgmma.mma_async.sync.aligned.m64n8k16.f32.bf16.bf16 {%0, %1, %2, %3}, {%12, %13, %14, %15}, dx1, 1, 1, 1, 0;\n"
      "wgmma.mma_async.sync.aligned.m64n8k16.f32.bf16.bf16 {%0, %1, %2, %3}, {%16, %17, %18, %19}, dx2, 1, 1, 1, 0;\n"
      "wgmma.mma_async.sync.aligned.m64n8k16.f32.bf16.bf16 {%0, %1, %2, %3}, {%20, %21, %22, %23}, dx3, 1, 1, 1, 0;\n"
      "wgmma.commit_group.sync.aligned;\n"
      "wgmma.mma_async.sync.aligned.m64n8k16.f32.bf16.bf16 {%4, %5, %6, %7}, {%28, %29, %30, %31}, dx0, 0, 1, 1, 0;\n"
      "wgmma.mma_async.sync.aligned.m64n8k16.f32.bf16.bf16 {%4, %5, %6, %7}, {%32, %33, %34, %35}, dx1, 1, 1, 1, 0;\n"
      "wgmma.mma_async.sync.aligned.m64n8k16.f32.bf16.bf16 {%4, %5, %6, %7}, {%36, %37, %38, %39}, dx2, 1, 1, 1, 0;\n"
      "wgmma.mma_async.sync.aligned.m64n8k16.f32.bf16.bf16 {%4, %5, %6, %7}, {%40, %41, %42, %43}, dx3, 1, 1, 1, 0;\n"
      "wgmma.commit_group.sync.aligned;\n}\n"
      : "=f"(g[0]), "=f"(g[1]), "=f"(g[2]), "=f"(g[3]),
        "=f"(h[0]), "=f"(h[1]), "=f"(h[2]), "=f"(h[3])
      : "r"(w[0]), "r"(w[1]), "r"(w[2]), "r"(w[3]), "r"(w[4]), "r"(w[5]), "r"(w[6]), "r"(w[7]), "r"(w[8]), "r"(w[9]), "r"(w[10]), "r"(w[11]), "r"(w[12]), "r"(w[13]), "r"(w[14]), "r"(w[15]), "r"(w[16]), "r"(w[17]), "r"(w[18]), "r"(w[19]), "r"(w[20]), "r"(w[21]), "r"(w[22]), "r"(w[23]), "r"(w[24]), "r"(w[25]), "r"(w[26]), "r"(w[27]), "r"(w[28]), "r"(w[29]), "r"(w[30]), "r"(w[31]), "r"(w[32]), "r"(w[33]), "r"(w[34]), "r"(w[35]), "r"(w[36]), "r"(w[37]), "r"(w[38]), "r"(w[39]), "r"(dx), "l"(de), "l"(dh)
      : "memory");
  }
  static __device__ __forceinline__ void wait_g(float* g) {
    asm volatile("wgmma.wait_group.sync.aligned 1;\n"
      : "+f"(g[0]), "+f"(g[1]), "+f"(g[2]), "+f"(g[3])
      :: "memory");
  }
  static __device__ __forceinline__ void wait_h(float* h) {
    asm volatile("wgmma.wait_group.sync.aligned 0;\n"
      : "+f"(h[0]), "+f"(h[1]), "+f"(h[2]), "+f"(h[3])
      :: "memory");
  }
};
template<> struct TileMMA<2> {
  static __device__ __forceinline__ void issue(float* g, float* h, const uint32_t* w, uint32_t dx, uint64_t de, uint64_t dh, uint64_t dc) {
    asm volatile(
      "{\n.reg .b64 dx0, dx1, dx2, dx3;\n.reg .b32 l1, l2, l3, hx;\nmov.b32 hx, 0x40000040;\n"
      "add.u32 l1, %56, 2;\nadd.u32 l2, %56, 4;\nadd.u32 l3, %56, 6;\n"
      "mov.b64 dx0, {%56, hx};\nmov.b64 dx1, {l1, hx};\nmov.b64 dx2, {l2, hx};\nmov.b64 dx3, {l3, hx};\n"
      "wgmma.fence.sync.aligned;\n"
      "wgmma.mma_async.sync.aligned.m64n16k16.f32.bf16.bf16 {%0, %1, %2, %3, %4, %5, %6, %7}, {%52, %53, %54, %55}, %58, 0, 1, 1, 0;\n"
      "wgmma.mma_async.sync.aligned.m64n16k16.f32.bf16.bf16 {%0, %1, %2, %3, %4, %5, %6, %7}, {%32, %33, %34, %35}, %57, 1, 1, 1, 0;\n"
      "wgmma.mma_async.sync.aligned.m64n16k16.f32.bf16.bf16 {%0, %1, %2, %3, %4, %5, %6, %7}, {%16, %17, %18, %19}, dx0, 1, 1, 1, 0;\n"
      "wgmma.mma_async.sync.aligned.m64n16k16.f32.bf16.bf16 {%0, %1, %2, %3, %4, %5, %6, %7}, {%20, %21, %22, %23}, dx1, 1, 1, 1, 0;\n"
      "wgmma.mma_async.sync.aligned.m64n16k16.f32.bf16.bf16 {%0, %1, %2, %3, %4, %5, %6, %7}, {%24, %25, %26, %27}, dx2, 1, 1, 1, 0;\n"
      "wgmma.mma_async.sync.aligned.m64n16k16.f32.bf16.bf16 {%0, %1, %2, %3, %4, %5, %6, %7}, {%28, %29, %30, %31}, dx3, 1, 1, 1, 0;\n"
      "wgmma.commit_group.sync.aligned;\n"
      "wgmma.mma_async.sync.aligned.m64n16k16.f32.bf16.bf16 {%8, %9, %10, %11, %12, %13, %14, %15}, {%36, %37, %38, %39}, dx0, 0, 1, 1, 0;\n"
      "wgmma.mma_async.sync.aligned.m64n16k16.f32.bf16.bf16 {%8, %9, %10, %11, %12, %13, %14, %15}, {%40, %41, %42, %43}, dx1, 1, 1, 1, 0;\n"
      "wgmma.mma_async.sync.aligned.m64n16k16.f32.bf16.bf16 {%8, %9, %10, %11, %12, %13, %14, %15}, {%44, %45, %46, %47}, dx2, 1, 1, 1, 0;\n"
      "wgmma.mma_async.sync.aligned.m64n16k16.f32.bf16.bf16 {%8, %9, %10, %11, %12, %13, %14, %15}, {%48, %49, %50, %51}, dx3, 1, 1, 1, 0;\n"
      "wgmma.commit_group.sync.aligned;\n}\n"
      : "=f"(g[0]), "=f"(g[1]), "=f"(g[2]), "=f"(g[3]), "=f"(g[4]), "=f"(g[5]), "=f"(g[6]), "=f"(g[7]),
        "=f"(h[0]), "=f"(h[1]), "=f"(h[2]), "=f"(h[3]), "=f"(h[4]), "=f"(h[5]), "=f"(h[6]), "=f"(h[7])
      : "r"(w[0]), "r"(w[1]), "r"(w[2]), "r"(w[3]), "r"(w[4]), "r"(w[5]), "r"(w[6]), "r"(w[7]), "r"(w[8]), "r"(w[9]), "r"(w[10]), "r"(w[11]), "r"(w[12]), "r"(w[13]), "r"(w[14]), "r"(w[15]), "r"(w[16]), "r"(w[17]), "r"(w[18]), "r"(w[19]), "r"(w[20]), "r"(w[21]), "r"(w[22]), "r"(w[23]), "r"(w[24]), "r"(w[25]), "r"(w[26]), "r"(w[27]), "r"(w[28]), "r"(w[29]), "r"(w[30]), "r"(w[31]), "r"(w[32]), "r"(w[33]), "r"(w[34]), "r"(w[35]), "r"(w[36]), "r"(w[37]), "r"(w[38]), "r"(w[39]), "r"(dx), "l"(de), "l"(dh)
      : "memory");
  }
  static __device__ __forceinline__ void wait_g(float* g) {
    asm volatile("wgmma.wait_group.sync.aligned 1;\n"
      : "+f"(g[0]), "+f"(g[1]), "+f"(g[2]), "+f"(g[3]), "+f"(g[4]), "+f"(g[5]), "+f"(g[6]), "+f"(g[7])
      :: "memory");
  }
  static __device__ __forceinline__ void wait_h(float* h) {
    asm volatile("wgmma.wait_group.sync.aligned 0;\n"
      : "+f"(h[0]), "+f"(h[1]), "+f"(h[2]), "+f"(h[3]), "+f"(h[4]), "+f"(h[5]), "+f"(h[6]), "+f"(h[7])
      :: "memory");
  }
};
template<> struct TileMMA<3> {
  static __device__ __forceinline__ void issue(float* g, float* h, const uint32_t* w, uint32_t dx, uint64_t de, uint64_t dh, uint64_t dc) {
    asm volatile(
      "{\n.reg .b64 dx0, dx1, dx2, dx3;\n.reg .b32 l1, l2, l3, hx;\nmov.b32 hx, 0x40000040;\n"
      "add.u32 l1, %64, 2;\nadd.u32 l2, %64, 4;\nadd.u32 l3, %64, 6;\n"
      "mov.b64 dx0, {%64, hx};\nmov.b64 dx1, {l1, hx};\nmov.b64 dx2, {l2, hx};\nmov.b64 dx3, {l3, hx};\n"
      "wgmma.fence.sync.aligned;\n"
      "wgmma.mma_async.sync.aligned.m64n24k16.f32.bf16.bf16 {%0, %1, %2, %3, %4, %5, %6, %7, %8, %9, %10, %11}, {%60, %61, %62, %63}, %66, 0, 1, 1, 0;\n"
      "wgmma.mma_async.sync.aligned.m64n24k16.f32.bf16.bf16 {%0, %1, %2, %3, %4, %5, %6, %7, %8, %9, %10, %11}, {%40, %41, %42, %43}, %65, 1, 1, 1, 0;\n"
      "wgmma.mma_async.sync.aligned.m64n24k16.f32.bf16.bf16 {%0, %1, %2, %3, %4, %5, %6, %7, %8, %9, %10, %11}, {%24, %25, %26, %27}, dx0, 1, 1, 1, 0;\n"
      "wgmma.mma_async.sync.aligned.m64n24k16.f32.bf16.bf16 {%0, %1, %2, %3, %4, %5, %6, %7, %8, %9, %10, %11}, {%28, %29, %30, %31}, dx1, 1, 1, 1, 0;\n"
      "wgmma.mma_async.sync.aligned.m64n24k16.f32.bf16.bf16 {%0, %1, %2, %3, %4, %5, %6, %7, %8, %9, %10, %11}, {%32, %33, %34, %35}, dx2, 1, 1, 1, 0;\n"
      "wgmma.mma_async.sync.aligned.m64n24k16.f32.bf16.bf16 {%0, %1, %2, %3, %4, %5, %6, %7, %8, %9, %10, %11}, {%36, %37, %38, %39}, dx3, 1, 1, 1, 0;\n"
      "wgmma.commit_group.sync.aligned;\n"
      "wgmma.mma_async.sync.aligned.m64n24k16.f32.bf16.bf16 {%12, %13, %14, %15, %16, %17, %18, %19, %20, %21, %22, %23}, {%44, %45, %46, %47}, dx0, 0, 1, 1, 0;\n"
      "wgmma.mma_async.sync.aligned.m64n24k16.f32.bf16.bf16 {%12, %13, %14, %15, %16, %17, %18, %19, %20, %21, %22, %23}, {%48, %49, %50, %51}, dx1, 1, 1, 1, 0;\n"
      "wgmma.mma_async.sync.aligned.m64n24k16.f32.bf16.bf16 {%12, %13, %14, %15, %16, %17, %18, %19, %20, %21, %22, %23}, {%52, %53, %54, %55}, dx2, 1, 1, 1, 0;\n"
      "wgmma.mma_async.sync.aligned.m64n24k16.f32.bf16.bf16 {%12, %13, %14, %15, %16, %17, %18, %19, %20, %21, %22, %23}, {%56, %57, %58, %59}, dx3, 1, 1, 1, 0;\n"
      "wgmma.commit_group.sync.aligned;\n}\n"
      : "=f"(g[0]), "=f"(g[1]), "=f"(g[2]), "=f"(g[3]), "=f"(g[4]), "=f"(g[5]), "=f"(g[6]), "=f"(g[7]), "=f"(g[8]), "=f"(g[9]), "=f"(g[10]), "=f"(g[11]),
        "=f"(h[0]), "=f"(h[1]), "=f"(h[2]), "=f"(h[3]), "=f"(h[4]), "=f"(h[5]), "=f"(h[6]), "=f"(h[7]), "=f"(h[8]), "=f"(h[9]), "=f"(h[10]), "=f"(h[11])
      : "r"(w[0]), "r"(w[1]), "r"(w[2]), "r"(w[3]), "r"(w[4]), "r"(w[5]), "r"(w[6]), "r"(w[7]), "r"(w[8]), "r"(w[9]), "r"(w[10]), "r"(w[11]), "r"(w[12]), "r"(w[13]), "r"(w[14]), "r"(w[15]), "r"(w[16]), "r"(w[17]), "r"(w[18]), "r"(w[19]), "r"(w[20]), "r"(w[21]), "r"(w[22]), "r"(w[23]), "r"(w[24]), "r"(w[25]), "r"(w[26]), "r"(w[27]), "r"(w[28]), "r"(w[29]), "r"(w[30]), "r"(w[31]), "r"(w[32]), "r"(w[33]), "r"(w[34]), "r"(w[35]), "r"(w[36]), "r"(w[37]), "r"(w[38]), "r"(w[39]), "r"(dx), "l"(de), "l"(dh)
      : "memory");
  }
  static __device__ __forceinline__ void wait_g(float* g) {
    asm volatile("wgmma.wait_group.sync.aligned 1;\n"
      : "+f"(g[0]), "+f"(g[1]), "+f"(g[2]), "+f"(g[3]), "+f"(g[4]), "+f"(g[5]), "+f"(g[6]), "+f"(g[7]), "+f"(g[8]), "+f"(g[9]), "+f"(g[10]), "+f"(g[11])
      :: "memory");
  }
  static __device__ __forceinline__ void wait_h(float* h) {
    asm volatile("wgmma.wait_group.sync.aligned 0;\n"
      : "+f"(h[0]), "+f"(h[1]), "+f"(h[2]), "+f"(h[3]), "+f"(h[4]), "+f"(h[5]), "+f"(h[6]), "+f"(h[7]), "+f"(h[8]), "+f"(h[9]), "+f"(h[10]), "+f"(h[11])
      :: "memory");
  }
};
template<> struct TileMMA<4> {
  static __device__ __forceinline__ void issue(float* g, float* h, const uint32_t* w, uint32_t dx, uint64_t de, uint64_t dh, uint64_t dc) {
    asm volatile(
      "{\n.reg .b64 dx0, dx1, dx2, dx3;\n.reg .b32 l1, l2, l3, hx;\nmov.b32 hx, 0x40000040;\n"
      "add.u32 l1, %72, 2;\nadd.u32 l2, %72, 4;\nadd.u32 l3, %72, 6;\n"
      "mov.b64 dx0, {%72, hx};\nmov.b64 dx1, {l1, hx};\nmov.b64 dx2, {l2, hx};\nmov.b64 dx3, {l3, hx};\n"
      "wgmma.fence.sync.aligned;\n"
      "wgmma.mma_async.sync.aligned.m64n32k16.f32.bf16.bf16 {%0, %1, %2, %3, %4, %5, %6, %7, %8, %9, %10, %11, %12, %13, %14, %15}, {%68, %69, %70, %71}, %74, 0, 1, 1, 0;\n"
      "wgmma.mma_async.sync.aligned.m64n32k16.f32.bf16.bf16 {%0, %1, %2, %3, %4, %5, %6, %7, %8, %9, %10, %11, %12, %13, %14, %15}, {%48, %49, %50, %51}, %73, 1, 1, 1, 0;\n"
      "wgmma.mma_async.sync.aligned.m64n32k16.f32.bf16.bf16 {%0, %1, %2, %3, %4, %5, %6, %7, %8, %9, %10, %11, %12, %13, %14, %15}, {%32, %33, %34, %35}, dx0, 1, 1, 1, 0;\n"
      "wgmma.mma_async.sync.aligned.m64n32k16.f32.bf16.bf16 {%0, %1, %2, %3, %4, %5, %6, %7, %8, %9, %10, %11, %12, %13, %14, %15}, {%36, %37, %38, %39}, dx1, 1, 1, 1, 0;\n"
      "wgmma.mma_async.sync.aligned.m64n32k16.f32.bf16.bf16 {%0, %1, %2, %3, %4, %5, %6, %7, %8, %9, %10, %11, %12, %13, %14, %15}, {%40, %41, %42, %43}, dx2, 1, 1, 1, 0;\n"
      "wgmma.mma_async.sync.aligned.m64n32k16.f32.bf16.bf16 {%0, %1, %2, %3, %4, %5, %6, %7, %8, %9, %10, %11, %12, %13, %14, %15}, {%44, %45, %46, %47}, dx3, 1, 1, 1, 0;\n"
      "wgmma.commit_group.sync.aligned;\n"
      "wgmma.mma_async.sync.aligned.m64n32k16.f32.bf16.bf16 {%16, %17, %18, %19, %20, %21, %22, %23, %24, %25, %26, %27, %28, %29, %30, %31}, {%52, %53, %54, %55}, dx0, 0, 1, 1, 0;\n"
      "wgmma.mma_async.sync.aligned.m64n32k16.f32.bf16.bf16 {%16, %17, %18, %19, %20, %21, %22, %23, %24, %25, %26, %27, %28, %29, %30, %31}, {%56, %57, %58, %59}, dx1, 1, 1, 1, 0;\n"
      "wgmma.mma_async.sync.aligned.m64n32k16.f32.bf16.bf16 {%16, %17, %18, %19, %20, %21, %22, %23, %24, %25, %26, %27, %28, %29, %30, %31}, {%60, %61, %62, %63}, dx2, 1, 1, 1, 0;\n"
      "wgmma.mma_async.sync.aligned.m64n32k16.f32.bf16.bf16 {%16, %17, %18, %19, %20, %21, %22, %23, %24, %25, %26, %27, %28, %29, %30, %31}, {%64, %65, %66, %67}, dx3, 1, 1, 1, 0;\n"
      "wgmma.commit_group.sync.aligned;\n}\n"
      : "=f"(g[0]), "=f"(g[1]), "=f"(g[2]), "=f"(g[3]), "=f"(g[4]), "=f"(g[5]), "=f"(g[6]), "=f"(g[7]), "=f"(g[8]), "=f"(g[9]), "=f"(g[10]), "=f"(g[11]), "=f"(g[12]), "=f"(g[13]), "=f"(g[14]), "=f"(g[15]),
        "=f"(h[0]), "=f"(h[1]), "=f"(h[2]), "=f"(h[3]), "=f"(h[4]), "=f"(h[5]), "=f"(h[6]), "=f"(h[7]), "=f"(h[8]), "=f"(h[9]), "=f"(h[10]), "=f"(h[11]), "=f"(h[12]), "=f"(h[13]), "=f"(h[14]), "=f"(h[15])
      : "r"(w[0]), "r"(w[1]), "r"(w[2]), "r"(w[3]), "r"(w[4]), "r"(w[5]), "r"(w[6]), "r"(w[7]), "r"(w[8]), "r"(w[9]), "r"(w[10]), "r"(w[11]), "r"(w[12]), "r"(w[13]), "r"(w[14]), "r"(w[15]), "r"(w[16]), "r"(w[17]), "r"(w[18]), "r"(w[19]), "r"(w[20]), "r"(w[21]), "r"(w[22]), "r"(w[23]), "r"(w[24]), "r"(w[25]), "r"(w[26]), "r"(w[27]), "r"(w[28]), "r"(w[29]), "r"(w[30]), "r"(w[31]), "r"(w[32]), "r"(w[33]), "r"(w[34]), "r"(w[35]), "r"(w[36]), "r"(w[37]), "r"(w[38]), "r"(w[39]), "r"(dx), "l"(de), "l"(dh)
      : "memory");
  }
  static __device__ __forceinline__ void wait_g(float* g) {
    asm volatile("wgmma.wait_group.sync.aligned 1;\n"
      : "+f"(g[0]), "+f"(g[1]), "+f"(g[2]), "+f"(g[3]), "+f"(g[4]), "+f"(g[5]), "+f"(g[6]), "+f"(g[7]), "+f"(g[8]), "+f"(g[9]), "+f"(g[10]), "+f"(g[11]), "+f"(g[12]), "+f"(g[13]), "+f"(g[14]), "+f"(g[15])
      :: "memory");
  }
  static __device__ __forceinline__ void wait_h(float* h) {
    asm volatile("wgmma.wait_group.sync.aligned 0;\n"
      : "+f"(h[0]), "+f"(h[1]), "+f"(h[2]), "+f"(h[3]), "+f"(h[4]), "+f"(h[5]), "+f"(h[6]), "+f"(h[7]), "+f"(h[8]), "+f"(h[9]), "+f"(h[10]), "+f"(h[11]), "+f"(h[12]), "+f"(h[13]), "+f"(h[14]), "+f"(h[15])
      :: "memory");
  }
};
template<> struct TileMMA<5> {
  static __device__ __forceinline__ void issue(float* g, float* h, const uint32_t* w, uint32_t dx, uint64_t de, uint64_t dh, uint64_t dc) {
    asm volatile(
      "{\n.reg .b64 dx0, dx1, dx2, dx3;\n.reg .b32 l1, l2, l3, hx;\nmov.b32 hx, 0x40000040;\n"
      "add.u32 l1, %80, 2;\nadd.u32 l2, %80, 4;\nadd.u32 l3, %80, 6;\n"
      "mov.b64 dx0, {%80, hx};\nmov.b64 dx1, {l1, hx};\nmov.b64 dx2, {l2, hx};\nmov.b64 dx3, {l3, hx};\n"
      "wgmma.fence.sync.aligned;\n"
      "wgmma.mma_async.sync.aligned.m64n40k16.f32.bf16.bf16 {%0, %1, %2, %3, %4, %5, %6, %7, %8, %9, %10, %11, %12, %13, %14, %15, %16, %17, %18, %19}, {%76, %77, %78, %79}, %82, 0, 1, 1, 0;\n"
      "wgmma.mma_async.sync.aligned.m64n40k16.f32.bf16.bf16 {%0, %1, %2, %3, %4, %5, %6, %7, %8, %9, %10, %11, %12, %13, %14, %15, %16, %17, %18, %19}, {%56, %57, %58, %59}, %81, 1, 1, 1, 0;\n"
      "wgmma.mma_async.sync.aligned.m64n40k16.f32.bf16.bf16 {%0, %1, %2, %3, %4, %5, %6, %7, %8, %9, %10, %11, %12, %13, %14, %15, %16, %17, %18, %19}, {%40, %41, %42, %43}, dx0, 1, 1, 1, 0;\n"
      "wgmma.mma_async.sync.aligned.m64n40k16.f32.bf16.bf16 {%0, %1, %2, %3, %4, %5, %6, %7, %8, %9, %10, %11, %12, %13, %14, %15, %16, %17, %18, %19}, {%44, %45, %46, %47}, dx1, 1, 1, 1, 0;\n"
      "wgmma.mma_async.sync.aligned.m64n40k16.f32.bf16.bf16 {%0, %1, %2, %3, %4, %5, %6, %7, %8, %9, %10, %11, %12, %13, %14, %15, %16, %17, %18, %19}, {%48, %49, %50, %51}, dx2, 1, 1, 1, 0;\n"
      "wgmma.mma_async.sync.aligned.m64n40k16.f32.bf16.bf16 {%0, %1, %2, %3, %4, %5, %6, %7, %8, %9, %10, %11, %12, %13, %14, %15, %16, %17, %18, %19}, {%52, %53, %54, %55}, dx3, 1, 1, 1, 0;\n"
      "wgmma.commit_group.sync.aligned;\n"
      "wgmma.mma_async.sync.aligned.m64n40k16.f32.bf16.bf16 {%20, %21, %22, %23, %24, %25, %26, %27, %28, %29, %30, %31, %32, %33, %34, %35, %36, %37, %38, %39}, {%60, %61, %62, %63}, dx0, 0, 1, 1, 0;\n"
      "wgmma.mma_async.sync.aligned.m64n40k16.f32.bf16.bf16 {%20, %21, %22, %23, %24, %25, %26, %27, %28, %29, %30, %31, %32, %33, %34, %35, %36, %37, %38, %39}, {%64, %65, %66, %67}, dx1, 1, 1, 1, 0;\n"
      "wgmma.mma_async.sync.aligned.m64n40k16.f32.bf16.bf16 {%20, %21, %22, %23, %24, %25, %26, %27, %28, %29, %30, %31, %32, %33, %34, %35, %36, %37, %38, %39}, {%68, %69, %70, %71}, dx2, 1, 1, 1, 0;\n"
      "wgmma.mma_async.sync.aligned.m64n40k16.f32.bf16.bf16 {%20, %21, %22, %23, %24, %25, %26, %27, %28, %29, %30, %31, %32, %33, %34, %35, %36, %37, %38, %39}, {%72, %73, %74, %75}, dx3, 1, 1, 1, 0;\n"
      "wgmma.commit_group.sync.aligned;\n}\n"
      : "=f"(g[0]), "=f"(g[1]), "=f"(g[2]), "=f"(g[3]), "=f"(g[4]), "=f"(g[5]), "=f"(g[6]), "=f"(g[7]), "=f"(g[8]), "=f"(g[9]), "=f"(g[10]), "=f"(g[11]), "=f"(g[12]), "=f"(g[13]), "=f"(g[14]), "=f"(g[15]), "=f"(g[16]), "=f"(g[17]), "=f"(g[18]), "=f"(g[19]),
        "=f"(h[0]), "=f"(h[1]), "=f"(h[2]), "=f"(h[3]), "=f"(h[4]), "=f"(h[5]), "=f"(h[6]), "=f"(h[7]), "=f"(h[8]), "=f"(h[9]), "=f"(h[10]), "=f"(h[11]), "=f"(h[12]), "=f"(h[13]), "=f"(h[14]), "=f"(h[15]), "=f"(h[16]), "=f"(h[17]), "=f"(h[18]), "=f"(h[19])
      : "r"(w[0]), "r"(w[1]), "r"(w[2]), "r"(w[3]), "r"(w[4]), "r"(w[5]), "r"(w[6]), "r"(w[7]), "r"(w[8]), "r"(w[9]), "r"(w[10]), "r"(w[11]), "r"(w[12]), "r"(w[13]), "r"(w[14]), "r"(w[15]), "r"(w[16]), "r"(w[17]), "r"(w[18]), "r"(w[19]), "r"(w[20]), "r"(w[21]), "r"(w[22]), "r"(w[23]), "r"(w[24]), "r"(w[25]), "r"(w[26]), "r"(w[27]), "r"(w[28]), "r"(w[29]), "r"(w[30]), "r"(w[31]), "r"(w[32]), "r"(w[33]), "r"(w[34]), "r"(w[35]), "r"(w[36]), "r"(w[37]), "r"(w[38]), "r"(w[39]), "r"(dx), "l"(de), "l"(dh)
      : "memory");
  }
  static __device__ __forceinline__ void wait_g(float* g) {
    asm volatile("wgmma.wait_group.sync.aligned 1;\n"
      : "+f"(g[0]), "+f"(g[1]), "+f"(g[2]), "+f"(g[3]), "+f"(g[4]), "+f"(g[5]), "+f"(g[6]), "+f"(g[7]), "+f"(g[8]), "+f"(g[9]), "+f"(g[10]), "+f"(g[11]), "+f"(g[12]), "+f"(g[13]), "+f"(g[14]), "+f"(g[15]), "+f"(g[16]), "+f"(g[17]), "+f"(g[18]), "+f"(g[19])
      :: "memory");
  }
  static __device__ __forceinline__ void wait_h(float* h) {
    asm volatile("wgmma.wait_group.sync.aligned 0;\n"
      : "+f"(h[0]), "+f"(h[1]), "+f"(h[2]), "+f"(h[3]), "+f"(h[4]), "+f"(h[5]), "+f"(h[6]), "+f"(h[7]), "+f"(h[8]), "+f"(h[9]), "+f"(h[10]), "+f"(h[11]), "+f"(h[12]), "+f"(h[13]), "+f"(h[14]), "+f"(h[15]), "+f"(h[16]), "+f"(h[17]), "+f"(h[18]), "+f"(h[19])
      :: "memory");
  }
};
template<> struct TileMMA<6> {
  static __device__ __forceinline__ void issue(float* g, float* h, const uint32_t* w, uint32_t dx, uint64_t de, uint64_t dh, uint64_t dc) {
    asm volatile(
      "{\n.reg .b64 dx0, dx1, dx2, dx3;\n.reg .b32 l1, l2, l3, hx;\nmov.b32 hx, 0x40000040;\n"
      "add.u32 l1, %88, 2;\nadd.u32 l2, %88, 4;\nadd.u32 l3, %88, 6;\n"
      "mov.b64 dx0, {%88, hx};\nmov.b64 dx1, {l1, hx};\nmov.b64 dx2, {l2, hx};\nmov.b64 dx3, {l3, hx};\n"
      "wgmma.fence.sync.aligned;\n"
      "wgmma.mma_async.sync.aligned.m64n48k16.f32.bf16.bf16 {%0, %1, %2, %3, %4, %5, %6, %7, %8, %9, %10, %11, %12, %13, %14, %15, %16, %17, %18, %19, %20, %21, %22, %23}, {%84, %85, %86, %87}, %90, 0, 1, 1, 0;\n"
      "wgmma.mma_async.sync.aligned.m64n48k16.f32.bf16.bf16 {%0, %1, %2, %3, %4, %5, %6, %7, %8, %9, %10, %11, %12, %13, %14, %15, %16, %17, %18, %19, %20, %21, %22, %23}, {%64, %65, %66, %67}, %89, 1, 1, 1, 0;\n"
      "wgmma.mma_async.sync.aligned.m64n48k16.f32.bf16.bf16 {%0, %1, %2, %3, %4, %5, %6, %7, %8, %9, %10, %11, %12, %13, %14, %15, %16, %17, %18, %19, %20, %21, %22, %23}, {%48, %49, %50, %51}, dx0, 1, 1, 1, 0;\n"
      "wgmma.mma_async.sync.aligned.m64n48k16.f32.bf16.bf16 {%0, %1, %2, %3, %4, %5, %6, %7, %8, %9, %10, %11, %12, %13, %14, %15, %16, %17, %18, %19, %20, %21, %22, %23}, {%52, %53, %54, %55}, dx1, 1, 1, 1, 0;\n"
      "wgmma.mma_async.sync.aligned.m64n48k16.f32.bf16.bf16 {%0, %1, %2, %3, %4, %5, %6, %7, %8, %9, %10, %11, %12, %13, %14, %15, %16, %17, %18, %19, %20, %21, %22, %23}, {%56, %57, %58, %59}, dx2, 1, 1, 1, 0;\n"
      "wgmma.mma_async.sync.aligned.m64n48k16.f32.bf16.bf16 {%0, %1, %2, %3, %4, %5, %6, %7, %8, %9, %10, %11, %12, %13, %14, %15, %16, %17, %18, %19, %20, %21, %22, %23}, {%60, %61, %62, %63}, dx3, 1, 1, 1, 0;\n"
      "wgmma.commit_group.sync.aligned;\n"
      "wgmma.mma_async.sync.aligned.m64n48k16.f32.bf16.bf16 {%24, %25, %26, %27, %28, %29, %30, %31, %32, %33, %34, %35, %36, %37, %38, %39, %40, %41, %42, %43, %44, %45, %46, %47}, {%68, %69, %70, %71}, dx0, 0, 1, 1, 0;\n"
      "wgmma.mma_async.sync.aligned.m64n48k16.f32.bf16.bf16 {%24, %25, %26, %27, %28, %29, %30, %31, %32, %33, %34, %35, %36, %37, %38, %39, %40, %41, %42, %43, %44, %45, %46, %47}, {%72, %73, %74, %75}, dx1, 1, 1, 1, 0;\n"
      "wgmma.mma_async.sync.aligned.m64n48k16.f32.bf16.bf16 {%24, %25, %26, %27, %28, %29, %30, %31, %32, %33, %34, %35, %36, %37, %38, %39, %40, %41, %42, %43, %44, %45, %46, %47}, {%76, %77, %78, %79}, dx2, 1, 1, 1, 0;\n"
      "wgmma.mma_async.sync.aligned.m64n48k16.f32.bf16.bf16 {%24, %25, %26, %27, %28, %29, %30, %31, %32, %33, %34, %35, %36, %37, %38, %39, %40, %41, %42, %43, %44, %45, %46, %47}, {%80, %81, %82, %83}, dx3, 1, 1, 1, 0;\n"
      "wgmma.commit_group.sync.aligned;\n}\n"
      : "=f"(g[0]), "=f"(g[1]), "=f"(g[2]), "=f"(g[3]), "=f"(g[4]), "=f"(g[5]), "=f"(g[6]), "=f"(g[7]), "=f"(g[8]), "=f"(g[9]), "=f"(g[10]), "=f"(g[11]), "=f"(g[12]), "=f"(g[13]), "=f"(g[14]), "=f"(g[15]), "=f"(g[16]), "=f"(g[17]), "=f"(g[18]), "=f"(g[19]), "=f"(g[20]), "=f"(g[21]), "=f"(g[22]), "=f"(g[23]),
        "=f"(h[0]), "=f"(h[1]), "=f"(h[2]), "=f"(h[3]), "=f"(h[4]), "=f"(h[5]), "=f"(h[6]), "=f"(h[7]), "=f"(h[8]), "=f"(h[9]), "=f"(h[10]), "=f"(h[11]), "=f"(h[12]), "=f"(h[13]), "=f"(h[14]), "=f"(h[15]), "=f"(h[16]), "=f"(h[17]), "=f"(h[18]), "=f"(h[19]), "=f"(h[20]), "=f"(h[21]), "=f"(h[22]), "=f"(h[23])
      : "r"(w[0]), "r"(w[1]), "r"(w[2]), "r"(w[3]), "r"(w[4]), "r"(w[5]), "r"(w[6]), "r"(w[7]), "r"(w[8]), "r"(w[9]), "r"(w[10]), "r"(w[11]), "r"(w[12]), "r"(w[13]), "r"(w[14]), "r"(w[15]), "r"(w[16]), "r"(w[17]), "r"(w[18]), "r"(w[19]), "r"(w[20]), "r"(w[21]), "r"(w[22]), "r"(w[23]), "r"(w[24]), "r"(w[25]), "r"(w[26]), "r"(w[27]), "r"(w[28]), "r"(w[29]), "r"(w[30]), "r"(w[31]), "r"(w[32]), "r"(w[33]), "r"(w[34]), "r"(w[35]), "r"(w[36]), "r"(w[37]), "r"(w[38]), "r"(w[39]), "r"(dx), "l"(de), "l"(dh)
      : "memory");
  }
  static __device__ __forceinline__ void wait_g(float* g) {
    asm volatile("wgmma.wait_group.sync.aligned 1;\n"
      : "+f"(g[0]), "+f"(g[1]), "+f"(g[2]), "+f"(g[3]), "+f"(g[4]), "+f"(g[5]), "+f"(g[6]), "+f"(g[7]), "+f"(g[8]), "+f"(g[9]), "+f"(g[10]), "+f"(g[11]), "+f"(g[12]), "+f"(g[13]), "+f"(g[14]), "+f"(g[15]), "+f"(g[16]), "+f"(g[17]), "+f"(g[18]), "+f"(g[19]), "+f"(g[20]), "+f"(g[21]), "+f"(g[22]), "+f"(g[23])
      :: "memory");
  }
  static __device__ __forceinline__ void wait_h(float* h) {
    asm volatile("wgmma.wait_group.sync.aligned 0;\n"
      : "+f"(h[0]), "+f"(h[1]), "+f"(h[2]), "+f"(h[3]), "+f"(h[4]), "+f"(h[5]), "+f"(h[6]), "+f"(h[7]), "+f"(h[8]), "+f"(h[9]), "+f"(h[10]), "+f"(h[11]), "+f"(h[12]), "+f"(h[13]), "+f"(h[14]), "+f"(h[15]), "+f"(h[16]), "+f"(h[17]), "+f"(h[18]), "+f"(h[19]), "+f"(h[20]), "+f"(h[21]), "+f"(h[22]), "+f"(h[23])
      :: "memory");
  }
};
template<> struct TileMMA<7> {
  static __device__ __forceinline__ void issue(float* g, float* h, const uint32_t* w, uint32_t dx, uint64_t de, uint64_t dh, uint64_t dc) {
    asm volatile(
      "{\n.reg .b64 dx0, dx1, dx2, dx3;\n.reg .b32 l1, l2, l3, hx;\nmov.b32 hx, 0x40000040;\n"
      "add.u32 l1, %96, 2;\nadd.u32 l2, %96, 4;\nadd.u32 l3, %96, 6;\n"
      "mov.b64 dx0, {%96, hx};\nmov.b64 dx1, {l1, hx};\nmov.b64 dx2, {l2, hx};\nmov.b64 dx3, {l3, hx};\n"
      "wgmma.fence.sync.aligned;\n"
      "wgmma.mma_async.sync.aligned.m64n56k16.f32.bf16.bf16 {%0, %1, %2, %3, %4, %5, %6, %7, %8, %9, %10, %11, %12, %13, %14, %15, %16, %17, %18, %19, %20, %21, %22, %23, %24, %25, %26, %27}, {%92, %93, %94, %95}, %98, 0, 1, 1, 0;\n"
      "wgmma.mma_async.sync.aligned.m64n56k16.f32.bf16.bf16 {%0, %1, %2, %3, %4, %5, %6, %7, %8, %9, %10, %11, %12, %13, %14, %15, %16, %17, %18, %19, %20, %21, %22, %23, %24, %25, %26, %27}, {%72, %73, %74, %75}, %97, 1, 1, 1, 0;\n"
      "wgmma.mma_async.sync.aligned.m64n56k16.f32.bf16.bf16 {%0, %1, %2, %3, %4, %5, %6, %7, %8, %9, %10, %11, %12, %13, %14, %15, %16, %17, %18, %19, %20, %21, %22, %23, %24, %25, %26, %27}, {%56, %57, %58, %59}, dx0, 1, 1, 1, 0;\n"
      "wgmma.mma_async.sync.aligned.m64n56k16.f32.bf16.bf16 {%0, %1, %2, %3, %4, %5, %6, %7, %8, %9, %10, %11, %12, %13, %14, %15, %16, %17, %18, %19, %20, %21, %22, %23, %24, %25, %26, %27}, {%60, %61, %62, %63}, dx1, 1, 1, 1, 0;\n"
      "wgmma.mma_async.sync.aligned.m64n56k16.f32.bf16.bf16 {%0, %1, %2, %3, %4, %5, %6, %7, %8, %9, %10, %11, %12, %13, %14, %15, %16, %17, %18, %19, %20, %21, %22, %23, %24, %25, %26, %27}, {%64, %65, %66, %67}, dx2, 1, 1, 1, 0;\n"
      "wgmma.mma_async.sync.aligned.m64n56k16.f32.bf16.bf16 {%0, %1, %2, %3, %4, %5, %6, %7, %8, %9, %10, %11, %12, %13, %14, %15, %16, %17, %18, %19, %20, %21, %22, %23, %24, %25, %26, %27}, {%68, %69, %70, %71}, dx3, 1, 1, 1, 0;\n"
      "wgmma.commit_group.sync.aligned;\n"
      "wgmma.mma_async.sync.aligned.m64n56k16.f32.bf16.bf16 {%28, %29, %30, %31, %32, %33, %34, %35, %36, %37, %38, %39, %40, %41, %42, %43, %44, %45, %46, %47, %48, %49, %50, %51, %52, %53, %54, %55}, {%76, %77, %78, %79}, dx0, 0, 1, 1, 0;\n"
      "wgmma.mma_async.sync.aligned.m64n56k16.f32.bf16.bf16 {%28, %29, %30, %31, %32, %33, %34, %35, %36, %37, %38, %39, %40, %41, %42, %43, %44, %45, %46, %47, %48, %49, %50, %51, %52, %53, %54, %55}, {%80, %81, %82, %83}, dx1, 1, 1, 1, 0;\n"
      "wgmma.mma_async.sync.aligned.m64n56k16.f32.bf16.bf16 {%28, %29, %30, %31, %32, %33, %34, %35, %36, %37, %38, %39, %40, %41, %42, %43, %44, %45, %46, %47, %48, %49, %50, %51, %52, %53, %54, %55}, {%84, %85, %86, %87}, dx2, 1, 1, 1, 0;\n"
      "wgmma.mma_async.sync.aligned.m64n56k16.f32.bf16.bf16 {%28, %29, %30, %31, %32, %33, %34, %35, %36, %37, %38, %39, %40, %41, %42, %43, %44, %45, %46, %47, %48, %49, %50, %51, %52, %53, %54, %55}, {%88, %89, %90, %91}, dx3, 1, 1, 1, 0;\n"
      "wgmma.commit_group.sync.aligned;\n}\n"
      : "=f"(g[0]), "=f"(g[1]), "=f"(g[2]), "=f"(g[3]), "=f"(g[4]), "=f"(g[5]), "=f"(g[6]), "=f"(g[7]), "=f"(g[8]), "=f"(g[9]), "=f"(g[10]), "=f"(g[11]), "=f"(g[12]), "=f"(g[13]), "=f"(g[14]), "=f"(g[15]), "=f"(g[16]), "=f"(g[17]), "=f"(g[18]), "=f"(g[19]), "=f"(g[20]), "=f"(g[21]), "=f"(g[22]), "=f"(g[23]), "=f"(g[24]), "=f"(g[25]), "=f"(g[26]), "=f"(g[27]),
        "=f"(h[0]), "=f"(h[1]), "=f"(h[2]), "=f"(h[3]), "=f"(h[4]), "=f"(h[5]), "=f"(h[6]), "=f"(h[7]), "=f"(h[8]), "=f"(h[9]), "=f"(h[10]), "=f"(h[11]), "=f"(h[12]), "=f"(h[13]), "=f"(h[14]), "=f"(h[15]), "=f"(h[16]), "=f"(h[17]), "=f"(h[18]), "=f"(h[19]), "=f"(h[20]), "=f"(h[21]), "=f"(h[22]), "=f"(h[23]), "=f"(h[24]), "=f"(h[25]), "=f"(h[26]), "=f"(h[27])
      : "r"(w[0]), "r"(w[1]), "r"(w[2]), "r"(w[3]), "r"(w[4]), "r"(w[5]), "r"(w[6]), "r"(w[7]), "r"(w[8]), "r"(w[9]), "r"(w[10]), "r"(w[11]), "r"(w[12]), "r"(w[13]), "r"(w[14]), "r"(w[15]), "r"(w[16]), "r"(w[17]), "r"(w[18]), "r"(w[19]), "r"(w[20]), "r"(w[21]), "r"(w[22]), "r"(w[23]), "r"(w[24]), "r"(w[25]), "r"(w[26]), "r"(w[27]), "r"(w[28]), "r"(w[29]), "r"(w[30]), "r"(w[31]), "r"(w[32]), "r"(w[33]), "r"(w[34]), "r"(w[35]), "r"(w[36]), "r"(w[37]), "r"(w[38]), "r"(w[39]), "r"(dx), "l"(de), "l"(dh)
      : "memory");
  }
  static __device__ __forceinline__ void wait_g(float* g) {
    asm volatile("wgmma.wait_group.sync.aligned 1;\n"
      : "+f"(g[0]), "+f"(g[1]), "+f"(g[2]), "+f"(g[3]), "+f"(g[4]), "+f"(g[5]), "+f"(g[6]), "+f"(g[7]), "+f"(g[8]), "+f"(g[9]), "+f"(g[10]), "+f"(g[11]), "+f"(g[12]), "+f"(g[13]), "+f"(g[14]), "+f"(g[15]), "+f"(g[16]), "+f"(g[17]), "+f"(g[18]), "+f"(g[19]), "+f"(g[20]), "+f"(g[21]), "+f"(g[22]), "+f"(g[23]), "+f"(g[24]), "+f"(g[25]), "+f"(g[26]), "+f"(g[27])
      :: "memory");
  }
  static __device__ __forceinline__ void wait_h(float* h) {
    asm volatile("wgmma.wait_group.sync.aligned 0;\n"
      : "+f"(h[0]), "+f"(h[1]), "+f"(h[2]), "+f"(h[3]), "+f"(h[4]), "+f"(h[5]), "+f"(h[6]), "+f"(h[7]), "+f"(h[8]), "+f"(h[9]), "+f"(h[10]), "+f"(h[11]), "+f"(h[12]), "+f"(h[13]), "+f"(h[14]), "+f"(h[15]), "+f"(h[16]), "+f"(h[17]), "+f"(h[18]), "+f"(h[19]), "+f"(h[20]), "+f"(h[21]), "+f"(h[22]), "+f"(h[23]), "+f"(h[24]), "+f"(h[25]), "+f"(h[26]), "+f"(h[27])
      :: "memory");
  }
};
template<> struct TileMMA<8> {
  static __device__ __forceinline__ void issue(float* g, float* h, const uint32_t* w, uint32_t dx, uint64_t de, uint64_t dh, uint64_t dc) {
    asm volatile(
      "{\n.reg .b64 dx0, dx1, dx2, dx3;\n.reg .b32 l1, l2, l3, hx;\nmov.b32 hx, 0x40000040;\n"
      "add.u32 l1, %104, 2;\nadd.u32 l2, %104, 4;\nadd.u32 l3, %104, 6;\n"
      "mov.b64 dx0, {%104, hx};\nmov.b64 dx1, {l1, hx};\nmov.b64 dx2, {l2, hx};\nmov.b64 dx3, {l3, hx};\n"
      "wgmma.fence.sync.aligned;\n"
      "wgmma.mma_async.sync.aligned.m64n64k16.f32.bf16.bf16 {%0, %1, %2, %3, %4, %5, %6, %7, %8, %9, %10, %11, %12, %13, %14, %15, %16, %17, %18, %19, %20, %21, %22, %23, %24, %25, %26, %27, %28, %29, %30, %31}, {%100, %101, %102, %103}, %106, 0, 1, 1, 0;\n"
      "wgmma.mma_async.sync.aligned.m64n64k16.f32.bf16.bf16 {%0, %1, %2, %3, %4, %5, %6, %7, %8, %9, %10, %11, %12, %13, %14, %15, %16, %17, %18, %19, %20, %21, %22, %23, %24, %25, %26, %27, %28, %29, %30, %31}, {%80, %81, %82, %83}, %105, 1, 1, 1, 0;\n"
      "wgmma.mma_async.sync.aligned.m64n64k16.f32.bf16.bf16 {%0, %1, %2, %3, %4, %5, %6, %7, %8, %9, %10, %11, %12, %13, %14, %15, %16, %17, %18, %19, %20, %21, %22, %23, %24, %25, %26, %27, %28, %29, %30, %31}, {%64, %65, %66, %67}, dx0, 1, 1, 1, 0;\n"
      "wgmma.mma_async.sync.aligned.m64n64k16.f32.bf16.bf16 {%0, %1, %2, %3, %4, %5, %6, %7, %8, %9, %10, %11, %12, %13, %14, %15, %16, %17, %18, %19, %20, %21, %22, %23, %24, %25, %26, %27, %28, %29, %30, %31}, {%68, %69, %70, %71}, dx1, 1, 1, 1, 0;\n"
      "wgmma.mma_async.sync.aligned.m64n64k16.f32.bf16.bf16 {%0, %1, %2, %3, %4, %5, %6, %7, %8, %9, %10, %11, %12, %13, %14, %15, %16, %17, %18, %19, %20, %21, %22, %23, %24, %25, %26, %27, %28, %29, %30, %31}, {%72, %73, %74, %75}, dx2, 1, 1, 1, 0;\n"
      "wgmma.mma_async.sync.aligned.m64n64k16.f32.bf16.bf16 {%0, %1, %2, %3, %4, %5, %6, %7, %8, %9, %10, %11, %12, %13, %14, %15, %16, %17, %18, %19, %20, %21, %22, %23, %24, %25, %26, %27, %28, %29, %30, %31}, {%76, %77, %78, %79}, dx3, 1, 1, 1, 0;\n"
      "wgmma.commit_group.sync.aligned;\n"
      "wgmma.mma_async.sync.aligned.m64n64k16.f32.bf16.bf16 {%32, %33, %34, %35, %36, %37, %38, %39, %40, %41, %42, %43, %44, %45, %46, %47, %48, %49, %50, %51, %52, %53, %54, %55, %56, %57, %58, %59, %60, %61, %62, %63}, {%84, %85, %86, %87}, dx0, 0, 1, 1, 0;\n"
      "wgmma.mma_async.sync.aligned.m64n64k16.f32.bf16.bf16 {%32, %33, %34, %35, %36, %37, %38, %39, %40, %41, %42, %43, %44, %45, %46, %47, %48, %49, %50, %51, %52, %53, %54, %55, %56, %57, %58, %59, %60, %61, %62, %63}, {%88, %89, %90, %91}, dx1, 1, 1, 1, 0;\n"
      "wgmma.mma_async.sync.aligned.m64n64k16.f32.bf16.bf16 {%32, %33, %34, %35, %36, %37, %38, %39, %40, %41, %42, %43, %44, %45, %46, %47, %48, %49, %50, %51, %52, %53, %54, %55, %56, %57, %58, %59, %60, %61, %62, %63}, {%92, %93, %94, %95}, dx2, 1, 1, 1, 0;\n"
      "wgmma.mma_async.sync.aligned.m64n64k16.f32.bf16.bf16 {%32, %33, %34, %35, %36, %37, %38, %39, %40, %41, %42, %43, %44, %45, %46, %47, %48, %49, %50, %51, %52, %53, %54, %55, %56, %57, %58, %59, %60, %61, %62, %63}, {%96, %97, %98, %99}, dx3, 1, 1, 1, 0;\n"
      "wgmma.commit_group.sync.aligned;\n}\n"
      : "=f"(g[0]), "=f"(g[1]), "=f"(g[2]), "=f"(g[3]), "=f"(g[4]), "=f"(g[5]), "=f"(g[6]), "=f"(g[7]), "=f"(g[8]), "=f"(g[9]), "=f"(g[10]), "=f"(g[11]), "=f"(g[12]), "=f"(g[13]), "=f"(g[14]), "=f"(g[15]), "=f"(g[16]), "=f"(g[17]), "=f"(g[18]), "=f"(g[19]), "=f"(g[20]), "=f"(g[21]), "=f"(g[22]), "=f"(g[23]), "=f"(g[24]), "=f"(g[25]), "=f"(g[26]), "=f"(g[27]), "=f"(g[28]), "=f"(g[29]), "=f"(g[30]), "=f"(g[31]),
        "=f"(h[0]), "=f"(h[1]), "=f"(h[2]), "=f"(h[3]), "=f"(h[4]), "=f"(h[5]), "=f"(h[6]), "=f"(h[7]), "=f"(h[8]), "=f"(h[9]), "=f"(h[10]), "=f"(h[11]), "=f"(h[12]), "=f"(h[13]), "=f"(h[14]), "=f"(h[15]), "=f"(h[16]), "=f"(h[17]), "=f"(h[18]), "=f"(h[19]), "=f"(h[20]), "=f"(h[21]), "=f"(h[22]), "=f"(h[23]), "=f"(h[24]), "=f"(h[25]), "=f"(h[26]), "=f"(h[27]), "=f"(h[28]), "=f"(h[29]), "=f"(h[30]), "=f"(h[31])
      : "r"(w[0]), "r"(w[1]), "r"(w[2]), "r"(w[3]), "r"(w[4]), "r"(w[5]), "r"(w[6]), "r"(w[7]), "r"(w[8]), "r"(w[9]), "r"(w[10]), "r"(w[11]), "r"(w[12]), "r"(w[13]), "r"(w[14]), "r"(w[15]), "r"(w[16]), "r"(w[17]), "r"(w[18]), "r"(w[19]), "r"(w[20]), "r"(w[21]), "r"(w[22]), "r"(w[23]), "r"(w[24]), "r"(w[25]), "r"(w[26]), "r"(w[27]), "r"(w[28]), "r"(w[29]), "r"(w[30]), "r"(w[31]), "r"(w[32]), "r"(w[33]), "r"(w[34]), "r"(w[35]), "r"(w[36]), "r"(w[37]), "r"(w[38]), "r"(w[39]), "r"(dx), "l"(de), "l"(dh)
      : "memory");
  }
  static __device__ __forceinline__ void wait_g(float* g) {
    asm volatile("wgmma.wait_group.sync.aligned 1;\n"
      : "+f"(g[0]), "+f"(g[1]), "+f"(g[2]), "+f"(g[3]), "+f"(g[4]), "+f"(g[5]), "+f"(g[6]), "+f"(g[7]), "+f"(g[8]), "+f"(g[9]), "+f"(g[10]), "+f"(g[11]), "+f"(g[12]), "+f"(g[13]), "+f"(g[14]), "+f"(g[15]), "+f"(g[16]), "+f"(g[17]), "+f"(g[18]), "+f"(g[19]), "+f"(g[20]), "+f"(g[21]), "+f"(g[22]), "+f"(g[23]), "+f"(g[24]), "+f"(g[25]), "+f"(g[26]), "+f"(g[27]), "+f"(g[28]), "+f"(g[29]), "+f"(g[30]), "+f"(g[31])
      :: "memory");
  }
  static __device__ __forceinline__ void wait_h(float* h) {
    asm volatile("wgmma.wait_group.sync.aligned 0;\n"
      : "+f"(h[0]), "+f"(h[1]), "+f"(h[2]), "+f"(h[3]), "+f"(h[4]), "+f"(h[5]), "+f"(h[6]), "+f"(h[7]), "+f"(h[8]), "+f"(h[9]), "+f"(h[10]), "+f"(h[11]), "+f"(h[12]), "+f"(h[13]), "+f"(h[14]), "+f"(h[15]), "+f"(h[16]), "+f"(h[17]), "+f"(h[18]), "+f"(h[19]), "+f"(h[20]), "+f"(h[21]), "+f"(h[22]), "+f"(h[23]), "+f"(h[24]), "+f"(h[25]), "+f"(h[26]), "+f"(h[27]), "+f"(h[28]), "+f"(h[29]), "+f"(h[30]), "+f"(h[31])
      :: "memory");
  }
};
template<> struct TileMMA<9> {
  static __device__ __forceinline__ void issue(float* g, float* h, const uint32_t* w, uint32_t dx, uint64_t de, uint64_t dh, uint64_t dc) {
    asm volatile(
      "{\n.reg .b64 dx0, dx1, dx2, dx3;\n.reg .b32 l1, l2, l3, hx;\nmov.b32 hx, 0x40000040;\n"
      "add.u32 l1, %112, 2;\nadd.u32 l2, %112, 4;\nadd.u32 l3, %112, 6;\n"
      "mov.b64 dx0, {%112, hx};\nmov.b64 dx1, {l1, hx};\nmov.b64 dx2, {l2, hx};\nmov.b64 dx3, {l3, hx};\n"
      "wgmma.fence.sync.aligned;\n"
      "wgmma.mma_async.sync.aligned.m64n72k16.f32.bf16.bf16 {%0, %1, %2, %3, %4, %5, %6, %7, %8, %9, %10, %11, %12, %13, %14, %15, %16, %17, %18, %19, %20, %21, %22, %23, %24, %25, %26, %27, %28, %29, %30, %31, %32, %33, %34, %35}, {%108, %109, %110, %111}, %114, 0, 1, 1, 0;\n"
      "wgmma.mma_async.sync.aligned.m64n72k16.f32.bf16.bf16 {%0, %1, %2, %3, %4, %5, %6, %7, %8, %9, %10, %11, %12, %13, %14, %15, %16, %17, %18, %19, %20, %21, %22, %23, %24, %25, %26, %27, %28, %29, %30, %31, %32, %33, %34, %35}, {%88, %89, %90, %91}, %113, 1, 1, 1, 0;\n"
      "wgmma.mma_async.sync.aligned.m64n72k16.f32.bf16.bf16 {%0, %1, %2, %3, %4, %5, %6, %7, %8, %9, %10, %11, %12, %13, %14, %15, %16, %17, %18, %19, %20, %21, %22, %23, %24, %25, %26, %27, %28, %29, %30, %31, %32, %33, %34, %35}, {%72, %73, %74, %75}, dx0, 1, 1, 1, 0;\n"
      "wgmma.mma_async.sync.aligned.m64n72k16.f32.bf16.bf16 {%0, %1, %2, %3, %4, %5, %6, %7, %8, %9, %10, %11, %12, %13, %14, %15, %16, %17, %18, %19, %20, %21, %22, %23, %24, %25, %26, %27, %28, %29, %30, %31, %32, %33, %34, %35}, {%76, %77, %78, %79}, dx1, 1, 1, 1, 0;\n"
      "wgmma.mma_async.sync.aligned.m64n72k16.f32.bf16.bf16 {%0, %1, %2, %3, %4, %5, %6, %7, %8, %9, %10, %11, %12, %13, %14, %15, %16, %17, %18, %19, %20, %21, %22, %23, %24, %25, %26, %27, %28, %29, %30, %31, %32, %33, %34, %35}, {%80, %81, %82, %83}, dx2, 1, 1, 1, 0;\n"
      "wgmma.mma_async.sync.aligned.m64n72k16.f32.bf16.bf16 {%0, %1, %2, %3, %4, %5, %6, %7, %8, %9, %10, %11, %12, %13, %14, %15, %16, %17, %18, %19, %20, %21, %22, %23, %24, %25, %26, %27, %28, %29, %30, %31, %32, %33, %34, %35}, {%84, %85, %86, %87}, dx3, 1, 1, 1, 0;\n"
      "wgmma.commit_group.sync.aligned;\n"
      "wgmma.mma_async.sync.aligned.m64n72k16.f32.bf16.bf16 {%36, %37, %38, %39, %40, %41, %42, %43, %44, %45, %46, %47, %48, %49, %50, %51, %52, %53, %54, %55, %56, %57, %58, %59, %60, %61, %62, %63, %64, %65, %66, %67, %68, %69, %70, %71}, {%92, %93, %94, %95}, dx0, 0, 1, 1, 0;\n"
      "wgmma.mma_async.sync.aligned.m64n72k16.f32.bf16.bf16 {%36, %37, %38, %39, %40, %41, %42, %43, %44, %45, %46, %47, %48, %49, %50, %51, %52, %53, %54, %55, %56, %57, %58, %59, %60, %61, %62, %63, %64, %65, %66, %67, %68, %69, %70, %71}, {%96, %97, %98, %99}, dx1, 1, 1, 1, 0;\n"
      "wgmma.mma_async.sync.aligned.m64n72k16.f32.bf16.bf16 {%36, %37, %38, %39, %40, %41, %42, %43, %44, %45, %46, %47, %48, %49, %50, %51, %52, %53, %54, %55, %56, %57, %58, %59, %60, %61, %62, %63, %64, %65, %66, %67, %68, %69, %70, %71}, {%100, %101, %102, %103}, dx2, 1, 1, 1, 0;\n"
      "wgmma.mma_async.sync.aligned.m64n72k16.f32.bf16.bf16 {%36, %37, %38, %39, %40, %41, %42, %43, %44, %45, %46, %47, %48, %49, %50, %51, %52, %53, %54, %55, %56, %57, %58, %59, %60, %61, %62, %63, %64, %65, %66, %67, %68, %69, %70, %71}, {%104, %105, %106, %107}, dx3, 1, 1, 1, 0;\n"
      "wgmma.commit_group.sync.aligned;\n}\n"
      : "=f"(g[0]), "=f"(g[1]), "=f"(g[2]), "=f"(g[3]), "=f"(g[4]), "=f"(g[5]), "=f"(g[6]), "=f"(g[7]), "=f"(g[8]), "=f"(g[9]), "=f"(g[10]), "=f"(g[11]), "=f"(g[12]), "=f"(g[13]), "=f"(g[14]), "=f"(g[15]), "=f"(g[16]), "=f"(g[17]), "=f"(g[18]), "=f"(g[19]), "=f"(g[20]), "=f"(g[21]), "=f"(g[22]), "=f"(g[23]), "=f"(g[24]), "=f"(g[25]), "=f"(g[26]), "=f"(g[27]), "=f"(g[28]), "=f"(g[29]), "=f"(g[30]), "=f"(g[31]), "=f"(g[32]), "=f"(g[33]), "=f"(g[34]), "=f"(g[35]),
        "=f"(h[0]), "=f"(h[1]), "=f"(h[2]), "=f"(h[3]), "=f"(h[4]), "=f"(h[5]), "=f"(h[6]), "=f"(h[7]), "=f"(h[8]), "=f"(h[9]), "=f"(h[10]), "=f"(h[11]), "=f"(h[12]), "=f"(h[13]), "=f"(h[14]), "=f"(h[15]), "=f"(h[16]), "=f"(h[17]), "=f"(h[18]), "=f"(h[19]), "=f"(h[20]), "=f"(h[21]), "=f"(h[22]), "=f"(h[23]), "=f"(h[24]), "=f"(h[25]), "=f"(h[26]), "=f"(h[27]), "=f"(h[28]), "=f"(h[29]), "=f"(h[30]), "=f"(h[31]), "=f"(h[32]), "=f"(h[33]), "=f"(h[34]), "=f"(h[35])
      : "r"(w[0]), "r"(w[1]), "r"(w[2]), "r"(w[3]), "r"(w[4]), "r"(w[5]), "r"(w[6]), "r"(w[7]), "r"(w[8]), "r"(w[9]), "r"(w[10]), "r"(w[11]), "r"(w[12]), "r"(w[13]), "r"(w[14]), "r"(w[15]), "r"(w[16]), "r"(w[17]), "r"(w[18]), "r"(w[19]), "r"(w[20]), "r"(w[21]), "r"(w[22]), "r"(w[23]), "r"(w[24]), "r"(w[25]), "r"(w[26]), "r"(w[27]), "r"(w[28]), "r"(w[29]), "r"(w[30]), "r"(w[31]), "r"(w[32]), "r"(w[33]), "r"(w[34]), "r"(w[35]), "r"(w[36]), "r"(w[37]), "r"(w[38]), "r"(w[39]), "r"(dx), "l"(de), "l"(dh)
      : "memory");
  }
  static __device__ __forceinline__ void wait_g(float* g) {
    asm volatile("wgmma.wait_group.sync.aligned 1;\n"
      : "+f"(g[0]), "+f"(g[1]), "+f"(g[2]), "+f"(g[3]), "+f"(g[4]), "+f"(g[5]), "+f"(g[6]), "+f"(g[7]), "+f"(g[8]), "+f"(g[9]), "+f"(g[10]), "+f"(g[11]), "+f"(g[12]), "+f"(g[13]), "+f"(g[14]), "+f"(g[15]), "+f"(g[16]), "+f"(g[17]), "+f"(g[18]), "+f"(g[19]), "+f"(g[20]), "+f"(g[21]), "+f"(g[22]), "+f"(g[23]), "+f"(g[24]), "+f"(g[25]), "+f"(g[26]), "+f"(g[27]), "+f"(g[28]), "+f"(g[29]), "+f"(g[30]), "+f"(g[31]), "+f"(g[32]), "+f"(g[33]), "+f"(g[34]), "+f"(g[35])
      :: "memory");
  }
  static __device__ __forceinline__ void wait_h(float* h) {
    asm volatile("wgmma.wait_group.sync.aligned 0;\n"
      : "+f"(h[0]), "+f"(h[1]), "+f"(h[2]), "+f"(h[3]), "+f"(h[4]), "+f"(h[5]), "+f"(h[6]), "+f"(h[7]), "+f"(h[8]), "+f"(h[9]), "+f"(h[10]), "+f"(h[11]), "+f"(h[12]), "+f"(h[13]), "+f"(h[14]), "+f"(h[15]), "+f"(h[16]), "+f"(h[17]), "+f"(h[18]), "+f"(h[19]), "+f"(h[20]), "+f"(h[21]), "+f"(h[22]), "+f"(h[23]), "+f"(h[24]), "+f"(h[25]), "+f"(h[26]), "+f"(h[27]), "+f"(h[28]), "+f"(h[29]), "+f"(h[30]), "+f"(h[31]), "+f"(h[32]), "+f"(h[33]), "+f"(h[34]), "+f"(h[35])
      :: "memory");
  }
};
template<> struct TileMMA<10> {
  static __device__ __forceinline__ void issue(float* g, float* h, const uint32_t* w, uint32_t dx, uint64_t de, uint64_t dh, uint64_t dc) {
    asm volatile(
      "{\n.reg .b64 dx0, dx1, dx2, dx3;\n.reg .b32 l1, l2, l3, hx;\nmov.b32 hx, 0x40000040;\n"
      "add.u32 l1, %120, 2;\nadd.u32 l2, %120, 4;\nadd.u32 l3, %120, 6;\n"
      "mov.b64 dx0, {%120, hx};\nmov.b64 dx1, {l1, hx};\nmov.b64 dx2, {l2, hx};\nmov.b64 dx3, {l3, hx};\n"
      "wgmma.fence.sync.aligned;\n"
      "wgmma.mma_async.sync.aligned.m64n80k16.f32.bf16.bf16 {%0, %1, %2, %3, %4, %5, %6, %7, %8, %9, %10, %11, %12, %13, %14, %15, %16, %17, %18, %19, %20, %21, %22, %23, %24, %25, %26, %27, %28, %29, %30, %31, %32, %33, %34, %35, %36, %37, %38, %39}, {%116, %117, %118, %119}, %122, 0, 1, 1, 0;\n"
      "wgmma.mma_async.sync.aligned.m64n80k16.f32.bf16.bf16 {%0, %1, %2, %3, %4, %5, %6, %7, %8, %9, %10, %11, %12, %13, %14, %15, %16, %17, %18, %19, %20, %21, %22, %23, %24, %25, %26, %27, %28, %29, %30, %31, %32, %33, %34, %35, %36, %37, %38, %39}, {%96, %97, %98, %99}, %121, 1, 1, 1, 0;\n"
      "wgmma.mma_async.sync.aligned.m64n80k16.f32.bf16.bf16 {%0, %1, %2, %3, %4, %5, %6, %7, %8, %9, %10, %11, %12, %13, %14, %15, %16, %17, %18, %19, %20, %21, %22, %23, %24, %25, %26, %27, %28, %29, %30, %31, %32, %33, %34, %35, %36, %37, %38, %39}, {%80, %81, %82, %83}, dx0, 1, 1, 1, 0;\n"
      "wgmma.mma_async.sync.aligned.m64n80k16.f32.bf16.bf16 {%0, %1, %2, %3, %4, %5, %6, %7, %8, %9, %10, %11, %12, %13, %14, %15, %16, %17, %18, %19, %20, %21, %22, %23, %24, %25, %26, %27, %28, %29, %30, %31, %32, %33, %34, %35, %36, %37, %38, %39}, {%84, %85, %86, %87}, dx1, 1, 1, 1, 0;\n"
      "wgmma.mma_async.sync.aligned.m64n80k16.f32.bf16.bf16 {%0, %1, %2, %3, %4, %5, %6, %7, %8, %9, %10, %11, %12, %13, %14, %15, %16, %17, %18, %19, %20, %21, %22, %23, %24, %25, %26, %27, %28, %29, %30, %31, %32, %33, %34, %35, %36, %37, %38, %39}, {%88, %89, %90, %91}, dx2, 1, 1, 1, 0;\n"
      "wgmma.mma_async.sync.aligned.m64n80k16.f32.bf16.bf16 {%0, %1, %2, %3, %4, %5, %6, %7, %8, %9, %10, %11, %12, %13, %14, %15, %16, %17, %18, %19, %20, %21, %22, %23, %24, %25, %26, %27, %28, %29, %30, %31, %32, %33, %34, %35, %36, %37, %38, %39}, {%92, %93, %94, %95}, dx3, 1, 1, 1, 0;\n"
      "wgmma.commit_group.sync.aligned;\n"
      "wgmma.mma_async.sync.aligned.m64n80k16.f32.bf16.bf16 {%40, %41, %42, %43, %44, %45, %46, %47, %48, %49, %50, %51, %52, %53, %54, %55, %56, %57, %58, %59, %60, %61, %62, %63, %64, %65, %66, %67, %68, %69, %70, %71, %72, %73, %74, %75, %76, %77, %78, %79}, {%100, %101, %102, %103}, dx0, 0, 1, 1, 0;\n"
      "wgmma.mma_async.sync.aligned.m64n80k16.f32.bf16.bf16 {%40, %41, %42, %43, %44, %45, %46, %47, %48, %49, %50, %51, %52, %53, %54, %55, %56, %57, %58, %59, %60, %61, %62, %63, %64, %65, %66, %67, %68, %69, %70, %71, %72, %73, %74, %75, %76, %77, %78, %79}, {%104, %105, %106, %107}, dx1, 1, 1, 1, 0;\n"
      "wgmma.mma_async.sync.aligned.m64n80k16.f32.bf16.bf16 {%40, %41, %42, %43, %44, %45, %46, %47, %48, %49, %50, %51, %52, %53, %54, %55, %56, %57, %58, %59, %60, %61, %62, %63, %64, %65, %66, %67, %68, %69, %70, %71, %72, %73, %74, %75, %76, %77, %78, %79}, {%108, %109, %110, %111}, dx2, 1, 1, 1, 0;\n"
      "wgmma.mma_async.sync.aligned.m64n80k16.f32.bf16.bf16 {%40, %41, %42, %43, %44, %45, %46, %47, %48, %49, %50, %51, %52, %53, %54, %55, %56, %57, %58, %59, %60, %61, %62, %63, %64, %65, %66, %67, %68, %69, %70, %71, %72, %73, %74, %75, %76, %77, %78, %79}, {%112, %113, %114, %115}, dx3, 1, 1, 1, 0;\n"
      "wgmma.commit_group.sync.aligned;\n}\n"
      : "=f"(g[0]), "=f"(g[1]), "=f"(g[2]), "=f"(g[3]), "=f"(g[4]), "=f"(g[5]), "=f"(g[6]), "=f"(g[7]), "=f"(g[8]), "=f"(g[9]), "=f"(g[10]), "=f"(g[11]), "=f"(g[12]), "=f"(g[13]), "=f"(g[14]), "=f"(g[15]), "=f"(g[16]), "=f"(g[17]), "=f"(g[18]), "=f"(g[19]), "=f"(g[20]), "=f"(g[21]), "=f"(g[22]), "=f"(g[23]), "=f"(g[24]), "=f"(g[25]), "=f"(g[26]), "=f"(g[27]), "=f"(g[28]), "=f"(g[29]), "=f"(g[30]), "=f"(g[31]), "=f"(g[32]), "=f"(g[33]), "=f"(g[34]), "=f"(g[35]), "=f"(g[36]), "=f"(g[37]), "=f"(g[38]), "=f"(g[39]),
        "=f"(h[0]), "=f"(h[1]), "=f"(h[2]), "=f"(h[3]), "=f"(h[4]), "=f"(h[5]), "=f"(h[6]), "=f"(h[7]), "=f"(h[8]), "=f"(h[9]), "=f"(h[10]), "=f"(h[11]), "=f"(h[12]), "=f"(h[13]), "=f"(h[14]), "=f"(h[15]), "=f"(h[16]), "=f"(h[17]), "=f"(h[18]), "=f"(h[19]), "=f"(h[20]), "=f"(h[21]), "=f"(h[22]), "=f"(h[23]), "=f"(h[24]), "=f"(h[25]), "=f"(h[26]), "=f"(h[27]), "=f"(h[28]), "=f"(h[29]), "=f"(h[30]), "=f"(h[31]), "=f"(h[32]), "=f"(h[33]), "=f"(h[34]), "=f"(h[35]), "=f"(h[36]), "=f"(h[37]), "=f"(h[38]), "=f"(h[39])
      : "r"(w[0]), "r"(w[1]), "r"(w[2]), "r"(w[3]), "r"(w[4]), "r"(w[5]), "r"(w[6]), "r"(w[7]), "r"(w[8]), "r"(w[9]), "r"(w[10]), "r"(w[11]), "r"(w[12]), "r"(w[13]), "r"(w[14]), "r"(w[15]), "r"(w[16]), "r"(w[17]), "r"(w[18]), "r"(w[19]), "r"(w[20]), "r"(w[21]), "r"(w[22]), "r"(w[23]), "r"(w[24]), "r"(w[25]), "r"(w[26]), "r"(w[27]), "r"(w[28]), "r"(w[29]), "r"(w[30]), "r"(w[31]), "r"(w[32]), "r"(w[33]), "r"(w[34]), "r"(w[35]), "r"(w[36]), "r"(w[37]), "r"(w[38]), "r"(w[39]), "r"(dx), "l"(de), "l"(dh)
      : "memory");
  }
  static __device__ __forceinline__ void wait_g(float* g) {
    asm volatile("wgmma.wait_group.sync.aligned 1;\n"
      : "+f"(g[0]), "+f"(g[1]), "+f"(g[2]), "+f"(g[3]), "+f"(g[4]), "+f"(g[5]), "+f"(g[6]), "+f"(g[7]), "+f"(g[8]), "+f"(g[9]), "+f"(g[10]), "+f"(g[11]), "+f"(g[12]), "+f"(g[13]), "+f"(g[14]), "+f"(g[15]), "+f"(g[16]), "+f"(g[17]), "+f"(g[18]), "+f"(g[19]), "+f"(g[20]), "+f"(g[21]), "+f"(g[22]), "+f"(g[23]), "+f"(g[24]), "+f"(g[25]), "+f"(g[26]), "+f"(g[27]), "+f"(g[28]), "+f"(g[29]), "+f"(g[30]), "+f"(g[31]), "+f"(g[32]), "+f"(g[33]), "+f"(g[34]), "+f"(g[35]), "+f"(g[36]), "+f"(g[37]), "+f"(g[38]), "+f"(g[39])
      :: "memory");
  }
  static __device__ __forceinline__ void wait_h(float* h) {
    asm volatile("wgmma.wait_group.sync.aligned 0;\n"
      : "+f"(h[0]), "+f"(h[1]), "+f"(h[2]), "+f"(h[3]), "+f"(h[4]), "+f"(h[5]), "+f"(h[6]), "+f"(h[7]), "+f"(h[8]), "+f"(h[9]), "+f"(h[10]), "+f"(h[11]), "+f"(h[12]), "+f"(h[13]), "+f"(h[14]), "+f"(h[15]), "+f"(h[16]), "+f"(h[17]), "+f"(h[18]), "+f"(h[19]), "+f"(h[20]), "+f"(h[21]), "+f"(h[22]), "+f"(h[23]), "+f"(h[24]), "+f"(h[25]), "+f"(h[26]), "+f"(h[27]), "+f"(h[28]), "+f"(h[29]), "+f"(h[30]), "+f"(h[31]), "+f"(h[32]), "+f"(h[33]), "+f"(h[34]), "+f"(h[35]), "+f"(h[36]), "+f"(h[37]), "+f"(h[38]), "+f"(h[39])
      :: "memory");
  }
};
template<> struct TileMMA<11> {
  static __device__ __forceinline__ void issue(float* g, float* h, const uint32_t* w, uint32_t dx, uint64_t de, uint64_t dh, uint64_t dc) {
    asm volatile(
      "{\n.reg .b64 dx0, dx1, dx2, dx3;\n.reg .b32 l1, l2, l3, hx;\nmov.b32 hx, 0x40000040;\n"
      "add.u32 l1, %124, 2;\nadd.u32 l2, %124, 4;\nadd.u32 l3, %124, 6;\n"
      "mov.b64 dx0, {%124, hx};\nmov.b64 dx1, {l1, hx};\nmov.b64 dx2, {l2, hx};\nmov.b64 dx3, {l3, hx};\n"
      "wgmma.fence.sync.aligned;\n"
      "wgmma.mma_async.sync.aligned.m64n88k16.f32.bf16.bf16 {%0, %1, %2, %3, %4, %5, %6, %7, %8, %9, %10, %11, %12, %13, %14, %15, %16, %17, %18, %19, %20, %21, %22, %23, %24, %25, %26, %27, %28, %29, %30, %31, %32, %33, %34, %35, %36, %37, %38, %39, %40, %41, %42, %43}, {%120, %121, %122, %123}, %126, 0, 1, 1, 0;\n"
      "wgmma.mma_async.sync.aligned.m64n88k16.f32.bf16.bf16 {%0, %1, %2, %3, %4, %5, %6, %7, %8, %9, %10, %11, %12, %13, %14, %15, %16, %17, %18, %19, %20, %21, %22, %23, %24, %25, %26, %27, %28, %29, %30, %31, %32, %33, %34, %35, %36, %37, %38, %39, %40, %41, %42, %43}, %127, %125, 1, 1, 1, 0, 0;\n"
      "wgmma.mma_async.sync.aligned.m64n88k16.f32.bf16.bf16 {%0, %1, %2, %3, %4, %5, %6, %7, %8, %9, %10, %11, %12, %13, %14, %15, %16, %17, %18, %19, %20, %21, %22, %23, %24, %25, %26, %27, %28, %29, %30, %31, %32, %33, %34, %35, %36, %37, %38, %39, %40, %41, %42, %43}, {%88, %89, %90, %91}, dx0, 1, 1, 1, 0;\n"
      "wgmma.mma_async.sync.aligned.m64n88k16.f32.bf16.bf16 {%0, %1, %2, %3, %4, %5, %6, %7, %8, %9, %10, %11, %12, %13, %14, %15, %16, %17, %18, %19, %20, %21, %22, %23, %24, %25, %26, %27, %28, %29, %30, %31, %32, %33, %34, %35, %36, %37, %38, %39, %40, %41, %42, %43}, {%92, %93, %94, %95}, dx1, 1, 1, 1, 0;\n"
      "wgmma.mma_async.sync.aligned.m64n88k16.f32.bf16.bf16 {%0, %1, %2, %3, %4, %5, %6, %7, %8, %9, %10, %11, %12, %13, %14, %15, %16, %17, %18, %19, %20, %21, %22, %23, %24, %25, %26, %27, %28, %29, %30, %31, %32, %33, %34, %35, %36, %37, %38, %39, %40, %41, %42, %43}, {%96, %97, %98, %99}, dx2, 1, 1, 1, 0;\n"
      "wgmma.mma_async.sync.aligned.m64n88k16.f32.bf16.bf16 {%0, %1, %2, %3, %4, %5, %6, %7, %8, %9, %10, %11, %12, %13, %14, %15, %16, %17, %18, %19, %20, %21, %22, %23, %24, %25, %26, %27, %28, %29, %30, %31, %32, %33, %34, %35, %36, %37, %38, %39, %40, %41, %42, %43}, {%100, %101, %102, %103}, dx3, 1, 1, 1, 0;\n"
      "wgmma.commit_group.sync.aligned;\n"
      "wgmma.mma_async.sync.aligned.m64n88k16.f32.bf16.bf16 {%44, %45, %46, %47, %48, %49, %50, %51, %52, %53, %54, %55, %56, %57, %58, %59, %60, %61, %62, %63, %64, %65, %66, %67, %68, %69, %70, %71, %72, %73, %74, %75, %76, %77, %78, %79, %80, %81, %82, %83, %84, %85, %86, %87}, {%104, %105, %106, %107}, dx0, 0, 1, 1, 0;\n"
      "wgmma.mma_async.sync.aligned.m64n88k16.f32.bf16.bf16 {%44, %45, %46, %47, %48, %49, %50, %51, %52, %53, %54, %55, %56, %57, %58, %59, %60, %61, %62, %63, %64, %65, %66, %67, %68, %69, %70, %71, %72, %73, %74, %75, %76, %77, %78, %79, %80, %81, %82, %83, %84, %85, %86, %87}, {%108, %109, %110, %111}, dx1, 1, 1, 1, 0;\n"
      "wgmma.mma_async.sync.aligned.m64n88k16.f32.bf16.bf16 {%44, %45, %46, %47, %48, %49, %50, %51, %52, %53, %54, %55, %56, %57, %58, %59, %60, %61, %62, %63, %64, %65, %66, %67, %68, %69, %70, %71, %72, %73, %74, %75, %76, %77, %78, %79, %80, %81, %82, %83, %84, %85, %86, %87}, {%112, %113, %114, %115}, dx2, 1, 1, 1, 0;\n"
      "wgmma.mma_async.sync.aligned.m64n88k16.f32.bf16.bf16 {%44, %45, %46, %47, %48, %49, %50, %51, %52, %53, %54, %55, %56, %57, %58, %59, %60, %61, %62, %63, %64, %65, %66, %67, %68, %69, %70, %71, %72, %73, %74, %75, %76, %77, %78, %79, %80, %81, %82, %83, %84, %85, %86, %87}, {%116, %117, %118, %119}, dx3, 1, 1, 1, 0;\n"
      "wgmma.commit_group.sync.aligned;\n}\n"
      : "=f"(g[0]), "=f"(g[1]), "=f"(g[2]), "=f"(g[3]), "=f"(g[4]), "=f"(g[5]), "=f"(g[6]), "=f"(g[7]), "=f"(g[8]), "=f"(g[9]), "=f"(g[10]), "=f"(g[11]), "=f"(g[12]), "=f"(g[13]), "=f"(g[14]), "=f"(g[15]), "=f"(g[16]), "=f"(g[17]), "=f"(g[18]), "=f"(g[19]), "=f"(g[20]), "=f"(g[21]), "=f"(g[22]), "=f"(g[23]), "=f"(g[24]), "=f"(g[25]), "=f"(g[26]), "=f"(g[27]), "=f"(g[28]), "=f"(g[29]), "=f"(g[30]), "=f"(g[31]), "=f"(g[32]), "=f"(g[33]), "=f"(g[34]), "=f"(g[35]), "=f"(g[36]), "=f"(g[37]), "=f"(g[38]), "=f"(g[39]), "=f"(g[40]), "=f"(g[41]), "=f"(g[42]), "=f"(g[43]),
        "=f"(h[0]), "=f"(h[1]), "=f"(h[2]), "=f"(h[3]), "=f"(h[4]), "=f"(h[5]), "=f"(h[6]), "=f"(h[7]), "=f"(h[8]), "=f"(h[9]), "=f"(h[10]), "=f"(h[11]), "=f"(h[12]), "=f"(h[13]), "=f"(h[14]), "=f"(h[15]), "=f"(h[16]), "=f"(h[17]), "=f"(h[18]), "=f"(h[19]), "=f"(h[20]), "=f"(h[21]), "=f"(h[22]), "=f"(h[23]), "=f"(h[24]), "=f"(h[25]), "=f"(h[26]), "=f"(h[27]), "=f"(h[28]), "=f"(h[29]), "=f"(h[30]), "=f"(h[31]), "=f"(h[32]), "=f"(h[33]), "=f"(h[34]), "=f"(h[35]), "=f"(h[36]), "=f"(h[37]), "=f"(h[38]), "=f"(h[39]), "=f"(h[40]), "=f"(h[41]), "=f"(h[42]), "=f"(h[43])
      : "r"(w[0]), "r"(w[1]), "r"(w[2]), "r"(w[3]), "r"(w[4]), "r"(w[5]), "r"(w[6]), "r"(w[7]), "r"(w[8]), "r"(w[9]), "r"(w[10]), "r"(w[11]), "r"(w[12]), "r"(w[13]), "r"(w[14]), "r"(w[15]), "r"(w[20]), "r"(w[21]), "r"(w[22]), "r"(w[23]), "r"(w[24]), "r"(w[25]), "r"(w[26]), "r"(w[27]), "r"(w[28]), "r"(w[29]), "r"(w[30]), "r"(w[31]), "r"(w[32]), "r"(w[33]), "r"(w[34]), "r"(w[35]), "r"(w[36]), "r"(w[37]), "r"(w[38]), "r"(w[39]), "r"(dx), "l"(de), "l"(dh), "l"(dc)
      : "memory");
  }
  static __device__ __forceinline__ void wait_g(float* g) {
    asm volatile("wgmma.wait_group.sync.aligned 1;\n"
      : "+f"(g[0]), "+f"(g[1]), "+f"(g[2]), "+f"(g[3]), "+f"(g[4]), "+f"(g[5]), "+f"(g[6]), "+f"(g[7]), "+f"(g[8]), "+f"(g[9]), "+f"(g[10]), "+f"(g[11]), "+f"(g[12]), "+f"(g[13]), "+f"(g[14]), "+f"(g[15]), "+f"(g[16]), "+f"(g[17]), "+f"(g[18]), "+f"(g[19]), "+f"(g[20]), "+f"(g[21]), "+f"(g[22]), "+f"(g[23]), "+f"(g[24]), "+f"(g[25]), "+f"(g[26]), "+f"(g[27]), "+f"(g[28]), "+f"(g[29]), "+f"(g[30]), "+f"(g[31]), "+f"(g[32]), "+f"(g[33]), "+f"(g[34]), "+f"(g[35]), "+f"(g[36]), "+f"(g[37]), "+f"(g[38]), "+f"(g[39]), "+f"(g[40]), "+f"(g[41]), "+f"(g[42]), "+f"(g[43])
      :: "memory");
  }
  static __device__ __forceinline__ void wait_h(float* h) {
    asm volatile("wgmma.wait_group.sync.aligned 0;\n"
      : "+f"(h[0]), "+f"(h[1]), "+f"(h[2]), "+f"(h[3]), "+f"(h[4]), "+f"(h[5]), "+f"(h[6]), "+f"(h[7]), "+f"(h[8]), "+f"(h[9]), "+f"(h[10]), "+f"(h[11]), "+f"(h[12]), "+f"(h[13]), "+f"(h[14]), "+f"(h[15]), "+f"(h[16]), "+f"(h[17]), "+f"(h[18]), "+f"(h[19]), "+f"(h[20]), "+f"(h[21]), "+f"(h[22]), "+f"(h[23]), "+f"(h[24]), "+f"(h[25]), "+f"(h[26]), "+f"(h[27]), "+f"(h[28]), "+f"(h[29]), "+f"(h[30]), "+f"(h[31]), "+f"(h[32]), "+f"(h[33]), "+f"(h[34]), "+f"(h[35]), "+f"(h[36]), "+f"(h[37]), "+f"(h[38]), "+f"(h[39]), "+f"(h[40]), "+f"(h[41]), "+f"(h[42]), "+f"(h[43])
      :: "memory");
  }
};
__device__ __forceinline__ void node_mma(float* g, const uint32_t* w, uint64_t dx) {
    asm volatile(
      "{\n.reg .b64 dx1, dx2, dx3;\n"
      "add.s64 dx1, %48, 2;\nadd.s64 dx2, %48, 4;\nadd.s64 dx3, %48, 6;\n"
      "wgmma.fence.sync.aligned;\n"
      "wgmma.mma_async.sync.aligned.m64n64k16.f32.bf16.bf16 {%0, %1, %2, %3, %4, %5, %6, %7, %8, %9, %10, %11, %12, %13, %14, %15, %16, %17, %18, %19, %20, %21, %22, %23, %24, %25, %26, %27, %28, %29, %30, %31}, {%32, %33, %34, %35}, %48, 0, 1, 1, 0;\n"
      "wgmma.mma_async.sync.aligned.m64n64k16.f32.bf16.bf16 {%0, %1, %2, %3, %4, %5, %6, %7, %8, %9, %10, %11, %12, %13, %14, %15, %16, %17, %18, %19, %20, %21, %22, %23, %24, %25, %26, %27, %28, %29, %30, %31}, {%36, %37, %38, %39}, dx1, 1, 1, 1, 0;\n"
      "wgmma.mma_async.sync.aligned.m64n64k16.f32.bf16.bf16 {%0, %1, %2, %3, %4, %5, %6, %7, %8, %9, %10, %11, %12, %13, %14, %15, %16, %17, %18, %19, %20, %21, %22, %23, %24, %25, %26, %27, %28, %29, %30, %31}, {%40, %41, %42, %43}, dx2, 1, 1, 1, 0;\n"
      "wgmma.mma_async.sync.aligned.m64n64k16.f32.bf16.bf16 {%0, %1, %2, %3, %4, %5, %6, %7, %8, %9, %10, %11, %12, %13, %14, %15, %16, %17, %18, %19, %20, %21, %22, %23, %24, %25, %26, %27, %28, %29, %30, %31}, {%44, %45, %46, %47}, dx3, 1, 1, 1, 0;\n"
      "wgmma.commit_group.sync.aligned;\n}\n"
      : "=f"(g[0]), "=f"(g[1]), "=f"(g[2]), "=f"(g[3]), "=f"(g[4]), "=f"(g[5]), "=f"(g[6]), "=f"(g[7]), "=f"(g[8]), "=f"(g[9]), "=f"(g[10]), "=f"(g[11]), "=f"(g[12]), "=f"(g[13]), "=f"(g[14]), "=f"(g[15]), "=f"(g[16]), "=f"(g[17]), "=f"(g[18]), "=f"(g[19]), "=f"(g[20]), "=f"(g[21]), "=f"(g[22]), "=f"(g[23]), "=f"(g[24]), "=f"(g[25]), "=f"(g[26]), "=f"(g[27]), "=f"(g[28]), "=f"(g[29]), "=f"(g[30]), "=f"(g[31])
      : "r"(w[0]), "r"(w[1]), "r"(w[2]), "r"(w[3]), "r"(w[4]), "r"(w[5]), "r"(w[6]), "r"(w[7]), "r"(w[8]), "r"(w[9]), "r"(w[10]), "r"(w[11]), "r"(w[12]), "r"(w[13]), "r"(w[14]), "r"(w[15]), "l"(dx)
      : "memory");
}

__device__ __forceinline__ uint32_t smem_u32(const void* p) { return (uint32_t)__cvta_generic_to_shared(p); }
__device__ __forceinline__ float ex2f(float x) { float y; asm("ex2.approx.ftz.f32 %0, %1;" : "=f"(y) : "f"(x)); return y; }
__device__ __forceinline__ float rcpf(float x) { float y; asm("rcp.approx.ftz.f32 %0, %1;" : "=f"(y) : "f"(x)); return y; }
__device__ __forceinline__ uint32_t pack_bf16(float lo, float hi) {
    uint32_t r; asm("cvt.rn.bf16x2.f32 %0, %1, %2;" : "=r"(r) : "f"(hi), "f"(lo)); return r;
}
__device__ __forceinline__ float bf_lo(uint32_t v) { return __uint_as_float(v << 16); }
__device__ __forceinline__ float bf_hi(uint32_t v) { return __uint_as_float(v & 0xFFFF0000u); }
template<int STRIDE>
__device__ __forceinline__ void cp16i(uint32_t dst, const char* base, uint32_t idx) {
    asm volatile("{\n.reg .b64 a;\nmad.wide.u32 a, %2, %3, %1;\ncp.async.cg.shared.global [%0], [a], 16;\n}\n" :: "r"(dst), "l"(base), "r"(idx), "n"(STRIDE) : "memory");
}
__device__ __forceinline__ void cp16e(uint32_t dst, const char* base, uint32_t idx, uint64_t pol) {
    asm volatile("{\n.reg .b64 a;\nmad.wide.u32 a, %2, 32, %1;\ncp.async.cg.shared.global.L2::cache_hint [%0], [a], 16, %3;\n}\n" :: "r"(dst), "l"(base), "r"(idx), "l"(pol) : "memory");
}
template<int STRIDE>
__device__ __forceinline__ void cp16z(uint32_t dst, const char* base, uint32_t idx, int k, int n, uint64_t pol) {
    if (STRIDE == 32)
        asm volatile("{\n.reg .b64 a;\n.reg .pred p;\nsetp.ge.s32 p, %3, %4;\nmad.wide.u32 a, %2, 32, %1;\ncp.async.cg.shared.global.L2::cache_hint [%0], [a], 16, p, %5;\n}\n"
                     :: "r"(dst), "l"(base), "r"(idx), "r"(k), "r"(n), "l"(pol) : "memory");
    else
        asm volatile("{\n.reg .b64 a;\n.reg .pred p;\nsetp.ge.s32 p, %3, %4;\nmad.wide.u32 a, %2, 128, %1;\ncp.async.cg.shared.global [%0], [a], 16, p;\n}\n"
                     :: "r"(dst), "l"(base), "r"(idx), "r"(k), "r"(n) : "memory");
}
template<int HI, bool Z>
__device__ __forceinline__ void cpx(uint32_t hi, uint32_t dst, uint32_t p, uint32_t lo, int k, int n) {
    if (Z) asm volatile("{\n.reg .b32 l;\n.reg .b64 a;\n.reg .pred q;\nsetp.ge.s32 q, %5, %6;\ndp2a.lo.u32.u32 l, %1, %2, %3;\nmov.b64 a, {l, %0};\ncp.async.cg.shared.global [%4], [a], 16, q;\n}\n"
                        :: "r"(hi), "r"(p), "r"(HI ? 0x8000u : 0x80u), "r"(lo), "r"(dst), "r"(k), "r"(n) : "memory");
    else asm volatile("{\n.reg .b32 l;\n.reg .b64 a;\ndp2a.lo.u32.u32 l, %1, %2, %3;\nmov.b64 a, {l, %0};\ncp.async.cg.shared.global [%4], [a], 16;\n}\n"
                      :: "r"(hi), "r"(p), "r"(HI ? 0x8000u : 0x80u), "r"(lo), "r"(dst) : "memory");
}
template<bool Z>
__device__ __forceinline__ void cpe(uint32_t hi, uint32_t dst, uint32_t idx, uint32_t lo, int k, int n, uint64_t pol) {
    if (Z) asm volatile("{\n.reg .b32 l;\n.reg .b64 a;\n.reg .pred q;\nsetp.ge.s32 q, %5, %6;\nmad.lo.u32 l, %1, 32, %2;\nmov.b64 a, {l, %0};\ncp.async.cg.shared.global.L2::cache_hint [%3], [a], 16, q, %4;\n}\n"
                        :: "r"(hi), "r"(idx), "r"(lo), "r"(dst), "l"(pol), "r"(k), "r"(n) : "memory");
    else asm volatile("{\n.reg .b32 l;\n.reg .b64 a;\nmad.lo.u32 l, %1, 32, %2;\nmov.b64 a, {l, %0};\ncp.async.cg.shared.global.L2::cache_hint [%3], [a], 16, %4;\n}\n"
                      :: "r"(hi), "r"(idx), "r"(lo), "r"(dst), "l"(pol) : "memory");
}
__device__ __forceinline__ void cp_commit() { asm volatile("cp.async.commit_group;" ::: "memory"); }
template<int N> __device__ __forceinline__ void cp_wait() { asm volatile("cp.async.wait_group %0;" :: "n"(N) : "memory"); }
__device__ __forceinline__ void mbar_init(uint32_t bar, int cnt) { asm volatile("mbarrier.init.shared.b64 [%0], %1;" :: "r"(bar), "r"(cnt) : "memory"); }
__device__ __forceinline__ void mbar_arrive(uint32_t bar) { asm volatile("mbarrier.arrive.shared.b64 _, [%0];" :: "r"(bar) : "memory"); }
__device__ __forceinline__ void mbar_expect(uint32_t bar, uint32_t bytes) { asm volatile("mbarrier.arrive.expect_tx.shared.b64 _, [%0], %1;" :: "r"(bar), "r"(bytes) : "memory"); }
__device__ __forceinline__ void mbar_cp_arrive(uint32_t bar) { asm volatile("cp.async.mbarrier.arrive.noinc.shared.b64 [%0];" :: "r"(bar) : "memory"); }
__device__ __forceinline__ void mbar_wait(uint32_t bar, uint32_t parity) {
    asm volatile("{\n.reg .pred p;\n.reg .u32 n;\nmbarrier.try_wait.parity.shared.b64 p, [%0], %1;\n@p bra DONE_%=;\nmov.u32 n, 0;\n"
                 "WAIT_%=:\nmbarrier.try_wait.parity.shared.b64 p, [%0], %1, 0x100000;\n@p bra DONE_%=;\n"
                 "add.u32 n, n, 1;\nsetp.lt.u32 p, n, 0x400000;\n@p bra WAIT_%=;\ntrap;\nDONE_%=:\n}\n"
                 :: "r"(bar), "r"(parity) : "memory");
}
__device__ __forceinline__ void mbar_wait_s(uint32_t bar, uint32_t parity) {
    asm volatile("{\n.reg .pred p;\n.reg .u32 n;\nmov.u32 n, 0;\n"
                 "WAIT_%=:\nmbarrier.test_wait.parity.shared.b64 p, [%0], %1;\n@p bra DONE_%=;\n"
                 "add.u32 n, n, 1;\nsetp.lt.u32 p, n, 0x10000000;\n@p bra WAIT_%=;\ntrap;\nDONE_%=:\n}\n"
                 :: "r"(bar), "r"(parity) : "memory");
}
__device__ __forceinline__ void mbar_wait_c(uint32_t bar, uint32_t parity) {
    asm volatile("{\n.reg .pred p;\nWAIT_%=:\nmbarrier.try_wait.parity.shared.b64 p, [%0], %1;\n@p bra DONE_%=;\nbra WAIT_%=;\nDONE_%=:\n}\n"
                 :: "r"(bar), "r"(parity) : "memory");
}
__device__ __forceinline__ void mbar_wait_h(uint32_t bar, uint32_t parity) {
    asm volatile("{\n.reg .pred p;\nWAIT_%=:\nmbarrier.try_wait.parity.shared.b64 p, [%0], %1, 0x100000;\n@p bra DONE_%=;\nbra WAIT_%=;\nDONE_%=:\n}\n"
                 :: "r"(bar), "r"(parity) : "memory");
}
__device__ __forceinline__ uint32_t lds32(uint32_t a) { uint32_t v; asm volatile("ld.shared.u32 %0, [%1];" : "=r"(v) : "r"(a) : "memory"); return v; }
__device__ __forceinline__ void sts32(uint32_t a, uint32_t v) { asm volatile("st.shared.u32 [%0], %1;" :: "r"(a), "r"(v) : "memory"); }
__device__ __forceinline__ uint2 lds64(uint32_t a) { uint2 v; asm volatile("ld.shared.v2.u32 {%0,%1}, [%2];" : "=r"(v.x), "=r"(v.y) : "r"(a) : "memory"); return v; }
__device__ __forceinline__ uint4 lds128(uint32_t a) { uint4 v; asm volatile("ld.shared.v4.u32 {%0,%1,%2,%3}, [%4];" : "=r"(v.x), "=r"(v.y), "=r"(v.z), "=r"(v.w) : "r"(a) : "memory"); return v; }
__device__ __forceinline__ void sts128(uint32_t a, uint4 v) { asm volatile("st.shared.v4.u32 [%0], {%1,%2,%3,%4};" :: "r"(a), "r"(v.x), "r"(v.y), "r"(v.z), "r"(v.w) : "memory"); }
__device__ __forceinline__ void ldsm4t(uint32_t* v, uint32_t a) {
    asm volatile("ldmatrix.sync.aligned.m8n8.x4.trans.shared.b16 {%0,%1,%2,%3}, [%4];" : "=r"(v[0]), "=r"(v[1]), "=r"(v[2]), "=r"(v[3]) : "r"(a) : "memory");
}
__device__ __forceinline__ void stsm4t(uint32_t a, const uint32_t* v) {
    asm volatile("stmatrix.sync.aligned.m8n8.x4.trans.shared.b16 [%0], {%1,%2,%3,%4};" :: "r"(a), "r"(v[0]), "r"(v[1]), "r"(v[2]), "r"(v[3]) : "memory");
}
__device__ __forceinline__ int atoms_inc(uint32_t a) { int v; asm volatile("atom.shared.add.u32 %0, [%1], 1;" : "=r"(v) : "r"(a) : "memory"); return v; }
__device__ __forceinline__ bool elect_one() {
    uint32_t el;
    asm volatile("{\n.reg .pred p;\nelect.sync _|p, 0xffffffff;\nselp.u32 %0, 1, 0, p;\n}" : "=r"(el));
    return el != 0;
}
__device__ __forceinline__ float tanhf_a(float x) { float y; asm("tanh.approx.f32 %0, %1;" : "=f"(y) : "f"(x)); return y; }
__device__ __forceinline__ const char* as_pair(const void* p, uint32_t scratch) {
    const char* r;
    asm volatile("st.shared.u64 [%1], %2;\nld.volatile.shared.u64 %0, [%1];" : "=l"(r) : "r"(scratch), "l"(p) : "memory");
    return r;
}
__device__ __forceinline__ void ld_unit(uint4& v, const char* p, bool ok) {
    asm volatile("{\n.reg .pred q;\nsetp.ne.u32 q, %5, 0;\n@q ld.relaxed.gpu.global.v4.u32 {%0,%1,%2,%3}, [%4];\n}"
                 : "+r"(v.x), "+r"(v.y), "+r"(v.z), "+r"(v.w) : "l"(p), "r"((uint32_t)ok) : "memory");
}
__device__ __forceinline__ void ld_unit(uint2& v, const char* p, bool ok) {
    asm volatile("{\n.reg .pred q;\nsetp.ne.u32 q, %3, 0;\n@q ld.relaxed.gpu.global.v2.u32 {%0,%1}, [%2];\n}"
                 : "+r"(v.x), "+r"(v.y) : "l"(p), "r"((uint32_t)ok) : "memory");
}
__device__ __forceinline__ void bulk_ld(uint32_t dst, const void* src, int bytes, uint32_t bar) {
    mbar_expect(bar, bytes);
    if (bytes > 0) asm volatile("cp.async.bulk.shared::cluster.global.mbarrier::complete_tx::bytes [%0], [%1], %2, [%3];" :: "r"(dst), "l"(src), "r"(bytes), "r"(bar) : "memory");
}
#define ELECT "{\n.reg .pred p;\nelect.sync _|p, 0xffffffff;\n@p "
__device__ __forceinline__ void w_init(uint32_t bar, int n) { asm volatile(ELECT "mbarrier.init.shared.b64 [%0], %1;\n}" :: "r"(bar), "r"(n) : "memory"); }
__device__ __forceinline__ void w_expect(uint32_t bar, uint32_t bytes) { asm volatile(ELECT "mbarrier.arrive.expect_tx.shared.b64 _, [%0], %1;\n}" :: "r"(bar), "r"(bytes) : "memory"); }
__device__ __forceinline__ void w_ld(uint32_t dst, const void* src, int bytes, uint32_t bar) {
    asm volatile(ELECT "cp.async.bulk.shared::cluster.global.mbarrier::complete_tx::bytes [%0], [%1], %2, [%3];\n}" :: "r"(dst), "l"(src), "r"(bytes), "r"(bar) : "memory");
}
__device__ __forceinline__ void w_box_ld(uint32_t dst, const CUtensorMap* tm, int row, uint32_t bar) {
    asm volatile(ELECT "cp.async.bulk.tensor.2d.shared::cluster.global.mbarrier::complete_tx::bytes [%0], [%1, {%3, %4}], [%2];\n}"
        :: "r"(dst), "l"((uint64_t)tm), "r"(bar), "r"(0), "r"(row) : "memory");
}
__device__ __forceinline__ void w_st(void* dst, uint32_t src, int bytes) {
    asm volatile(ELECT "cp.async.bulk.global.shared::cta.bulk_group [%0], [%1], %2;\n}" :: "l"(dst), "r"(src), "r"(bytes) : "memory");
}
__device__ __forceinline__ void w_box_st(const CUtensorMap* tm, int col, uint32_t src) {
    asm volatile(ELECT "cp.async.bulk.tensor.2d.global.shared::cta.bulk_group [%0, {%2, %3}], [%1];\n}" :: "l"((uint64_t)tm), "r"(src), "r"(col), "r"(0) : "memory");
}
__device__ __forceinline__ void w_sent(unsigned* p, uint32_t src) {
    asm volatile(ELECT "cp.reduce.async.bulk.global.shared::cta.bulk_group.add.u32 [%0], [%1], 16;\n}" :: "l"(p), "r"(src) : "memory");
}
__device__ __forceinline__ void w_inc(unsigned* p) { asm volatile(ELECT "red.relaxed.gpu.global.add.u32 [%0], 1;\n}" :: "l"(p) : "memory"); }
__device__ __forceinline__ void w_hint(unsigned* p, uint32_t all) {
    #pragma unroll 1
    for (int i = 0; i < 4096; i++) {
        uint32_t v; asm volatile("ld.relaxed.gpu.global.u32 %0, [%1];" : "=r"(v) : "l"(p) : "memory");
        if (__all_sync(~0u, (int)(v - all) >= 0)) break;
    }
}

__device__ __forceinline__ void finish(uint4& a, const uint4& xu, const uint4& xv) {
    asm("{\n.reg .b32 z;\nfma.rn.relu.bf16x2 z, %0, %3, %1;\nadd.rn.bf16x2 %0, z, %2;\n}" : "+r"(a.x) : "r"(xu.x), "r"(xv.x), "r"(0x3F803F80u));
    asm("{\n.reg .b32 z;\nfma.rn.relu.bf16x2 z, %0, %3, %1;\nadd.rn.bf16x2 %0, z, %2;\n}" : "+r"(a.y) : "r"(xu.y), "r"(xv.y), "r"(0x3F803F80u));
    asm("{\n.reg .b32 z;\nfma.rn.relu.bf16x2 z, %0, %3, %1;\nadd.rn.bf16x2 %0, z, %2;\n}" : "+r"(a.z) : "r"(xu.z), "r"(xv.z), "r"(0x3F803F80u));
    asm("{\n.reg .b32 z;\nfma.rn.relu.bf16x2 z, %0, %3, %1;\nadd.rn.bf16x2 %0, z, %2;\n}" : "+r"(a.w) : "r"(xu.w), "r"(xv.w), "r"(0x3F803F80u));
}

constexpr float EPS2 = 2e-6f;
constexpr float TAU = 2.5e-5f;

constexpr uint32_t TAU_BITS = 0x3A103000u;
template<int NP>
__device__ __forceinline__ void epi_fast(const float* g, const float* h, float m2,
                                         float& n0, float& d0, float& n1, float& d1, float& dmin)
{
    constexpr int JC = NP >= 6 ? NP - 1 - 2 : NP >= 4 ? NP - 2 : NP - 1;
    constexpr int JT = NP < 3 ? -1 : JC < NP - 1 ? JC : NP - 2;
    #pragma unroll
    for (int j = 0; j < NP; j++) {
        float t0 = tanhf_a(g[4*j+0]), t1 = tanhf_a(g[4*j+1]), t2 = tanhf_a(g[4*j+2]), t3 = tanhf_a(g[4*j+3]);
        auto add_d = [&]() {
            if (j == 0) { d0 = t0 + (2.f * (JT + 1) + EPS2); d1 = t2 + (2.f * (JT + 1) + EPS2); } else { d0 += t0; d1 += t2; }
            d0 += t1; d1 += t3;
        };
        if (j <= JT) add_d();
        if (UFORM && j <= JT) {
            const float u0 = fmaf(t0, h[4*j], h[4*j]), u1 = fmaf(t1, h[4*j+1], h[4*j+1]), u2 = fmaf(t2, h[4*j+2], h[4*j+2]), u3 = fmaf(t3, h[4*j+3], h[4*j+3]);
            if (j == 0) { n0 = u0 + u1; n1 = u2 + u3; } else { n0 += u0; n1 += u2; n0 += u1; n1 += u3; }
            if (j == JC) dmin = fminf(d0, d1);
            continue;
        }
        if (j == NP - 1) { t0 += 1.f; t1 = fmaf(t1, m2, m2); t2 += 1.f; t3 = fmaf(t3, m2, m2); }
        else { t0 += 1.f; t1 += 1.f; t2 += 1.f; t3 += 1.f; }
        if (j > JT) add_d();
        if (j == 0) { n0 = t0 * h[0]; n1 = t2 * h[2]; } else { n0 = fmaf(t0, h[4*j], n0); n1 = fmaf(t2, h[4*j+2], n1); }
        n0 = fmaf(t1, h[4*j+1], n0); n1 = fmaf(t3, h[4*j+3], n1);
        if (j == JC) dmin = fminf(d0, d1);
    }
}

__device__ __noinline__ void slow_bin(const __nv_bfloat16* x, const __nv_bfloat16* ea, const int* src, const int* dst,
                                      const __nv_bfloat16* wa, const __nv_bfloat16* wb, const __nv_bfloat16* wc,
                                      const __nv_bfloat16* wu, const __nv_bfloat16* wv, __nv_bfloat16* out,
                                      int E, int node0, int nn, int nthr)
{
    const int tid = threadIdx.x, lane = tid & 31;
    for (int i = tid; i < nn * 128; i += nthr) g_slow[(size_t)node0 * 128 + i] = 0.f;
    asm volatile("bar.sync 1, %0;" :: "r"(nthr) : "memory");
    for (int e0 = (tid >> 5) * 32; e0 < E; e0 += nthr) {
        int d = (e0 + lane < E) ? dst[e0 + lane] - node0 : -1;
        unsigned m = __ballot_sync(~0u, d >= 0 && d < nn);
        while (m) {
            int l = __ffs(m) - 1; m &= m - 1;
            int e = e0 + l, n = node0 + __shfl_sync(~0u, d, l), s = src[e];
            float g0 = 0, g1 = 0, h0 = 0, h1 = 0;
            for (int k = 0; k < 64; k++) {
                float xs = __bfloat162float(x[(size_t)s * 64 + k]), xd = __bfloat162float(x[(size_t)n * 64 + k]);
                uint32_t b2 = *(const uint32_t*)(wb + k * 64 + 2 * lane), v2 = *(const uint32_t*)(wv + k * 64 + 2 * lane);
                uint32_t a2 = *(const uint32_t*)(wa + k * 64 + 2 * lane);
                g0 = fmaf(xs, bf_lo(b2), fmaf(xd, bf_lo(a2), g0)); g1 = fmaf(xs, bf_hi(b2), fmaf(xd, bf_hi(a2), g1));
                h0 = fmaf(xs, bf_lo(v2), h0); h1 = fmaf(xs, bf_hi(v2), h1);
            }
            for (int k = 0; k < 16; k++) {
                float ev = __bfloat162float(ea[(size_t)e * 16 + k]);
                uint32_t c2 = *(const uint32_t*)(wc + k * 64 + 2 * lane);
                g0 = fmaf(ev, bf_lo(c2), g0); g1 = fmaf(ev, bf_hi(c2), g1);
            }
            float s0 = rcpf(1.f + ex2f(-LOG2E * g0)), s1 = rcpf(1.f + ex2f(-LOG2E * g1));
            float* acc = g_slow + (size_t)n * 128 + 4 * lane;
            atomicAdd(acc + 0, s0 * h0); atomicAdd(acc + 1, s0);
            atomicAdd(acc + 2, s1 * h1); atomicAdd(acc + 3, s1);
        }
    }
    __threadfence();
    asm volatile("bar.sync 1, %0;" :: "r"(nthr) : "memory");
    for (int i = tid; i < nn * 32; i += nthr) {
        int n = node0 + (i >> 5), cp = i & 31;
        float4 a = __ldcg((const float4*)(g_slow + (size_t)n * 128 + 4 * cp));
        float u0 = 0, u1 = 0;
        for (int k = 0; k < 64; k++) {
            float xd = __bfloat162float(x[(size_t)n * 64 + k]);
            uint32_t w2 = *(const uint32_t*)(wu + k * 64 + 2 * cp);
            u0 = fmaf(xd, bf_lo(w2), u0); u1 = fmaf(xd, bf_hi(w2), u1);
        }
        uint32_t xv = *(const uint32_t*)(x + (size_t)n * 64 + 2 * cp);
        float z0 = u0 + a.x / (a.y + 1e-6f), z1 = u1 + a.z / (a.w + 1e-6f);
        *(uint32_t*)(out + (size_t)n * 64 + 2 * cp) = pack_bf16(bf_lo(xv) + fmaxf(z0, 0.f), bf_hi(xv) + fmaxf(z1, 0.f));
    }
}

__global__ void __launch_bounds__(256) slow_kernel(const __nv_bfloat16* x, const __nv_bfloat16* ea, const int* src, const int* dst,
        const __nv_bfloat16* wa, const __nv_bfloat16* wb, const __nv_bfloat16* wc, const __nv_bfloat16* wu, const __nv_bfloat16* wv,
        __nv_bfloat16* out, int N, int E, int npb)
{
    int node0 = blockIdx.x * npb;
    slow_bin(x, ea, src, dst, wa, wb, wc, wu, wv, out, E, node0, max(0, min(npb, N - node0)), 256);
}

constexpr int XS_BYTES = NPMAX * 1024;
constexpr int ES_BYTES = NPMAX * 256;
constexpr int SM_XS = 0;
constexpr int SM_XU = SM_XS + 3 * NSTAGE * XS_BYTES;
constexpr int SM_TAB = SM_XU + NPB_MAX * 128;
constexpr int SM_ES = SM_TAB + NPB_MAX * 128;
constexpr int SM_WC = SM_ES + 3 * NSTAGE * ES_BYTES;
constexpr int SM_OH = SM_WC + 2048;
constexpr int SM_EID = SM_OH + 128;
constexpr int SM_SRC = SM_EID + SLOT_CAP * 4;
constexpr int SM_TINFO = SM_SRC + SLOT_CAP * 2;
constexpr int SM_MISC = SM_TINFO + TILE_CAP * 32;
constexpr int SM_CLAIM = SM_MISC + 32 * 4;
constexpr int STG = 272;
constexpr int SM_BARS = SM_CLAIM + 32 * 4;
constexpr int SM_ABAR = SM_BARS + 6 * STG;
constexpr int SM_GBAR = SM_ABAR + 16 * 8;
constexpr int SMEM_BYTES = SM_GBAR + 97 * 8;
constexpr int SM_P2 = 0, SM_P1 = P2B + 256;
constexpr int SM_DEG = SM_P1 + P1B + 256;
constexpr int SM_CLS = SM_DEG + 512 * 4;
constexpr int SM_HIST = SM_CLS + NCLS * 4;
constexpr int SM_XLIST = SM_HIST + NB_MAX * 4;
constexpr int SM_SORT = SM_XLIST + 8;
constexpr int SM_SDEG = SM_SORT + NPB_MAX * 4;
constexpr int SM_PAIR = SM_SDEG + NPB_MAX * 2;
constexpr int SM_ENT = SM_ES + 1024;
constexpr int SM_H1 = SM_P1 + HB, SM_H2 = SM_P1;
constexpr int SM_IDX = SM_EID;
constexpr int SM_WR = SM_TAB;
static_assert(TILE_CAP <= 128 && TR >= 2 && SM_ES % 256 == 0 && NSTAGE == 2 && SM_BARS % 16 == 0 && SM_TINFO % 16 == 0 && SM_EID % 128 == 0 && SM_TAB % 1024 == 0 && SM_XU % 1024 == 0 && SM_TINFO % 8 == 0 && SM_OH % 16 == 0 && SM_XLIST % 8 == 0 && SM_PAIR % 8 == 0, "align");
static_assert(SM_P1 % 128 == 0 && P1B + HB <= SM_SRC - SM_EID && 2 * HB <= P1B && SM_H1 + 5 * 128 * 16 <= SM_XU && NB_MAX * (CE / 4) <= 6 * 384 && NB_MAX * 4 <= 5 * 128 && NB_MIN * 4 >= 3 * 128 && SM_PAIR + 128 * 8 <= SM_XU && CH_MAX * 4 <= SM_SRC - SM_EID && SM_DEG >= 3 << 14, "alias");
static_assert(CE == 64 && SMEM_BYTES <= 232448, "smem");
constexpr uint32_t C_BRK = 16  , C_CONT = 32, C_MORE = 64;
constexpr uint32_t ONE_F = 0x3F800000u;
constexpr int NONE = NPB_MAX - 1;
__host__ __device__ constexpr uint32_t tab_at(uint32_t n) { return (n >> 2) * 512 + (n & 3) * 32 + ((n >> 2) & 1) * 16; }

__device__ __forceinline__ uint32_t unpad(uint32_t w1, int np, float ga, float gb, float& d0, float& d1, int& dv) {
    const int pad = (w1 >> 8) & 31;
    dv = 2 * np - 1 - pad + (w1 >= ONE_F);
    float t0 = TAU * 2 * np, t1 = t0;
    if (pad) {
        t0 = fmaxf(t0, d0 * (1.f / 1024)); t1 = fmaxf(t1, d1 * (1.f / 1024));
        asm volatile("tanh.approx.f32 %0, %0;\ntanh.approx.f32 %1, %1;" : "+f"(ga), "+f"(gb));
        d0 -= pad * (1.f + ga); d1 -= pad * (1.f + gb);
    }
    if (dv == 0) { d0 = d1 = EPS2; t0 = t1 = 0.f; }
    return __ballot_sync(~0u, d0 < t0 || d1 < t1);
}
__device__ __noinline__ float4* exact_copy(uint32_t bad, float4* own)
{
    extern __shared__ __align__(1024) uint8_t smem[];
    uint32_t old = 1;
    if (bad == 1u << (threadIdx.x & 31)) old = atomicExch((uint32_t*)(smem + SM_MISC + 12), 1u);
    if (__all_sync(~0u, old)) return own;
    return old ? nullptr : (float4*)(smem + SM_XU + tab_at(NPB_MAX - 4) - 16);
}
__device__ __noinline__ float4 epi_exact(const float4* gh, int np, int dv)
{
    extern __shared__ __align__(1024) uint8_t smem[];
    float n0 = 0.f, d0 = 0.f, n1 = 0.f, d1 = 0.f;
    int j = 0, je = np;
    const uint32_t own = __ballot_sync(~0u, gh != nullptr);
    if (own != ~0u) {
        dv = __shfl_sync(~0u, dv, __ffs(own) - 1); j = min(threadIdx.x & 15, np); je = j + 1;
        gh = (const float4*)(smem + SM_XU + tab_at(NPB_MAX - 4) - 16);
        __syncwarp();
    }
    #pragma unroll 1
    for (; j < je; j++) {
        const float4 g = gh[j], h = gh[NPMAX + j];
        const bool ma = 2 * j < dv, mb = 2 * j + 1 < dv;
        const float e0 = 2.f * rcpf(1.f + ex2f(-2.f * LOG2E * g.x)), e1 = 2.f * rcpf(1.f + ex2f(-2.f * LOG2E * g.y));
        const float e2 = 2.f * rcpf(1.f + ex2f(-2.f * LOG2E * g.z)), e3 = 2.f * rcpf(1.f + ex2f(-2.f * LOG2E * g.w));
        if (ma) { d0 += e0; n0 = fmaf(e0, h.x, n0); d1 += e2; n1 = fmaf(e2, h.z, n1); }
        if (mb) { d0 += e1; n0 = fmaf(e1, h.y, n0); d1 += e3; n1 = fmaf(e3, h.w, n1); }
    }
    if (own != ~0u) {
        #pragma unroll
        for (int o = 1; o < 16; o <<= 1) {
            n0 += __shfl_xor_sync(~0u, n0, o); d0 += __shfl_xor_sync(~0u, d0, o);
            n1 += __shfl_xor_sync(~0u, n1, o); d1 += __shfl_xor_sync(~0u, d1, o);
        }
        *(volatile uint32_t*)(smem + SM_MISC + 12) = 0;
    }
    return make_float4(n0, d0 + EPS2, n1, d1 + EPS2);
}
template<int NP>
__device__ __forceinline__ void epi_dump(const float* g, const float* h, float4* gh) {
    #pragma unroll
    for (int i = 0; i < 2 * NP; i++) {
        const float* v = i < NP ? g + 4 * i : h + 4 * (i - NP);
        asm volatile("{\n.reg .pred p;\nsetp.ne.u64 p, %5, 0;\n@p st.v4.f32 [%0], {%1,%2,%3,%4};\n}"
                     :: "l"((uint64_t)gh + (i < NP ? i : NPMAX + i - NP) * 16), "f"(v[0]), "f"(v[1]), "f"(v[2]), "f"(v[3]), "l"(gh) : "memory");
    }
}
__device__ __forceinline__ void place(uint32_t sbase, uint32_t slot, uint32_t v, uint32_t eb) {
    asm volatile("{\n.reg .pred p;\nsetp.lt.u32 p, %0, %5;\n@p st.shared.u32 [%1], %2;\n@p st.shared.u16 [%3], %4;\n}"
                 :: "r"(slot), "r"(sbase + SM_EID + slot * 4), "r"(eb + (v >> 19)), "r"(sbase + SM_SRC + slot * 2), "r"(v), "n"(SLOT_CAP) : "memory");
}
__device__ __forceinline__ uint64_t desc_sw128(uint32_t a) {
    return (uint64_t)((a & 0x3FFFF) >> 4) | ((uint64_t)1 << 16) | ((uint64_t)64 << 32) | ((uint64_t)1 << 62);
}

template<bool LO32>
__global__ void __launch_bounds__(THREADS, 1)
gcn_kernel(const int* __restrict__ dst, unsigned* gbar, char* gs, const int* __restrict__ src, int E, int ch, int N, int npb, uint32_t magic,
           const __nv_bfloat16* __restrict__ x, const __nv_bfloat16* __restrict__ ea,
           const __nv_bfloat16* __restrict__ wa, const __nv_bfloat16* __restrict__ wb, const __nv_bfloat16* __restrict__ wc,
           const __nv_bfloat16* __restrict__ wu, const __nv_bfloat16* __restrict__ wv,
           __nv_bfloat16* out, int4 wrow, const __grid_constant__ CUtensorMap tm1, const __grid_constant__ CUtensorMap tm2,
           const __grid_constant__ CUtensorMap tmw, const __grid_constant__ CUtensorMap tmx)
{
    extern __shared__ __align__(1024) uint8_t smem[];
    int* cls = (int*)(smem + SM_CLS);
    int* misc = (int*)(smem + SM_MISC);
    WG0(); WS(0); CG(0);
    const uint32_t sbase = smem_u32(smem);
    const int tid = threadIdx.x, lane = tid & 31;
    const int b = blockIdx.x, nb = gridDim.x;
    const int cnt = max(0, min(ch, E - b * ch));
    const int node0 = b * npb;
    uint32_t tag = 0, cstart; asm volatile("mov.u32 %0, %%clock;" : "=r"(cstart));
    const int warp = (int)__reduce_max_sync(~0u, (unsigned)tid >> 5);
    const uint32_t su = __reduce_or_sync(~0u, sbase);
    auto weights = [&]() {
        w_box_ld(su + SM_WR, &tmw, wrow.x, su + SM_ABAR + 24); w_box_ld(su + SM_WR + 8192, &tmw, wrow.y, su + SM_ABAR + 24);
        w_box_ld(su + SM_WR + 16384, &tmw, wrow.z, su + SM_ABAR + 24); w_ld(su + SM_WR + 24576, wc, 2048, su + SM_ABAR + 24);
        w_box_ld(su + SM_WR + 40960, &tmw, wrow.w, su + SM_ABAR + 24);
    };
    if (warp >= 12) {
        const int v = warp & 3;
        const uint32_t a1 = su + SM_ABAR + (v == 0 ? 80 : v == 1 ? 120 : v == 2 ? 32 : 40);
        w_init(su + SM_ABAR + v * 8, 1); w_init(a1, 1);
        w_expect(su + SM_ABAR + v * 8, v < 3 ? min(max(cnt * 4 - v * 8192, 0), 8192) : 4 * 8192 + 2048);
        if (P1S) { if (v < 3) w_expect(a1, v == 0 ? 3 * 384 * 8 : v == 1 ? nb * 64 : nb * (CE * 2) - 3 * 384 * 8); }
        else if (v < 2) w_expect(a1, v == 0 ? nb * (CE * 2) : nb * 64);
        asm volatile("fence.mbarrier_init.release.cluster;" ::: "memory");
    }
    asm volatile("{\n.reg .pred q;\nsetp.lt.u32 q, %2, 384;\n@q ld.relaxed.gpu.global.u32 %0, [%1];\n}" : "+r"(tag) : "l"(gbar), "r"(tid));
    #pragma unroll
    for (int v = 0; v < EPT / 4; v++) {
        const uint32_t off = v * (THREADS * 4) + tid * 4;
        if (PD && v) { uint32_t c0, c1; asm volatile("mov.u32 %0, %%clock;" : "=r"(c0)); do { asm volatile("mov.u32 %0, %%clock;" : "=r"(c1)); } while (__all_sync(~0u, c1 - c0 < PD)); }
        asm volatile("{\n.reg .pred q;\nsetp.lt.u32 q, %2, %3;\n@q cp.async.cg.shared.global [%0], [%1], 16;\n}"
                     :: "r"(sbase + SM_IDX + off * 4), "l"(dst + b * ch + off), "r"(off), "r"(cnt) : "memory");
        cp_commit();
        if (WV == 7 + v && warp == 15) weights();
    }
    const int wg = warp >> 2, w = warp & 3;
    const int q = lane >> 2, t = lane & 3;
    const int nn = max(0, min(npb, N - node0));
    if (sbase & 1023) __trap();

    sts32(sbase + SM_DEG + tid * 4, tid < NPB_MAX ? 0 : 0x80000000u);
    if (tid < NCLS + NB_MAX) cls[tid] = tid < NCLS ? 0 : ((tid - NCLS) * 20) & 63;
    else if (warp == 8) sts32(sbase + SM_OH + lane * 4, t != (q >> 1) ? 0u : 0x00003F00u);
    else if (warp == 11) misc[lane] = lane == 5 ? TILE_CAP - TILE_X : lane == 8 || lane == 3;
    if (warp == 14) sts32(sbase + SM_TINFO + 96 * 32 + lane * 4, lane & 1 ? tab_at(NONE) : 0);
    if (warp == 15) sts32(sbase + SM_CLAIM + lane * 4, lane == 0 ? 3 * 32 : 0x40000000);
    if (tid == 0) sts32(sbase + SM_XLIST, tag);
    tag = (tag & 1) | 2;
    if (wg < 3) {
        const uint32_t d0 = ((NPB_MAX + ((2 * lane) & 15) + 16 * (b & 1)) * 4 | (tag << 14)) * 0x10001u, d1 = d0 + 0x40004u, d2 = tag << 16;
        #pragma unroll 1
        for (int i = tid; i < (P1B + 256) / 16; i += 384) {
            sts128(sbase + SM_P1 + i * 16, make_uint4(d0, d0, d1, d1));
            sts128(sbase + SM_P2 + i * 16, make_uint4(d2, d2, d2, d2)); sts128(sbase + SM_P2 + P1B + i * 16, make_uint4(d2, d2, d2, d2));
        }
    }
    WS(1);
    __syncthreads();
    if (wg == 3) tag = lds32(sbase + SM_P2) >> 16;
    uint32_t all = 0;
    if (wg == 3) all = (lds32(sbase + SM_XLIST) + 1) * nb;
    if (tid == 128) {
        asm volatile("prefetch.tensormap [%0];" :: "l"((uint64_t)&tmw) : "memory");
        asm volatile("prefetch.tensormap [%0];" :: "l"((uint64_t)&tm1) : "memory");
        asm volatile("prefetch.tensormap [%0];" :: "l"((uint64_t)&tm2) : "memory");
        asm volatile("prefetch.tensormap [%0];" :: "l"((uint64_t)&tmx) : "memory");
    }
    if (WPF && warp == 9 && b < 5) asm volatile(ELECT "cp.async.bulk.prefetch.L2.global [%0], %1;\n}" :: "l"(b == 0 ? wa : b == 1 ? wb : b == 2 ? wu : b == 3 ? wv : wc), "r"(b < 4 ? 8192 : 2048) : "memory");
    uint32_t ent[EPT];
    #pragma unroll
    for (int v = 0; v < EPT / 4; v++) {
        if (v == 0) cp_wait<2>(); else if (v == 1) cp_wait<1>(); else cp_wait<0>();
        if (v == SRCV && wg == 2 && w < 3) {
            const int n = min(cnt * 4 - w * 8192, 8192);
            if (n > 0) w_ld(su + SM_XU + w * 8192, src + b * ch + w * 2048, n, su + SM_ABAR + w * 8);
        }
        if (v == WV) {
            if (warp == 11) w_ld(su + SM_WR + 24576, wc, 2048, su + SM_ABAR + 24);
            else if (wg == 3) w_box_ld(su + SM_WR + (w == 3 ? 5 : w) * 8192, &tmw, w == 0 ? wrow.x : w == 1 ? wrow.y : w == 2 ? wrow.z : wrow.w, su + SM_ABAR + 24);
        }
        const uint32_t off = v * (THREADS * 4) + tid * 4;
        if (off < (uint32_t)cnt) {
            const uint4 u = lds128(sbase + SM_IDX + off * 4);
            uint32_t dv[4] = {u.x, u.y, u.z, u.w}, ps[4], ck[4];
            uint32_t* en = ent + 4 * v;
            #pragma unroll
            for (int k = 0; k < 4; k++) {
                dv[k] = min(dv[k], (uint32_t)(nb * npb - 1));
                ps[k] = __umulhi(dv[k], magic);
                asm volatile("atom.shared.add.u32 %0, [%1], 0x10001;" : "=r"(ck[k]) : "r"(sbase + SM_HIST + ps[k] * 4) : "memory");
            }
            #pragma unroll
            for (int k = 0; k < 4; k++) {
                dv[k] = (dv[k] - ps[k] * npb) * 4 + (tag << 14);
                en[k] = (ck[k] & 63) + ps[k] * CE;
            }
            if (__builtin_expect(max(max(ck[0], ck[1]), max(ck[2], ck[3])) >= CE << 16, 0)) {
                auto step = [&]() {
                    uint32_t e = en[0];
                    const uint32_t d = dv[0];
                    if (ck[0] >= CE << 16) {
                        uint32_t j; asm volatile("atom.shared.inc.u32 %0, [%1], 0x7fffffff;" : "=r"(j) : "r"(sbase + SM_MISC + 8) : "memory");
                        if (j >= 15) { sts32(sbase + SM_P1 + P1B + 60, 0xFE0000u | (tag << 14)); j = min(j + 1, 63u); }
                        sts32(sbase + SM_P1 + P1B + j * 4, d | ((j < 63 ? e / CE : 255u) << 16));
                        e = NB_MAX * CE + j;
                    }
                    en[0] = en[1]; en[1] = en[2]; en[2] = en[3]; en[3] = e;
                    dv[0] = dv[1]; dv[1] = dv[2]; dv[2] = dv[3]; dv[3] = d;
                    ck[0] = ck[1]; ck[1] = ck[2]; ck[2] = ck[3];
                };
                if (v == 2 && OVU) { step(); step(); step(); step(); }
                else {
                    #pragma unroll 1
                    for (int k = 0; k < 4; k++) step();
                }
            }
            #pragma unroll
            for (int k = 0; k < 4; k++)
                asm volatile("{\n.reg .pred p;\nsetp.lt.u32 p, %2, %3;\n@p st.shared.u16 [%0], %1;\n}" :: "r"(sbase + SM_P1 + en[k] * 2), "r"(dv[k]), "r"(en[k]), "n"(NB_MAX * CE) : "memory");
        }
    }
    if (warp == 15) {
        #pragma unroll
        for (int v = 0; v < EPT / 4; v++) sts128(sbase + SM_ENT + v * 512 + lane * 16, make_uint4(ent[4*v], ent[4*v+1], ent[4*v+2], ent[4*v+3]));
    }
    asm volatile("fence.proxy.async.shared::cta;" ::: "memory");
    WS(5);
    __syncthreads();
    auto delay = [&](uint32_t d) { uint32_t c0, c1; asm volatile("mov.u32 %0, %%clock;" : "=r"(c0)); do { asm volatile("mov.u32 %0, %%clock;" : "=r"(c1)); } while (__all_sync(~0u, c1 - c0 < d)); };
    if (warp == 15) {
        if (HORD != 2) w_inc(gbar + HI1);
        w_st(gs + G_H1 + b * 64, su + SM_P1 + P1B, 64);
        w_box_st(&tm1, b * (CE / 2), su + SM_P1);
        w_st(gs + G_L + b * 512, su + SM_P1 + P1B, 256);
        asm volatile("cp.async.bulk.commit_group;" ::: "memory");
        if (WV == 3) {
            w_box_ld(su + SM_WR, &tmw, wrow.x, su + SM_ABAR + 24); w_box_ld(su + SM_WR + 8192, &tmw, wrow.y, su + SM_ABAR + 24);
            w_box_ld(su + SM_WR + 16384, &tmw, wrow.z, su + SM_ABAR + 24); w_ld(su + SM_WR + 24576, wc, 2048, su + SM_ABAR + 24);
            w_box_ld(su + SM_WR + 40960, &tmw, wrow.w, su + SM_ABAR + 24);
        }
    } else {
        mbar_wait_c(su + SM_ABAR, 0);
        auto put = [&](uint32_t off, const uint32_t* uu) {
            if (off < (uint32_t)cnt) {
                const uint4 sv = lds128(sbase + SM_XU + off * 4);
                const uint32_t ss[4] = {sv.x, sv.y, sv.z, sv.w};
                #pragma unroll
                for (int k = 0; k < 4; k++) sts32(sbase + SM_P2 + uu[k] * 4, (ss[k] & 0xFFFF) | (((off + k) << 19) + (tag << 16)));
            }
        };
        #pragma unroll
        for (int v = 0; v < EPT / 4; v++) { if (v) mbar_wait_c(su + SM_ABAR + v * 8, 0); put(v * (THREADS * 4) + tid * 4, ent + 4 * v); }
        if (wg == 3) {
            const uint4 e = lds128(sbase + SM_ENT + w * 512 + lane * 16);
            const uint32_t uu[4] = {e.x, e.y, e.z, e.w};
            put(w * (THREADS * 4) + (480 + lane) * 4, uu);
        }
        asm volatile("fence.proxy.async.shared::cta;" ::: "memory");
        WS(7);
        __syncwarp();
        asm volatile("bar.arrive 12, 512;" ::: "memory");
    }
    WS(8);

    const int ngroups = (nn + 3) >> 2;
    if (warp < 12) {
        asm volatile("setmaxnreg.inc.sync.aligned.u32 152;");
        const uint32_t ab = su + SM_ABAR;
        uint32_t wf[40], wn[16];
        const uint32_t mo = sbase + (8 * (lane >> 4) + (lane & 7)) * 128 + (((2 * w + ((lane >> 3) & 1)) ^ (lane & 7)) << 4);
        const uint32_t wca = __shfl_sync(~0u, sbase + SM_WC + (16 * w + q) * 32 + t * 4 + ((q >> 2) << 4), lane), l16 = __shfl_sync(~0u, (lane & 15) * 16, lane);
        WS(1);
        BW(ab + 24, 0);
        WS(5);
        {
            #pragma unroll
            for (int ks = 0; ks < 4; ks++) { ldsm4t(wf + 4 * ks, mo + SM_WR + ks * 2048); ldsm4t(wf + 20 + 4 * ks, mo + SM_WR + 8192 + ks * 2048); ldsm4t(wn + 4 * ks, mo + SM_WR + 16384 + ks * 2048); }
            auto half = [](uint32_t& v) { asm("mul.rn.bf16x2 %0, %0, %1;" : "+r"(v) : "r"(0x3F003F00u)); };
            uint32_t z = 0;
            #pragma unroll
            for (int i = 0; i < 16; i++) { half(wf[i]); z ^= wf[i]; }
            sts32(sbase + SM_ES + lane * 4, z);
            if (wg == 2) {
                uint32_t f[4];
                ldsm4t(f, (mo ^ ((lane & 7) << 4)) + SM_WR + 24576);
                half(f[0]); half(f[1]); half(f[2]); half(f[3]);
                sts32(wca, f[0]); sts32(wca + 256, f[1]); sts32(wca ^ 16, f[2]); sts32((wca ^ 16) + 256, f[3]);
                asm volatile("fence.proxy.async.shared::cta;" ::: "memory");
            }
        }
        const uint64_t wcd = __reduce_or_sync(~0u, (((sbase + SM_WC) & 0x3FFFF) >> 4) | (8u << 16)) | EDHI;
        const uint32_t bar0 = __reduce_or_sync(~0u, sbase + SM_BARS + wg * 2 * STG);
        const uint32_t xd0 = __reduce_or_sync(~0u, (((sbase + SM_XS + wg * NSTAGE * XS_BYTES) & 0x3FFFF) >> 4) | (1u << 16));
        const uint32_t ed0 = __reduce_or_sync(~0u, (((sbase + SM_ES + wg * NSTAGE * ES_BYTES) & 0x3FFFF) >> 4) | (8u << 16));
        const uint64_t ohd = __reduce_or_sync(~0u, ((sbase + SM_OH) & 0x3FFFF) >> 4);
        const uint32_t tabx = __reduce_or_sync(~0u, sbase + SM_TAB + w * 128);
        const uint32_t bars = __reduce_or_sync(~0u, 2 * bar0 + STG), xds = __reduce_or_sync(~0u, 2 * xd0 + XS_BYTES / 16), eds = __reduce_or_sync(~0u, 2 * ed0 + ES_BYTES / 16);
        const uint32_t xuo = __reduce_or_sync(~0u, sbase + SM_XU + wg * 16384);
        { const uint2 z = lds64(sbase + SM_OH + 8); wf[38] = z.x; wf[39] = z.y; }
        WS(9);
        constexpr int NU = 6;
        const uint32_t dm = ((NPB_MAX + lane) * 4 | (tag << 14)) * 0x10001u;
        const uint32_t db = sbase + SM_DEG - (tag << 14);
        const char* const g1 = gs + (uint32_t)(b * (P1B + P2B) + tid * 8);
        int rk[NU][4];
        uint32_t spins = 0;
        constexpr int NH = P1S ? 2 : 1, NUH = NU / NH;
        #pragma unroll
        for (int hf = 0; hf < NH; hf++) {
            uint2 r1[NUH];
            BW(ab + (hf ? 32 : 80), 0);
            if (hf == 0) WS(2);
            #pragma unroll
            for (int k = 0; k < NUH; k++) {
                const int i = hf * NUH + k;
                r1[k] = make_uint2(dm, dm);
                if (i < 5 && NB_MIN * 16 >= 384 * (i + 1) || tid + 384 * i < nb * 16) r1[k] = lds64(sbase + SM_IDX + (tid + 384 * i) * 8);
            }
            #pragma unroll 1
            while (true) {
                uint32_t bad = 0;
                #pragma unroll
                for (int k = 0; k < NUH; k++) bad |= r1[k].y ^ dm;
                if (__builtin_expect(!__any_sync(~0u, bad & 0xC000), 1)) break;
                #pragma unroll
                for (int k = 0; k < NUH; k++) ld_unit(r1[k], g1 + 384 * 8 * (hf * NUH + k), (r1[k].y ^ dm) & 0xC000);
                if (++spins > (1u << 22)) break;
            }
            if (hf == 0) WS(3);
            #pragma unroll
            for (int k = 0; k < NUH; k++) {
                int* r = rk[hf * NUH + k];
                r[0] = r1[k].x & 0xFFFF; r[1] = r1[k].x >> 16; r[2] = r1[k].y & 0xFFFF; r[3] = r1[k].y >> 16;
                #pragma unroll
                for (int m = 0; m < 4; m++) asm volatile("red.shared.add.u32 [%0], 1;" :: "r"(db + min((uint32_t)r[m], NPB_MAX * 4 + (tag << 14))) : "memory");
            }
        }
        WS(10);
        asm volatile("bar.sync 11, 512;" ::: "memory");
        int mycls = 0, mycr = 0, dg = lds32(sbase + SM_DEG + tid * 4);
        if (tid < nn) {
            mycls = NCLS - 1 - (dg <= 40 ? dg : min(41 + ((dg - 41) >> 3), NCLS - 1)); mycr = atomicAdd(&cls[mycls], 1);
        }
        int s0 = 0;
        if (__builtin_expect(dg > 40, 0)) s0 = max(SLOT_CAP - ((dg + 1) & ~1) - atomicAdd(&misc[6], (dg + 1) & ~1), 0);
        asm volatile("bar.sync 1, 384;" ::: "memory");
        WS(12);
        {
            const uint2 c = lds64(sbase + SM_CLS + lane * 8);
            const int v0 = c.x * (lane > 11 ? ((64 - 2 * lane) << 16) + 1 : 1), v1 = c.y * (lane >= 11 ? ((62 - 2 * lane) << 16) + 1 : 1);
            int inc = v0 + v1;
            #pragma unroll
            for (int o = 1; o < 32; o <<= 1) { int y = __shfl_up_sync(~0u, inc, o); if (lane >= o) inc += y; }
            const int e0 = __shfl_sync(~0u, inc - v0 - v1, mycls >> 1), e1 = __shfl_sync(~0u, inc - v1, mycls >> 1);
            const int e = (mycls & 1) ? e1 : e0;
            if (tid < nn) {
                if (dg <= 40) s0 = min((e >> 16) + mycr * ((dg + 1) & ~1), SLOT_CAP - 40);
                sts32(sbase + SM_DEG + tid * 4, s0);
            }
            const uint32_t pos = tid < nn ? (e & 0xFFFF) + mycr : tid;
            sts32(sbase + SM_SORT + pos * 4, tid < nn ? (uint32_t)tid | ((uint32_t)s0 << 16) : NONE);
            asm volatile("st.shared.u16 [%0], %1;" :: "r"(sbase + SM_SDEG + pos * 2), "r"(min(dg, 65535)) : "memory");
            if (tid == 383) { misc[4] = (nn - c.y + 3) >> 2; if ((inc >> 16) + misc[6] > SLOT_CAP - 40) misc[1] = 1; }
        }
        asm volatile("bar.sync 1, 384;" ::: "memory");
        WS(13);
        const uint32_t sv = lds32(sbase + SM_SORT + tid * 4);
        const uint2 d4 = lds64(sbase + SM_SDEG + (tid >> 2) * 8);
        const uint32_t slow = lds32(sbase + SM_MISC + 4);
        #pragma unroll
        for (int i = 0; i < NU; i++) {
            #pragma unroll
            for (int k = 0; k < 4; k++) rk[i][k] = atoms_inc(db + rk[i][k]);
        }
        if (__reduce_or_sync(~0u, slow) == 0) {
            const uint32_t nd = sv & 0xFFFF;
            const int g = tid >> 2;
            dg = ((t & 2 ? d4.y : d4.x) >> (16 * (t & 1))) & 0xFFFF;
            const uint32_t hi2 = __vmaxu2(d4.x, d4.y), lo2 = __vminu2(d4.x, d4.y);
            const int mx = max(hi2 >> 16, hi2 & 0xFFFF), mn = min(lo2 >> 16, lo2 & 0xFFFF);
            int left = (mx + 1) >> 1;
            int tl = g, nx = ngroups + 4 + g, nt = left > NPMAX ? 2 : 1;
            const bool odd = left > 2 * NPMAX || (nt == 2 && nx >= TILE_CAP - TILE_X);
            if (__builtin_expect(__any_sync(~0u, odd), 0)) {
                if (odd) nt = (left + NPMAX - 1) / NPMAX;
                if (odd && t == 0) { asm volatile("atom.shared.add.u32 %0, [%1], %2;" : "=r"(nx) : "r"(sbase + SM_MISC + 20), "r"(nt - 1) : "memory"); if (nx + nt - 1 > TILE_CAP) misc[1] = 1; }
                nx = __shfl_sync(~0u, nx, lane & ~3);
                if (odd && nx + nt - 1 > TILE_CAP) left = 0;
            }
            const uint32_t w0 = tab_at(nd);
            if (g >= ngroups + 4) tl = ngroups;
            uint32_t cont = 0;
            int done = 0;
            bool act = true;
            do {
                int np = nt <= 2 ? (left + nt - 1) >> (nt - 1) : (left + nt - 1) / nt;
                left -= np; nt = max(nt - 1, 1);
                if (np) np = max(np, NPMIN);
                const int dv = min(max(dg - done, 0), 2 * np);
                uint32_t code = (uint32_t)np | cont | (left > 0 ? C_MORE : 0u);
                const bool gen = mn - done < 2 * np - (np == NPMIN ? 1 : 2);
                if (np == 0) code = 0;
                const uint32_t w1 = code | (dv == 2 * np ? 0x8000u : (2 * np - 1 - dv) << 8);
                if (act) *(uint2*)(smem + SM_TINFO + tl * 32 + t * 8) = make_uint2((dv ? (sv >> 16) + done : 0) | ((gen ? (np > 8 ? 15 : np > 5 ? 14 : 13) : np) << 16) | ((left > 0 ? nx : 0) << 20) | ((uint32_t)dv << 27), w0 | (np == 0 ? 0u : w1 << 16));
                tl = nx++; cont = C_CONT; done += 2 * np; act = left > 0;
            } while (__any_sync(~0u, act));
        }
        __syncwarp();
        asm volatile("bar.arrive 4, 512;" ::: "memory");
        WS(14);
        wf[16] = lds32(wca); wf[17] = lds32(wca + 256); wf[18] = lds32(wca ^ 16); wf[19] = lds32((wca ^ 16) + 256);
        #pragma unroll
        for (int pc = 0; pc < 3; pc++) {
            uint4 r2[2];
            BW(ab + pc * 8, 1);
            if (pc == 0) WS(4); if (pc == 2) WS(16);
            #pragma unroll
            for (int k = 0; k < 2; k++) {
                r2[k] = lds128(sbase + SM_P2 + (tid + 384 * (2 * pc + k)) * 16);
                if (rk[2 * pc + k][0] < 0) r2[k].w = tag << 16;
            }
            while (__builtin_expect(__any_sync(~0u, ((r2[0].w ^ (tag << 16)) | (r2[1].w ^ (tag << 16))) & 0x30000), 0)) {
                #pragma unroll
                for (int k = 0; k < 2; k++)
                    ld_unit(r2[k], g1 + (uint32_t)(tid * 8) + (P1B + 384 * 16 * (2 * pc + k)), (r2[k].w ^ (tag << 16)) & 0x30000);
                if (++spins > (1u << 22)) break;
            }
            #pragma unroll
            for (int k = 0; k < 2; k++) {
                const int i = 2 * pc + k;
                const uint32_t eb = ((tid >> 4) + 24 * i) * ch;
                place(sbase, rk[i][0], r2[k].x, eb); place(sbase, rk[i][1], r2[k].y, eb); place(sbase, rk[i][2], r2[k].z, eb); place(sbase, rk[i][3], r2[k].w, eb);
            }
        }
        WGD();
        __syncwarp();
        asm volatile("bar.arrive 3, 480;" ::: "memory");
        float g[4 * NPMAX], h[4 * NPMAX];
        float4 lgh[2 * NPMAX];
        float4 cyr = make_float4(0.f, 0.f, 0.f, 0.f);
        WS(15); CG(1);
        if (GD) { uint32_t c0, c1; asm volatile("mov.u32 %0, %%clock;" : "=r"(c0)); do { asm volatile("mov.u32 %0, %%clock;" : "=r"(c1)); } while (__all_sync(~0u, c1 - c0 < GD)); }
        BW(ab + 88 + wg * 8, 0);
        WSG(1);
        auto pack = [&](uint32_t* v, const float* u) {
            #pragma unroll
            for (int i = 0; i < 16; i++) v[i] = pack_bf16(u[2*i], u[2*i+1]);
        };
        auto rows_st = [&](uint32_t p, const uint32_t* v) {
            #pragma unroll
            for (int i = 0; i < 4; i++) stsm4t(p + i * 2048, v + 4 * i);
        };
        {
            const uint64_t d0 = desc_sw128(xuo), d1 = d0 + 512;
            const uint32_t mr = sbase + wg * 16384 + w * 128 + (tab_at(8 * (lane >> 4) + (lane & 7)) ^ ((lane & 8) << 1));
            uint32_t v[16];
            node_mma(g, wn, d0); node_mma(h, wn, d1);
            TileMMA<8>::wait_g(g);
            pack(v, g); rows_st(mr + SM_TAB, v);
            TileMMA<8>::wait_h(h);
            WSG(5);
            #pragma unroll
            for (int ks = 0; ks < 4; ks++) ldsm4t(wn + 4 * ks, mo + SM_WR + 40960 + ks * 2048);
            node_mma(g, wn, d0);
            if (wg == 2) asm volatile("bar.sync 5, 384;" ::: "memory"); else asm volatile("bar.arrive 5, 384;" ::: "memory");
            pack(v, h); rows_st(mr + SM_TAB + 8192, v);
            node_mma(h, wn, d1);
            __syncwarp();
            if (lane == 0) mbar_arrive(sbase + SM_ABAR + 112);
            WSG(7);
            TileMMA<8>::wait_g(g);
            pack(v, g);
            asm volatile("bar.sync %0, 128;" :: "r"(8 + wg) : "memory");
            rows_st(mr + SM_XU, v);
            TileMMA<8>::wait_h(h);
            WSG(11);
            pack(v, h);
            asm volatile("bar.sync %0, 128;" :: "r"(8 + wg) : "memory");
            rows_st(mr + SM_XU + 8192, v);
            __syncwarp();
            if (lane == 0) mbar_arrive(sbase + SM_ABAR + 72);
            BW(ab + 112, 0);
            __syncwarp();
            if (__builtin_expect(__reduce_or_sync(~0u, misc[1]) != 0, 0)) { slow_bin(x, ea, src, dst, wa, wb, wc, wu, wv, out, E, node0, nn, 384); asm volatile("exit;"); }
            WS(6);
        }
        uint32_t bar = bar0, xd = xd0, ed = ed0, ph = 0;
        float pn0 = 0.f, pd0 = 1.f, pn1 = 0.f, pd1 = 1.f;
        uint4 rc;
        rc.x = lds32(sbase + SM_TINFO + wg * 32 + ((lane >> 1) & 3) * 8 + 4);
        uint32_t code = __reduce_or_sync(~0u, rc.x >> 16);
        rc.x = (rc.x & 0xFFFF) ^ ((lane & 8) << 1); rc.y = tab_at(NONE);
        auto fetch_a = [&]() {
            asm volatile("ldmatrix.sync.aligned.m8n8.x2.trans.shared.b16 {%0,%1}, [%2];" : "=r"(wf[36]), "=r"(wf[37]) : "r"(tabx + rc.x) : "memory");
        };
        auto emit = [&]() {
            asm volatile("stmatrix.sync.aligned.m8n8.x1.trans.shared.b16 [%0], {%1};" :: "r"(tabx + rc.y), "r"(pack_bf16(pn0 * rcpf(pd0), pn1 * rcpf(pd1))) : "memory");
        };
        auto carry = [&]() {
            if (rc.z & C_CONT) { pn0 += cyr.x; pd0 += cyr.y; pn1 += cyr.z; pd1 += cyr.w; }
            if (rc.z & C_MORE) { cyr = make_float4(pn0, pd0 - EPS2, pn1, pd1 - EPS2); pn0 = pn1 = 0.f; rc.y = tab_at(NONE); }
        };
        fetch_a();
        while (true) {
            switch (code & 15) {
                default: goto finished;
#define TILE(P) { \
                    float dmin; \
                    do { \
                        mbar_wait_c(bar, ph); \
                        TileMMA<P>::issue(g, h, wf, xd, ed | EDHI, ohd, wcd); \
                        const uint32_t eb = bar + 8; \
                        ph ^= bar != bar0; bar = bars - bar; xd = xds - xd; ed = eds - ed; \
                          \
                        asm volatile("{\n.reg .pred p;\nsetp.eq.u32 p, %0, 77;\n@p trap;\n}" :: "r"(xds) : "memory"); \
                        emit(); rc = lds128(eb + 8 + l16); \
                        TileMMA<P>::wait_g(g); fetch_a(); TileMMA<P>::wait_h(h); \
                        mbar_arrive(eb); \
                        epi_fast<P>(g, h, __uint_as_float(rc.z), pn0, pd0, pn1, pd1, dmin); \
                    } while (!__any_sync(~0u, !(dmin >= __uint_as_float(rc.w)))); \
                    code = __reduce_or_sync(~0u, rc.w); \
                    if (__builtin_expect(__any_sync(~0u, (rc.z & 0x1F00) != 0 || dmin < TAU * 2 * P), 0)) { \
                        int dv; \
                        const uint32_t bad = unpad(rc.z, P, g[4 * P - 4], g[4 * P - 2], pd0, pd1, dv); \
                        if (bad) { \
                            FBLOG(P); \
                            float4* gh = exact_copy(bad, lgh); \
                            epi_dump<P>(g, h, gh); \
                            const float4 r = epi_exact(gh, P, dv); \
                            if (gh) { pn0 = r.x; pd0 = r.y; pn1 = r.z; pd1 = r.w; } \
                        } \
                    } \
                    if (code & C_BRK) { carry(); if (P != 11 && (code & 15) == P) goto L##P; } \
                    if (P == 11) {         \
                        wf[16] = lds32(wca); wf[17] = lds32(wca + 256); wf[18] = lds32(wca ^ 16); wf[19] = lds32((wca ^ 16) + 256); \
                    } }
#define CASE(P, UP, DN) case P: L##P: TILE(P) \
                    if (P > NPMIN && (code & 15) == P - 1) goto L##DN; \
                    if ((code & 15) == UP) goto L##UP; \
                    break;
                CASE(11, 11, 10) CASE(10, 11, 9) CASE(9, 10, 8) CASE(8, 9, 7) CASE(7, 8, 6) CASE(6, 7, 5) CASE(5, 6, 4) CASE(4, 5, 4)
#undef CASE
#undef TILE
            }
        }
finished:
        emit();
        __syncwarp();
        if (lane == 0) mbar_arrive(sbase + SM_ABAR + 48 + wg * 8);
    } else {
        asm volatile("setmaxnreg.dec.sync.aligned.u32 56;");
        auto x_ld = [&](int i0, int i1) {
            #pragma unroll
            for (int i = i0; i < i1; i++) w_box_ld(su + SM_XU + i * 8192, &tmx, node0 + i * 64, su + SM_ABAR + 88 + (i >> 1) * 8);
        };
        if (w < 3) {
            #pragma unroll
            for (int i = 0; i < 2; i++) { w_init(su + SM_BARS + (w * 2 + i) * STG, 64); w_init(su + SM_BARS + (w * 2 + i) * STG + 8, 128); }
            w_init(su + SM_ABAR + 48 + w * 8, 4);
            w_init(su + (w == 0 ? SM_GBAR + 96 * 8 : w == 1 ? SM_ABAR + 72 : SM_ABAR + 112), w == 0 ? 32 : 12);
        } else {
            #pragma unroll
            for (int i = 0; i < 4; i++) { w_init(su + SM_ABAR + (i < 3 ? 88 + i * 8 : 40), 1); w_expect(su + SM_ABAR + (i < 3 ? 88 + i * 8 : 40), i < 3 ? 16384 : nb * 64); }
            asm volatile("fence.mbarrier_init.release.cluster;" ::: "memory");
            if (HORD == 3) { uint32_t c; do { asm volatile("mov.u32 %0, %%clock;" : "=r"(c)); } while (__all_sync(~0u, c - cstart < T1)); }
            if (!HORD || HORD == 3) w_hint(gbar + HI1, all);
            asm volatile("cp.async.bulk.wait_group.read 0;" ::: "memory");
            WS(9);
            if (HORD == 1) w_hint(gbar + HI1, all);
            if (HORD == 2) { uint32_t c; do { asm volatile("mov.u32 %0, %%clock;" : "=r"(c)); } while (__all_sync(~0u, c - cstart < T1)); }
            if (D1) delay(D1);
            WS(2);
            if (H1F) w_ld(su + SM_H1, gs + G_H1, nb * 64, su + SM_ABAR + 120);
            if (P1S) {
                w_ld(su + SM_IDX, gs + b * (P1B + P2B), 3 * 384 * 8, su + SM_ABAR + 80);
                w_ld(su + SM_IDX + 3 * 384 * 8, gs + b * (P1B + P2B) + 3 * 384 * 8, nb * (CE * 2) - 3 * 384 * 8, su + SM_ABAR + 32);
            } else w_ld(su + SM_IDX, gs + b * (P1B + P2B), nb * (CE * 2), su + SM_ABAR + 80);
            if (!H1F) w_ld(su + SM_H1, gs + G_H1, nb * 64, su + SM_ABAR + 120);
        asm volatile("bar.sync 12, 512;" ::: "memory");
            if (D3) delay(D3);
            if (H2M == 1) w_inc(gbar + HI2);
            w_box_st(&tm2, P1B / 4 + b * CE, su + SM_P2);
            w_st(gs + G_H2 + b * 64, su + SM_P2 + P2B, 64);
            w_st(gs + G_L + b * 512 + 256, su + SM_P2 + P2B, 256);
            if (H2M == 0) w_sent(gbar + HI2, su + SM_MISC + 32);
            asm volatile("cp.async.bulk.commit_group;" ::: "memory");
            if (!XAFT) x_ld(0, XSPL);
        }
        const uint32_t ab = su + SM_ABAR;
        uint32_t todo = 0;
        WS(12);
        BW(ab + 120, 0);
        WS(13);
        {
            uint4 r[5];
            #pragma unroll
            for (int i = 0; i < 5; i++) r[i] = lds128(sbase + SM_H1 + (tid - 384 + 128 * i) * 16);
            #pragma unroll
            for (int i = 0; i < 5; i++) {
                const uint32_t bb = b << 16;
                const uint32_t m = min(min(min(r[i].x ^ bb, r[i].y ^ bb), min(r[i].z ^ bb, r[i].w ^ bb)), r[i].w ^ 0xFE0000u) >> 16;
                if ((m == 0) | (((r[i].w ^ (tag << 14)) & 0xC000) != 0)) todo |= 1 << i;
            }
            todo &= tid - 384 + 512 < nb * 4 ? 31 : tid - 384 + 384 < nb * 4 ? 15 : 7;
        }
        #pragma unroll 1
        for (int put = 0; put < 2; put++) {
            uint32_t any = __reduce_or_sync(~0u, todo), m = 0, u = 0;
            #pragma unroll 1
            while (any | m) {
                uint4 r = make_uint4(0, 0, 0, 0), r2 = r;
                uint32_t s, go, gd;
                bool on;
                if (__builtin_expect(m == 0, 1)) {
                    const uint32_t i = __ffs(any) - 1;
                    any &= any - 1; u = tid - 384 + 128 * i; on = (todo >> i) & 1;
                    r = lds128(sbase + SM_H1 + u * 16); if (!NOH2) r2 = lds128(sbase + SM_H2 + u * 16);
                    s = u >> 2; go = G_H1 + u * 16; gd = HB;
                } else {
                    s = ((u & ~31) + __ffs(m) - 1) >> 2; m &= m - 1; on = lane < 12;
                    go = G_L + s * 512 + 64 + lane * 16; gd = 256;
                }
                #pragma unroll 1
                for (int n = 0; n < (1 << 22); n++) {
                    const bool b1 = on && ((r.w >> 14) & 3) != tag, b2 = on && put && ((r2.w >> 16) & 3) != tag;
                    if (__builtin_expect(!__any_sync(~0u, b1 | b2), 1)) break;
                    ld_unit(r, gs + go, b1); ld_unit(r2, gs + go + gd, b2);
                }
                if (gd == HB) m = __ballot_sync(~0u, on && r.w >> 16 == 0xFE);
                if (on && r.w >> 16 == 255) sts32(sbase + SM_MISC + 4, 1);
                const uint32_t e[4] = {r.x, r.y, r.z, r.w}, v[4] = {r2.x, r2.y, r2.z, r2.w};
                uint32_t slot[4];
                #pragma unroll
                for (int k = 0; k < 4; k++) slot[k] = atoms_inc(sbase + SM_DEG + (on && e[k] >> 16 == (uint32_t)b ? (e[k] & 0x3FFF) : (NPB_MAX + lane) * 4));
                if (put) {
                    #pragma unroll
                    for (int k = 0; k < 4; k++) place(sbase, slot[k], v[k], s * ch);
                }
            }
            if (put == 0) {
                WS(4);
                asm volatile("bar.arrive 11, 512;" ::: "memory");
                if (w == 3) {
                    if (XAFT) x_ld(0, XSPL);
                    w_expect(su + SM_ABAR, 12288); w_expect(su + SM_ABAR + 8, 12288); w_expect(su + SM_ABAR + 16, nb * (CE * 4) - 24576);
                    w_hint(gbar + HI2, all);
                    if (D2) delay(D2);
                    asm volatile("cp.async.bulk.wait_group.read 0;" ::: "memory");
                    WS(3);
                    const char* g2 = gs + b * (P1B + P2B) + P1B;
                    w_ld(su + SM_P2, g2, 12288, su + SM_ABAR);
                    w_ld(su + SM_P2 + 12288, g2 + 12288, 12288, su + SM_ABAR + 8);
                    w_ld(su + SM_P2 + 24576, g2 + 24576, nb * (CE * 4) - 24576, su + SM_ABAR + 16);
                    if (!NOH2) w_ld(su + SM_H2, gs + G_H2, nb * 64, su + SM_ABAR + 40);
                    if (XW2) mbar_wait(ab + (XW2 - 1) * 8, 1);
                    x_ld(XSPL, 6);
                } else {
                    #pragma unroll 8
                    for (int i = 0; i < 32; i++) w_init(su + SM_GBAR + (w * 32 + i) * 8, 32);
                }
                asm volatile("bar.sync 4, 512;" ::: "memory");
                if (NOH2) mbar_wait(ab, 1); else BW(ab + 40, 0);
            }
        }
        __syncwarp();
        WS(10);
        WGD();
        const uint32_t scr = sbase + SM_PAIR + (tid & 127) * 8;
        const int r4 = lane >> 3, c8 = lane & 7;
        const uint32_t sb = su;
        const uint32_t tk = ((c8 & 1) << 4) | ((c8 >> 1) << 7);
        auto row_bytes = [](uint32_t o) { return (o & 0xFE00) | ((o << 2) & 0x180); };
        if (w < 3) {
            const char* gx = as_pair((const char*)x + c8 * 16, scr);
            const char* ge = as_pair((const char*)ea + (lane & 1) * 16, scr);
            const uint32_t gx0 = (uint32_t)(uint64_t)gx, ge0 = (uint32_t)(uint64_t)ge, hi = (uint64_t)gx >> 32, he = (uint64_t)ge >> 32;
            const int s = (lane >> 1) & 3;
            const uint32_t xs0 = sb + SM_XS + w * NSTAGE * XS_BYTES;
            const uint32_t es0 = sb + SM_ES + w * NSTAGE * ES_BYTES + r4 * 64 + (((lane ^ (r4 >> 1)) & 1) << 4) + (s >> 1) * 256 + (s & 1) * 32;
            const uint32_t bars = sb + SM_BARS + w * 2 * STG;
            const uint32_t xoffA = (2 * r4) * 128 + ((c8 ^ (2 * r4)) << 4), xoffB = (2 * r4 + 1) * 128 + ((c8 ^ (2 * r4 + 1)) << 4);
            uint64_t pol;
            asm volatile("createpolicy.fractional.L2::evict_first.b64 %0, 1.0;" : "=l"(pol));
            if (TLBW) {
                const uint32_t k = w * 32 + lane;
                asm volatile("prefetch.global.L2 [%0];" :: "l"(k < 64 ? (const char*)ea + (size_t)(E >> 6) * k * 32 : (const char*)x + (size_t)(N >> 5) * (k - 64) * 128));
            }
            asm volatile("bar.sync 6, 128;" ::: "memory");
            bool first = true; int tcount = 0;
            WS(15);
            uint32_t ph = 1, cur = w;
            uint32_t hist = 96 * 0x010101u;
            auto done3 = [&]() { mbar_arrive(sb + SM_GBAR + ((hist >> 16) & 0xFF) * 8); };
            const bool go = misc[1] == 0 && nn > 0;
            const uint32_t ca = sb + SM_CLAIM + lane * 4, pa = sb + SM_TINFO + r4 * 8;
            const uint32_t pb = sb + SM_TINFO + s * 8 + 4, pc = sb + SM_TINFO + (lane & 3) * 8 + 6, xl = (lane & 8) << 1, xs = (lane & 1) << 4, ra = (lane & 15) * 16 + 16;
            auto row_of = [&](uint32_t o) { uint32_t v; asm volatile("ld.shared.u16 %0, [%1];" : "=r"(v) : "r"(pb + o) : "memory"); return v; };
            auto code_of = [&](uint32_t o) { uint32_t v; asm volatile("ld.shared.s16 %0, [%1];" : "=r"(v) : "r"(pc + o) : "memory"); return v; };
            uint32_t pw = lds32(pa + w * 32), pt = __reduce_or_sync(~0u, pw), cont = 0;
            uint4 rc = make_uint4(0, row_of(w * 32) ^ xs, code_of(w * 32) & (ONE_F | 0x1FFFu), 0);
            const uint32_t se0 = sb + SM_EID + s * 4, xab = xoffB - xoffA, das = 2 * (xs0 + xoffA) + XS_BYTES, des = 2 * es0 + ES_BYTES, brs = 2 * bars + STG;
            uint32_t da = xs0 + xoffA, de = es0, br = bars;
            #pragma unroll 1
            while (go) {
                uint32_t se, sx;
                asm("dp2a.lo.u32.u32 %0, %1, 4, %2;" : "=r"(se) : "r"(pw), "r"(se0));
                asm("dp2a.lo.u32.u32 %0, %1, 2, %2;" : "=r"(sx) : "r"(pw), "r"(sb + SM_SRC));
                const int dv = pw >> 27;
                const uint32_t db = da + xab;
                const uint32_t sel = (pt >> 16) & 15, nx = (pt >> 15) & (127 << 5);
                uint32_t g;
                auto claim = [&]() { asm volatile("atom.shared.add.u32 %0, [%1], %2;" : "=r"(g) : "r"(ca), "r"(nx == 0 ? 32u : 0u) : "memory"); };
                if (sel == 0) break;
                if (first) { asm volatile("bar.sync 3, 480;" ::: "memory"); first = false;
                }
                if (S2W && hist == 96 * 0x010101u * 256 + (cont ? 96u : (uint32_t)w)) mbar_wait_c(sb + SM_ABAR + (S2W == 1 ? 112 : 72), 0);
                switch (sel) {
#define CASE(L, P, GEN) case L: { \
                        uint32_t oe[(P + 1) / 2], o[P]; \
                        _Pragma("unroll") for (int j = 0; j < (P + 1) / 2; j++) oe[j] = lds32(se + j * 16); \
                        _Pragma("unroll") for (int j = 0; j < P; j++) o[j] = lds32(sx + j * 4); \
                        mbar_wait_h(br + 8, ph); \
                        _Pragma("unroll") for (int j = 0; j < (P + 1) / 2; j++) \
                            if (LO32) { if (!GEN && 2 * j + 2 < P) cpe<false>(he, de + j * 512, oe[j], ge0, 0, 0, pol); \
                                else if (2 * j + 1 < NPMAX || s < 2) cpe<true>(he, de + j * 512, oe[j], ge0, 4 * j + s, dv, pol); } \
                            else if (!GEN && 2 * j + 2 < P) cp16e(de + j * 512, ge, oe[j], pol); else if (2 * j + 1 < NPMAX || s < 2) cp16z<32>(de + j * 512, ge, oe[j], 4 * j + s, dv, pol); \
                        _Pragma("unroll") for (int j = 0; j < P - 1; j++) { \
                            if (LO32) { cpx<0, GEN>(hi, da + j * 1024, o[j], gx0, 2 * j, dv); cpx<1, GEN>(hi, db + j * 1024, o[j], gx0, 2 * j + 1, dv); } \
                            else if (GEN) { cp16z<128>(da + j * 1024, gx, o[j] & 0xFFFFu, 2 * j, dv, 0); cp16z<128>(db + j * 1024, gx, o[j] >> 16, 2 * j + 1, dv, 0); } \
                            else { cp16i<128>(da + j * 1024, gx, o[j] & 0xFFFFu); cp16i<128>(db + j * 1024, gx, o[j] >> 16); } } \
                        if (LO32) { cpx<0, true>(hi, da + (P - 1) * 1024, o[P - 1], gx0, 2 * P - 2, dv); cpx<1, true>(hi, db + (P - 1) * 1024, o[P - 1], gx0, 2 * P - 1, dv); } \
                        else { cp16z<128>(da + (P - 1) * 1024, gx, o[P - 1] & 0xFFFFu, 2 * P - 2, dv, 0); cp16z<128>(db + (P - 1) * 1024, gx, o[P - 1] >> 16, 2 * P - 1, dv, 0); } \
                    } break;
                    CASE(4, 4, false) CASE(5, 5, false) CASE(6, 6, false) CASE(7, 7, false) CASE(8, 8, false) CASE(9, 9, false) CASE(10, 10, false) CASE(11, 11, false)
                    CASE(15, NPMAX, true) CASE(14, 8, true) default: CASE(13, 5, true)
#undef CASE
                }
                claim();
                mbar_cp_arrive(br);
                done3();
                g = __reduce_min_sync(~0u, g);
                {
                    const uint32_t o = nx == 0 ? g : nx;
                    pw = lds32(pa + o);
                    const uint32_t ya = row_of(o), yb = code_of(o);
                    pt = __reduce_or_sync(~0u, pw);
                    const uint32_t brk = (cont | nx) ? C_BRK : 0u;
                    rc.x = ya ^ xl;
                    const uint32_t lv = brk | ((sel + (15 - NPMAX)) & 16) | (((pt >> 16) & 15) ^ sel);
                    rc.w = (yb & 15) | (lv ? 0x70000000u | brk : TAU_BITS);
                    asm volatile("st.shared.v4.u32 [%2], {%3, %0, %1, %4};\nxor.b32 %0, %5, %6;\nand.b32 %1, %7, %8;"
                                 : "+r"(rc.y), "+r"(rc.z) : "r"(br + ra), "r"(rc.x), "r"(rc.w), "r"(ya), "r"(xs), "r"(yb), "n"(ONE_F | 0x1FFFu) : "memory");
                    cont = nx;
                }
                mbar_arrive(br);
                hist = (hist << 8) | (nx == 0 ? cur : 96u);
                cur = nx == 0 ? g >> 5 : cur;
                ph ^= br != bars; br = brs - br; da = das - da; de = des - de;
            }
            if (first) asm volatile("bar.sync 3, 480;" ::: "memory");
            if (go) {
                mbar_wait(sb + SM_ABAR + 72, 0);
                const int g0 = 3 * max((ngroups + 2) / 3 - TR, 0) + w;
                uint32_t nd[TR]; uint4 xv[TR];
                #pragma unroll
                for (int k = 0; k < TR; k++) {
                    asm volatile("ld.shared.u16 %0, [%1];" : "=r"(nd[k]) : "r"(pa + (g0 + 3 * k) * 32 + 4) : "memory");
                    xv[k] = __ldg((const uint4*)(gx + (size_t)node0 * 128 + (nd[k] == tab_at(NONE) ? 0u : row_bytes(nd[k]))));
                }
                #pragma unroll 1
                for (int k = 0; k < 3; k++) {
                    if (TSPIN && k == 2) mbar_wait_s(sb + SM_ABAR + 48 + w * 8, 0); else mbar_wait(k < 2 ? br + 8 : sb + SM_ABAR + 48 + w * 8, k < 2 ? ph : 0);
                    done3(); hist <<= 8;
                    ph ^= br != bars; br = brs - br;
                }
                #pragma unroll
                for (int k = 0; k < TR; k++) {
                    const uint32_t ro = sb + (nd[k] ^ tk);
                    const uint4 xu = lds128(ro + SM_XU);
                    uint4 a = make_uint4(0, 0, 0, 0);
                    if (g0 + 3 * k < misc[4]) { if (TSPIN) mbar_wait_s(sb + SM_GBAR + (g0 + 3 * k) * 8, 0); else mbar_wait(sb + SM_GBAR + (g0 + 3 * k) * 8, 0); a = lds128(ro + SM_TAB); }
                    finish(a, xu, xv[k]);
                    if (nd[k] != tab_at(NONE)) *(uint4*)((char*)out + (size_t)node0 * 128 + row_bytes(nd[k]) + c8 * 16) = a;
                }
            }
            cp_wait<0>();
        } else {
            const int r4 = WMAP ? (lane >> 1) & 3 : lane >> 3, c8 = WMAP ? (lane >> 3) * 2 + (lane & 1) : lane & 7;
            const uint32_t tk = ((c8 & 1) << 4) | ((c8 >> 1) << 7);
            const char* gx = as_pair((const char*)x + (size_t)node0 * 128 + c8 * 16, scr);
            const char* ob = as_pair((const char*)out + (size_t)node0 * 128 + c8 * 16, scr);
            asm volatile("bar.arrive 6, 128;" ::: "memory");
            WS(15);
            if (b == 0 && lane == 0) asm volatile("red.relaxed.gpu.global.add.u32 [%0], 1;" :: "l"(gbar) : "memory");
            if (misc[1] == 0) mbar_wait(sb + SM_ABAR + 72, 0);
            if (npb <= NPB_MAX - 4) sts32(sb + SM_MISC + 12, 0);
            const int rounds = misc[1] ? 0 : max((ngroups + 2) / 3 - TR, 0);
            const int gz = misc[4], fast = __reduce_min_sync(~0u, min(rounds, gz / 3));
            uint32_t wl = sb + SM_TINFO + r4 * 8 + 4, gbar = sb + SM_GBAR;
            auto row_at = [&](uint32_t a) { uint32_t n; asm volatile("ld.shared.u16 %0, [%1];" : "=r"(n) : "r"(a) : "memory"); return n; };
            auto fetch = [&](uint32_t n, uint4& v) {
                asm volatile("{\n.reg .b64 p;\ncvt.u64.u32 p, %5;\nadd.u64 p, p, %4;\nld.global.nc.L1::no_allocate.v4.u32 {%0,%1,%2,%3}, [p];\n}"
                             : "=r"(v.x), "=r"(v.y), "=r"(v.z), "=r"(v.w) : "l"(gx), "r"(n));
            };
            auto store = [&](uint32_t n, const uint4& a) {
                asm volatile("{\n.reg .b64 p;\ncvt.u64.u32 p, %1;\nadd.u64 p, p, %0;\nst.global.v4.u32 [p], {%2,%3,%4,%5};\n}" :: "l"(ob), "r"(n), "r"(a.x), "r"(a.y), "r"(a.z), "r"(a.w) : "memory");
            };
            uint32_t n0[3], o0[3]; uint4 x0[3];
            const uint32_t tw = __shfl_sync(~0u, tk, lane);
            if (fast) {
                #pragma unroll
                for (int r = 0; r < 3; r++) { const uint32_t v = row_at(wl + r * 32); n0[r] = row_bytes(v); o0[r] = v ^ tw; fetch(n0[r], x0[r]); }
            }
            #pragma unroll 1
            for (int k = 0; k < fast; k++) {
                wl += 96;
                #pragma unroll
                for (int r = 0; r < 3; r++) {
                    const uint32_t nd = n0[r];
                    const uint4 xu = lds128(sb + o0[r] + SM_XU);
                    const uint32_t v = row_at(wl + r * 32);
                    mbar_wait(gbar + r * 8, 0);
                    uint4 a = lds128(sb + o0[r] + SM_TAB);
                    n0[r] = row_bytes(v); o0[r] = v ^ tw;
                    finish(a, xu, x0[r]);
                    fetch(n0[r], x0[r]);
                    store(nd, a);
                }
                gbar += 24;
            }
            #pragma unroll 1
            for (int g = 3 * fast; g < 3 * rounds; g++) {
                const uint32_t v = row_at(sb + SM_TINFO + r4 * 8 + 4 + g * 32), nd = row_bytes(v), ro = sb + (v ^ tw);
                uint4 xv, a = make_uint4(0, 0, 0, 0);
                fetch(nd, xv);
                if (g < gz) { mbar_wait(sb + SM_GBAR + g * 8, 0); a = lds128(ro + SM_TAB); }
                finish(a, lds128(ro + SM_XU), xv);
                store(nd, a);
            }
        }
    }
    WS(17); WG1(); CG(2);
}

}

extern "C" void kernel_launch(void* const* d_in, const int* in_sizes, int n_in, void* d_out, int out_size) {
    const __nv_bfloat16* x = (const __nv_bfloat16*)d_in[0];
    const __nv_bfloat16* ea = (const __nv_bfloat16*)d_in[1];
    const int* src = (const int*)d_in[2];
    const int* dst = (const int*)d_in[3];
    const __nv_bfloat16* wa = (const __nv_bfloat16*)d_in[4];
    const __nv_bfloat16* wb = (const __nv_bfloat16*)d_in[5];
    const __nv_bfloat16* wc = (const __nv_bfloat16*)d_in[6];
    const __nv_bfloat16* wu = (const __nv_bfloat16*)d_in[7];
    const __nv_bfloat16* wv = (const __nv_bfloat16*)d_in[8];
    __nv_bfloat16* out = (__nv_bfloat16*)d_out;
    int N = in_sizes[0] / 64, E = in_sizes[2];
    static int sms = 0;
    static CUtensorMap tm1, tm2, tmw, tmx;
    static bool tm_ok = false;
    static void* gp = nullptr; static void* gb = nullptr;
    typedef CUresult (*EncFn)(CUtensorMap*, CUtensorMapDataType, cuuint32_t, void*, const cuuint64_t*, const cuuint64_t*, const cuuint32_t*,
                              const cuuint32_t*, CUtensorMapInterleave, CUtensorMapSwizzle, CUtensorMapL2promotion, CUtensorMapFloatOOBfill);
    static void* fn = nullptr;
    auto enc = [&](CUtensorMap* tm, const void* base, cuuint64_t cols, cuuint64_t rows, cuuint32_t bc, cuuint32_t br, CUtensorMapSwizzle sw) {
        cuuint64_t g2[2] = {cols, rows}, gs[1] = {cols * 4};
        cuuint32_t b2[2] = {bc, br}, es[2] = {1, 1};
        return ((EncFn)fn)(tm, CU_TENSOR_MAP_DATA_TYPE_UINT32, 2, (void*)base, g2, gs, b2, es, CU_TENSOR_MAP_INTERLEAVE_NONE, sw,
                           CU_TENSOR_MAP_L2_PROMOTION_NONE, CU_TENSOR_MAP_FLOAT_OOB_FILL_NONE) == CUDA_SUCCESS;
    };
    if (!sms) {
        cudaDeviceGetAttribute(&sms, cudaDevAttrMultiProcessorCount, 0);
        cudaDriverEntryPointQueryResult qr;
        cudaGetDriverEntryPoint("cuTensorMapEncodeTiled", &fn, cudaEnableDefault, &qr);
        cudaGetSymbolAddress(&gp, g_str); cudaGetSymbolAddress(&gb, g_bar);
        if (fn && gp && gb) {
            const cuuint32_t rows = sms < NB_MAX ? sms : NB_MAX;
            tm_ok = enc(&tm1, gp, (P1B + P2B) / 4, NB_MAX, CE / 2, rows, CU_TENSOR_MAP_SWIZZLE_NONE) && enc(&tm2, gp, (P1B + P2B) / 4, NB_MAX, CE, rows, CU_TENSOR_MAP_SWIZZLE_NONE);
        }
        cudaFuncSetAttribute(gcn_kernel<true>, cudaFuncAttributeMaxDynamicSharedMemorySize, SMEM_LAUNCH);
        cudaFuncSetAttribute(gcn_kernel<false>, cudaFuncAttributeMaxDynamicSharedMemorySize, SMEM_LAUNCH);
    }
    int nb = sms < NB_MAX ? sms : NB_MAX;
    int npb = (N + nb - 1) / nb;
    int ch = (((E + nb - 1) / nb) + 3) & ~3;
    const uintptr_t wp[4] = {(uintptr_t)wb, (uintptr_t)wv, (uintptr_t)wa, (uintptr_t)wu};
    uintptr_t wlo = wp[0], whi = wp[0], wal = 0;
    for (int i = 0; i < 4; i++) { wlo = wp[i] < wlo ? wp[i] : wlo; whi = wp[i] > whi ? wp[i] : whi; wal |= wp[i] - wp[0]; }
    bool ok = tm_ok && nb >= NB_MIN && npb < NPB_MAX && ch <= CH_MAX && !(E & 3) && N <= 65535 && npb >= 2 && !(wal & 127) && (whi - wlo) >> 7 < (1u << 30) &&
              !(((uintptr_t)src | (uintptr_t)dst | (uintptr_t)x | (uintptr_t)wb | (uintptr_t)wc) & 15);
    ok = ok && enc(&tmw, (const void*)wlo, 32, ((whi - wlo) >> 7) + 64, 32, 64, CU_TENSOR_MAP_SWIZZLE_128B) && enc(&tmx, x, 32, N, 32, 64, CU_TENSOR_MAP_SWIZZLE_128B);
    if (!ok) {
        int g = 1024, p = (N + g - 1) / g;
        slow_kernel<<<g, 256>>>(x, ea, src, dst, wa, wb, wc, wu, wv, out, N, E, p < 1 ? 1 : p);
        return;
    }
    int4 wrow = make_int4((int)((wp[0] - wlo) >> 7), (int)((wp[1] - wlo) >> 7), (int)((wp[2] - wlo) >> 7), (int)((wp[3] - wlo) >> 7));
    uint32_t magic = (uint32_t)((1ull << 32) / (uint32_t)npb) + 1u;
    void* args[] = {&dst, &gb, &gp, &src, &E, &ch, &N, &npb, &magic, &x, &ea, &wa, &wb, &wc, &wu, &wv, &out, &wrow, &tm1, &tm2, &tmw, &tmx};
    const bool lo32 = ((uintptr_t)x >> 32) == (((uintptr_t)x + (size_t)N * 128 - 1) >> 32) && ((uintptr_t)ea >> 32) == (((uintptr_t)ea + (size_t)E * 32 - 1) >> 32);
    cudaLaunchCooperativeKernel(lo32 && !FORCE64 ? (const void*)gcn_kernel<true> : (const void*)gcn_kernel<false>, dim3(nb), dim3(THREADS), args, SMEM_LAUNCH, cudaStreamPerThread);
}
```

```cpp
#include <cuda_runtime.h>
#include <cuda.h>
#include <cuda_bf16.h>
#include <stdint.h>

namespace {

constexpr int N_MAX = 65536;
constexpr int NPMAX = 11;
constexpr int NPMIN = 4;
constexpr int THREADS = 512;
constexpr int EPT = 12;
constexpr int CH_MAX = THREADS * EPT;
constexpr int NB_MAX = 134, NB_MIN = 120;
constexpr int CE = 64;
constexpr int P1B = NB_MAX * CE * 2;
constexpr int P2B = NB_MAX * CE * 4;
constexpr int HB = NB_MAX * 64;
constexpr int G_H1 = NB_MAX * (P1B + P2B), G_H2 = G_H1 + HB, G_L = G_H2 + HB, G_END = G_L + NB_MAX * 512;
constexpr int NPB_MAX = 384;
constexpr int SLOT_CAP = 6784;
constexpr int TILE_CAP = 124;
constexpr int TILE_X = 8;
constexpr int NCLS = 64;
constexpr int NSTAGE = 2;
constexpr int TR = 2;
constexpr float LOG2E = 1.4426950408889634f;

__device__ __align__(256) uint4 g_str[G_END / 16];
__device__ __align__(128) unsigned g_bar[96];
__device__ float g_slow[N_MAX * 128];

#define WS(k)
#define WS1(k)
#define WSG(k)
#define WGD()
#define WG0()
#define WG1()
#define CG(k)
#define SMEM_LAUNCH SMEM_BYTES
#define EPOLL 0
#define WSPL 1
#define XT0 1000
#define XDT 800
#define D3 0
#define XMID 0
#define SRCE 0
#define XA 1
#define XC 0
#define XW 1
#define XE 0
#define XEW 1
#define XAFT 1
#define WDET 1
#define H1F 0
#define TSRC 1000
#define G3F 1
#define TLBW 0
#define OWNE 0
#define UFORM 0
#define XW2 0
#define XCNT(P)
#define FBLOG(P)
#define FBW 0
#define PD 300
#define SRCV 0
#define SD 0
#define WV 9
#define WLATE 2
#define WPF 0
#define HI1 1
#define HI2 4
#define HORD 0
#define T1 6000
#define NOH2 0
#define TSPIN 0
#define WMAP 0
#define P1S 0
#define BW mbar_wait_c
#define OVU 1
#define S2W 0
#define GD 0
#define HSF 1
#define XPF 0
#define XLD 4
#define XSPL 1
#define P2W 1
#define H2M 0
#define D1 0
#define D2 0
#define FORCE64 0
#define EDHI ((16ull << 32) | (3ull << 62))
template<int NP> struct TileMMA;
template<> struct TileMMA<1> {
  static __device__ __forceinline__ void issue(float* g, float* h, const uint32_t* w, uint32_t dx, uint64_t de, uint64_t dh, uint64_t dc) {
    asm volatile(
      "{\n.reg .b64 dx0, dx1, dx2, dx3;\n.reg .b32 l1, l2, l3, hx;\nmov.b32 hx, 0x40000040;\n"
      "add.u32 l1, %48, 2;\nadd.u32 l2, %48, 4;\nadd.u32 l3, %48, 6;\n"
      "mov.b64 dx0, {%48, hx};\nmov.b64 dx1, {l1, hx};\nmov.b64 dx2, {l2, hx};\nmov.b64 dx3, {l3, hx};\n"
      "wgmma.fence.sync.aligned;\n"
      "wgmma.mma_async.sync.aligned.m64n8k16.f32.bf16.bf16 {%0, %1, %2, %3}, {%44, %45, %46, %47}, %50, 0, 1, 1, 0;\n"
      "wgmma.mma_async.sync.aligned.m64n8k16.f32.bf16.bf16 {%0, %1, %2, %3}, {%24, %25, %26, %27}, %49, 1, 1, 1, 0;\n"
      "wgmma.mma_async.sync.aligned.m64n8k16.f32.bf16.bf16 {%0, %1, %2, %3}, {%8, %9, %10, %11}, dx0, 1, 1, 1, 0;\n"
      "wgmma.mma_async.sync.aligned.m64n8k16.f32.bf16.bf16 {%0, %1, %2, %3}, {%12, %13, %14, %15}, dx1, 1, 1, 1, 0;\n"
      "wgmma.mma_async.sync.aligned.m64n8k16.f32.bf16.bf16 {%0, %1, %2, %3}, {%16, %17, %18, %19}, dx2, 1, 1, 1, 0;\n"
      "wgmma.mma_async.sync.aligned.m64n8k16.f32.bf16.bf16 {%0, %1, %2, %3}, {%20, %21, %22, %23}, dx3, 1, 1, 1, 0;\n"
      "wgmma.commit_group.sync.aligned;\n"
      "wgmma.mma_async.sync.aligned.m64n8k16.f32.bf16.bf16 {%4, %5, %6, %7}, {%28, %29, %30, %31}, dx0, 0, 1, 1, 0;\n"
      "wgmma.mma_async.sync.aligned.m64n8k16.f32.bf16.bf16 {%4, %5, %6, %7}, {%32, %33, %34, %35}, dx1, 1, 1, 1, 0;\n"
      "wgmma.mma_async.sync.aligned.m64n8k16.f32.bf16.bf16 {%4, %5, %6, %7}, {%36, %37, %38, %39}, dx2, 1, 1, 1, 0;\n"
      "wgmma.mma_async.sync.aligned.m64n8k16.f32.bf16.bf16 {%4, %5, %6, %7}, {%40, %41, %42, %43}, dx3, 1, 1, 1, 0;\n"
      "wgmma.commit_group.sync.aligned;\n}\n"
      : "=f"(g[0]), "=f"(g[1]), "=f"(g[2]), "=f"(g[3]),
        "=f"(h[0]), "=f"(h[1]), "=f"(h[2]), "=f"(h[3])
      : "r"(w[0]), "r"(w[1]), "r"(w[2]), "r"(w[3]), "r"(w[4]), "r"(w[5]), "r"(w[6]), "r"(w[7]), "r"(w[8]), "r"(w[9]), "r"(w[10]), "r"(w[11]), "r"(w[12]), "r"(w[13]), "r"(w[14]), "r"(w[15]), "r"(w[16]), "r"(w[17]), "r"(w[18]), "r"(w[19]), "r"(w[20]), "r"(w[21]), "r"(w[22]), "r"(w[23]), "r"(w[24]), "r"(w[25]), "r"(w[26]), "r"(w[27]), "r"(w[28]), "r"(w[29]), "r"(w[30]), "r"(w[31]), "r"(w[32]), "r"(w[33]), "r"(w[34]), "r"(w[35]), "r"(w[36]), "r"(w[37]), "r"(w[38]), "r"(w[39]), "r"(dx), "l"(de), "l"(dh)
      : "memory");
  }
  static __device__ __forceinline__ void wait_g(float* g) {
    asm volatile("wgmma.wait_group.sync.aligned 1;\n"
      : "+f"(g[0]), "+f"(g[1]), "+f"(g[2]), "+f"(g[3])
      :: "memory");
  }
  static __device__ __forceinline__ void wait_h(float* h) {
    asm volatile("wgmma.wait_group.sync.aligned 0;\n"
      : "+f"(h[0]), "+f"(h[1]), "+f"(h[2]), "+f"(h[3])
      :: "memory");
  }
};
template<> struct TileMMA<2> {
  static __device__ __forceinline__ void issue(float* g, float* h, const uint32_t* w, uint32_t dx, uint64_t de, uint64_t dh, uint64_t dc) {
    asm volatile(
      "{\n.reg .b64 dx0, dx1, dx2, dx3;\n.reg .b32 l1, l2, l3, hx;\nmov.b32 hx, 0x40000040;\n"
      "add.u32 l1, %56, 2;\nadd.u32 l2, %56, 4;\nadd.u32 l3, %56, 6;\n"
      "mov.b64 dx0, {%56, hx};\nmov.b64 dx1, {l1, hx};\nmov.b64 dx2, {l2, hx};\nmov.b64 dx3, {l3, hx};\n"
      "wgmma.fence.sync.aligned;\n"
      "wgmma.mma_async.sync.aligned.m64n16k16.f32.bf16.bf16 {%0, %1, %2, %3, %4, %5, %6, %7}, {%52, %53, %54, %55}, %58, 0, 1, 1, 0;\n"
      "wgmma.mma_async.sync.aligned.m64n16k16.f32.bf16.bf16 {%0, %1, %2, %3, %4, %5, %6, %7}, {%32, %33, %34, %35}, %57, 1, 1, 1, 0;\n"
      "wgmma.mma_async.sync.aligned.m64n16k16.f32.bf16.bf16 {%0, %1, %2, %3, %4, %5, %6, %7}, {%16, %17, %18, %19}, dx0, 1, 1, 1, 0;\n"
      "wgmma.mma_async.sync.aligned.m64n16k16.f32.bf16.bf16 {%0, %1, %2, %3, %4, %5, %6, %7}, {%20, %21, %22, %23}, dx1, 1, 1, 1, 0;\n"
      "wgmma.mma_async.sync.aligned.m64n16k16.f32.bf16.bf16 {%0, %1, %2, %3, %4, %5, %6, %7}, {%24, %25, %26, %27}, dx2, 1, 1, 1, 0;\n"
      "wgmma.mma_async.sync.aligned.m64n16k16.f32.bf16.bf16 {%0, %1, %2, %3, %4, %5, %6, %7}, {%28, %29, %30, %31}, dx3, 1, 1, 1, 0;\n"
      "wgmma.commit_group.sync.aligned;\n"
      "wgmma.mma_async.sync.aligned.m64n16k16.f32.bf16.bf16 {%8, %9, %10, %11, %12, %13, %14, %15}, {%36, %37, %38, %39}, dx0, 0, 1, 1, 0;\n"
      "wgmma.mma_async.sync.aligned.m64n16k16.f32.bf16.bf16 {%8, %9, %10, %11, %12, %13, %14, %15}, {%40, %41, %42, %43}, dx1, 1, 1, 1, 0;\n"
      "wgmma.mma_async.sync.aligned.m64n16k16.f32.bf16.bf16 {%8, %9, %10, %11, %12, %13, %14, %15}, {%44, %45, %46, %47}, dx2, 1, 1, 1, 0;\n"
      "wgmma.mma_async.sync.aligned.m64n16k16.f32.bf16.bf16 {%8, %9, %10, %11, %12, %13, %14, %15}, {%48, %49, %50, %51}, dx3, 1, 1, 1, 0;\n"
      "wgmma.commit_group.sync.aligned;\n}\n"
      : "=f"(g[0]), "=f"(g[1]), "=f"(g[2]), "=f"(g[3]), "=f"(g[4]), "=f"(g[5]), "=f"(g[6]), "=f"(g[7]),
        "=f"(h[0]), "=f"(h[1]), "=f"(h[2]), "=f"(h[3]), "=f"(h[4]), "=f"(h[5]), "=f"(h[6]), "=f"(h[7])
      : "r"(w[0]), "r"(w[1]), "r"(w[2]), "r"(w[3]), "r"(w[4]), "r"(w[5]), "r"(w[6]), "r"(w[7]), "r"(w[8]), "r"(w[9]), "r"(w[10]), "r"(w[11]), "r"(w[12]), "r"(w[13]), "r"(w[14]), "r"(w[15]), "r"(w[16]), "r"(w[17]), "r"(w[18]), "r"(w[19]), "r"(w[20]), "r"(w[21]), "r"(w[22]), "r"(w[23]), "r"(w[24]), "r"(w[25]), "r"(w[26]), "r"(w[27]), "r"(w[28]), "r"(w[29]), "r"(w[30]), "r"(w[31]), "r"(w[32]), "r"(w[33]), "r"(w[34]), "r"(w[35]), "r"(w[36]), "r"(w[37]), "r"(w[38]), "r"(w[39]), "r"(dx), "l"(de), "l"(dh)
      : "memory");
  }
  static __device__ __forceinline__ void wait_g(float* g) {
    asm volatile("wgmma.wait_group.sync.aligned 1;\n"
      : "+f"(g[0]), "+f"(g[1]), "+f"(g[2]), "+f"(g[3]), "+f"(g[4]), "+f"(g[5]), "+f"(g[6]), "+f"(g[7])
      :: "memory");
  }
  static __device__ __forceinline__ void wait_h(float* h) {
    asm volatile("wgmma.wait_group.sync.aligned 0;\n"
      : "+f"(h[0]), "+f"(h[1]), "+f"(h[2]), "+f"(h[3]), "+f"(h[4]), "+f"(h[5]), "+f"(h[6]), "+f"(h[7])
      :: "memory");
  }
};
template<> struct TileMMA<3> {
  static __device__ __forceinline__ void issue(float* g, float* h, const uint32_t* w, uint32_t dx, uint64_t de, uint64_t dh, uint64_t dc) {
    asm volatile(
      "{\n.reg .b64 dx0, dx1, dx2, dx3;\n.reg .b32 l1, l2, l3, hx;\nmov.b32 hx, 0x40000040;\n"
      "add.u32 l1, %64, 2;\nadd.u32 l2, %64, 4;\nadd.u32 l3, %64, 6;\n"
      "mov.b64 dx0, {%64, hx};\nmov.b64 dx1, {l1, hx};\nmov.b64 dx2, {l2, hx};\nmov.b64 dx3, {l3, hx};\n"
      "wgmma.fence.sync.aligned;\n"
      "wgmma.mma_async.sync.aligned.m64n24k16.f32.bf16.bf16 {%0, %1, %2, %3, %4, %5, %6, %7, %8, %9, %10, %11}, {%60, %61, %62, %63}, %66, 0, 1, 1, 0;\n"
      "wgmma.mma_async.sync.aligned.m64n24k16.f32.bf16.bf16 {%0, %1, %2, %3, %4, %5, %6, %7, %8, %9, %10, %11}, {%40, %41, %42, %43}, %65, 1, 1, 1, 0;\n"
      "wgmma.mma_async.sync.aligned.m64n24k16.f32.bf16.bf16 {%0, %1, %2, %3, %4, %5, %6, %7, %8, %9, %10, %11}, {%24, %25, %26, %27}, dx0, 1, 1, 1, 0;\n"
      "wgmma.mma_async.sync.aligned.m64n24k16.f32.bf16.bf16 {%0, %1, %2, %3, %4, %5, %6, %7, %8, %9, %10, %11}, {%28, %29, %30, %31}, dx1, 1, 1, 1, 0;\n"
      "wgmma.mma_async.sync.aligned.m64n24k16.f32.bf16.bf16 {%0, %1, %2, %3, %4, %5, %6, %7, %8, %9, %10, %11}, {%32, %33, %34, %35}, dx2, 1, 1, 1, 0;\n"
      "wgmma.mma_async.sync.aligned.m64n24k16.f32.bf16.bf16 {%0, %1, %2, %3, %4, %5, %6, %7, %8, %9, %10, %11}, {%36, %37, %38, %39}, dx3, 1, 1, 1, 0;\n"
      "wgmma.commit_group.sync.aligned;\n"
      "wgmma.mma_async.sync.aligned.m64n24k16.f32.bf16.bf16 {%12, %13, %14, %15, %16, %17, %18, %19, %20, %21, %22, %23}, {%44, %45, %46, %47}, dx0, 0, 1, 1, 0;\n"
      "wgmma.mma_async.sync.aligned.m64n24k16.f32.bf16.bf16 {%12, %13, %14, %15, %16, %17, %18, %19, %20, %21, %22, %23}, {%48, %49, %50, %51}, dx1, 1, 1, 1, 0;\n"
      "wgmma.mma_async.sync.aligned.m64n24k16.f32.bf16.bf16 {%12, %13, %14, %15, %16, %17, %18, %19, %20, %21, %22, %23}, {%52, %53, %54, %55}, dx2, 1, 1, 1, 0;\n"
      "wgmma.mma_async.sync.aligned.m64n24k16.f32.bf16.bf16 {%12, %13, %14, %15, %16, %17, %18, %19, %20, %21, %22, %23}, {%56, %57, %58, %59}, dx3, 1, 1, 1, 0;\n"
      "wgmma.commit_group.sync.aligned;\n}\n"
      : "=f"(g[0]), "=f"(g[1]), "=f"(g[2]), "=f"(g[3]), "=f"(g[4]), "=f"(g[5]), "=f"(g[6]), "=f"(g[7]), "=f"(g[8]), "=f"(g[9]), "=f"(g[10]), "=f"(g[11]),
        "=f"(h[0]), "=f"(h[1]), "=f"(h[2]), "=f"(h[3]), "=f"(h[4]), "=f"(h[5]), "=f"(h[6]), "=f"(h[7]), "=f"(h[8]), "=f"(h[9]), "=f"(h[10]), "=f"(h[11])
      : "r"(w[0]), "r"(w[1]), "r"(w[2]), "r"(w[3]), "r"(w[4]), "r"(w[5]), "r"(w[6]), "r"(w[7]), "r"(w[8]), "r"(w[9]), "r"(w[10]), "r"(w[11]), "r"(w[12]), "r"(w[13]), "r"(w[14]), "r"(w[15]), "r"(w[16]), "r"(w[17]), "r"(w[18]), "r"(w[19]), "r"(w[20]), "r"(w[21]), "r"(w[22]), "r"(w[23]), "r"(w[24]), "r"(w[25]), "r"(w[26]), "r"(w[27]), "r"(w[28]), "r"(w[29]), "r"(w[30]), "r"(w[31]), "r"(w[32]), "r"(w[33]), "r"(w[34]), "r"(w[35]), "r"(w[36]), "r"(w[37]), "r"(w[38]), "r"(w[39]), "r"(dx), "l"(de), "l"(dh)
      : "memory");
  }
  static __device__ __forceinline__ void wait_g(float* g) {
    asm volatile("wgmma.wait_group.sync.aligned 1;\n"
      : "+f"(g[0]), "+f"(g[1]), "+f"(g[2]), "+f"(g[3]), "+f"(g[4]), "+f"(g[5]), "+f"(g[6]), "+f"(g[7]), "+f"(g[8]), "+f"(g[9]), "+f"(g[10]), "+f"(g[11])
      :: "memory");
  }
  static __device__ __forceinline__ void wait_h(float* h) {
    asm volatile("wgmma.wait_group.sync.aligned 0;\n"
      : "+f"(h[0]), "+f"(h[1]), "+f"(h[2]), "+f"(h[3]), "+f"(h[4]), "+f"(h[5]), "+f"(h[6]), "+f"(h[7]), "+f"(h[8]), "+f"(h[9]), "+f"(h[10]), "+f"(h[11])
      :: "memory");
  }
};
template<> struct TileMMA<4> {
  static __device__ __forceinline__ void issue(float* g, float* h, const uint32_t* w, uint32_t dx, uint64_t de, uint64_t dh, uint64_t dc) {
    asm volatile(
      "{\n.reg .b64 dx0, dx1, dx2, dx3;\n.reg .b32 l1, l2, l3, hx;\nmov.b32 hx, 0x40000040;\n"
      "add.u32 l1, %72, 2;\nadd.u32 l2, %72, 4;\nadd.u32 l3, %72, 6;\n"
      "mov.b64 dx0, {%72, hx};\nmov.b64 dx1, {l1, hx};\nmov.b64 dx2, {l2, hx};\nmov.b64 dx3, {l3, hx};\n"
      "wgmma.fence.sync.aligned;\n"
      "wgmma.mma_async.sync.aligned.m64n32k16.f32.bf16.bf16 {%0, %1, %2, %3, %4, %5, %6, %7, %8, %9, %10, %11, %12, %13, %14, %15}, {%68, %69, %70, %71}, %74, 0, 1, 1, 0;\n"
      "wgmma.mma_async.sync.aligned.m64n32k16.f32.bf16.bf16 {%0, %1, %2, %3, %4, %5, %6, %7, %8, %9, %10, %11, %12, %13, %14, %15}, {%48, %49, %50, %51}, %73, 1, 1, 1, 0;\n"
      "wgmma.mma_async.sync.aligned.m64n32k16.f32.bf16.bf16 {%0, %1, %2, %3, %4, %5, %6, %7, %8, %9, %10, %11, %12, %13, %14, %15}, {%32, %33, %34, %35}, dx0, 1, 1, 1, 0;\n"
      "wgmma.mma_async.sync.aligned.m64n32k16.f32.bf16.bf16 {%0, %1, %2, %3, %4, %5, %6, %7, %8, %9, %10, %11, %12, %13, %14, %15}, {%36, %37, %38, %39}, dx1, 1, 1, 1, 0;\n"
      "wgmma.mma_async.sync.aligned.m64n32k16.f32.bf16.bf16 {%0, %1, %2, %3, %4, %5, %6, %7, %8, %9, %10, %11, %12, %13, %14, %15}, {%40, %41, %42, %43}, dx2, 1, 1, 1, 0;\n"
      "wgmma.mma_async.sync.aligned.m64n32k16.f32.bf16.bf16 {%0, %1, %2, %3, %4, %5, %6, %7, %8, %9, %10, %11, %12, %13, %14, %15}, {%44, %45, %46, %47}, dx3, 1, 1, 1, 0;\n"
      "wgmma.commit_group.sync.aligned;\n"
      "wgmma.mma_async.sync.aligned.m64n32k16.f32.bf16.bf16 {%16, %17, %18, %19, %20, %21, %22, %23, %24, %25, %26, %27, %28, %29, %30, %31}, {%52, %53, %54, %55}, dx0, 0, 1, 1, 0;\n"
      "wgmma.mma_async.sync.aligned.m64n32k16.f32.bf16.bf16 {%16, %17, %18, %19, %20, %21, %22, %23, %24, %25, %26, %27, %28, %29, %30, %31}, {%56, %57, %58, %59}, dx1, 1, 1, 1, 0;\n"
      "wgmma.mma_async.sync.aligned.m64n32k16.f32.bf16.bf16 {%16, %17, %18, %19, %20, %21, %22, %23, %24, %25, %26, %27, %28, %29, %30, %31}, {%60, %61, %62, %63}, dx2, 1, 1, 1, 0;\n"
      "wgmma.mma_async.sync.aligned.m64n32k16.f32.bf16.bf16 {%16, %17, %18, %19, %20, %21, %22, %23, %24, %25, %26, %27, %28, %29, %30, %31}, {%64, %65, %66, %67}, dx3, 1, 1, 1, 0;\n"
      "wgmma.commit_group.sync.aligned;\n}\n"
      : "=f"(g[0]), "=f"(g[1]), "=f"(g[2]), "=f"(g[3]), "=f"(g[4]), "=f"(g[5]), "=f"(g[6]), "=f"(g[7]), "=f"(g[8]), "=f"(g[9]), "=f"(g[10]), "=f"(g[11]), "=f"(g[12]), "=f"(g[13]), "=f"(g[14]), "=f"(g[15]),
        "=f"(h[0]), "=f"(h[1]), "=f"(h[2]), "=f"(h[3]), "=f"(h[4]), "=f"(h[5]), "=f"(h[6]), "=f"(h[7]), "=f"(h[8]), "=f"(h[9]), "=f"(h[10]), "=f"(h[11]), "=f"(h[12]), "=f"(h[13]), "=f"(h[14]), "=f"(h[15])
      : "r"(w[0]), "r"(w[1]), "r"(w[2]), "r"(w[3]), "r"(w[4]), "r"(w[5]), "r"(w[6]), "r"(w[7]), "r"(w[8]), "r"(w[9]), "r"(w[10]), "r"(w[11]), "r"(w[12]), "r"(w[13]), "r"(w[14]), "r"(w[15]), "r"(w[16]), "r"(w[17]), "r"(w[18]), "r"(w[19]), "r"(w[20]), "r"(w[21]), "r"(w[22]), "r"(w[23]), "r"(w[24]), "r"(w[25]), "r"(w[26]), "r"(w[27]), "r"(w[28]), "r"(w[29]), "r"(w[30]), "r"(w[31]), "r"(w[32]), "r"(w[33]), "r"(w[34]), "r"(w[35]), "r"(w[36]), "r"(w[37]), "r"(w[38]), "r"(w[39]), "r"(dx), "l"(de), "l"(dh)
      : "memory");
  }
  static __device__ __forceinline__ void wait_g(float* g) {
    asm volatile("wgmma.wait_group.sync.aligned 1;\n"
      : "+f"(g[0]), "+f"(g[1]), "+f"(g[2]), "+f"(g[3]), "+f"(g[4]), "+f"(g[5]), "+f"(g[6]), "+f"(g[7]), "+f"(g[8]), "+f"(g[9]), "+f"(g[10]), "+f"(g[11]), "+f"(g[12]), "+f"(g[13]), "+f"(g[14]), "+f"(g[15])
      :: "memory");
  }
  static __device__ __forceinline__ void wait_h(float* h) {
    asm volatile("wgmma.wait_group.sync.aligned 0;\n"
      : "+f"(h[0]), "+f"(h[1]), "+f"(h[2]), "+f"(h[3]), "+f"(h[4]), "+f"(h[5]), "+f"(h[6]), "+f"(h[7]), "+f"(h[8]), "+f"(h[9]), "+f"(h[10]), "+f"(h[11]), "+f"(h[12]), "+f"(h[13]), "+f"(h[14]), "+f"(h[15])
      :: "memory");
  }
};
template<> struct TileMMA<5> {
  static __device__ __forceinline__ void issue(float* g, float* h, const uint32_t* w, uint32_t dx, uint64_t de, uint64_t dh, uint64_t dc) {
    asm volatile(
      "{\n.reg .b64 dx0, dx1, dx2, dx3;\n.reg .b32 l1, l2, l3, hx;\nmov.b32 hx, 0x40000040;\n"
      "add.u32 l1, %80, 2;\nadd.u32 l2, %80, 4;\nadd.u32 l3, %80, 6;\n"
      "mov.b64 dx0, {%80, hx};\nmov.b64 dx1, {l1, hx};\nmov.b64 dx2, {l2, hx};\nmov.b64 dx3, {l3, hx};\n"
      "wgmma.fence.sync.aligned;\n"
      "wgmma.mma_async.sync.aligned.m64n40k16.f32.bf16.bf16 {%0, %1, %2, %3, %4, %5, %6, %7, %8, %9, %10, %11, %12, %13, %14, %15, %16, %17, %18, %19}, {%76, %77, %78, %79}, %82, 0, 1, 1, 0;\n"
      "wgmma.mma_async.sync.aligned.m64n40k16.f32.bf16.bf16 {%0, %1, %2, %3, %4, %5, %6, %7, %8, %9, %10, %11, %12, %13, %14, %15, %16, %17, %18, %19}, {%56, %57, %58, %59}, %81, 1, 1, 1, 0;\n"
      "wgmma.mma_async.sync.aligned.m64n40k16.f32.bf16.bf16 {%0, %1, %2, %3, %4, %5, %6, %7, %8, %9, %10, %11, %12, %13, %14, %15, %16, %17, %18, %19}, {%40, %41, %42, %43}, dx0, 1, 1, 1, 0;\n"
      "wgmma.mma_async.sync.aligned.m64n40k16.f32.bf16.bf16 {%0, %1, %2, %3, %4, %5, %6, %7, %8, %9, %10, %11, %12, %13, %14, %15, %16, %17, %18, %19}, {%44, %45, %46, %47}, dx1, 1, 1, 1, 0;\n"
      "wgmma.mma_async.sync.aligned.m64n40k16.f32.bf16.bf16 {%0, %1, %2, %3, %4, %5, %6, %7, %8, %9, %10, %11, %12, %13, %14, %15, %16, %17, %18, %19}, {%48, %49, %50, %51}, dx2, 1, 1, 1, 0;\n"
      "wgmma.mma_async.sync.aligned.m64n40k16.f32.bf16.bf16 {%0, %1, %2, %3, %4, %5, %6, %7, %8, %9, %10, %11, %12, %13, %14, %15, %16, %17, %18, %19}, {%52, %53, %54, %55}, dx3, 1, 1, 1, 0;\n"
      "wgmma.commit_group.sync.aligned;\n"
      "wgmma.mma_async.sync.aligned.m64n40k16.f32.bf16.bf16 {%20, %21, %22, %23, %24, %25, %26, %27, %28, %29, %30, %31, %32, %33, %34, %35, %36, %37, %38, %39}, {%60, %61, %62, %63}, dx0, 0, 1, 1, 0;\n"
      "wgmma.mma_async.sync.aligned.m64n40k16.f32.bf16.bf16 {%20, %21, %22, %23, %24, %25, %26, %27, %28, %29, %30, %31, %32, %33, %34, %35, %36, %37, %38, %39}, {%64, %65, %66, %67}, dx1, 1, 1, 1, 0;\n"
      "wgmma.mma_async.sync.aligned.m64n40k16.f32.bf16.bf16 {%20, %21, %22, %23, %24, %25, %26, %27, %28, %29, %30, %31, %32, %33, %34, %35, %36, %37, %38, %39}, {%68, %69, %70, %71}, dx2, 1, 1, 1, 0;\n"
      "wgmma.mma_async.sync.aligned.m64n40k16.f32.bf16.bf16 {%20, %21, %22, %23, %24, %25, %26, %27, %28, %29, %30, %31, %32, %33, %34, %35, %36, %37, %38, %39}, {%72, %73, %74, %75}, dx3, 1, 1, 1, 0;\n"
      "wgmma.commit_group.sync.aligned;\n}\n"
      : "=f"(g[0]), "=f"(g[1]), "=f"(g[2]), "=f"(g[3]), "=f"(g[4]), "=f"(g[5]), "=f"(g[6]), "=f"(g[7]), "=f"(g[8]), "=f"(g[9]), "=f"(g[10]), "=f"(g[11]), "=f"(g[12]), "=f"(g[13]), "=f"(g[14]), "=f"(g[15]), "=f"(g[16]), "=f"(g[17]), "=f"(g[18]), "=f"(g[19]),
        "=f"(h[0]), "=f"(h[1]), "=f"(h[2]), "=f"(h[3]), "=f"(h[4]), "=f"(h[5]), "=f"(h[6]), "=f"(h[7]), "=f"(h[8]), "=f"(h[9]), "=f"(h[10]), "=f"(h[11]), "=f"(h[12]), "=f"(h[13]), "=f"(h[14]), "=f"(h[15]), "=f"(h[16]), "=f"(h[17]), "=f"(h[18]), "=f"(h[19])
      : "r"(w[0]), "r"(w[1]), "r"(w[2]), "r"(w[3]), "r"(w[4]), "r"(w[5]), "r"(w[6]), "r"(w[7]), "r"(w[8]), "r"(w[9]), "r"(w[10]), "r"(w[11]), "r"(w[12]), "r"(w[13]), "r"(w[14]), "r"(w[15]), "r"(w[16]), "r"(w[17]), "r"(w[18]), "r"(w[19]), "r"(w[20]), "r"(w[21]), "r"(w[22]), "r"(w[23]), "r"(w[24]), "r"(w[25]), "r"(w[26]), "r"(w[27]), "r"(w[28]), "r"(w[29]), "r"(w[30]), "r"(w[31]), "r"(w[32]), "r"(w[33]), "r"(w[34]), "r"(w[35]), "r"(w[36]), "r"(w[37]), "r"(w[38]), "r"(w[39]), "r"(dx), "l"(de), "l"(dh)
      : "memory");
  }
  static __device__ __forceinline__ void wait_g(float* g) {
    asm volatile("wgmma.wait_group.sync.aligned 1;\n"
      : "+f"(g[0]), "+f"(g[1]), "+f"(g[2]), "+f"(g[3]), "+f"(g[4]), "+f"(g[5]), "+f"(g[6]), "+f"(g[7]), "+f"(g[8]), "+f"(g[9]), "+f"(g[10]), "+f"(g[11]), "+f"(g[12]), "+f"(g[13]), "+f"(g[14]), "+f"(g[15]), "+f"(g[16]), "+f"(g[17]), "+f"(g[18]), "+f"(g[19])
      :: "memory");
  }
  static __device__ __forceinline__ void wait_h(float* h) {
    asm volatile("wgmma.wait_group.sync.aligned 0;\n"
      : "+f"(h[0]), "+f"(h[1]), "+f"(h[2]), "+f"(h[3]), "+f"(h[4]), "+f"(h[5]), "+f"(h[6]), "+f"(h[7]), "+f"(h[8]), "+f"(h[9]), "+f"(h[10]), "+f"(h[11]), "+f"(h[12]), "+f"(h[13]), "+f"(h[14]), "+f"(h[15]), "+f"(h[16]), "+f"(h[17]), "+f"(h[18]), "+f"(h[19])
      :: "memory");
  }
};
template<> struct TileMMA<6> {
  static __device__ __forceinline__ void issue(float* g, float* h, const uint32_t* w, uint32_t dx, uint64_t de, uint64_t dh, uint64_t dc) {
    asm volatile(
      "{\n.reg .b64 dx0, dx1, dx2, dx3;\n.reg .b32 l1, l2, l3, hx;\nmov.b32 hx, 0x40000040;\n"
      "add.u32 l1, %88, 2;\nadd.u32 l2, %88, 4;\nadd.u32 l3, %88, 6;\n"
      "mov.b64 dx0, {%88, hx};\nmov.b64 dx1, {l1, hx};\nmov.b64 dx2, {l2, hx};\nmov.b64 dx3, {l3, hx};\n"
      "wgmma.fence.sync.aligned;\n"
      "wgmma.mma_async.sync.aligned.m64n48k16.f32.bf16.bf16 {%0, %1, %2, %3, %4, %5, %6, %7, %8, %9, %10, %11, %12, %13, %14, %15, %16, %17, %18, %19, %20, %21, %22, %23}, {%84, %85, %86, %87}, %90, 0, 1, 1, 0;\n"
      "wgmma.mma_async.sync.aligned.m64n48k16.f32.bf16.bf16 {%0, %1, %2, %3, %4, %5, %6, %7, %8, %9, %10, %11, %12, %13, %14, %15, %16, %17, %18, %19, %20, %21, %22, %23}, {%64, %65, %66, %67}, %89, 1, 1, 1, 0;\n"
      "wgmma.mma_async.sync.aligned.m64n48k16.f32.bf16.bf16 {%0, %1, %2, %3, %4, %5, %6, %7, %8, %9, %10, %11, %12, %13, %14, %15, %16, %17, %18, %19, %20, %21, %22, %23}, {%48, %49, %50, %51}, dx0, 1, 1, 1, 0;\n"
      "wgmma.mma_async.sync.aligned.m64n48k16.f32.bf16.bf16 {%0, %1, %2, %3, %4, %5, %6, %7, %8, %9, %10, %11, %12, %13, %14, %15, %16, %17, %18, %19, %20, %21, %22, %23}, {%52, %53, %54, %55}, dx1, 1, 1, 1, 0;\n"
      "wgmma.mma_async.sync.aligned.m64n48k16.f32.bf16.bf16 {%0, %1, %2, %3, %4, %5, %6, %7, %8, %9, %10, %11, %12, %13, %14, %15, %16, %17, %18, %19, %20, %21, %22, %23}, {%56, %57, %58, %59}, dx2, 1, 1, 1, 0;\n"
      "wgmma.mma_async.sync.aligned.m64n48k16.f32.bf16.bf16 {%0, %1, %2, %3, %4, %5, %6, %7, %8, %9, %10, %11, %12, %13, %14, %15, %16, %17, %18, %19, %20, %21, %22, %23}, {%60, %61, %62, %63}, dx3, 1, 1, 1, 0;\n"
      "wgmma.commit_group.sync.aligned;\n"
      "wgmma.mma_async.sync.aligned.m64n48k16.f32.bf16.bf16 {%24, %25, %26, %27, %28, %29, %30, %31, %32, %33, %34, %35, %36, %37, %38, %39, %40, %41, %42, %43, %44, %45, %46, %47}, {%68, %69, %70, %71}, dx0, 0, 1, 1, 0;\n"
      "wgmma.mma_async.sync.aligned.m64n48k16.f32.bf16.bf16 {%24, %25, %26, %27, %28, %29, %30, %31, %32, %33, %34, %35, %36, %37, %38, %39, %40, %41, %42, %43, %44, %45, %46, %47}, {%72, %73, %74, %75}, dx1, 1, 1, 1, 0;\n"
      "wgmma.mma_async.sync.aligned.m64n48k16.f32.bf16.bf16 {%24, %25, %26, %27, %28, %29, %30, %31, %32, %33, %34, %35, %36, %37, %38, %39, %40, %41, %42, %43, %44, %45, %46, %47}, {%76, %77, %78, %79}, dx2, 1, 1, 1, 0;\n"
      "wgmma.mma_async.sync.aligned.m64n48k16.f32.bf16.bf16 {%24, %25, %26, %27, %28, %29, %30, %31, %32, %33, %34, %35, %36, %37, %38, %39, %40, %41, %42, %43, %44, %45, %46, %47}, {%80, %81, %82, %83}, dx3, 1, 1, 1, 0;\n"
      "wgmma.commit_group.sync.aligned;\n}\n"
      : "=f"(g[0]), "=f"(g[1]), "=f"(g[2]), "=f"(g[3]), "=f"(g[4]), "=f"(g[5]), "=f"(g[6]), "=f"(g[7]), "=f"(g[8]), "=f"(g[9]), "=f"(g[10]), "=f"(g[11]), "=f"(g[12]), "=f"(g[13]), "=f"(g[14]), "=f"(g[15]), "=f"(g[16]), "=f"(g[17]), "=f"(g[18]), "=f"(g[19]), "=f"(g[20]), "=f"(g[21]), "=f"(g[22]), "=f"(g[23]),
        "=f"(h[0]), "=f"(h[1]), "=f"(h[2]), "=f"(h[3]), "=f"(h[4]), "=f"(h[5]), "=f"(h[6]), "=f"(h[7]), "=f"(h[8]), "=f"(h[9]), "=f"(h[10]), "=f"(h[11]), "=f"(h[12]), "=f"(h[13]), "=f"(h[14]), "=f"(h[15]), "=f"(h[16]), "=f"(h[17]), "=f"(h[18]), "=f"(h[19]), "=f"(h[20]), "=f"(h[21]), "=f"(h[22]), "=f"(h[23])
      : "r"(w[0]), "r"(w[1]), "r"(w[2]), "r"(w[3]), "r"(w[4]), "r"(w[5]), "r"(w[6]), "r"(w[7]), "r"(w[8]), "r"(w[9]), "r"(w[10]), "r"(w[11]), "r"(w[12]), "r"(w[13]), "r"(w[14]), "r"(w[15]), "r"(w[16]), "r"(w[17]), "r"(w[18]), "r"(w[19]), "r"(w[20]), "r"(w[21]), "r"(w[22]), "r"(w[23]), "r"(w[24]), "r"(w[25]), "r"(w[26]), "r"(w[27]), "r"(w[28]), "r"(w[29]), "r"(w[30]), "r"(w[31]), "r"(w[32]), "r"(w[33]), "r"(w[34]), "r"(w[35]), "r"(w[36]), "r"(w[37]), "r"(w[38]), "r"(w[39]), "r"(dx), "l"(de), "l"(dh)
      : "memory");
  }
  static __device__ __forceinline__ void wait_g(float* g) {
    asm volatile("wgmma.wait_group.sync.aligned 1;\n"
      : "+f"(g[0]), "+f"(g[1]), "+f"(g[2]), "+f"(g[3]), "+f"(g[4]), "+f"(g[5]), "+f"(g[6]), "+f"(g[7]), "+f"(g[8]), "+f"(g[9]), "+f"(g[10]), "+f"(g[11]), "+f"(g[12]), "+f"(g[13]), "+f"(g[14]), "+f"(g[15]), "+f"(g[16]), "+f"(g[17]), "+f"(g[18]), "+f"(g[19]), "+f"(g[20]), "+f"(g[21]), "+f"(g[22]), "+f"(g[23])
      :: "memory");
  }
  static __device__ __forceinline__ void wait_h(float* h) {
    asm volatile("wgmma.wait_group.sync.aligned 0;\n"
      : "+f"(h[0]), "+f"(h[1]), "+f"(h[2]), "+f"(h[3]), "+f"(h[4]), "+f"(h[5]), "+f"(h[6]), "+f"(h[7]), "+f"(h[8]), "+f"(h[9]), "+f"(h[10]), "+f"(h[11]), "+f"(h[12]), "+f"(h[13]), "+f"(h[14]), "+f"(h[15]), "+f"(h[16]), "+f"(h[17]), "+f"(h[18]), "+f"(h[19]), "+f"(h[20]), "+f"(h[21]), "+f"(h[22]), "+f"(h[23])
      :: "memory");
  }
};
template<> struct TileMMA<7> {
  static __device__ __forceinline__ void issue(float* g, float* h, const uint32_t* w, uint32_t dx, uint64_t de, uint64_t dh, uint64_t dc) {
    asm volatile(
      "{\n.reg .b64 dx0, dx1, dx2, dx3;\n.reg .b32 l1, l2, l3, hx;\nmov.b32 hx, 0x40000040;\n"
      "add.u32 l1, %96, 2;\nadd.u32 l2, %96, 4;\nadd.u32 l3, %96, 6;\n"
      "mov.b64 dx0, {%96, hx};\nmov.b64 dx1, {l1, hx};\nmov.b64 dx2, {l2, hx};\nmov.b64 dx3, {l3, hx};\n"
      "wgmma.fence.sync.aligned;\n"
      "wgmma.mma_async.sync.aligned.m64n56k16.f32.bf16.bf16 {%0, %1, %2, %3, %4, %5, %6, %7, %8, %9, %10, %11, %12, %13, %14, %15, %16, %17, %18, %19, %20, %21, %22, %23, %24, %25, %26, %27}, {%92, %93, %94, %95}, %98, 0, 1, 1, 0;\n"
      "wgmma.mma_async.sync.aligned.m64n56k16.f32.bf16.bf16 {%0, %1, %2, %3, %4, %5, %6, %7, %8, %9, %10, %11, %12, %13, %14, %15, %16, %17, %18, %19, %20, %21, %22, %23, %24, %25, %26, %27}, {%72, %73, %74, %75}, %97, 1, 1, 1, 0;\n"
      "wgmma.mma_async.sync.aligned.m64n56k16.f32.bf16.bf16 {%0, %1, %2, %3, %4, %5, %6, %7, %8, %9, %10, %11, %12, %13, %14, %15, %16, %17, %18, %19, %20, %21, %22, %23, %24, %25, %26, %27}, {%56, %57, %58, %59}, dx0, 1, 1, 1, 0;\n"
      "wgmma.mma_async.sync.aligned.m64n56k16.f32.bf16.bf16 {%0, %1, %2, %3, %4, %5, %6, %7, %8, %9, %10, %11, %12, %13, %14, %15, %16, %17, %18, %19, %20, %21, %22, %23, %24, %25, %26, %27}, {%60, %61, %62, %63}, dx1, 1, 1, 1, 0;\n"
      "wgmma.mma_async.sync.aligned.m64n56k16.f32.bf16.bf16 {%0, %1, %2, %3, %4, %5, %6, %7, %8, %9, %10, %11, %12, %13, %14, %15, %16, %17, %18, %19, %20, %21, %22, %23, %24, %25, %26, %27}, {%64, %65, %66, %67}, dx2, 1, 1, 1, 0;\n"
      "wgmma.mma_async.sync.aligned.m64n56k16.f32.bf16.bf16 {%0, %1, %2, %3, %4, %5, %6, %7, %8, %9, %10, %11, %12, %13, %14, %15, %16, %17, %18, %19, %20, %21, %22, %23, %24, %25, %26, %27}, {%68, %69, %70, %71}, dx3, 1, 1, 1, 0;\n"
      "wgmma.commit_group.sync.aligned;\n"
      "wgmma.mma_async.sync.aligned.m64n56k16.f32.bf16.bf16 {%28, %29, %30, %31, %32, %33, %34, %35, %36, %37, %38, %39, %40, %41, %42, %43, %44, %45, %46, %47, %48, %49, %50, %51, %52, %53, %54, %55}, {%76, %77, %78, %79}, dx0, 0, 1, 1, 0;\n"
      "wgmma.mma_async.sync.aligned.m64n56k16.f32.bf16.bf16 {%28, %29, %30, %31, %32, %33, %34, %35, %36, %37, %38, %39, %40, %41, %42, %43, %44, %45, %46, %47, %48, %49, %50, %51, %52, %53, %54, %55}, {%80, %81, %82, %83}, dx1, 1, 1, 1, 0;\n"
      "wgmma.mma_async.sync.aligned.m64n56k16.f32.bf16.bf16 {%28, %29, %30, %31, %32, %33, %34, %35, %36, %37, %38, %39, %40, %41, %42, %43, %44, %45, %46, %47, %48, %49, %50, %51, %52, %53, %54, %55}, {%84, %85, %86, %87}, dx2, 1, 1, 1, 0;\n"
      "wgmma.mma_async.sync.aligned.m64n56k16.f32.bf16.bf16 {%28, %29, %30, %31, %32, %33, %34, %35, %36, %37, %38, %39, %40, %41, %42, %43, %44, %45, %46, %47, %48, %49, %50, %51, %52, %53, %54, %55}, {%88, %89, %90, %91}, dx3, 1, 1, 1, 0;\n"
      "wgmma.commit_group.sync.aligned;\n}\n"
      : "=f"(g[0]), "=f"(g[1]), "=f"(g[2]), "=f"(g[3]), "=f"(g[4]), "=f"(g[5]), "=f"(g[6]), "=f"(g[7]), "=f"(g[8]), "=f"(g[9]), "=f"(g[10]), "=f"(g[11]), "=f"(g[12]), "=f"(g[13]), "=f"(g[14]), "=f"(g[15]), "=f"(g[16]), "=f"(g[17]), "=f"(g[18]), "=f"(g[19]), "=f"(g[20]), "=f"(g[21]), "=f"(g[22]), "=f"(g[23]), "=f"(g[24]), "=f"(g[25]), "=f"(g[26]), "=f"(g[27]),
        "=f"(h[0]), "=f"(h[1]), "=f"(h[2]), "=f"(h[3]), "=f"(h[4]), "=f"(h[5]), "=f"(h[6]), "=f"(h[7]), "=f"(h[8]), "=f"(h[9]), "=f"(h[10]), "=f"(h[11]), "=f"(h[12]), "=f"(h[13]), "=f"(h[14]), "=f"(h[15]), "=f"(h[16]), "=f"(h[17]), "=f"(h[18]), "=f"(h[19]), "=f"(h[20]), "=f"(h[21]), "=f"(h[22]), "=f"(h[23]), "=f"(h[24]), "=f"(h[25]), "=f"(h[26]), "=f"(h[27])
      : "r"(w[0]), "r"(w[1]), "r"(w[2]), "r"(w[3]), "r"(w[4]), "r"(w[5]), "r"(w[6]), "r"(w[7]), "r"(w[8]), "r"(w[9]), "r"(w[10]), "r"(w[11]), "r"(w[12]), "r"(w[13]), "r"(w[14]), "r"(w[15]), "r"(w[16]), "r"(w[17]), "r"(w[18]), "r"(w[19]), "r"(w[20]), "r"(w[21]), "r"(w[22]), "r"(w[23]), "r"(w[24]), "r"(w[25]), "r"(w[26]), "r"(w[27]), "r"(w[28]), "r"(w[29]), "r"(w[30]), "r"(w[31]), "r"(w[32]), "r"(w[33]), "r"(w[34]), "r"(w[35]), "r"(w[36]), "r"(w[37]), "r"(w[38]), "r"(w[39]), "r"(dx), "l"(de), "l"(dh)
      : "memory");
  }
  static __device__ __forceinline__ void wait_g(float* g) {
    asm volatile("wgmma.wait_group.sync.aligned 1;\n"
      : "+f"(g[0]), "+f"(g[1]), "+f"(g[2]), "+f"(g[3]), "+f"(g[4]), "+f"(g[5]), "+f"(g[6]), "+f"(g[7]), "+f"(g[8]), "+f"(g[9]), "+f"(g[10]), "+f"(g[11]), "+f"(g[12]), "+f"(g[13]), "+f"(g[14]), "+f"(g[15]), "+f"(g[16]), "+f"(g[17]), "+f"(g[18]), "+f"(g[19]), "+f"(g[20]), "+f"(g[21]), "+f"(g[22]), "+f"(g[23]), "+f"(g[24]), "+f"(g[25]), "+f"(g[26]), "+f"(g[27])
      :: "memory");
  }
  static __device__ __forceinline__ void wait_h(float* h) {
    asm volatile("wgmma.wait_group.sync.aligned 0;\n"
      : "+f"(h[0]), "+f"(h[1]), "+f"(h[2]), "+f"(h[3]), "+f"(h[4]), "+f"(h[5]), "+f"(h[6]), "+f"(h[7]), "+f"(h[8]), "+f"(h[9]), "+f"(h[10]), "+f"(h[11]), "+f"(h[12]), "+f"(h[13]), "+f"(h[14]), "+f"(h[15]), "+f"(h[16]), "+f"(h[17]), "+f"(h[18]), "+f"(h[19]), "+f"(h[20]), "+f"(h[21]), "+f"(h[22]), "+f"(h[23]), "+f"(h[24]), "+f"(h[25]), "+f"(h[26]), "+f"(h[27])
      :: "memory");
  }
};
template<> struct TileMMA<8> {
  static __device__ __forceinline__ void issue(float* g, float* h, const uint32_t* w, uint32_t dx, uint64_t de, uint64_t dh, uint64_t dc) {
    asm volatile(
      "{\n.reg .b64 dx0, dx1, dx2, dx3;\n.reg .b32 l1, l2, l3, hx;\nmov.b32 hx, 0x40000040;\n"
      "add.u32 l1, %104, 2;\nadd.u32 l2, %104, 4;\nadd.u32 l3, %104, 6;\n"
      "mov.b64 dx0, {%104, hx};\nmov.b64 dx1, {l1, hx};\nmov.b64 dx2, {l2, hx};\nmov.b64 dx3, {l3, hx};\n"
      "wgmma.fence.sync.aligned;\n"
      "wgmma.mma_async.sync.aligned.m64n64k16.f32.bf16.bf16 {%0, %1, %2, %3, %4, %5, %6, %7, %8, %9, %10, %11, %12, %13, %14, %15, %16, %17, %18, %19, %20, %21, %22, %23, %24, %25, %26, %27, %28, %29, %30, %31}, {%100, %101, %102, %103}, %106, 0, 1, 1, 0;\n"
      "wgmma.mma_async.sync.aligned.m64n64k16.f32.bf16.bf16 {%0, %1, %2, %3, %4, %5, %6, %7, %8, %9, %10, %11, %12, %13, %14, %15, %16, %17, %18, %19, %20, %21, %22, %23, %24, %25, %26, %27, %28, %29, %30, %31}, {%80, %81, %82, %83}, %105, 1, 1, 1, 0;\n"
      "wgmma.mma_async.sync.aligned.m64n64k16.f32.bf16.bf16 {%0, %1, %2, %3, %4, %5, %6, %7, %8, %9, %10, %11, %12, %13, %14, %15, %16, %17, %18, %19, %20, %21, %22, %23, %24, %25, %26, %27, %28, %29, %30, %31}, {%64, %65, %66, %67}, dx0, 1, 1, 1, 0;\n"
      "wgmma.mma_async.sync.aligned.m64n64k16.f32.bf16.bf16 {%0, %1, %2, %3, %4, %5, %6, %7, %8, %9, %10, %11, %12, %13, %14, %15, %16, %17, %18, %19, %20, %21, %22, %23, %24, %25, %26, %27, %28, %29, %30, %31}, {%68, %69, %70, %71}, dx1, 1, 1, 1, 0;\n"
      "wgmma.mma_async.sync.aligned.m64n64k16.f32.bf16.bf16 {%0, %1, %2, %3, %4, %5, %6, %7, %8, %9, %10, %11, %12, %13, %14, %15, %16, %17, %18, %19, %20, %21, %22, %23, %24, %25, %26, %27, %28, %29, %30, %31}, {%72, %73, %74, %75}, dx2, 1, 1, 1, 0;\n"
      "wgmma.mma_async.sync.aligned.m64n64k16.f32.bf16.bf16 {%0, %1, %2, %3, %4, %5, %6, %7, %8, %9, %10, %11, %12, %13, %14, %15, %16, %17, %18, %19, %20, %21, %22, %23, %24, %25, %26, %27, %28, %29, %30, %31}, {%76, %77, %78, %79}, dx3, 1, 1, 1, 0;\n"
      "wgmma.commit_group.sync.aligned;\n"
      "wgmma.mma_async.sync.aligned.m64n64k16.f32.bf16.bf16 {%32, %33, %34, %35, %36, %37, %38, %39, %40, %41, %42, %43, %44, %45, %46, %47, %48, %49, %50, %51, %52, %53, %54, %55, %56, %57, %58, %59, %60, %61, %62, %63}, {%84, %85, %86, %87}, dx0, 0, 1, 1, 0;\n"
      "wgmma.mma_async.sync.aligned.m64n64k16.f32.bf16.bf16 {%32, %33, %34, %35, %36, %37, %38, %39, %40, %41, %42, %43, %44, %45, %46, %47, %48, %49, %50, %51, %52, %53, %54, %55, %56, %57, %58, %59, %60, %61, %62, %63}, {%88, %89, %90, %91}, dx1, 1, 1, 1, 0;\n"
      "wgmma.mma_async.sync.aligned.m64n64k16.f32.bf16.bf16 {%32, %33, %34, %35, %36, %37, %38, %39, %40, %41, %42, %43, %44, %45, %46, %47, %48, %49, %50, %51, %52, %53, %54, %55, %56, %57, %58, %59, %60, %61, %62, %63}, {%92, %93, %94, %95}, dx2, 1, 1, 1, 0;\n"
      "wgmma.mma_async.sync.aligned.m64n64k16.f32.bf16.bf16 {%32, %33, %34, %35, %36, %37, %38, %39, %40, %41, %42, %43, %44, %45, %46, %47, %48, %49, %50, %51, %52, %53, %54, %55, %56, %57, %58, %59, %60, %61, %62, %63}, {%96, %97, %98, %99}, dx3, 1, 1, 1, 0;\n"
      "wgmma.commit_group.sync.aligned;\n}\n"
      : "=f"(g[0]), "=f"(g[1]), "=f"(g[2]), "=f"(g[3]), "=f"(g[4]), "=f"(g[5]), "=f"(g[6]), "=f"(g[7]), "=f"(g[8]), "=f"(g[9]), "=f"(g[10]), "=f"(g[11]), "=f"(g[12]), "=f"(g[13]), "=f"(g[14]), "=f"(g[15]), "=f"(g[16]), "=f"(g[17]), "=f"(g[18]), "=f"(g[19]), "=f"(g[20]), "=f"(g[21]), "=f"(g[22]), "=f"(g[23]), "=f"(g[24]), "=f"(g[25]), "=f"(g[26]), "=f"(g[27]), "=f"(g[28]), "=f"(g[29]), "=f"(g[30]), "=f"(g[31]),
        "=f"(h[0]), "=f"(h[1]), "=f"(h[2]), "=f"(h[3]), "=f"(h[4]), "=f"(h[5]), "=f"(h[6]), "=f"(h[7]), "=f"(h[8]), "=f"(h[9]), "=f"(h[10]), "=f"(h[11]), "=f"(h[12]), "=f"(h[13]), "=f"(h[14]), "=f"(h[15]), "=f"(h[16]), "=f"(h[17]), "=f"(h[18]), "=f"(h[19]), "=f"(h[20]), "=f"(h[21]), "=f"(h[22]), "=f"(h[23]), "=f"(h[24]), "=f"(h[25]), "=f"(h[26]), "=f"(h[27]), "=f"(h[28]), "=f"(h[29]), "=f"(h[30]), "=f"(h[31])
      : "r"(w[0]), "r"(w[1]), "r"(w[2]), "r"(w[3]), "r"(w[4]), "r"(w[5]), "r"(w[6]), "r"(w[7]), "r"(w[8]), "r"(w[9]), "r"(w[10]), "r"(w[11]), "r"(w[12]), "r"(w[13]), "r"(w[14]), "r"(w[15]), "r"(w[16]), "r"(w[17]), "r"(w[18]), "r"(w[19]), "r"(w[20]), "r"(w[21]), "r"(w[22]), "r"(w[23]), "r"(w[24]), "r"(w[25]), "r"(w[26]), "r"(w[27]), "r"(w[28]), "r"(w[29]), "r"(w[30]), "r"(w[31]), "r"(w[32]), "r"(w[33]), "r"(w[34]), "r"(w[35]), "r"(w[36]), "r"(w[37]), "r"(w[38]), "r"(w[39]), "r"(dx), "l"(de), "l"(dh)
      : "memory");
  }
  static __device__ __forceinline__ void wait_g(float* g) {
    asm volatile("wgmma.wait_group.sync.aligned 1;\n"
      : "+f"(g[0]), "+f"(g[1]), "+f"(g[2]), "+f"(g[3]), "+f"(g[4]), "+f"(g[5]), "+f"(g[6]), "+f"(g[7]), "+f"(g[8]), "+f"(g[9]), "+f"(g[10]), "+f"(g[11]), "+f"(g[12]), "+f"(g[13]), "+f"(g[14]), "+f"(g[15]), "+f"(g[16]), "+f"(g[17]), "+f"(g[18]), "+f"(g[19]), "+f"(g[20]), "+f"(g[21]), "+f"(g[22]), "+f"(g[23]), "+f"(g[24]), "+f"(g[25]), "+f"(g[26]), "+f"(g[27]), "+f"(g[28]), "+f"(g[29]), "+f"(g[30]), "+f"(g[31])
      :: "memory");
  }
  static __device__ __forceinline__ void wait_h(float* h) {
    asm volatile("wgmma.wait_group.sync.aligned 0;\n"
      : "+f"(h[0]), "+f"(h[1]), "+f"(h[2]), "+f"(h[3]), "+f"(h[4]), "+f"(h[5]), "+f"(h[6]), "+f"(h[7]), "+f"(h[8]), "+f"(h[9]), "+f"(h[10]), "+f"(h[11]), "+f"(h[12]), "+f"(h[13]), "+f"(h[14]), "+f"(h[15]), "+f"(h[16]), "+f"(h[17]), "+f"(h[18]), "+f"(h[19]), "+f"(h[20]), "+f"(h[21]), "+f"(h[22]), "+f"(h[23]), "+f"(h[24]), "+f"(h[25]), "+f"(h[26]), "+f"(h[27]), "+f"(h[28]), "+f"(h[29]), "+f"(h[30]), "+f"(h[31])
      :: "memory");
  }
};
template<> struct TileMMA<9> {
  static __device__ __forceinline__ void issue(float* g, float* h, const uint32_t* w, uint32_t dx, uint64_t de, uint64_t dh, uint64_t dc) {
    asm volatile(
      "{\n.reg .b64 dx0, dx1, dx2, dx3;\n.reg .b32 l1, l2, l3, hx;\nmov.b32 hx, 0x40000040;\n"
      "add.u32 l1, %112, 2;\nadd.u32 l2, %112, 4;\nadd.u32 l3, %112, 6;\n"
      "mov.b64 dx0, {%112, hx};\nmov.b64 dx1, {l1, hx};\nmov.b64 dx2, {l2, hx};\nmov.b64 dx3, {l3, hx};\n"
      "wgmma.fence.sync.aligned;\n"
      "wgmma.mma_async.sync.aligned.m64n72k16.f32.bf16.bf16 {%0, %1, %2, %3, %4, %5, %6, %7, %8, %9, %10, %11, %12, %13, %14, %15, %16, %17, %18, %19, %20, %21, %22, %23, %24, %25, %26, %27, %28, %29, %30, %31, %32, %33, %34, %35}, {%108, %109, %110, %111}, %114, 0, 1, 1, 0;\n"
      "wgmma.mma_async.sync.aligned.m64n72k16.f32.bf16.bf16 {%0, %1, %2, %3, %4, %5, %6, %7, %8, %9, %10, %11, %12, %13, %14, %15, %16, %17, %18, %19, %20, %21, %22, %23, %24, %25, %26, %27, %28, %29, %30, %31, %32, %33, %34, %35}, {%88, %89, %90, %91}, %113, 1, 1, 1, 0;\n"
      "wgmma.mma_async.sync.aligned.m64n72k16.f32.bf16.bf16 {%0, %1, %2, %3, %4, %5, %6, %7, %8, %9, %10, %11, %12, %13, %14, %15, %16, %17, %18, %19, %20, %21, %22, %23, %24, %25, %26, %27, %28, %29, %30, %31, %32, %33, %34, %35}, {%72, %73, %74, %75}, dx0, 1, 1, 1, 0;\n"
      "wgmma.mma_async.sync.aligned.m64n72k16.f32.bf16.bf16 {%0, %1, %2, %3, %4, %5, %6, %7, %8, %9, %10, %11, %12, %13, %14, %15, %16, %17, %18, %19, %20, %21, %22, %23, %24, %25, %26, %27, %28, %29, %30, %31, %32, %33, %34, %35}, {%76, %77, %78, %79}, dx1, 1, 1, 1, 0;\n"
      "wgmma.mma_async.sync.aligned.m64n72k16.f32.bf16.bf16 {%0, %1, %2, %3, %4, %5, %6, %7, %8, %9, %10, %11, %12, %13, %14, %15, %16, %17, %18, %19, %20, %21, %22, %23, %24, %25, %26, %27, %28, %29, %30, %31, %32, %33, %34, %35}, {%80, %81, %82, %83}, dx2, 1, 1, 1, 0;\n"
      "wgmma.mma_async.sync.aligned.m64n72k16.f32.bf16.bf16 {%0, %1, %2, %3, %4, %5, %6, %7, %8, %9, %10, %11, %12, %13, %14, %15, %16, %17, %18, %19, %20, %21, %22, %23, %24, %25, %26, %27, %28, %29, %30, %31, %32, %33, %34, %35}, {%84, %85, %86, %87}, dx3, 1, 1, 1, 0;\n"
      "wgmma.commit_group.sync.aligned;\n"
      "wgmma.mma_async.sync.aligned.m64n72k16.f32.bf16.bf16 {%36, %37, %38, %39, %40, %41, %42, %43, %44, %45, %46, %47, %48, %49, %50, %51, %52, %53, %54, %55, %56, %57, %58, %59, %60, %61, %62, %63, %64, %65, %66, %67, %68, %69, %70, %71}, {%92, %93, %94, %95}, dx0, 0, 1, 1, 0;\n"
      "wgmma.mma_async.sync.aligned.m64n72k16.f32.bf16.bf16 {%36, %37, %38, %39, %40, %41, %42, %43, %44, %45, %46, %47, %48, %49, %50, %51, %52, %53, %54, %55, %56, %57, %58, %59, %60, %61, %62, %63, %64, %65, %66, %67, %68, %69, %70, %71}, {%96, %97, %98, %99}, dx1, 1, 1, 1, 0;\n"
      "wgmma.mma_async.sync.aligned.m64n72k16.f32.bf16.bf16 {%36, %37, %38, %39, %40, %41, %42, %43, %44, %45, %46, %47, %48, %49, %50, %51, %52, %53, %54, %55, %56, %57, %58, %59, %60, %61, %62, %63, %64, %65, %66, %67, %68, %69, %70, %71}, {%100, %101, %102, %103}, dx2, 1, 1, 1, 0;\n"
      "wgmma.mma_async.sync.aligned.m64n72k16.f32.bf16.bf16 {%36, %37, %38, %39, %40, %41, %42, %43, %44, %45, %46, %47, %48, %49, %50, %51, %52, %53, %54, %55, %56, %57, %58, %59, %60, %61, %62, %63, %64, %65, %66, %67, %68, %69, %70, %71}, {%104, %105, %106, %107}, dx3, 1, 1, 1, 0;\n"
      "wgmma.commit_group.sync.aligned;\n}\n"
      : "=f"(g[0]), "=f"(g[1]), "=f"(g[2]), "=f"(g[3]), "=f"(g[4]), "=f"(g[5]), "=f"(g[6]), "=f"(g[7]), "=f"(g[8]), "=f"(g[9]), "=f"(g[10]), "=f"(g[11]), "=f"(g[12]), "=f"(g[13]), "=f"(g[14]), "=f"(g[15]), "=f"(g[16]), "=f"(g[17]), "=f"(g[18]), "=f"(g[19]), "=f"(g[20]), "=f"(g[21]), "=f"(g[22]), "=f"(g[23]), "=f"(g[24]), "=f"(g[25]), "=f"(g[26]), "=f"(g[27]), "=f"(g[28]), "=f"(g[29]), "=f"(g[30]), "=f"(g[31]), "=f"(g[32]), "=f"(g[33]), "=f"(g[34]), "=f"(g[35]),
        "=f"(h[0]), "=f"(h[1]), "=f"(h[2]), "=f"(h[3]), "=f"(h[4]), "=f"(h[5]), "=f"(h[6]), "=f"(h[7]), "=f"(h[8]), "=f"(h[9]), "=f"(h[10]), "=f"(h[11]), "=f"(h[12]), "=f"(h[13]), "=f"(h[14]), "=f"(h[15]), "=f"(h[16]), "=f"(h[17]), "=f"(h[18]), "=f"(h[19]), "=f"(h[20]), "=f"(h[21]), "=f"(h[22]), "=f"(h[23]), "=f"(h[24]), "=f"(h[25]), "=f"(h[26]), "=f"(h[27]), "=f"(h[28]), "=f"(h[29]), "=f"(h[30]), "=f"(h[31]), "=f"(h[32]), "=f"(h[33]), "=f"(h[34]), "=f"(h[35])
      : "r"(w[0]), "r"(w[1]), "r"(w[2]), "r"(w[3]), "r"(w[4]), "r"(w[5]), "r"(w[6]), "r"(w[7]), "r"(w[8]), "r"(w[9]), "r"(w[10]), "r"(w[11]), "r"(w[12]), "r"(w[13]), "r"(w[14]), "r"(w[15]), "r"(w[16]), "r"(w[17]), "r"(w[18]), "r"(w[19]), "r"(w[20]), "r"(w[21]), "r"(w[22]), "r"(w[23]), "r"(w[24]), "r"(w[25]), "r"(w[26]), "r"(w[27]), "r"(w[28]), "r"(w[29]), "r"(w[30]), "r"(w[31]), "r"(w[32]), "r"(w[33]), "r"(w[34]), "r"(w[35]), "r"(w[36]), "r"(w[37]), "r"(w[38]), "r"(w[39]), "r"(dx), "l"(de), "l"(dh)
      : "memory");
  }
  static __device__ __forceinline__ void wait_g(float* g) {
    asm volatile("wgmma.wait_group.sync.aligned 1;\n"
      : "+f"(g[0]), "+f"(g[1]), "+f"(g[2]), "+f"(g[3]), "+f"(g[4]), "+f"(g[5]), "+f"(g[6]), "+f"(g[7]), "+f"(g[8]), "+f"(g[9]), "+f"(g[10]), "+f"(g[11]), "+f"(g[12]), "+f"(g[13]), "+f"(g[14]), "+f"(g[15]), "+f"(g[16]), "+f"(g[17]), "+f"(g[18]), "+f"(g[19]), "+f"(g[20]), "+f"(g[21]), "+f"(g[22]), "+f"(g[23]), "+f"(g[24]), "+f"(g[25]), "+f"(g[26]), "+f"(g[27]), "+f"(g[28]), "+f"(g[29]), "+f"(g[30]), "+f"(g[31]), "+f"(g[32]), "+f"(g[33]), "+f"(g[34]), "+f"(g[35])
      :: "memory");
  }
  static __device__ __forceinline__ void wait_h(float* h) {
    asm volatile("wgmma.wait_group.sync.aligned 0;\n"
      : "+f"(h[0]), "+f"(h[1]), "+f"(h[2]), "+f"(h[3]), "+f"(h[4]), "+f"(h[5]), "+f"(h[6]), "+f"(h[7]), "+f"(h[8]), "+f"(h[9]), "+f"(h[10]), "+f"(h[11]), "+f"(h[12]), "+f"(h[13]), "+f"(h[14]), "+f"(h[15]), "+f"(h[16]), "+f"(h[17]), "+f"(h[18]), "+f"(h[19]), "+f"(h[20]), "+f"(h[21]), "+f"(h[22]), "+f"(h[23]), "+f"(h[24]), "+f"(h[25]), "+f"(h[26]), "+f"(h[27]), "+f"(h[28]), "+f"(h[29]), "+f"(h[30]), "+f"(h[31]), "+f"(h[32]), "+f"(h[33]), "+f"(h[34]), "+f"(h[35])
      :: "memory");
  }
};
template<> struct TileMMA<10> {
  static __device__ __forceinline__ void issue(float* g, float* h, const uint32_t* w, uint32_t dx, uint64_t de, uint64_t dh, uint64_t dc) {
    asm volatile(
      "{\n.reg .b64 dx0, dx1, dx2, dx3;\n.reg .b32 l1, l2, l3, hx;\nmov.b32 hx, 0x40000040;\n"
      "add.u32 l1, %120, 2;\nadd.u32 l2, %120, 4;\nadd.u32 l3, %120, 6;\n"
      "mov.b64 dx0, {%120, hx};\nmov.b64 dx1, {l1, hx};\nmov.b64 dx2, {l2, hx};\nmov.b64 dx3, {l3, hx};\n"
      "wgmma.fence.sync.aligned;\n"
      "wgmma.mma_async.sync.aligned.m64n80k16.f32.bf16.bf16 {%0, %1, %2, %3, %4, %5, %6, %7, %8, %9, %10, %11, %12, %13, %14, %15, %16, %17, %18, %19, %20, %21, %22, %23, %24, %25, %26, %27, %28, %29, %30, %31, %32, %33, %34, %35, %36, %37, %38, %39}, {%116, %117, %118, %119}, %122, 0, 1, 1, 0;\n"
      "wgmma.mma_async.sync.aligned.m64n80k16.f32.bf16.bf16 {%0, %1, %2, %3, %4, %5, %6, %7, %8, %9, %10, %11, %12, %13, %14, %15, %16, %17, %18, %19, %20, %21, %22, %23, %24, %25, %26, %27, %28, %29, %30, %31, %32, %33, %34, %35, %36, %37, %38, %39}, {%96, %97, %98, %99}, %121, 1, 1, 1, 0;\n"
      "wgmma.mma_async.sync.aligned.m64n80k16.f32.bf16.bf16 {%0, %1, %2, %3, %4, %5, %6, %7, %8, %9, %10, %11, %12, %13, %14, %15, %16, %17, %18, %19, %20, %21, %22, %23, %24, %25, %26, %27, %28, %29, %30, %31, %32, %33, %34, %35, %36, %37, %38, %39}, {%80, %81, %82, %83}, dx0, 1, 1, 1, 0;\n"
      "wgmma.mma_async.sync.aligned.m64n80k16.f32.bf16.bf16 {%0, %1, %2, %3, %4, %5, %6, %7, %8, %9, %10, %11, %12, %13, %14, %15, %16, %17, %18, %19, %20, %21, %22, %23, %24, %25, %26, %27, %28, %29, %30, %31, %32, %33, %34, %35, %36, %37, %38, %39}, {%84, %85, %86, %87}, dx1, 1, 1, 1, 0;\n"
      "wgmma.mma_async.sync.aligned.m64n80k16.f32.bf16.bf16 {%0, %1, %2, %3, %4, %5, %6, %7, %8, %9, %10, %11, %12, %13, %14, %15, %16, %17, %18, %19, %20, %21, %22, %23, %24, %25, %26, %27, %28, %29, %30, %31, %32, %33, %34, %35, %36, %37, %38, %39}, {%88, %89, %90, %91}, dx2, 1, 1, 1, 0;\n"
      "wgmma.mma_async.sync.aligned.m64n80k16.f32.bf16.bf16 {%0, %1, %2, %3, %4, %5, %6, %7, %8, %9, %10, %11, %12, %13, %14, %15, %16, %17, %18, %19, %20, %21, %22, %23, %24, %25, %26, %27, %28, %29, %30, %31, %32, %33, %34, %35, %36, %37, %38, %39}, {%92, %93, %94, %95}, dx3, 1, 1, 1, 0;\n"
      "wgmma.commit_group.sync.aligned;\n"
      "wgmma.mma_async.sync.aligned.m64n80k16.f32.bf16.bf16 {%40, %41, %42, %43, %44, %45, %46, %47, %48, %49, %50, %51, %52, %53, %54, %55, %56, %57, %58, %59, %60, %61, %62, %63, %64, %65, %66, %67, %68, %69, %70, %71, %72, %73, %74, %75, %76, %77, %78, %79}, {%100, %101, %102, %103}, dx0, 0, 1, 1, 0;\n"
      "wgmma.mma_async.sync.aligned.m64n80k16.f32.bf16.bf16 {%40, %41, %42, %43, %44, %45, %46, %47, %48, %49, %50, %51, %52, %53, %54, %55, %56, %57, %58, %59, %60, %61, %62, %63, %64, %65, %66, %67, %68, %69, %70, %71, %72, %73, %74, %75, %76, %77, %78, %79}, {%104, %105, %106, %107}, dx1, 1, 1, 1, 0;\n"
      "wgmma.mma_async.sync.aligned.m64n80k16.f32.bf16.bf16 {%40, %41, %42, %43, %44, %45, %46, %47, %48, %49, %50, %51, %52, %53, %54, %55, %56, %57, %58, %59, %60, %61, %62, %63, %64, %65, %66, %67, %68, %69, %70, %71, %72, %73, %74, %75, %76, %77, %78, %79}, {%108, %109, %110, %111}, dx2, 1, 1, 1, 0;\n"
      "wgmma.mma_async.sync.aligned.m64n80k16.f32.bf16.bf16 {%40, %41, %42, %43, %44, %45, %46, %47, %48, %49, %50, %51, %52, %53, %54, %55, %56, %57, %58, %59, %60, %61, %62, %63, %64, %65, %66, %67, %68, %69, %70, %71, %72, %73, %74, %75, %76, %77, %78, %79}, {%112, %113, %114, %115}, dx3, 1, 1, 1, 0;\n"
      "wgmma.commit_group.sync.aligned;\n}\n"
      : "=f"(g[0]), "=f"(g[1]), "=f"(g[2]), "=f"(g[3]), "=f"(g[4]), "=f"(g[5]), "=f"(g[6]), "=f"(g[7]), "=f"(g[8]), "=f"(g[9]), "=f"(g[10]), "=f"(g[11]), "=f"(g[12]), "=f"(g[13]), "=f"(g[14]), "=f"(g[15]), "=f"(g[16]), "=f"(g[17]), "=f"(g[18]), "=f"(g[19]), "=f"(g[20]), "=f"(g[21]), "=f"(g[22]), "=f"(g[23]), "=f"(g[24]), "=f"(g[25]), "=f"(g[26]), "=f"(g[27]), "=f"(g[28]), "=f"(g[29]), "=f"(g[30]), "=f"(g[31]), "=f"(g[32]), "=f"(g[33]), "=f"(g[34]), "=f"(g[35]), "=f"(g[36]), "=f"(g[37]), "=f"(g[38]), "=f"(g[39]),
        "=f"(h[0]), "=f"(h[1]), "=f"(h[2]), "=f"(h[3]), "=f"(h[4]), "=f"(h[5]), "=f"(h[6]), "=f"(h[7]), "=f"(h[8]), "=f"(h[9]), "=f"(h[10]), "=f"(h[11]), "=f"(h[12]), "=f"(h[13]), "=f"(h[14]), "=f"(h[15]), "=f"(h[16]), "=f"(h[17]), "=f"(h[18]), "=f"(h[19]), "=f"(h[20]), "=f"(h[21]), "=f"(h[22]), "=f"(h[23]), "=f"(h[24]), "=f"(h[25]), "=f"(h[26]), "=f"(h[27]), "=f"(h[28]), "=f"(h[29]), "=f"(h[30]), "=f"(h[31]), "=f"(h[32]), "=f"(h[33]), "=f"(h[34]), "=f"(h[35]), "=f"(h[36]), "=f"(h[37]), "=f"(h[38]), "=f"(h[39])
      : "r"(w[0]), "r"(w[1]), "r"(w[2]), "r"(w[3]), "r"(w[4]), "r"(w[5]), "r"(w[6]), "r"(w[7]), "r"(w[8]), "r"(w[9]), "r"(w[10]), "r"(w[11]), "r"(w[12]), "r"(w[13]), "r"(w[14]), "r"(w[15]), "r"(w[16]), "r"(w[17]), "r"(w[18]), "r"(w[19]), "r"(w[20]), "r"(w[21]), "r"(w[22]), "r"(w[23]), "r"(w[24]), "r"(w[25]), "r"(w[26]), "r"(w[27]), "r"(w[28]), "r"(w[29]), "r"(w[30]), "r"(w[31]), "r"(w[32]), "r"(w[33]), "r"(w[34]), "r"(w[35]), "r"(w[36]), "r"(w[37]), "r"(w[38]), "r"(w[39]), "r"(dx), "l"(de), "l"(dh)
      : "memory");
  }
  static __device__ __forceinline__ void wait_g(float* g) {
    asm volatile("wgmma.wait_group.sync.aligned 1;\n"
      : "+f"(g[0]), "+f"(g[1]), "+f"(g[2]), "+f"(g[3]), "+f"(g[4]), "+f"(g[5]), "+f"(g[6]), "+f"(g[7]), "+f"(g[8]), "+f"(g[9]), "+f"(g[10]), "+f"(g[11]), "+f"(g[12]), "+f"(g[13]), "+f"(g[14]), "+f"(g[15]), "+f"(g[16]), "+f"(g[17]), "+f"(g[18]), "+f"(g[19]), "+f"(g[20]), "+f"(g[21]), "+f"(g[22]), "+f"(g[23]), "+f"(g[24]), "+f"(g[25]), "+f"(g[26]), "+f"(g[27]), "+f"(g[28]), "+f"(g[29]), "+f"(g[30]), "+f"(g[31]), "+f"(g[32]), "+f"(g[33]), "+f"(g[34]), "+f"(g[35]), "+f"(g[36]), "+f"(g[37]), "+f"(g[38]), "+f"(g[39])
      :: "memory");
  }
  static __device__ __forceinline__ void wait_h(float* h) {
    asm volatile("wgmma.wait_group.sync.aligned 0;\n"
      : "+f"(h[0]), "+f"(h[1]), "+f"(h[2]), "+f"(h[3]), "+f"(h[4]), "+f"(h[5]), "+f"(h[6]), "+f"(h[7]), "+f"(h[8]), "+f"(h[9]), "+f"(h[10]), "+f"(h[11]), "+f"(h[12]), "+f"(h[13]), "+f"(h[14]), "+f"(h[15]), "+f"(h[16]), "+f"(h[17]), "+f"(h[18]), "+f"(h[19]), "+f"(h[20]), "+f"(h[21]), "+f"(h[22]), "+f"(h[23]), "+f"(h[24]), "+f"(h[25]), "+f"(h[26]), "+f"(h[27]), "+f"(h[28]), "+f"(h[29]), "+f"(h[30]), "+f"(h[31]), "+f"(h[32]), "+f"(h[33]), "+f"(h[34]), "+f"(h[35]), "+f"(h[36]), "+f"(h[37]), "+f"(h[38]), "+f"(h[39])
      :: "memory");
  }
};
template<> struct TileMMA<11> {
  static __device__ __forceinline__ void issue(float* g, float* h, const uint32_t* w, uint32_t dx, uint64_t de, uint64_t dh, uint64_t dc) {
    asm volatile(
      "{\n.reg .b64 dx0, dx1, dx2, dx3;\n.reg .b32 l1, l2, l3, hx;\nmov.b32 hx, 0x40000040;\n"
      "add.u32 l1, %124, 2;\nadd.u32 l2, %124, 4;\nadd.u32 l3, %124, 6;\n"
      "mov.b64 dx0, {%124, hx};\nmov.b64 dx1, {l1, hx};\nmov.b64 dx2, {l2, hx};\nmov.b64 dx3, {l3, hx};\n"
      "wgmma.fence.sync.aligned;\n"
      "wgmma.mma_async.sync.aligned.m64n88k16.f32.bf16.bf16 {%0, %1, %2, %3, %4, %5, %6, %7, %8, %9, %10, %11, %12, %13, %14, %15, %16, %17, %18, %19, %20, %21, %22, %23, %24, %25, %26, %27, %28, %29, %30, %31, %32, %33, %34, %35, %36, %37, %38, %39, %40, %41, %42, %43}, {%120, %121, %122, %123}, %126, 0, 1, 1, 0;\n"
      "wgmma.mma_async.sync.aligned.m64n88k16.f32.bf16.bf16 {%0, %1, %2, %3, %4, %5, %6, %7, %8, %9, %10, %11, %12, %13, %14, %15, %16, %17, %18, %19, %20, %21, %22, %23, %24, %25, %26, %27, %28, %29, %30, %31, %32, %33, %34, %35, %36, %37, %38, %39, %40, %41, %42, %43}, %127, %125, 1, 1, 1, 0, 0;\n"
      "wgmma.mma_async.sync.aligned.m64n88k16.f32.bf16.bf16 {%0, %1, %2, %3, %4, %5, %6, %7, %8, %9, %10, %11, %12, %13, %14, %15, %16, %17, %18, %19, %20, %21, %22, %23, %24, %25, %26, %27, %28, %29, %30, %31, %32, %33, %34, %35, %36, %37, %38, %39, %40, %41, %42, %43}, {%88, %89, %90, %91}, dx0, 1, 1, 1, 0;\n"
      "wgmma.mma_async.sync.aligned.m64n88k16.f32.bf16.bf16 {%0, %1, %2, %3, %4, %5, %6, %7, %8, %9, %10, %11, %12, %13, %14, %15, %16, %17, %18, %19, %20, %21, %22, %23, %24, %25, %26, %27, %28, %29, %30, %31, %32, %33, %34, %35, %36, %37, %38, %39, %40, %41, %42, %43}, {%92, %93, %94, %95}, dx1, 1, 1, 1, 0;\n"
      "wgmma.mma_async.sync.aligned.m64n88k16.f32.bf16.bf16 {%0, %1, %2, %3, %4, %5, %6, %7, %8, %9, %10, %11, %12, %13, %14, %15, %16, %17, %18, %19, %20, %21, %22, %23, %24, %25, %26, %27, %28, %29, %30, %31, %32, %33, %34, %35, %36, %37, %38, %39, %40, %41, %42, %43}, {%96, %97, %98, %99}, dx2, 1, 1, 1, 0;\n"
      "wgmma.mma_async.sync.aligned.m64n88k16.f32.bf16.bf16 {%0, %1, %2, %3, %4, %5, %6, %7, %8, %9, %10, %11, %12, %13, %14, %15, %16, %17, %18, %19, %20, %21, %22, %23, %24, %25, %26, %27, %28, %29, %30, %31, %32, %33, %34, %35, %36, %37, %38, %39, %40, %41, %42, %43}, {%100, %101, %102, %103}, dx3, 1, 1, 1, 0;\n"
      "wgmma.commit_group.sync.aligned;\n"
      "wgmma.mma_async.sync.aligned.m64n88k16.f32.bf16.bf16 {%44, %45, %46, %47, %48, %49, %50, %51, %52, %53, %54, %55, %56, %57, %58, %59, %60, %61, %62, %63, %64, %65, %66, %67, %68, %69, %70, %71, %72, %73, %74, %75, %76, %77, %78, %79, %80, %81, %82, %83, %84, %85, %86, %87}, {%104, %105, %106, %107}, dx0, 0, 1, 1, 0;\n"
      "wgmma.mma_async.sync.aligned.m64n88k16.f32.bf16.bf16 {%44, %45, %46, %47, %48, %49, %50, %51, %52, %53, %54, %55, %56, %57, %58, %59, %60, %61, %62, %63, %64, %65, %66, %67, %68, %69, %70, %71, %72, %73, %74, %75, %76, %77, %78, %79, %80, %81, %82, %83, %84, %85, %86, %87}, {%108, %109, %110, %111}, dx1, 1, 1, 1, 0;\n"
      "wgmma.mma_async.sync.aligned.m64n88k16.f32.bf16.bf16 {%44, %45, %46, %47, %48, %49, %50, %51, %52, %53, %54, %55, %56, %57, %58, %59, %60, %61, %62, %63, %64, %65, %66, %67, %68, %69, %70, %71, %72, %73, %74, %75, %76, %77, %78, %79, %80, %81, %82, %83, %84, %85, %86, %87}, {%112, %113, %114, %115}, dx2, 1, 1, 1, 0;\n"
      "wgmma.mma_async.sync.aligned.m64n88k16.f32.bf16.bf16 {%44, %45, %46, %47, %48, %49, %50, %51, %52, %53, %54, %55, %56, %57, %58, %59, %60, %61, %62, %63, %64, %65, %66, %67, %68, %69, %70, %71, %72, %73, %74, %75, %76, %77, %78, %79, %80, %81, %82, %83, %84, %85, %86, %87}, {%116, %117, %118, %119}, dx3, 1, 1, 1, 0;\n"
      "wgmma.commit_group.sync.aligned;\n}\n"
      : "=f"(g[0]), "=f"(g[1]), "=f"(g[2]), "=f"(g[3]), "=f"(g[4]), "=f"(g[5]), "=f"(g[6]), "=f"(g[7]), "=f"(g[8]), "=f"(g[9]), "=f"(g[10]), "=f"(g[11]), "=f"(g[12]), "=f"(g[13]), "=f"(g[14]), "=f"(g[15]), "=f"(g[16]), "=f"(g[17]), "=f"(g[18]), "=f"(g[19]), "=f"(g[20]), "=f"(g[21]), "=f"(g[22]), "=f"(g[23]), "=f"(g[24]), "=f"(g[25]), "=f"(g[26]), "=f"(g[27]), "=f"(g[28]), "=f"(g[29]), "=f"(g[30]), "=f"(g[31]), "=f"(g[32]), "=f"(g[33]), "=f"(g[34]), "=f"(g[35]), "=f"(g[36]), "=f"(g[37]), "=f"(g[38]), "=f"(g[39]), "=f"(g[40]), "=f"(g[41]), "=f"(g[42]), "=f"(g[43]),
        "=f"(h[0]), "=f"(h[1]), "=f"(h[2]), "=f"(h[3]), "=f"(h[4]), "=f"(h[5]), "=f"(h[6]), "=f"(h[7]), "=f"(h[8]), "=f"(h[9]), "=f"(h[10]), "=f"(h[11]), "=f"(h[12]), "=f"(h[13]), "=f"(h[14]), "=f"(h[15]), "=f"(h[16]), "=f"(h[17]), "=f"(h[18]), "=f"(h[19]), "=f"(h[20]), "=f"(h[21]), "=f"(h[22]), "=f"(h[23]), "=f"(h[24]), "=f"(h[25]), "=f"(h[26]), "=f"(h[27]), "=f"(h[28]), "=f"(h[29]), "=f"(h[30]), "=f"(h[31]), "=f"(h[32]), "=f"(h[33]), "=f"(h[34]), "=f"(h[35]), "=f"(h[36]), "=f"(h[37]), "=f"(h[38]), "=f"(h[39]), "=f"(h[40]), "=f"(h[41]), "=f"(h[42]), "=f"(h[43])
      : "r"(w[0]), "r"(w[1]), "r"(w[2]), "r"(w[3]), "r"(w[4]), "r"(w[5]), "r"(w[6]), "r"(w[7]), "r"(w[8]), "r"(w[9]), "r"(w[10]), "r"(w[11]), "r"(w[12]), "r"(w[13]), "r"(w[14]), "r"(w[15]), "r"(w[20]), "r"(w[21]), "r"(w[22]), "r"(w[23]), "r"(w[24]), "r"(w[25]), "r"(w[26]), "r"(w[27]), "r"(w[28]), "r"(w[29]), "r"(w[30]), "r"(w[31]), "r"(w[32]), "r"(w[33]), "r"(w[34]), "r"(w[35]), "r"(w[36]), "r"(w[37]), "r"(w[38]), "r"(w[39]), "r"(dx), "l"(de), "l"(dh), "l"(dc)
      : "memory");
  }
  static __device__ __forceinline__ void wait_g(float* g) {
    asm volatile("wgmma.wait_group.sync.aligned 1;\n"
      : "+f"(g[0]), "+f"(g[1]), "+f"(g[2]), "+f"(g[3]), "+f"(g[4]), "+f"(g[5]), "+f"(g[6]), "+f"(g[7]), "+f"(g[8]), "+f"(g[9]), "+f"(g[10]), "+f"(g[11]), "+f"(g[12]), "+f"(g[13]), "+f"(g[14]), "+f"(g[15]), "+f"(g[16]), "+f"(g[17]), "+f"(g[18]), "+f"(g[19]), "+f"(g[20]), "+f"(g[21]), "+f"(g[22]), "+f"(g[23]), "+f"(g[24]), "+f"(g[25]), "+f"(g[26]), "+f"(g[27]), "+f"(g[28]), "+f"(g[29]), "+f"(g[30]), "+f"(g[31]), "+f"(g[32]), "+f"(g[33]), "+f"(g[34]), "+f"(g[35]), "+f"(g[36]), "+f"(g[37]), "+f"(g[38]), "+f"(g[39]), "+f"(g[40]), "+f"(g[41]), "+f"(g[42]), "+f"(g[43])
      :: "memory");
  }
  static __device__ __forceinline__ void wait_h(float* h) {
    asm volatile("wgmma.wait_group.sync.aligned 0;\n"
      : "+f"(h[0]), "+f"(h[1]), "+f"(h[2]), "+f"(h[3]), "+f"(h[4]), "+f"(h[5]), "+f"(h[6]), "+f"(h[7]), "+f"(h[8]), "+f"(h[9]), "+f"(h[10]), "+f"(h[11]), "+f"(h[12]), "+f"(h[13]), "+f"(h[14]), "+f"(h[15]), "+f"(h[16]), "+f"(h[17]), "+f"(h[18]), "+f"(h[19]), "+f"(h[20]), "+f"(h[21]), "+f"(h[22]), "+f"(h[23]), "+f"(h[24]), "+f"(h[25]), "+f"(h[26]), "+f"(h[27]), "+f"(h[28]), "+f"(h[29]), "+f"(h[30]), "+f"(h[31]), "+f"(h[32]), "+f"(h[33]), "+f"(h[34]), "+f"(h[35]), "+f"(h[36]), "+f"(h[37]), "+f"(h[38]), "+f"(h[39]), "+f"(h[40]), "+f"(h[41]), "+f"(h[42]), "+f"(h[43])
      :: "memory");
  }
};
__device__ __forceinline__ void node_mma(float* g, const uint32_t* w, uint64_t dx) {
    asm volatile(
      "{\n.reg .b64 dx1, dx2, dx3;\n"
      "add.s64 dx1, %48, 2;\nadd.s64 dx2, %48, 4;\nadd.s64 dx3, %48, 6;\n"
      "wgmma.fence.sync.aligned;\n"
      "wgmma.mma_async.sync.aligned.m64n64k16.f32.bf16.bf16 {%0, %1, %2, %3, %4, %5, %6, %7, %8, %9, %10, %11, %12, %13, %14, %15, %16, %17, %18, %19, %20, %21, %22, %23, %24, %25, %26, %27, %28, %29, %30, %31}, {%32, %33, %34, %35}, %48, 0, 1, 1, 0;\n"
      "wgmma.mma_async.sync.aligned.m64n64k16.f32.bf16.bf16 {%0, %1, %2, %3, %4, %5, %6, %7, %8, %9, %10, %11, %12, %13, %14, %15, %16, %17, %18, %19, %20, %21, %22, %23, %24, %25, %26, %27, %28, %29, %30, %31}, {%36, %37, %38, %39}, dx1, 1, 1, 1, 0;\n"
      "wgmma.mma_async.sync.aligned.m64n64k16.f32.bf16.bf16 {%0, %1, %2, %3, %4, %5, %6, %7, %8, %9, %10, %11, %12, %13, %14, %15, %16, %17, %18, %19, %20, %21, %22, %23, %24, %25, %26, %27, %28, %29, %30, %31}, {%40, %41, %42, %43}, dx2, 1, 1, 1, 0;\n"
      "wgmma.mma_async.sync.aligned.m64n64k16.f32.bf16.bf16 {%0, %1, %2, %3, %4, %5, %6, %7, %8, %9, %10, %11, %12, %13, %14, %15, %16, %17, %18, %19, %20, %21, %22, %23, %24, %25, %26, %27, %28, %29, %30, %31}, {%44, %45, %46, %47}, dx3, 1, 1, 1, 0;\n"
      "wgmma.commit_group.sync.aligned;\n}\n"
      : "=f"(g[0]), "=f"(g[1]), "=f"(g[2]), "=f"(g[3]), "=f"(g[4]), "=f"(g[5]), "=f"(g[6]), "=f"(g[7]), "=f"(g[8]), "=f"(g[9]), "=f"(g[10]), "=f"(g[11]), "=f"(g[12]), "=f"(g[13]), "=f"(g[14]), "=f"(g[15]), "=f"(g[16]), "=f"(g[17]), "=f"(g[18]), "=f"(g[19]), "=f"(g[20]), "=f"(g[21]), "=f"(g[22]), "=f"(g[23]), "=f"(g[24]), "=f"(g[25]), "=f"(g[26]), "=f"(g[27]), "=f"(g[28]), "=f"(g[29]), "=f"(g[30]), "=f"(g[31])
      : "r"(w[0]), "r"(w[1]), "r"(w[2]), "r"(w[3]), "r"(w[4]), "r"(w[5]), "r"(w[6]), "r"(w[7]), "r"(w[8]), "r"(w[9]), "r"(w[10]), "r"(w[11]), "r"(w[12]), "r"(w[13]), "r"(w[14]), "r"(w[15]), "l"(dx)
      : "memory");
}

__device__ __forceinline__ uint32_t smem_u32(const void* p) { return (uint32_t)__cvta_generic_to_shared(p); }
__device__ __forceinline__ float ex2f(float x) { float y; asm("ex2.approx.ftz.f32 %0, %1;" : "=f"(y) : "f"(x)); return y; }
__device__ __forceinline__ float rcpf(float x) { float y; asm("rcp.approx.ftz.f32 %0, %1;" : "=f"(y) : "f"(x)); return y; }
__device__ __forceinline__ uint32_t pack_bf16(float lo, float hi) {
    uint32_t r; asm("cvt.rn.bf16x2.f32 %0, %1, %2;" : "=r"(r) : "f"(hi), "f"(lo)); return r;
}
__device__ __forceinline__ float bf_lo(uint32_t v) { return __uint_as_float(v << 16); }
__device__ __forceinline__ float bf_hi(uint32_t v) { return __uint_as_float(v & 0xFFFF0000u); }
template<int STRIDE>
__device__ __forceinline__ void cp16i(uint32_t dst, const char* base, uint32_t idx) {
    asm volatile("{\n.reg .b64 a;\nmad.wide.u32 a, %2, %3, %1;\ncp.async.cg.shared.global [%0], [a], 16;\n}\n" :: "r"(dst), "l"(base), "r"(idx), "n"(STRIDE) : "memory");
}
__device__ __forceinline__ void cp16e(uint32_t dst, const char* base, uint32_t idx, uint64_t pol) {
    asm volatile("{\n.reg .b64 a;\nmad.wide.u32 a, %2, 32, %1;\ncp.async.cg.shared.global.L2::cache_hint [%0], [a], 16, %3;\n}\n" :: "r"(dst), "l"(base), "r"(idx), "l"(pol) : "memory");
}
template<int STRIDE>
__device__ __forceinline__ void cp16z(uint32_t dst, const char* base, uint32_t idx, int k, int n, uint64_t pol) {
    if (STRIDE == 32)
        asm volatile("{\n.reg .b64 a;\n.reg .pred p;\nsetp.ge.s32 p, %3, %4;\nmad.wide.u32 a, %2, 32, %1;\ncp.async.cg.shared.global.L2::cache_hint [%0], [a], 16, p, %5;\n}\n"
                     :: "r"(dst), "l"(base), "r"(idx), "r"(k), "r"(n), "l"(pol) : "memory");
    else
        asm volatile("{\n.reg .b64 a;\n.reg .pred p;\nsetp.ge.s32 p, %3, %4;\nmad.wide.u32 a, %2, 128, %1;\ncp.async.cg.shared.global [%0], [a], 16, p;\n}\n"
                     :: "r"(dst), "l"(base), "r"(idx), "r"(k), "r"(n) : "memory");
}
template<int HI, bool Z>
__device__ __forceinline__ void cpx(uint32_t hi, uint32_t dst, uint32_t p, uint32_t lo, int k, int n) {
    if (Z) asm volatile("{\n.reg .b32 l;\n.reg .b64 a;\n.reg .pred q;\nsetp.ge.s32 q, %5, %6;\ndp2a.lo.u32.u32 l, %1, %2, %3;\nmov.b64 a, {l, %0};\ncp.async.cg.shared.global [%4], [a], 16, q;\n}\n"
                        :: "r"(hi), "r"(p), "r"(HI ? 0x8000u : 0x80u), "r"(lo), "r"(dst), "r"(k), "r"(n) : "memory");
    else asm volatile("{\n.reg .b32 l;\n.reg .b64 a;\ndp2a.lo.u32.u32 l, %1, %2, %3;\nmov.b64 a, {l, %0};\ncp.async.cg.shared.global [%4], [a], 16;\n}\n"
                      :: "r"(hi), "r"(p), "r"(HI ? 0x8000u : 0x80u), "r"(lo), "r"(dst) : "memory");
}
template<bool Z>
__device__ __forceinline__ void cpe(uint32_t hi, uint32_t dst, uint32_t idx, uint32_t lo, int k, int n, uint64_t pol) {
    if (Z) asm volatile("{\n.reg .b32 l;\n.reg .b64 a;\n.reg .pred q;\nsetp.ge.s32 q, %5, %6;\nmad.lo.u32 l, %1, 32, %2;\nmov.b64 a, {l, %0};\ncp.async.cg.shared.global.L2::cache_hint [%3], [a], 16, q, %4;\n}\n"
                        :: "r"(hi), "r"(idx), "r"(lo), "r"(dst), "l"(pol), "r"(k), "r"(n) : "memory");
    else asm volatile("{\n.reg .b32 l;\n.reg .b64 a;\nmad.lo.u32 l, %1, 32, %2;\nmov.b64 a, {l, %0};\ncp.async.cg.shared.global.L2::cache_hint [%3], [a], 16, %4;\n}\n"
                      :: "r"(hi), "r"(idx), "r"(lo), "r"(dst), "l"(pol) : "memory");
}
__device__ __forceinline__ void cp_commit() { asm volatile("cp.async.commit_group;" ::: "memory"); }
template<int N> __device__ __forceinline__ void cp_wait() { asm volatile("cp.async.wait_group %0;" :: "n"(N) : "memory"); }
__device__ __forceinline__ void mbar_init(uint32_t bar, int cnt) { asm volatile("mbarrier.init.shared.b64 [%0], %1;" :: "r"(bar), "r"(cnt) : "memory"); }
__device__ __forceinline__ void mbar_arrive(uint32_t bar) { asm volatile("mbarrier.arrive.shared.b64 _, [%0];" :: "r"(bar) : "memory"); }
__device__ __forceinline__ void mbar_expect(uint32_t bar, uint32_t bytes) { asm volatile("mbarrier.arrive.expect_tx.shared.b64 _, [%0], %1;" :: "r"(bar), "r"(bytes) : "memory"); }
__device__ __forceinline__ void mbar_cp_arrive(uint32_t bar) { asm volatile("cp.async.mbarrier.arrive.noinc.shared.b64 [%0];" :: "r"(bar) : "memory"); }
__device__ __forceinline__ void mbar_wait(uint32_t bar, uint32_t parity) {
    asm volatile("{\n.reg .pred p;\n.reg .u32 n;\nmbarrier.try_wait.parity.shared.b64 p, [%0], %1;\n@p bra DONE_%=;\nmov.u32 n, 0;\n"
                 "WAIT_%=:\nmbarrier.try_wait.parity.shared.b64 p, [%0], %1, 0x100000;\n@p bra DONE_%=;\n"
                 "add.u32 n, n, 1;\nsetp.lt.u32 p, n, 0x400000;\n@p bra WAIT_%=;\ntrap;\nDONE_%=:\n}\n"
                 :: "r"(bar), "r"(parity) : "memory");
}
__device__ __forceinline__ void mbar_wait_s(uint32_t bar, uint32_t parity) {
    asm volatile("{\n.reg .pred p;\n.reg .u32 n;\nmov.u32 n, 0;\n"
                 "WAIT_%=:\nmbarrier.test_wait.parity.shared.b64 p, [%0], %1;\n@p bra DONE_%=;\n"
                 "add.u32 n, n, 1;\nsetp.lt.u32 p, n, 0x10000000;\n@p bra WAIT_%=;\ntrap;\nDONE_%=:\n}\n"
                 :: "r"(bar), "r"(parity) : "memory");
}
__device__ __forceinline__ void mbar_wait_c(uint32_t bar, uint32_t parity) {
    asm volatile("{\n.reg .pred p;\nWAIT_%=:\nmbarrier.try_wait.parity.shared.b64 p, [%0], %1;\n@p bra DONE_%=;\nbra WAIT_%=;\nDONE_%=:\n}\n"
                 :: "r"(bar), "r"(parity) : "memory");
}
__device__ __forceinline__ void mbar_wait_h(uint32_t bar, uint32_t parity) {
    asm volatile("{\n.reg .pred p;\nWAIT_%=:\nmbarrier.try_wait.parity.shared.b64 p, [%0], %1, 0x100000;\n@p bra DONE_%=;\nbra WAIT_%=;\nDONE_%=:\n}\n"
                 :: "r"(bar), "r"(parity) : "memory");
}
__device__ __forceinline__ uint32_t lds32(uint32_t a) { uint32_t v; asm volatile("ld.shared.u32 %0, [%1];" : "=r"(v) : "r"(a) : "memory"); return v; }
__device__ __forceinline__ void sts32(uint32_t a, uint32_t v) { asm volatile("st.shared.u32 [%0], %1;" :: "r"(a), "r"(v) : "memory"); }
__device__ __forceinline__ uint2 lds64(uint32_t a) { uint2 v; asm volatile("ld.shared.v2.u32 {%0,%1}, [%2];" : "=r"(v.x), "=r"(v.y) : "r"(a) : "memory"); return v; }
__device__ __forceinline__ uint4 lds128(uint32_t a) { uint4 v; asm volatile("ld.shared.v4.u32 {%0,%1,%2,%3}, [%4];" : "=r"(v.x), "=r"(v.y), "=r"(v.z), "=r"(v.w) : "r"(a) : "memory"); return v; }
__device__ __forceinline__ void sts128(uint32_t a, uint4 v) { asm volatile("st.shared.v4.u32 [%0], {%1,%2,%3,%4};" :: "r"(a), "r"(v.x), "r"(v.y), "r"(v.z), "r"(v.w) : "memory"); }
__device__ __forceinline__ void ldsm4t(uint32_t* v, uint32_t a) {
    asm volatile("ldmatrix.sync.aligned.m8n8.x4.trans.shared.b16 {%0,%1,%2,%3}, [%4];" : "=r"(v[0]), "=r"(v[1]), "=r"(v[2]), "=r"(v[3]) : "r"(a) : "memory");
}
__device__ __forceinline__ void stsm4t(uint32_t a, const uint32_t* v) {
    asm volatile("stmatrix.sync.aligned.m8n8.x4.trans.shared.b16 [%0], {%1,%2,%3,%4};" :: "r"(a), "r"(v[0]), "r"(v[1]), "r"(v[2]), "r"(v[3]) : "memory");
}
__device__ __forceinline__ int atoms_inc(uint32_t a) { int v; asm volatile("atom.shared.add.u32 %0, [%1], 1;" : "=r"(v) : "r"(a) : "memory"); return v; }
__device__ __forceinline__ bool elect_one() {
    uint32_t el;
    asm volatile("{\n.reg .pred p;\nelect.sync _|p, 0xffffffff;\nselp.u32 %0, 1, 0, p;\n}" : "=r"(el));
    return el != 0;
}
__device__ __forceinline__ float tanhf_a(float x) { float y; asm("tanh.approx.f32 %0, %1;" : "=f"(y) : "f"(x)); return y; }
__device__ __forceinline__ const char* as_pair(const void* p, uint32_t scratch) {
    const char* r;
    asm volatile("st.shared.u64 [%1], %2;\nld.volatile.shared.u64 %0, [%1];" : "=l"(r) : "r"(scratch), "l"(p) : "memory");
    return r;
}
__device__ __forceinline__ void ld_unit(uint4& v, const char* p, bool ok) {
    asm volatile("{\n.reg .pred q;\nsetp.ne.u32 q, %5, 0;\n@q ld.relaxed.gpu.global.v4.u32 {%0,%1,%2,%3}, [%4];\n}"
                 : "+r"(v.x), "+r"(v.y), "+r"(v.z), "+r"(v.w) : "l"(p), "r"((uint32_t)ok) : "memory");
}
__device__ __forceinline__ void ld_unit(uint2& v, const char* p, bool ok) {
    asm volatile("{\n.reg .pred q;\nsetp.ne.u32 q, %3, 0;\n@q ld.relaxed.gpu.global.v2.u32 {%0,%1}, [%2];\n}"
                 : "+r"(v.x), "+r"(v.y) : "l"(p), "r"((uint32_t)ok) : "memory");
}
__device__ __forceinline__ void bulk_ld(uint32_t dst, const void* src, int bytes, uint32_t bar) {
    mbar_expect(bar, bytes);
    if (bytes > 0) asm volatile("cp.async.bulk.shared::cluster.global.mbarrier::complete_tx::bytes [%0], [%1], %2, [%3];" :: "r"(dst), "l"(src), "r"(bytes), "r"(bar) : "memory");
}
#define ELECT "{\n.reg .pred p;\nelect.sync _|p, 0xffffffff;\n@p "
__device__ __forceinline__ void w_init(uint32_t bar, int n) { asm volatile(ELECT "mbarrier.init.shared.b64 [%0], %1;\n}" :: "r"(bar), "r"(n) : "memory"); }
__device__ __forceinline__ void w_expect(uint32_t bar, uint32_t bytes) { asm volatile(ELECT "mbarrier.arrive.expect_tx.shared.b64 _, [%0], %1;\n}" :: "r"(bar), "r"(bytes) : "memory"); }
__device__ __forceinline__ void w_ld(uint32_t dst, const void* src, int bytes, uint32_t bar) {
    asm volatile(ELECT "cp.async.bulk.shared::cluster.global.mbarrier::complete_tx::bytes [%0], [%1], %2, [%3];\n}" :: "r"(dst), "l"(src), "r"(bytes), "r"(bar) : "memory");
}
__device__ __forceinline__ void w_box_ld(uint32_t dst, const CUtensorMap* tm, int row, uint32_t bar) {
    asm volatile(ELECT "cp.async.bulk.tensor.2d.shared::cluster.global.mbarrier::complete_tx::bytes [%0], [%1, {%3, %4}], [%2];\n}"
        :: "r"(dst), "l"((uint64_t)tm), "r"(bar), "r"(0), "r"(row) : "memory");
}
__device__ __forceinline__ void w_st(void* dst, uint32_t src, int bytes) {
    asm volatile(ELECT "cp.async.bulk.global.shared::cta.bulk_group [%0], [%1], %2;\n}" :: "l"(dst), "r"(src), "r"(bytes) : "memory");
}
__device__ __forceinline__ void w_box_st(const CUtensorMap* tm, int col, uint32_t src) {
    asm volatile(ELECT "cp.async.bulk.tensor.2d.global.shared::cta.bulk_group [%0, {%2, %3}], [%1];\n}" :: "l"((uint64_t)tm), "r"(src), "r"(col), "r"(0) : "memory");
}
__device__ __forceinline__ void w_sent(unsigned* p, uint32_t src) {
    asm volatile(ELECT "cp.reduce.async.bulk.global.shared::cta.bulk_group.add.u32 [%0], [%1], 16;\n}" :: "l"(p), "r"(src) : "memory");
}
__device__ __forceinline__ void w_inc(unsigned* p) { asm volatile(ELECT "red.relaxed.gpu.global.add.u32 [%0], 1;\n}" :: "l"(p) : "memory"); }
__device__ __forceinline__ void w_hint(unsigned* p, uint32_t all) {
    #pragma unroll 1
    for (int i = 0; i < 4096; i++) {
        uint32_t v; asm volatile("ld.relaxed.gpu.global.u32 %0, [%1];" : "=r"(v) : "l"(p) : "memory");
        if (__all_sync(~0u, (int)(v - all) >= 0)) break;
    }
}

__device__ __forceinline__ void finish(uint4& a, const uint4& xu, const uint4& xv) {
    asm("{\n.reg .b32 z;\nfma.rn.relu.bf16x2 z, %0, %3, %1;\nadd.rn.bf16x2 %0, z, %2;\n}" : "+r"(a.x) : "r"(xu.x), "r"(xv.x), "r"(0x3F803F80u));
    asm("{\n.reg .b32 z;\nfma.rn.relu.bf16x2 z, %0, %3, %1;\nadd.rn.bf16x2 %0, z, %2;\n}" : "+r"(a.y) : "r"(xu.y), "r"(xv.y), "r"(0x3F803F80u));
    asm("{\n.reg .b32 z;\nfma.rn.relu.bf16x2 z, %0, %3, %1;\nadd.rn.bf16x2 %0, z, %2;\n}" : "+r"(a.z) : "r"(xu.z), "r"(xv.z), "r"(0x3F803F80u));
    asm("{\n.reg .b32 z;\nfma.rn.relu.bf16x2 z, %0, %3, %1;\nadd.rn.bf16x2 %0, z, %2;\n}" : "+r"(a.w) : "r"(xu.w), "r"(xv.w), "r"(0x3F803F80u));
}

constexpr float EPS2 = 2e-6f;
constexpr float TAU = 2.5e-5f;

constexpr uint32_t TAU_BITS = 0x3A103000u;
template<int NP>
__device__ __forceinline__ void epi_fast(const float* g, const float* h, float m2,
                                         float& n0, float& d0, float& n1, float& d1, float& dmin)
{
    constexpr int JC = NP >= 6 ? NP - 1 - 2 : NP >= 4 ? NP - 2 : NP - 1;
    constexpr int JT = NP < 3 ? -1 : JC < NP - 1 ? JC : NP - 2;
    #pragma unroll
    for (int j = 0; j < NP; j++) {
        float t0 = tanhf_a(g[4*j+0]), t1 = tanhf_a(g[4*j+1]), t2 = tanhf_a(g[4*j+2]), t3 = tanhf_a(g[4*j+3]);
        auto add_d = [&]() {
            if (j == 0) { d0 = t0 + (2.f * (JT + 1) + EPS2); d1 = t2 + (2.f * (JT + 1) + EPS2); } else { d0 += t0; d1 += t2; }
            d0 += t1; d1 += t3;
        };
        if (j <= JT) add_d();
        if (UFORM && j <= JT) {
            const float u0 = fmaf(t0, h[4*j], h[4*j]), u1 = fmaf(t1, h[4*j+1], h[4*j+1]), u2 = fmaf(t2, h[4*j+2], h[4*j+2]), u3 = fmaf(t3, h[4*j+3], h[4*j+3]);
            if (j == 0) { n0 = u0 + u1; n1 = u2 + u3; } else { n0 += u0; n1 += u2; n0 += u1; n1 += u3; }
            if (j == JC) dmin = fminf(d0, d1);
            continue;
        }
        if (j == NP - 1) { t0 += 1.f; t1 = fmaf(t1, m2, m2); t2 += 1.f; t3 = fmaf(t3, m2, m2); }
        else { t0 += 1.f; t1 += 1.f; t2 += 1.f; t3 += 1.f; }
        if (j > JT) add_d();
        if (j == 0) { n0 = t0 * h[0]; n1 = t2 * h[2]; } else { n0 = fmaf(t0, h[4*j], n0); n1 = fmaf(t2, h[4*j+2], n1); }
        n0 = fmaf(t1, h[4*j+1], n0); n1 = fmaf(t3, h[4*j+3], n1);
        if (j == JC) dmin = fminf(d0, d1);
    }
}

__device__ __noinline__ void slow_bin(const __nv_bfloat16* x, const __nv_bfloat16* ea, const int* src, const int* dst,
                                      const __nv_bfloat16* wa, const __nv_bfloat16* wb, const __nv_bfloat16* wc,
                                      const __nv_bfloat16* wu, const __nv_bfloat16* wv, __nv_bfloat16* out,
                                      int E, int node0, int nn, int nthr)
{
    const int tid = threadIdx.x, lane = tid & 31;
    for (int i = tid; i < nn * 128; i += nthr) g_slow[(size_t)node0 * 128 + i] = 0.f;
    asm volatile("bar.sync 1, %0;" :: "r"(nthr) : "memory");
    for (int e0 = (tid >> 5) * 32; e0 < E; e0 += nthr) {
        int d = (e0 + lane < E) ? dst[e0 + lane] - node0 : -1;
        unsigned m = __ballot_sync(~0u, d >= 0 && d < nn);
        while (m) {
            int l = __ffs(m) - 1; m &= m - 1;
            int e = e0 + l, n = node0 + __shfl_sync(~0u, d, l), s = src[e];
            float g0 = 0, g1 = 0, h0 = 0, h1 = 0;
            for (int k = 0; k < 64; k++) {
                float xs = __bfloat162float(x[(size_t)s * 64 + k]), xd = __bfloat162float(x[(size_t)n * 64 + k]);
                uint32_t b2 = *(const uint32_t*)(wb + k * 64 + 2 * lane), v2 = *(const uint32_t*)(wv + k * 64 + 2 * lane);
                uint32_t a2 = *(const uint32_t*)(wa + k * 64 + 2 * lane);
                g0 = fmaf(xs, bf_lo(b2), fmaf(xd, bf_lo(a2), g0)); g1 = fmaf(xs, bf_hi(b2), fmaf(xd, bf_hi(a2), g1));
                h0 = fmaf(xs, bf_lo(v2), h0); h1 = fmaf(xs, bf_hi(v2), h1);
            }
            for (int k = 0; k < 16; k++) {
                float ev = __bfloat162float(ea[(size_t)e * 16 + k]);
                uint32_t c2 = *(const uint32_t*)(wc + k * 64 + 2 * lane);
                g0 = fmaf(ev, bf_lo(c2), g0); g1 = fmaf(ev, bf_hi(c2), g1);
            }
            float s0 = rcpf(1.f + ex2f(-LOG2E * g0)), s1 = rcpf(1.f + ex2f(-LOG2E * g1));
            float* acc = g_slow + (size_t)n * 128 + 4 * lane;
            atomicAdd(acc + 0, s0 * h0); atomicAdd(acc + 1, s0);
            atomicAdd(acc + 2, s1 * h1); atomicAdd(acc + 3, s1);
        }
    }
    __threadfence();
    asm volatile("bar.sync 1, %0;" :: "r"(nthr) : "memory");
    for (int i = tid; i < nn * 32; i += nthr) {
        int n = node0 + (i >> 5), cp = i & 31;
        float4 a = __ldcg((const float4*)(g_slow + (size_t)n * 128 + 4 * cp));
        float u0 = 0, u1 = 0;
        for (int k = 0; k < 64; k++) {
            float xd = __bfloat162float(x[(size_t)n * 64 + k]);
            uint32_t w2 = *(const uint32_t*)(wu + k * 64 + 2 * cp);
            u0 = fmaf(xd, bf_lo(w2), u0); u1 = fmaf(xd, bf_hi(w2), u1);
        }
        uint32_t xv = *(const uint32_t*)(x + (size_t)n * 64 + 2 * cp);
        float z0 = u0 + a.x / (a.y + 1e-6f), z1 = u1 + a.z / (a.w + 1e-6f);
        *(uint32_t*)(out + (size_t)n * 64 + 2 * cp) = pack_bf16(bf_lo(xv) + fmaxf(z0, 0.f), bf_hi(xv) + fmaxf(z1, 0.f));
    }
}

__global__ void __launch_bounds__(256) slow_kernel(const __nv_bfloat16* x, const __nv_bfloat16* ea, const int* src, const int* dst,
        const __nv_bfloat16* wa, const __nv_bfloat16* wb, const __nv_bfloat16* wc, const __nv_bfloat16* wu, const __nv_bfloat16* wv,
        __nv_bfloat16* out, int N, int E, int npb)
{
    int node0 = blockIdx.x * npb;
    slow_bin(x, ea, src, dst, wa, wb, wc, wu, wv, out, E, node0, max(0, min(npb, N - node0)), 256);
}

constexpr int XS_BYTES = NPMAX * 1024;
constexpr int ES_BYTES = NPMAX * 256;
constexpr int SM_XS = 0;
constexpr int SM_XU = SM_XS + 3 * NSTAGE * XS_BYTES;
constexpr int SM_TAB = SM_XU + NPB_MAX * 128;
constexpr int SM_ES = SM_TAB + NPB_MAX * 128;
constexpr int SM_WC = SM_ES + 3 * NSTAGE * ES_BYTES;
constexpr int SM_OH = SM_WC + 2048;
constexpr int SM_EID = SM_OH + 128;
constexpr int SM_SRC = SM_EID + SLOT_CAP * 4;
constexpr int SM_TINFO = SM_SRC + SLOT_CAP * 2;
constexpr int SM_MISC = SM_TINFO + TILE_CAP * 32;
constexpr int SM_CLAIM = SM_MISC + 32 * 4;
constexpr int STG = 272;
constexpr int SM_BARS = SM_CLAIM + 32 * 4;
constexpr int SM_ABAR = SM_BARS + 6 * STG;
constexpr int SM_GBAR = SM_ABAR + 16 * 8;
constexpr int SMEM_BYTES = SM_GBAR + 97 * 8;
constexpr int SM_P2 = 0, SM_P1 = P2B + 256;
constexpr int SM_L1 = SM_P1 + P1B + 128;
constexpr int SM_DEG = SM_L1 + 256;
constexpr int SM_CLS = SM_DEG + 512 * 4;
constexpr int SM_HIST = SM_CLS + NCLS * 4;
constexpr int SM_XLIST = SM_HIST + NB_MAX * 4;
constexpr int SM_SORT = SM_XLIST + 8;
constexpr int SM_SDEG = SM_SORT + NPB_MAX * 4;
constexpr int SM_PAIR = SM_SDEG + NPB_MAX * 2;
constexpr int SM_ENT = SM_ES + 1024;
constexpr int SM_H1 = SM_P1 + HB, SM_H2 = SM_P1;
constexpr int SM_IDX = SM_EID;
constexpr int SM_WR = SM_TAB;
static_assert(TILE_CAP <= 128 && TR >= 2 && SM_ES % 256 == 0 && NSTAGE == 2 && SM_BARS % 16 == 0 && SM_TINFO % 16 == 0 && SM_EID % 128 == 0 && SM_TAB % 1024 == 0 && SM_XU % 1024 == 0 && SM_TINFO % 8 == 0 && SM_OH % 16 == 0 && SM_XLIST % 8 == 0 && SM_PAIR % 8 == 0, "align");
static_assert(SM_P1 % 128 == 0 && P1B + HB <= SM_SRC - SM_EID && 2 * HB <= P1B && SM_H1 + 5 * 128 * 16 <= SM_XU && NB_MAX * (CE / 4) <= 6 * 384 && NB_MAX * 4 <= 5 * 128 && NB_MIN * 4 >= 3 * 128 && SM_PAIR + 128 * 8 <= SM_XU && CH_MAX * 4 <= SM_SRC - SM_EID && SM_DEG >= 3 << 14, "alias");
static_assert(CE == 64 && SMEM_BYTES <= 232448, "smem");
constexpr uint32_t C_BRK = 16  , C_CONT = 32, C_MORE = 64;
constexpr uint32_t ONE_F = 0x3F800000u;
constexpr int NONE = NPB_MAX - 1;
__host__ __device__ constexpr uint32_t tab_at(uint32_t n) { return (n >> 2) * 512 + (n & 3) * 32 + ((n >> 2) & 1) * 16; }

__device__ __forceinline__ uint32_t unpad(uint32_t w1, int np, float ga, float gb, float& d0, float& d1, int& dv) {
    const int pad = (w1 >> 8) & 31;
    dv = 2 * np - 1 - pad + (w1 >= ONE_F);
    float t0 = TAU * 2 * np, t1 = t0;
    if (pad) {
        t0 = fmaxf(t0, d0 * (1.f / 1024)); t1 = fmaxf(t1, d1 * (1.f / 1024));
        asm volatile("tanh.approx.f32 %0, %0;\ntanh.approx.f32 %1, %1;" : "+f"(ga), "+f"(gb));
        d0 -= pad * (1.f + ga); d1 -= pad * (1.f + gb);
    }
    if (dv == 0) { d0 = d1 = EPS2; t0 = t1 = 0.f; }
    return __ballot_sync(~0u, d0 < t0 || d1 < t1);
}
__device__ __noinline__ float4* exact_copy(uint32_t bad, float4* own)
{
    extern __shared__ __align__(1024) uint8_t smem[];
    uint32_t old = 1;
    if (bad == 1u << (threadIdx.x & 31)) old = atomicExch((uint32_t*)(smem + SM_MISC + 12), 1u);
    if (__all_sync(~0u, old)) return own;
    return old ? nullptr : (float4*)(smem + SM_XU + tab_at(NPB_MAX - 4) - 16);
}
__device__ __noinline__ float4 epi_exact(const float4* gh, int np, int dv)
{
    extern __shared__ __align__(1024) uint8_t smem[];
    float n0 = 0.f, d0 = 0.f, n1 = 0.f, d1 = 0.f;
    int j = 0, je = np;
    const uint32_t own = __ballot_sync(~0u, gh != nullptr);
    if (own != ~0u) {
        dv = __shfl_sync(~0u, dv, __ffs(own) - 1); j = min(threadIdx.x & 15, np); je = j + 1;
        gh = (const float4*)(smem + SM_XU + tab_at(NPB_MAX - 4) - 16);
        __syncwarp();
    }
    #pragma unroll 1
    for (; j < je; j++) {
        const float4 g = gh[j], h = gh[NPMAX + j];
        const bool ma = 2 * j < dv, mb = 2 * j + 1 < dv;
        const float e0 = 2.f * rcpf(1.f + ex2f(-2.f * LOG2E * g.x)), e1 = 2.f * rcpf(1.f + ex2f(-2.f * LOG2E * g.y));
        const float e2 = 2.f * rcpf(1.f + ex2f(-2.f * LOG2E * g.z)), e3 = 2.f * rcpf(1.f + ex2f(-2.f * LOG2E * g.w));
        if (ma) { d0 += e0; n0 = fmaf(e0, h.x, n0); d1 += e2; n1 = fmaf(e2, h.z, n1); }
        if (mb) { d0 += e1; n0 = fmaf(e1, h.y, n0); d1 += e3; n1 = fmaf(e3, h.w, n1); }
    }
    if (own != ~0u) {
        #pragma unroll
        for (int o = 1; o < 16; o <<= 1) {
            n0 += __shfl_xor_sync(~0u, n0, o); d0 += __shfl_xor_sync(~0u, d0, o);
            n1 += __shfl_xor_sync(~0u, n1, o); d1 += __shfl_xor_sync(~0u, d1, o);
        }
        *(volatile uint32_t*)(smem + SM_MISC + 12) = 0;
    }
    return make_float4(n0, d0 + EPS2, n1, d1 + EPS2);
}
template<int NP>
__device__ __forceinline__ void epi_dump(const float* g, const float* h, float4* gh) {
    #pragma unroll
    for (int i = 0; i < 2 * NP; i++) {
        const float* v = i < NP ? g + 4 * i : h + 4 * (i - NP);
        asm volatile("{\n.reg .pred p;\nsetp.ne.u64 p, %5, 0;\n@p st.v4.f32 [%0], {%1,%2,%3,%4};\n}"
                     :: "l"((uint64_t)gh + (i < NP ? i : NPMAX + i - NP) * 16), "f"(v[0]), "f"(v[1]), "f"(v[2]), "f"(v[3]), "l"(gh) : "memory");
    }
}
__device__ __forceinline__ uint32_t bin_bits(uint32_t b) { return (1u << (b & 7)) | ((b < 48 ? 0x100u : 0x400u) << (b >> 3)); }
__device__ __forceinline__ void place(uint32_t sbase, uint32_t slot, uint32_t v, uint32_t eb) {
    asm volatile("{\n.reg .pred p;\nsetp.lt.u32 p, %0, %5;\n@p st.shared.u32 [%1], %2;\n@p st.shared.u16 [%3], %4;\n}"
                 :: "r"(slot), "r"(sbase + SM_EID + slot * 4), "r"(eb + (v >> 19)), "r"(sbase + SM_SRC + slot * 2), "r"(v), "n"(SLOT_CAP) : "memory");
}
__device__ __forceinline__ uint64_t desc_sw128(uint32_t a) {
    return (uint64_t)((a & 0x3FFFF) >> 4) | ((uint64_t)1 << 16) | ((uint64_t)64 << 32) | ((uint64_t)1 << 62);
}

template<bool LO32>
__global__ void __launch_bounds__(THREADS, 1)
gcn_kernel(const int* __restrict__ dst, unsigned* gbar, char* gs, const int* __restrict__ src, int E, int ch, int N, int npb, uint32_t magic,
           const __nv_bfloat16* __restrict__ x, const __nv_bfloat16* __restrict__ ea,
           const __nv_bfloat16* __restrict__ wa, const __nv_bfloat16* __restrict__ wb, const __nv_bfloat16* __restrict__ wc,
           const __nv_bfloat16* __restrict__ wu, const __nv_bfloat16* __restrict__ wv,
           __nv_bfloat16* out, int4 wrow, const __grid_constant__ CUtensorMap tm1, const __grid_constant__ CUtensorMap tm2,
           const __grid_constant__ CUtensorMap tmw, const __grid_constant__ CUtensorMap tmx)
{
    extern __shared__ __align__(1024) uint8_t smem[];
    int* cls = (int*)(smem + SM_CLS);
    int* misc = (int*)(smem + SM_MISC);
    WG0(); WS(0); CG(0);
    const uint32_t sbase = smem_u32(smem);
    const int tid = threadIdx.x, lane = tid & 31;
    const int b = blockIdx.x, nb = gridDim.x;
    const int cnt = max(0, min(ch, E - b * ch));
    const int node0 = b * npb;
    uint32_t tag = 0, cstart; asm volatile("mov.u32 %0, %%clock;" : "=r"(cstart));
    const int warp = (int)__reduce_max_sync(~0u, (unsigned)tid >> 5);
    const uint32_t su = __reduce_or_sync(~0u, sbase);
    auto weights = [&]() {
        w_box_ld(su + SM_WR, &tmw, wrow.x, su + SM_ABAR + 24); w_box_ld(su + SM_WR + 8192, &tmw, wrow.y, su + SM_ABAR + 24);
        w_box_ld(su + SM_WR + 16384, &tmw, wrow.z, su + SM_ABAR + 24); w_ld(su + SM_WR + 24576, wc, 2048, su + SM_ABAR + 24);
        w_box_ld(su + SM_WR + 40960, &tmw, wrow.w, su + SM_ABAR + 24);
    };
    if (warp >= 12) {
        const int v = warp & 3;
        const uint32_t a1 = su + SM_ABAR + (v == 0 ? 80 : v == 1 ? 120 : v == 2 ? 32 : 40);
        w_init(su + SM_ABAR + v * 8, 1); w_init(a1, 1);
        w_expect(su + SM_ABAR + v * 8, v < 3 ? min(max(cnt * 4 - v * 8192, 0), 8192) : 4 * 8192 + 2048);
        if (P1S) { if (v < 3) w_expect(a1, v == 0 ? 3 * 384 * 8 : v == 1 ? nb * 64 : nb * (CE * 2) - 3 * 384 * 8); }
        else if (v < 2) w_expect(a1, v == 0 ? nb * (CE * 2) : nb * 64);
        asm volatile("fence.mbarrier_init.release.cluster;" ::: "memory");
    }
    asm volatile("{\n.reg .pred q;\nsetp.lt.u32 q, %2, 384;\n@q ld.relaxed.gpu.global.u32 %0, [%1];\n}" : "+r"(tag) : "l"(gbar), "r"(tid));
    #pragma unroll
    for (int v = 0; v < EPT / 4; v++) {
        const uint32_t off = v * (THREADS * 4) + tid * 4;
        if (PD && v) { uint32_t c0, c1; asm volatile("mov.u32 %0, %%clock;" : "=r"(c0)); do { asm volatile("mov.u32 %0, %%clock;" : "=r"(c1)); } while (__all_sync(~0u, c1 - c0 < PD)); }
        asm volatile("{\n.reg .pred q;\nsetp.lt.u32 q, %2, %3;\n@q cp.async.cg.shared.global [%0], [%1], 16;\n}"
                     :: "r"(sbase + SM_IDX + off * 4), "l"(dst + b * ch + off), "r"(off), "r"(cnt) : "memory");
        cp_commit();
        if (WV == 7 + v && warp == 15) weights();
    }
    const int wg = warp >> 2, w = warp & 3;
    const int q = lane >> 2, t = lane & 3;
    const int nn = max(0, min(npb, N - node0));
    if (sbase & 1023) __trap();

    sts32(sbase + SM_DEG + tid * 4, tid < NPB_MAX ? 0 : 0x80000000u);
    if (tid < NCLS + NB_MAX) cls[tid] = tid < NCLS ? 0 : ((tid - NCLS) * 20) & 63;
    else if (warp == 8) sts32(sbase + SM_OH + lane * 4, t != (q >> 1) ? 0u : 0x00003F00u);
    else if (warp == 11) misc[lane] = lane == 5 ? TILE_CAP - TILE_X : lane == 8 || lane == 3;
    if (warp == 14) sts32(sbase + SM_TINFO + 96 * 32 + lane * 4, lane & 1 ? tab_at(NONE) : 0);
    if (warp == 15) sts32(sbase + SM_CLAIM + lane * 4, lane == 0 ? 3 * 32 : 0x40000000);
    if (tid == 0) sts32(sbase + SM_XLIST, tag);
    tag = (tag & 1) | 2;
    if (wg < 3) {
        const uint32_t d0 = ((NPB_MAX + ((2 * lane) & 15) + 16 * (b & 1)) * 4 | (tag << 14)) * 0x10001u, d1 = d0 + 0x40004u, d2 = tag << 16;
        #pragma unroll 1
        for (int i = tid; i < (P1B + 384) / 16; i += 384) {
            sts128(sbase + SM_P1 + i * 16, make_uint4(d0, d0, d1, i == P1B / 16 + 11 ? 0x80000000u | (tag << 14) : d1));
            sts128(sbase + SM_P2 + i * 16, make_uint4(d2, d2, d2, d2)); sts128(sbase + SM_P2 + P1B - 128 + i * 16, make_uint4(d2, d2, d2, d2));
        }
    }
    WS(1);
    __syncthreads();
    if (wg == 3) tag = lds32(sbase + SM_P2) >> 16;
    uint32_t all = 0;
    if (wg == 3) all = (lds32(sbase + SM_XLIST) + 1) * nb;
    if (tid == 128) {
        asm volatile("prefetch.tensormap [%0];" :: "l"((uint64_t)&tmw) : "memory");
        asm volatile("prefetch.tensormap [%0];" :: "l"((uint64_t)&tm1) : "memory");
        asm volatile("prefetch.tensormap [%0];" :: "l"((uint64_t)&tm2) : "memory");
        asm volatile("prefetch.tensormap [%0];" :: "l"((uint64_t)&tmx) : "memory");
    }
    if (WPF && warp == 9 && b < 5) asm volatile(ELECT "cp.async.bulk.prefetch.L2.global [%0], %1;\n}" :: "l"(b == 0 ? wa : b == 1 ? wb : b == 2 ? wu : b == 3 ? wv : wc), "r"(b < 4 ? 8192 : 2048) : "memory");
    const uint32_t m4 = __reduce_or_sync(~0u, -4 * npb);
    uint32_t ent[EPT];
    #pragma unroll
    for (int v = 0; v < EPT / 4; v++) {
        if (v == 0) cp_wait<2>(); else if (v == 1) cp_wait<1>(); else cp_wait<0>();
        if (v == SRCV && wg == 2 && w < 3) {
            const int n = min(cnt * 4 - w * 8192, 8192);
            if (n > 0) w_ld(su + SM_XU + w * 8192, src + b * ch + w * 2048, n, su + SM_ABAR + w * 8);
        }
        if (v == WV) {
            if (warp == 11) w_ld(su + SM_WR + 24576, wc, 2048, su + SM_ABAR + 24);
            else if (wg == 3) w_box_ld(su + SM_WR + (w == 3 ? 5 : w) * 8192, &tmw, w == 0 ? wrow.x : w == 1 ? wrow.y : w == 2 ? wrow.z : wrow.w, su + SM_ABAR + 24);
        }
        const uint32_t off = v * (THREADS * 4) + tid * 4;
        if (off < (uint32_t)cnt) {
            const uint4 u = lds128(sbase + SM_IDX + off * 4);
            uint32_t dv[4] = {u.x, u.y, u.z, u.w}, ps[4], ck[4];
            uint32_t* en = ent + 4 * v;
            #pragma unroll
            for (int k = 0; k < 4; k++) {
                dv[k] = min(dv[k], (uint32_t)(nb * npb - 1));
                ps[k] = __umulhi(dv[k], magic);
                asm volatile("atom.shared.add.u32 %0, [%1], 0x10001;" : "=r"(ck[k]) : "r"(sbase + SM_HIST + ps[k] * 4) : "memory");
            }
            #pragma unroll
            for (int k = 0; k < 4; k++) {
                dv[k] = ps[k] * m4 + (dv[k] * 4 + (tag << 14));
                en[k] = (ck[k] & 63) + ps[k] * CE;
            }
            if (__builtin_expect(max(max(ck[0], ck[1]), max(ck[2], ck[3])) >= CE << 16, 0)) {
                auto step = [&]() {
                    uint32_t e = en[0];
                    const uint32_t d = dv[0];
                    if (ck[0] >= CE << 16) {
                        uint32_t j; asm volatile("atom.shared.inc.u32 %0, [%1], 0x7fffffff;" : "=r"(j) : "r"(sbase + SM_MISC + 8) : "memory");
                        j = min(j + (j >= 15), 63u);
                        sts32(sbase + SM_L1 + j * 4, d | ((j < 63 ? e / CE : 255u) << 16));
                        e = NB_MAX * CE + j;
                    }
                    en[0] = en[1]; en[1] = en[2]; en[2] = en[3]; en[3] = e;
                    dv[0] = dv[1]; dv[1] = dv[2]; dv[2] = dv[3]; dv[3] = d;
                    ck[0] = ck[1]; ck[1] = ck[2]; ck[2] = ck[3];
                };
                if (v == 2 && OVU) { step(); step(); step(); step(); }
                else {
                    #pragma unroll 1
                    for (int k = 0; k < 4; k++) step();
                }
            }
            #pragma unroll
            for (int k = 0; k < 4; k++)
                asm volatile("st.shared.u16 [%0], %1;" :: "r"(sbase + SM_P1 + en[k] * 2), "r"(dv[k]) : "memory");
        }
    }
    if (warp == 15) {
        #pragma unroll
        for (int v = 0; v < EPT / 4; v++) sts128(sbase + SM_ENT + v * 512 + lane * 16, make_uint4(ent[4*v], ent[4*v+1], ent[4*v+2], ent[4*v+3]));
    }
    asm volatile("fence.proxy.async.shared::cta;" ::: "memory");
    WS(5);
    __syncthreads();
    auto delay = [&](uint32_t d) { uint32_t c0, c1; asm volatile("mov.u32 %0, %%clock;" : "=r"(c0)); do { asm volatile("mov.u32 %0, %%clock;" : "=r"(c1)); } while (__all_sync(~0u, c1 - c0 < d)); };
    if (warp == 15) {
        if (HORD != 2) w_inc(gbar + HI1);
        if (!HSF) w_box_st(&tm1, b * (CE / 2), su + SM_P1);
        const uint32_t n = __reduce_or_sync(~0u, lds32(su + SM_MISC + 8));
        if (__builtin_expect(n > 15, 0)) {
            const uint2 r = lds64(su + SM_L1 + lane * 8);
            uint32_t m = lane < 8 ? 0 : (r.x >> 24 ? 0 : bin_bits(r.x >> 16)) | (r.y >> 24 ? 0 : bin_bits(r.y >> 16));
            m = n > 62 ? 0x7FFF3FFFu : __reduce_or_sync(~0u, m);
            sts32(su + SM_L1 + 60, m | 0x80000000u | (tag << 14));
            asm volatile("fence.proxy.async.shared::cta;" ::: "memory");
            __syncwarp();
        }
        w_st(gs + G_H1 + b * 64, su + SM_L1, 64);
        if (HSF) w_box_st(&tm1, b * (CE / 2), su + SM_P1);
        w_st(gs + G_L + b * 512, su + SM_L1, 256);
        asm volatile("cp.async.bulk.commit_group;" ::: "memory");
        if (WV == 3) {
            w_box_ld(su + SM_WR, &tmw, wrow.x, su + SM_ABAR + 24); w_box_ld(su + SM_WR + 8192, &tmw, wrow.y, su + SM_ABAR + 24);
            w_box_ld(su + SM_WR + 16384, &tmw, wrow.z, su + SM_ABAR + 24); w_ld(su + SM_WR + 24576, wc, 2048, su + SM_ABAR + 24);
            w_box_ld(su + SM_WR + 40960, &tmw, wrow.w, su + SM_ABAR + 24);
        }
    } else {
        mbar_wait_c(su + SM_ABAR, 0);
        auto put = [&](uint32_t off, const uint32_t* uu) {
            if (off < (uint32_t)cnt) {
                const uint4 sv = lds128(sbase + SM_XU + off * 4);
                const uint32_t ss[4] = {sv.x, sv.y, sv.z, sv.w};
                #pragma unroll
                for (int k = 0; k < 4; k++) sts32(sbase + SM_P2 + uu[k] * 4, (ss[k] & 0xFFFF) | (((off + k) << 19) + (tag << 16)));
            }
        };
        #pragma unroll
        for (int v = 0; v < EPT / 4; v++) { if (v) mbar_wait_c(su + SM_ABAR + v * 8, 0); put(v * (THREADS * 4) + tid * 4, ent + 4 * v); }
        if (wg == 3) {
            const uint4 e = lds128(sbase + SM_ENT + w * 512 + lane * 16);
            const uint32_t uu[4] = {e.x, e.y, e.z, e.w};
            put(w * (THREADS * 4) + (480 + lane) * 4, uu);
        }
        asm volatile("fence.proxy.async.shared::cta;" ::: "memory");
        WS(7);
        __syncwarp();
        asm volatile("bar.arrive 12, 512;" ::: "memory");
    }
    WS(8);

    const int ngroups = (nn + 3) >> 2;
    if (warp < 12) {
        asm volatile("setmaxnreg.inc.sync.aligned.u32 152;");
        const uint32_t ab = su + SM_ABAR;
        uint32_t wf[40], wn[16];
        const uint32_t mo = sbase + (8 * (lane >> 4) + (lane & 7)) * 128 + (((2 * w + ((lane >> 3) & 1)) ^ (lane & 7)) << 4);
        const uint32_t wca = __shfl_sync(~0u, sbase + SM_WC + (16 * w + q) * 32 + t * 4 + ((q >> 2) << 4), lane), l16 = __shfl_sync(~0u, (lane & 15) * 16, lane);
        WS(1);
        BW(ab + 24, 0);
        WS(5);
        {
            #pragma unroll
            for (int ks = 0; ks < 4; ks++) { ldsm4t(wf + 4 * ks, mo + SM_WR + ks * 2048); ldsm4t(wf + 20 + 4 * ks, mo + SM_WR + 8192 + ks * 2048); ldsm4t(wn + 4 * ks, mo + SM_WR + 16384 + ks * 2048); }
            auto half = [](uint32_t& v) { asm("mul.rn.bf16x2 %0, %0, %1;" : "+r"(v) : "r"(0x3F003F00u)); };
            uint32_t z = 0;
            #pragma unroll
            for (int i = 0; i < 16; i++) { half(wf[i]); z ^= wf[i]; }
            sts32(sbase + SM_ES + lane * 4, z);
            if (wg == 2) {
                uint32_t f[4];
                ldsm4t(f, (mo ^ ((lane & 7) << 4)) + SM_WR + 24576);
                half(f[0]); half(f[1]); half(f[2]); half(f[3]);
                sts32(wca, f[0]); sts32(wca + 256, f[1]); sts32(wca ^ 16, f[2]); sts32((wca ^ 16) + 256, f[3]);
                asm volatile("fence.proxy.async.shared::cta;" ::: "memory");
            }
        }
        const uint64_t wcd = __reduce_or_sync(~0u, (((sbase + SM_WC) & 0x3FFFF) >> 4) | (8u << 16)) | EDHI;
        const uint32_t bar0 = __reduce_or_sync(~0u, sbase + SM_BARS + wg * 2 * STG);
        const uint32_t xd0 = __reduce_or_sync(~0u, (((sbase + SM_XS + wg * NSTAGE * XS_BYTES) & 0x3FFFF) >> 4) | (1u << 16));
        const uint32_t ed0 = __reduce_or_sync(~0u, (((sbase + SM_ES + wg * NSTAGE * ES_BYTES) & 0x3FFFF) >> 4) | (8u << 16));
        const uint64_t ohd = __reduce_or_sync(~0u, ((sbase + SM_OH) & 0x3FFFF) >> 4);
        const uint32_t tabx = __reduce_or_sync(~0u, sbase + SM_TAB + w * 128);
        const uint32_t bars = __reduce_or_sync(~0u, 2 * bar0 + STG), xds = __reduce_or_sync(~0u, 2 * xd0 + XS_BYTES / 16), eds = __reduce_or_sync(~0u, 2 * ed0 + ES_BYTES / 16);
        const uint32_t xuo = __reduce_or_sync(~0u, sbase + SM_XU + wg * 16384);
        { const uint2 z = lds64(sbase + SM_OH + 8); wf[38] = z.x; wf[39] = z.y; }
        WS(9);
        constexpr int NU = 6;
        const uint32_t dm = ((NPB_MAX + lane) * 4 | (tag << 14)) * 0x10001u;
        const uint32_t db = sbase + SM_DEG - (tag << 14);
        const char* const g1 = gs + (uint32_t)(b * (P1B + P2B) + tid * 8);
        int rk[NU][4];
        uint32_t spins = 0;
        constexpr int NH = P1S ? 2 : 1, NUH = NU / NH;
        #pragma unroll
        for (int hf = 0; hf < NH; hf++) {
            uint2 r1[NUH];
            BW(ab + (hf ? 32 : 80), 0);
            if (hf == 0) WS(2);
            #pragma unroll
            for (int k = 0; k < NUH; k++) {
                const int i = hf * NUH + k;
                r1[k] = make_uint2(dm, dm);
                if (i < 5 && NB_MIN * 16 >= 384 * (i + 1) || tid + 384 * i < nb * 16) r1[k] = lds64(sbase + SM_IDX + (tid + 384 * i) * 8);
            }
            #pragma unroll 1
            while (true) {
                uint32_t bad = 0;
                #pragma unroll
                for (int k = 0; k < NUH; k++) bad |= r1[k].y ^ dm;
                if (__builtin_expect(!__any_sync(~0u, bad & 0xC000), 1)) break;
                #pragma unroll
                for (int k = 0; k < NUH; k++) ld_unit(r1[k], g1 + 384 * 8 * (hf * NUH + k), (r1[k].y ^ dm) & 0xC000);
                if (++spins > (1u << 22)) break;
            }
            if (hf == 0) WS(3);
            #pragma unroll
            for (int k = 0; k < NUH; k++) {
                int* r = rk[hf * NUH + k];
                r[0] = r1[k].x & 0xFFFF; r[1] = r1[k].x >> 16; r[2] = r1[k].y & 0xFFFF; r[3] = r1[k].y >> 16;
                #pragma unroll
                for (int m = 0; m < 4; m++) asm volatile("red.shared.add.u32 [%0], 1;" :: "r"(db + min((uint32_t)r[m], NPB_MAX * 4 + (tag << 14))) : "memory");
            }
        }
        WS(10);
        asm volatile("bar.sync 11, 512;" ::: "memory");
        int mycls = 0, mycr = 0, dg = lds32(sbase + SM_DEG + tid * 4);
        if (tid < nn) {
            mycls = NCLS - 1 - (dg <= 40 ? dg : min(41 + ((dg - 41) >> 3), NCLS - 1)); mycr = atomicAdd(&cls[mycls], 1);
        }
        int s0 = 0;
        if (__builtin_expect(dg > 40, 0)) s0 = max(SLOT_CAP - ((dg + 1) & ~1) - atomicAdd(&misc[6], (dg + 1) & ~1), 0);
        asm volatile("bar.sync 1, 384;" ::: "memory");
        WS(12);
        {
            const uint2 c = lds64(sbase + SM_CLS + lane * 8);
            const int v0 = c.x * (lane > 11 ? ((64 - 2 * lane) << 16) + 1 : 1), v1 = c.y * (lane >= 11 ? ((62 - 2 * lane) << 16) + 1 : 1);
            int inc = v0 + v1;
            #pragma unroll
            for (int o = 1; o < 32; o <<= 1) { int y = __shfl_up_sync(~0u, inc, o); if (lane >= o) inc += y; }
            const int e0 = __shfl_sync(~0u, inc - v0 - v1, mycls >> 1), e1 = __shfl_sync(~0u, inc - v1, mycls >> 1);
            const int e = (mycls & 1) ? e1 : e0;
            if (tid < nn) {
                if (dg <= 40) s0 = min((e >> 16) + mycr * ((dg + 1) & ~1), SLOT_CAP - 40);
                sts32(sbase + SM_DEG + tid * 4, s0);
            }
            const uint32_t pos = tid < nn ? (e & 0xFFFF) + mycr : tid;
            sts32(sbase + SM_SORT + pos * 4, tid < nn ? (uint32_t)tid | ((uint32_t)s0 << 16) : NONE);
            asm volatile("st.shared.u16 [%0], %1;" :: "r"(sbase + SM_SDEG + pos * 2), "r"(min(dg, 65535)) : "memory");
            if (tid == 383) { misc[4] = (nn - c.y + 3) >> 2; if ((inc >> 16) + misc[6] > SLOT_CAP - 40) misc[1] = 1; }
        }
        asm volatile("bar.sync 1, 384;" ::: "memory");
        WS(13);
        const uint32_t sv = lds32(sbase + SM_SORT + tid * 4);
        const uint2 d4 = lds64(sbase + SM_SDEG + (tid >> 2) * 8);
        const uint32_t slow = lds32(sbase + SM_MISC + 4);
        #pragma unroll
        for (int i = 0; i < NU; i++) {
            #pragma unroll
            for (int k = 0; k < 4; k++) rk[i][k] = atoms_inc(db + rk[i][k]);
        }
        if (__reduce_or_sync(~0u, slow) == 0) {
            const uint32_t nd = sv & 0xFFFF;
            const int g = tid >> 2;
            dg = ((t & 2 ? d4.y : d4.x) >> (16 * (t & 1))) & 0xFFFF;
            const uint32_t hi2 = __vmaxu2(d4.x, d4.y), lo2 = __vminu2(d4.x, d4.y);
            const int mx = max(hi2 >> 16, hi2 & 0xFFFF), mn = min(lo2 >> 16, lo2 & 0xFFFF);
            int left = (mx + 1) >> 1;
            int tl = g, nx = ngroups + 4 + g, nt = left > NPMAX ? 2 : 1;
            const bool odd = left > 2 * NPMAX || (nt == 2 && nx >= TILE_CAP - TILE_X);
            if (__builtin_expect(__any_sync(~0u, odd), 0)) {
                if (odd) nt = (left + NPMAX - 1) / NPMAX;
                if (odd && t == 0) { asm volatile("atom.shared.add.u32 %0, [%1], %2;" : "=r"(nx) : "r"(sbase + SM_MISC + 20), "r"(nt - 1) : "memory"); if (nx + nt - 1 > TILE_CAP) misc[1] = 1; }
                nx = __shfl_sync(~0u, nx, lane & ~3);
                if (odd && nx + nt - 1 > TILE_CAP) left = 0;
            }
            const uint32_t w0 = tab_at(nd);
            if (g >= ngroups + 4) tl = ngroups;
            uint32_t cont = 0;
            int done = 0;
            bool act = true;
            do {
                int np = nt <= 2 ? (left + nt - 1) >> (nt - 1) : (left + nt - 1) / nt;
                left -= np; nt = max(nt - 1, 1);
                if (np) np = max(np, NPMIN);
                const int dv = min(max(dg - done, 0), 2 * np);
                uint32_t code = (uint32_t)np | cont | (left > 0 ? C_MORE : 0u);
                const bool gen = mn - done < 2 * np - (np == NPMIN ? 1 : 2);
                if (np == 0) code = 0;
                const uint32_t w1 = code | (dv == 2 * np ? 0x8000u : (2 * np - 1 - dv) << 8);
                if (act) *(uint2*)(smem + SM_TINFO + tl * 32 + t * 8) = make_uint2((dv ? (sv >> 16) + done : 0) | ((gen ? (np > 8 ? 15 : np > 5 ? 14 : 13) : np) << 16) | ((left > 0 ? nx : 0) << 20) | ((uint32_t)dv << 27), w0 | (np == 0 ? 0u : w1 << 16));
                tl = nx++; cont = C_CONT; done += 2 * np; act = left > 0;
            } while (__any_sync(~0u, act));
        }
        __syncwarp();
        asm volatile("bar.arrive 4, 512;" ::: "memory");
        WS(14);
        wf[16] = lds32(wca); wf[17] = lds32(wca + 256); wf[18] = lds32(wca ^ 16); wf[19] = lds32((wca ^ 16) + 256);
        #pragma unroll
        for (int pc = 0; pc < 3; pc++) {
            uint4 r2[2];
            BW(ab + pc * 8, 1);
            if (pc == 0) WS(4); if (pc == 2) WS(16);
            #pragma unroll
            for (int k = 0; k < 2; k++) {
                r2[k] = lds128(sbase + SM_P2 + (tid + 384 * (2 * pc + k)) * 16);
                if (rk[2 * pc + k][0] < 0) r2[k].w = tag << 16;
            }
            while (__builtin_expect(__any_sync(~0u, ((r2[0].w ^ (tag << 16)) | (r2[1].w ^ (tag << 16))) & 0x30000), 0)) {
                #pragma unroll
                for (int k = 0; k < 2; k++)
                    ld_unit(r2[k], g1 + (uint32_t)(tid * 8) + (P1B + 384 * 16 * (2 * pc + k)), (r2[k].w ^ (tag << 16)) & 0x30000);
                if (++spins > (1u << 22)) break;
            }
            #pragma unroll
            for (int k = 0; k < 2; k++) {
                const int i = 2 * pc + k;
                const uint32_t eb = ((tid >> 4) + 24 * i) * ch;
                place(sbase, rk[i][0], r2[k].x, eb); place(sbase, rk[i][1], r2[k].y, eb); place(sbase, rk[i][2], r2[k].z, eb); place(sbase, rk[i][3], r2[k].w, eb);
            }
        }
        WGD();
        __syncwarp();
        asm volatile("bar.arrive 3, 480;" ::: "memory");
        float g[4 * NPMAX], h[4 * NPMAX];
        float4 lgh[2 * NPMAX];
        float4 cyr = make_float4(0.f, 0.f, 0.f, 0.f);
        WS(15); CG(1);
        if (GD) { uint32_t c0, c1; asm volatile("mov.u32 %0, %%clock;" : "=r"(c0)); do { asm volatile("mov.u32 %0, %%clock;" : "=r"(c1)); } while (__all_sync(~0u, c1 - c0 < GD)); }
        BW(ab + 88 + wg * 8, 0);
        WSG(1);
        auto pack = [&](uint32_t* v, const float* u) {
            #pragma unroll
            for (int i = 0; i < 16; i++) v[i] = pack_bf16(u[2*i], u[2*i+1]);
        };
        auto rows_st = [&](uint32_t p, const uint32_t* v) {
            #pragma unroll
            for (int i = 0; i < 4; i++) stsm4t(p + i * 2048, v + 4 * i);
        };
        {
            const uint64_t d0 = desc_sw128(xuo), d1 = d0 + 512;
            const uint32_t mr = sbase + wg * 16384 + w * 128 + (tab_at(8 * (lane >> 4) + (lane & 7)) ^ ((lane & 8) << 1));
            uint32_t v[16];
            node_mma(g, wn, d0); node_mma(h, wn, d1);
            TileMMA<8>::wait_g(g);
            pack(v, g); rows_st(mr + SM_TAB, v);
            TileMMA<8>::wait_h(h);
            WSG(5);
            #pragma unroll
            for (int ks = 0; ks < 4; ks++) ldsm4t(wn + 4 * ks, mo + SM_WR + 40960 + ks * 2048);
            node_mma(g, wn, d0);
            if (wg == 2) asm volatile("bar.sync 5, 384;" ::: "memory"); else asm volatile("bar.arrive 5, 384;" ::: "memory");
            pack(v, h); rows_st(mr + SM_TAB + 8192, v);
            node_mma(h, wn, d1);
            __syncwarp();
            if (lane == 0) mbar_arrive(sbase + SM_ABAR + 112);
            WSG(7);
            TileMMA<8>::wait_g(g);
            pack(v, g);
            asm volatile("bar.sync %0, 128;" :: "r"(8 + wg) : "memory");
            rows_st(mr + SM_XU, v);
            TileMMA<8>::wait_h(h);
            WSG(11);
            pack(v, h);
            asm volatile("bar.sync %0, 128;" :: "r"(8 + wg) : "memory");
            rows_st(mr + SM_XU + 8192, v);
            __syncwarp();
            if (lane == 0) mbar_arrive(sbase + SM_ABAR + 72);
            BW(ab + 112, 0);
            __syncwarp();
            if (__builtin_expect(__reduce_or_sync(~0u, misc[1]) != 0, 0)) { slow_bin(x, ea, src, dst, wa, wb, wc, wu, wv, out, E, node0, nn, 384); asm volatile("exit;"); }
            WS(6);
        }
        uint32_t bar = bar0, xd = xd0, ed = ed0, ph = 0;
        float pn0 = 0.f, pd0 = 1.f, pn1 = 0.f, pd1 = 1.f;
        uint4 rc;
        rc.x = lds32(sbase + SM_TINFO + wg * 32 + ((lane >> 1) & 3) * 8 + 4);
        uint32_t code = __reduce_or_sync(~0u, rc.x >> 16);
        rc.x = (rc.x & 0xFFFF) ^ ((lane & 8) << 1); rc.y = tab_at(NONE);
        auto fetch_a = [&]() {
            asm volatile("ldmatrix.sync.aligned.m8n8.x2.trans.shared.b16 {%0,%1}, [%2];" : "=r"(wf[36]), "=r"(wf[37]) : "r"(tabx + rc.x) : "memory");
        };
        auto emit = [&]() {
            asm volatile("stmatrix.sync.aligned.m8n8.x1.trans.shared.b16 [%0], {%1};" :: "r"(tabx + rc.y), "r"(pack_bf16(pn0 * rcpf(pd0), pn1 * rcpf(pd1))) : "memory");
        };
        auto carry = [&]() {
            if (rc.z & C_CONT) { pn0 += cyr.x; pd0 += cyr.y; pn1 += cyr.z; pd1 += cyr.w; }
            if (rc.z & C_MORE) { cyr = make_float4(pn0, pd0 - EPS2, pn1, pd1 - EPS2); pn0 = pn1 = 0.f; rc.y = tab_at(NONE); }
        };
        fetch_a();
        while (true) {
            switch (code & 15) {
                default: goto finished;
#define TILE(P) { \
                    float dmin; \
                    do { \
                        mbar_wait_c(bar, ph); \
                        TileMMA<P>::issue(g, h, wf, xd, ed | EDHI, ohd, wcd); \
                        const uint32_t eb = bar + 8; \
                        ph ^= bar != bar0; bar = bars - bar; xd = xds - xd; ed = eds - ed; \
                          \
                        asm volatile("{\n.reg .pred p;\nsetp.eq.u32 p, %0, 77;\n@p trap;\n}" :: "r"(xds) : "memory"); \
                        emit(); rc = lds128(eb + 8 + l16); \
                        TileMMA<P>::wait_g(g); fetch_a(); TileMMA<P>::wait_h(h); \
                        mbar_arrive(eb); \
                        epi_fast<P>(g, h, __uint_as_float(rc.z), pn0, pd0, pn1, pd1, dmin); \
                    } while (!__any_sync(~0u, !(dmin >= __uint_as_float(rc.w)))); \
                    code = __reduce_or_sync(~0u, rc.w); \
                    XCNT(P); \
                    if (__builtin_expect(__any_sync(~0u, (rc.z & 0x1F00) != 0 || dmin < TAU * 2 * P), 0)) { \
                        int dv; \
                        const uint32_t bad = unpad(rc.z, P, g[4 * P - 4], g[4 * P - 2], pd0, pd1, dv); \
                        if (bad) { \
                            FBLOG(P); \
                            float4* gh = exact_copy(bad, lgh); \
                            epi_dump<P>(g, h, gh); \
                            const float4 r = epi_exact(gh, P, dv); \
                            if (gh) { pn0 = r.x; pd0 = r.y; pn1 = r.z; pd1 = r.w; } \
                        } \
                    } \
                    if (code & C_BRK) { carry(); if (P != 11 && (code & 15) == P) goto L##P; } \
                    if (P == 11) {         \
                        wf[16] = lds32(wca); wf[17] = lds32(wca + 256); wf[18] = lds32(wca ^ 16); wf[19] = lds32((wca ^ 16) + 256); \
                    } }
#define CASE(P, UP, DN) case P: L##P: TILE(P) \
                    if (P > NPMIN && (code & 15) == P - 1) goto L##DN; \
                    if ((code & 15) == UP) goto L##UP; \
                    break;
                CASE(11, 11, 10) CASE(10, 11, 9) CASE(9, 10, 8) CASE(8, 9, 7) CASE(7, 8, 6) CASE(6, 7, 5) CASE(5, 6, 4) CASE(4, 5, 4)
#undef CASE
#undef TILE
            }
        }
finished:
        emit();
        __syncwarp();
        if (lane == 0) mbar_arrive(sbase + SM_ABAR + 48 + wg * 8);
    } else {
        asm volatile("setmaxnreg.dec.sync.aligned.u32 56;");
        auto x_ld = [&](int i0, int i1) {
            #pragma unroll
            for (int i = i0; i < i1; i++) w_box_ld(su + SM_XU + i * 8192, &tmx, node0 + i * 64, su + SM_ABAR + 88 + (i >> 1) * 8);
        };
        if (w < 3) {
            #pragma unroll
            for (int i = 0; i < 2; i++) { w_init(su + SM_BARS + (w * 2 + i) * STG, 64); w_init(su + SM_BARS + (w * 2 + i) * STG + 8, 128); }
            w_init(su + SM_ABAR + 48 + w * 8, 4);
            w_init(su + (w == 0 ? SM_GBAR + 96 * 8 : w == 1 ? SM_ABAR + 72 : SM_ABAR + 112), w == 0 ? 32 : 12);
        } else {
            #pragma unroll
            for (int i = 0; i < 4; i++) { w_init(su + SM_ABAR + (i < 3 ? 88 + i * 8 : 40), 1); w_expect(su + SM_ABAR + (i < 3 ? 88 + i * 8 : 40), i < 3 ? 16384 : nb * 64); }
            asm volatile("fence.mbarrier_init.release.cluster;" ::: "memory");
            if (HORD == 3) { uint32_t c; do { asm volatile("mov.u32 %0, %%clock;" : "=r"(c)); } while (__all_sync(~0u, c - cstart < T1)); }
            if (!HORD || HORD == 3) w_hint(gbar + HI1, all);
            asm volatile("cp.async.bulk.wait_group.read 0;" ::: "memory");
            WS(9);
            if (HORD == 1) w_hint(gbar + HI1, all);
            if (HORD == 2) { uint32_t c; do { asm volatile("mov.u32 %0, %%clock;" : "=r"(c)); } while (__all_sync(~0u, c - cstart < T1)); }
            if (D1) delay(D1);
            WS(2);
            if (H1F) w_ld(su + SM_H1, gs + G_H1, nb * 64, su + SM_ABAR + 120);
            if (P1S) {
                w_ld(su + SM_IDX, gs + b * (P1B + P2B), 3 * 384 * 8, su + SM_ABAR + 80);
                w_ld(su + SM_IDX + 3 * 384 * 8, gs + b * (P1B + P2B) + 3 * 384 * 8, nb * (CE * 2) - 3 * 384 * 8, su + SM_ABAR + 32);
            } else w_ld(su + SM_IDX, gs + b * (P1B + P2B), nb * (CE * 2), su + SM_ABAR + 80);
            if (!H1F) w_ld(su + SM_H1, gs + G_H1, nb * 64, su + SM_ABAR + 120);
        asm volatile("bar.sync 12, 512;" ::: "memory");
            if (D3) delay(D3);
            if (H2M == 1) w_inc(gbar + HI2);
            w_box_st(&tm2, P1B / 4 + b * CE, su + SM_P2);
            w_st(gs + G_H2 + b * 64, su + SM_P2 + P2B, 64);
            w_st(gs + G_L + b * 512 + 256, su + SM_P2 + P2B, 256);
            if (H2M == 0) w_sent(gbar + HI2, su + SM_MISC + 32);
            asm volatile("cp.async.bulk.commit_group;" ::: "memory");
            if (!XAFT) x_ld(0, XSPL);
        }
        const uint32_t ab = su + SM_ABAR;
        uint32_t todo = 0;
        const uint32_t mb = (lane & 3) == 3 ? bin_bits(b) : ~0u;
        WS(12);
        BW(ab + 120, 0);
        WS(13);
        {
            uint4 r[5];
            #pragma unroll
            for (int i = 0; i < 5; i++) r[i] = lds128(sbase + SM_H1 + (tid - 384 + 128 * i) * 16);
            #pragma unroll
            for (int i = 0; i < 5; i++) {
                const uint32_t bb = b << 16;
                const uint32_t m = min(min(r[i].x ^ bb, r[i].y ^ bb), min(r[i].z ^ bb, r[i].w ^ bb)) >> 16;
                if ((m == 0) | (((r[i].w ^ (tag << 14)) & 0xC000) != 0) | ((~r[i].w & mb) == 0)) todo |= 1 << i;
            }
            todo &= tid - 384 + 512 < nb * 4 ? 31 : tid - 384 + 384 < nb * 4 ? 15 : 7;
        }
        #pragma unroll 1
        for (int put = 0; put < 2; put++) {
            uint32_t any = __reduce_or_sync(~0u, todo), m = 0, u = 0;
            #pragma unroll 1
            while (any | m) {
                uint4 r = make_uint4(0, 0, 0, 0), r2 = r;
                uint32_t s, go, gd;
                bool on;
                if (__builtin_expect(m == 0, 1)) {
                    const uint32_t i = __ffs(any) - 1;
                    any &= any - 1; u = tid - 384 + 128 * i; on = (todo >> i) & 1;
                    r = lds128(sbase + SM_H1 + u * 16); if (!NOH2) r2 = lds128(sbase + SM_H2 + u * 16);
                    s = u >> 2; go = G_H1 + u * 16; gd = HB;
                } else {
                    s = ((u & ~31) + __ffs(m) - 1) >> 2; m &= m - 1; on = lane < 12;
                    go = G_L + s * 512 + 64 + lane * 16; gd = 256;
                }
                #pragma unroll 1
                for (int n = 0; n < (1 << 22); n++) {
                    const bool b1 = on && ((r.w >> 14) & 3) != tag, b2 = on && put && ((r2.w >> 16) & 3) != tag;
                    if (__builtin_expect(!__any_sync(~0u, b1 | b2), 1)) break;
                    ld_unit(r, gs + go, b1); ld_unit(r2, gs + go + gd, b2);
                }
                if (gd == HB) m = __ballot_sync(~0u, on && (~r.w & mb) == 0);
                if (on && r.w >> 16 == 255) sts32(sbase + SM_MISC + 4, 1);
                const uint32_t e[4] = {r.x, r.y, r.z, r.w}, v[4] = {r2.x, r2.y, r2.z, r2.w};
                uint32_t slot[4];
                #pragma unroll
                for (int k = 0; k < 4; k++) slot[k] = atoms_inc(sbase + SM_DEG + (on && e[k] >> 16 == (uint32_t)b ? (e[k] & 0x3FFF) : (NPB_MAX + lane) * 4));
                if (put) {
                    #pragma unroll
                    for (int k = 0; k < 4; k++) place(sbase, slot[k], v[k], s * ch);
                }
            }
            if (put == 0) {
                WS(4);
                asm volatile("bar.arrive 11, 512;" ::: "memory");
                if (w == 3) {
                    if (XAFT) x_ld(0, XSPL);
                    w_expect(su + SM_ABAR, 12288); w_expect(su + SM_ABAR + 8, 12288); w_expect(su + SM_ABAR + 16, nb * (CE * 4) - 24576);
                    w_hint(gbar + HI2, all);
                    if (D2) delay(D2);
                    asm volatile("cp.async.bulk.wait_group.read 0;" ::: "memory");
                    WS(3);
                    const char* g2 = gs + b * (P1B + P2B) + P1B;
                    w_ld(su + SM_P2, g2, 12288, su + SM_ABAR);
                    w_ld(su + SM_P2 + 12288, g2 + 12288, 12288, su + SM_ABAR + 8);
                    w_ld(su + SM_P2 + 24576, g2 + 24576, nb * (CE * 4) - 24576, su + SM_ABAR + 16);
                    if (!NOH2) w_ld(su + SM_H2, gs + G_H2, nb * 64, su + SM_ABAR + 40);
                    if (XW2) mbar_wait(ab + (XW2 - 1) * 8, 1);
                    x_ld(XSPL, 6);
                } else {
                    #pragma unroll 8
                    for (int i = 0; i < 32; i++) w_init(su + SM_GBAR + (w * 32 + i) * 8, 32);
                }
                asm volatile("bar.sync 4, 512;" ::: "memory");
                if (NOH2) mbar_wait(ab, 1); else BW(ab + 40, 0);
            }
        }
        __syncwarp();
        WS(10);
        WGD();
        const uint32_t scr = sbase + SM_PAIR + (tid & 127) * 8;
        const int r4 = lane >> 3, c8 = lane & 7;
        const uint32_t sb = su;
        const uint32_t tk = ((c8 & 1) << 4) | ((c8 >> 1) << 7);
        auto row_bytes = [](uint32_t o) { return (o & 0xFE00) | ((o << 2) & 0x180); };
        if (w < 3) {
            const char* gx = as_pair((const char*)x + c8 * 16, scr);
            const char* ge = as_pair((const char*)ea + (lane & 1) * 16, scr);
            const uint32_t gx0 = (uint32_t)(uint64_t)gx, ge0 = (uint32_t)(uint64_t)ge, hi = (uint64_t)gx >> 32, he = (uint64_t)ge >> 32;
            const int s = (lane >> 1) & 3;
            const uint32_t xs0 = sb + SM_XS + w * NSTAGE * XS_BYTES;
            const uint32_t es0 = sb + SM_ES + w * NSTAGE * ES_BYTES + r4 * 64 + (((lane ^ (r4 >> 1)) & 1) << 4) + (s >> 1) * 256 + (s & 1) * 32;
            const uint32_t bars = sb + SM_BARS + w * 2 * STG;
            const uint32_t xoffA = (2 * r4) * 128 + ((c8 ^ (2 * r4)) << 4), xoffB = (2 * r4 + 1) * 128 + ((c8 ^ (2 * r4 + 1)) << 4);
            uint64_t pol;
            asm volatile("createpolicy.fractional.L2::evict_first.b64 %0, 1.0;" : "=l"(pol));
            if (TLBW) {
                const uint32_t k = w * 32 + lane;
                asm volatile("prefetch.global.L2 [%0];" :: "l"(k < 64 ? (const char*)ea + (size_t)(E >> 6) * k * 32 : (const char*)x + (size_t)(N >> 5) * (k - 64) * 128));
            }
            asm volatile("bar.sync 6, 128;" ::: "memory");
            bool first = true; int tcount = 0;
            WS(15);
            uint32_t ph = 1, cur = w;
            uint32_t hist = 96 * 0x010101u;
            auto done3 = [&]() { mbar_arrive(sb + SM_GBAR + ((hist >> 16) & 0xFF) * 8); };
            const bool go = misc[1] == 0 && nn > 0;
            const uint32_t ca = sb + SM_CLAIM + lane * 4, pa = sb + SM_TINFO + r4 * 8;
            const uint32_t pb = sb + SM_TINFO + s * 8 + 4, pc = sb + SM_TINFO + (lane & 3) * 8 + 6, xl = (lane & 8) << 1, xs = (lane & 1) << 4, ra = (lane & 15) * 16 + 16;
            auto row_of = [&](uint32_t o) { uint32_t v; asm volatile("ld.shared.u16 %0, [%1];" : "=r"(v) : "r"(pb + o) : "memory"); return v; };
            auto code_of = [&](uint32_t o) { uint32_t v; asm volatile("ld.shared.s16 %0, [%1];" : "=r"(v) : "r"(pc + o) : "memory"); return v; };
            uint32_t pw = lds32(pa + w * 32), pt = __reduce_or_sync(~0u, pw), cont = 0;
            uint4 rc = make_uint4(0, row_of(w * 32) ^ xs, code_of(w * 32) & (ONE_F | 0x1FFFu), 0);
            const uint32_t se0 = sb + SM_EID + s * 4, xab = xoffB - xoffA, das = 2 * (xs0 + xoffA) + XS_BYTES, des = 2 * es0 + ES_BYTES, brs = 2 * bars + STG;
            uint32_t da = xs0 + xoffA, de = es0, br = bars;
            #pragma unroll 1
            while (go) {
                uint32_t se, sx;
                asm("dp2a.lo.u32.u32 %0, %1, 4, %2;" : "=r"(se) : "r"(pw), "r"(se0));
                asm("dp2a.lo.u32.u32 %0, %1, 2, %2;" : "=r"(sx) : "r"(pw), "r"(sb + SM_SRC));
                const int dv = pw >> 27;
                const uint32_t db = da + xab;
                const uint32_t sel = (pt >> 16) & 15, nx = (pt >> 15) & (127 << 5);
                uint32_t g;
                auto claim = [&]() { asm volatile("atom.shared.add.u32 %0, [%1], %2;" : "=r"(g) : "r"(ca), "r"(nx == 0 ? 32u : 0u) : "memory"); };
                if (sel == 0) break;
                if (first) { asm volatile("bar.sync 3, 480;" ::: "memory"); first = false;
                }
                if (S2W && hist == 96 * 0x010101u * 256 + (cont ? 96u : (uint32_t)w)) mbar_wait_c(sb + SM_ABAR + (S2W == 1 ? 112 : 72), 0);
                switch (sel) {
#define CASE(L, P, GEN) case L: { \
                        uint32_t oe[(P + 1) / 2], o[P]; \
                        _Pragma("unroll") for (int j = 0; j < (P + 1) / 2; j++) oe[j] = lds32(se + j * 16); \
                        _Pragma("unroll") for (int j = 0; j < P; j++) o[j] = lds32(sx + j * 4); \
                        mbar_wait_h(br + 8, ph); \
                        _Pragma("unroll") for (int j = 0; j < (P + 1) / 2; j++) \
                            if (LO32) { if (!GEN && 2 * j + 2 < P) cpe<false>(he, de + j * 512, oe[j], ge0, 0, 0, pol); \
                                else if (2 * j + 1 < NPMAX || s < 2) cpe<true>(he, de + j * 512, oe[j], ge0, 4 * j + s, dv, pol); } \
                            else if (!GEN && 2 * j + 2 < P) cp16e(de + j * 512, ge, oe[j], pol); else if (2 * j + 1 < NPMAX || s < 2) cp16z<32>(de + j * 512, ge, oe[j], 4 * j + s, dv, pol); \
                        _Pragma("unroll") for (int j = 0; j < P - 1; j++) { \
                            if (LO32) { cpx<0, GEN>(hi, da + j * 1024, o[j], gx0, 2 * j, dv); cpx<1, GEN>(hi, db + j * 1024, o[j], gx0, 2 * j + 1, dv); } \
                            else if (GEN) { cp16z<128>(da + j * 1024, gx, o[j] & 0xFFFFu, 2 * j, dv, 0); cp16z<128>(db + j * 1024, gx, o[j] >> 16, 2 * j + 1, dv, 0); } \
                            else { cp16i<128>(da + j * 1024, gx, o[j] & 0xFFFFu); cp16i<128>(db + j * 1024, gx, o[j] >> 16); } } \
                        if (LO32) { cpx<0, true>(hi, da + (P - 1) * 1024, o[P - 1], gx0, 2 * P - 2, dv); cpx<1, true>(hi, db + (P - 1) * 1024, o[P - 1], gx0, 2 * P - 1, dv); } \
                        else { cp16z<128>(da + (P - 1) * 1024, gx, o[P - 1] & 0xFFFFu, 2 * P - 2, dv, 0); cp16z<128>(db + (P - 1) * 1024, gx, o[P - 1] >> 16, 2 * P - 1, dv, 0); } \
                    } break;
                    CASE(4, 4, false) CASE(5, 5, false) CASE(6, 6, false) CASE(7, 7, false) CASE(8, 8, false) CASE(9, 9, false) CASE(10, 10, false) CASE(11, 11, false)
                    CASE(15, NPMAX, true) CASE(14, 8, true) default: CASE(13, 5, true)
#undef CASE
                }
                claim();
                mbar_cp_arrive(br);
                done3();
                g = __reduce_min_sync(~0u, g);
                {
                    const uint32_t o = nx == 0 ? g : nx;
                    pw = lds32(pa + o);
                    const uint32_t ya = row_of(o), yb = code_of(o);
                    pt = __reduce_or_sync(~0u, pw);
                    const uint32_t brk = (cont | nx) ? C_BRK : 0u;
                    rc.x = ya ^ xl;
                    const uint32_t lv = brk | ((sel + (15 - NPMAX)) & 16) | (((pt >> 16) & 15) ^ sel);
                    rc.w = (yb & 15) | (lv ? 0x70000000u | brk : TAU_BITS);
                    asm volatile("st.shared.v4.u32 [%2], {%3, %0, %1, %4};\nxor.b32 %0, %5, %6;\nand.b32 %1, %7, %8;"
                                 : "+r"(rc.y), "+r"(rc.z) : "r"(br + ra), "r"(rc.x), "r"(rc.w), "r"(ya), "r"(xs), "r"(yb), "n"(ONE_F | 0x1FFFu) : "memory");
                    cont = nx;
                }
                mbar_arrive(br);
                hist = (hist << 8) | (nx == 0 ? cur : 96u);
                cur = nx == 0 ? g >> 5 : cur;
                ph ^= br != bars; br = brs - br; da = das - da; de = des - de;
            }
            if (first) asm volatile("bar.sync 3, 480;" ::: "memory");
            if (go) {
                mbar_wait(sb + SM_ABAR + 72, 0);
                const int g0 = 3 * max((ngroups + 2) / 3 - TR, 0) + w;
                uint32_t nd[TR]; uint4 xv[TR];
                #pragma unroll
                for (int k = 0; k < TR; k++) {
                    asm volatile("ld.shared.u16 %0, [%1];" : "=r"(nd[k]) : "r"(pa + (g0 + 3 * k) * 32 + 4) : "memory");
                    xv[k] = __ldg((const uint4*)(gx + (size_t)node0 * 128 + (nd[k] == tab_at(NONE) ? 0u : row_bytes(nd[k]))));
                }
                #pragma unroll 1
                for (int k = 0; k < 3; k++) {
                    if (TSPIN && k == 2) mbar_wait_s(sb + SM_ABAR + 48 + w * 8, 0); else mbar_wait(k < 2 ? br + 8 : sb + SM_ABAR + 48 + w * 8, k < 2 ? ph : 0);
                    done3(); hist <<= 8;
                    ph ^= br != bars; br = brs - br;
                }
                #pragma unroll
                for (int k = 0; k < TR; k++) {
                    const uint32_t ro = sb + (nd[k] ^ tk);
                    const uint4 xu = lds128(ro + SM_XU);
                    uint4 a = make_uint4(0, 0, 0, 0);
                    if (g0 + 3 * k < misc[4]) { if (TSPIN) mbar_wait_s(sb + SM_GBAR + (g0 + 3 * k) * 8, 0); else mbar_wait(sb + SM_GBAR + (g0 + 3 * k) * 8, 0); a = lds128(ro + SM_TAB); }
                    finish(a, xu, xv[k]);
                    if (nd[k] != tab_at(NONE)) *(uint4*)((char*)out + (size_t)node0 * 128 + row_bytes(nd[k]) + c8 * 16) = a;
                }
            }
            cp_wait<0>();
        } else {
            const int r4 = WMAP ? (lane >> 1) & 3 : lane >> 3, c8 = WMAP ? (lane >> 3) * 2 + (lane & 1) : lane & 7;
            const uint32_t tk = ((c8 & 1) << 4) | ((c8 >> 1) << 7);
            const char* gx = as_pair((const char*)x + (size_t)node0 * 128 + c8 * 16, scr);
            const char* ob = as_pair((const char*)out + (size_t)node0 * 128 + c8 * 16, scr);
            asm volatile("bar.arrive 6, 128;" ::: "memory");
            WS(15);
            if (b == 0 && lane == 0) asm volatile("red.relaxed.gpu.global.add.u32 [%0], 1;" :: "l"(gbar) : "memory");
            if (misc[1] == 0) mbar_wait(sb + SM_ABAR + 72, 0);
            if (npb <= NPB_MAX - 4) sts32(sb + SM_MISC + 12, 0);
            const int rounds = misc[1] ? 0 : max((ngroups + 2) / 3 - TR, 0);
            const int gz = misc[4], fast = __reduce_min_sync(~0u, min(rounds, gz / 3));
            uint32_t wl = sb + SM_TINFO + r4 * 8 + 4, gbar = sb + SM_GBAR;
            auto row_at = [&](uint32_t a) { uint32_t n; asm volatile("ld.shared.u16 %0, [%1];" : "=r"(n) : "r"(a) : "memory"); return n; };
            auto fetch = [&](uint32_t n, uint4& v) {
                asm volatile("{\n.reg .b64 p;\ncvt.u64.u32 p, %5;\nadd.u64 p, p, %4;\nld.global.nc.L1::no_allocate.v4.u32 {%0,%1,%2,%3}, [p];\n}"
                             : "=r"(v.x), "=r"(v.y), "=r"(v.z), "=r"(v.w) : "l"(gx), "r"(n));
            };
            auto store = [&](uint32_t n, const uint4& a) {
                asm volatile("{\n.reg .b64 p;\ncvt.u64.u32 p, %1;\nadd.u64 p, p, %0;\nst.global.v4.u32 [p], {%2,%3,%4,%5};\n}" :: "l"(ob), "r"(n), "r"(a.x), "r"(a.y), "r"(a.z), "r"(a.w) : "memory");
            };
            uint32_t n0[3], o0[3]; uint4 x0[3];
            const uint32_t tw = __shfl_sync(~0u, tk, lane);
            if (fast) {
                #pragma unroll
                for (int r = 0; r < 3; r++) { const uint32_t v = row_at(wl + r * 32); n0[r] = row_bytes(v); o0[r] = v ^ tw; fetch(n0[r], x0[r]); }
            }
            #pragma unroll 1
            for (int k = 0; k < fast; k++) {
                wl += 96;
                #pragma unroll
                for (int r = 0; r < 3; r++) {
                    const uint32_t nd = n0[r];
                    const uint4 xu = lds128(sb + o0[r] + SM_XU);
                    const uint32_t v = row_at(wl + r * 32);
                    mbar_wait(gbar + r * 8, 0);
                    uint4 a = lds128(sb + o0[r] + SM_TAB);
                    n0[r] = row_bytes(v); o0[r] = v ^ tw;
                    finish(a, xu, x0[r]);
                    fetch(n0[r], x0[r]);
                    store(nd, a);
                }
                gbar += 24;
            }
            #pragma unroll 1
            for (int g = 3 * fast; g < 3 * rounds; g++) {
                const uint32_t v = row_at(sb + SM_TINFO + r4 * 8 + 4 + g * 32), nd = row_bytes(v), ro = sb + (v ^ tw);
                uint4 xv, a = make_uint4(0, 0, 0, 0);
                fetch(nd, xv);
                if (g < gz) { mbar_wait(sb + SM_GBAR + g * 8, 0); a = lds128(ro + SM_TAB); }
                finish(a, lds128(ro + SM_XU), xv);
                store(nd, a);
            }
        }
    }
    WS(17); WG1(); CG(2);
}

}

extern "C" void kernel_launch(void* const* d_in, const int* in_sizes, int n_in, void* d_out, int out_size) {
    const __nv_bfloat16* x = (const __nv_bfloat16*)d_in[0];
    const __nv_bfloat16* ea = (const __nv_bfloat16*)d_in[1];
    const int* src = (const int*)d_in[2];
    const int* dst = (const int*)d_in[3];
    const __nv_bfloat16* wa = (const __nv_bfloat16*)d_in[4];
    const __nv_bfloat16* wb = (const __nv_bfloat16*)d_in[5];
    const __nv_bfloat16* wc = (const __nv_bfloat16*)d_in[6];
    const __nv_bfloat16* wu = (const __nv_bfloat16*)d_in[7];
    const __nv_bfloat16* wv = (const __nv_bfloat16*)d_in[8];
    __nv_bfloat16* out = (__nv_bfloat16*)d_out;
    int N = in_sizes[0] / 64, E = in_sizes[2];
    static int sms = 0;
    static CUtensorMap tm1, tm2, tmw, tmx;
    static bool tm_ok = false;
    static void* gp = nullptr; static void* gb = nullptr;
    typedef CUresult (*EncFn)(CUtensorMap*, CUtensorMapDataType, cuuint32_t, void*, const cuuint64_t*, const cuuint64_t*, const cuuint32_t*,
                              const cuuint32_t*, CUtensorMapInterleave, CUtensorMapSwizzle, CUtensorMapL2promotion, CUtensorMapFloatOOBfill);
    static void* fn = nullptr;
    auto enc = [&](CUtensorMap* tm, const void* base, cuuint64_t cols, cuuint64_t rows, cuuint32_t bc, cuuint32_t br, CUtensorMapSwizzle sw) {
        cuuint64_t g2[2] = {cols, rows}, gs[1] = {cols * 4};
        cuuint32_t b2[2] = {bc, br}, es[2] = {1, 1};
        return ((EncFn)fn)(tm, CU_TENSOR_MAP_DATA_TYPE_UINT32, 2, (void*)base, g2, gs, b2, es, CU_TENSOR_MAP_INTERLEAVE_NONE, sw,
                           CU_TENSOR_MAP_L2_PROMOTION_NONE, CU_TENSOR_MAP_FLOAT_OOB_FILL_NONE) == CUDA_SUCCESS;
    };
    if (!sms) {
        cudaDeviceGetAttribute(&sms, cudaDevAttrMultiProcessorCount, 0);
        cudaDriverEntryPointQueryResult qr;
        cudaGetDriverEntryPoint("cuTensorMapEncodeTiled", &fn, cudaEnableDefault, &qr);
        cudaGetSymbolAddress(&gp, g_str); cudaGetSymbolAddress(&gb, g_bar);
        if (fn && gp && gb) {
            const cuuint32_t rows = sms < NB_MAX ? sms : NB_MAX;
            tm_ok = enc(&tm1, gp, (P1B + P2B) / 4, NB_MAX, CE / 2, rows, CU_TENSOR_MAP_SWIZZLE_NONE) && enc(&tm2, gp, (P1B + P2B) / 4, NB_MAX, CE, rows, CU_TENSOR_MAP_SWIZZLE_NONE);
        }
        cudaFuncSetAttribute(gcn_kernel<true>, cudaFuncAttributeMaxDynamicSharedMemorySize, SMEM_LAUNCH);
        cudaFuncSetAttribute(gcn_kernel<false>, cudaFuncAttributeMaxDynamicSharedMemorySize, SMEM_LAUNCH);
    }
    int nb = sms < NB_MAX ? sms : NB_MAX;
    int npb = (N + nb - 1) / nb;
    int ch = (((E + nb - 1) / nb) + 3) & ~3;
    const uintptr_t wp[4] = {(uintptr_t)wb, (uintptr_t)wv, (uintptr_t)wa, (uintptr_t)wu};
    uintptr_t wlo = wp[0], whi = wp[0], wal = 0;
    for (int i = 0; i < 4; i++) { wlo = wp[i] < wlo ? wp[i] : wlo; whi = wp[i] > whi ? wp[i] : whi; wal |= wp[i] - wp[0]; }
    bool ok = tm_ok && nb >= NB_MIN && npb < NPB_MAX && ch <= CH_MAX && !(E & 3) && N <= 65535 && npb >= 2 && !(wal & 127) && (whi - wlo) >> 7 < (1u << 30) &&
              !(((uintptr_t)src | (uintptr_t)dst | (uintptr_t)x | (uintptr_t)wb | (uintptr_t)wc) & 15);
    ok = ok && enc(&tmw, (const void*)wlo, 32, ((whi - wlo) >> 7) + 64, 32, 64, CU_TENSOR_MAP_SWIZZLE_128B) && enc(&tmx, x, 32, N, 32, 64, CU_TENSOR_MAP_SWIZZLE_128B);
    if (!ok) {
        int g = 1024, p = (N + g - 1) / g;
        slow_kernel<<<g, 256>>>(x, ea, src, dst, wa, wb, wc, wu, wv, out, N, E, p < 1 ? 1 : p);
        return;
    }
    int4 wrow = make_int4((int)((wp[0] - wlo) >> 7), (int)((wp[1] - wlo) >> 7), (int)((wp[2] - wlo) >> 7), (int)((wp[3] - wlo) >> 7));
    uint32_t magic = (uint32_t)((1ull << 32) / (uint32_t)npb) + 1u;
    void* args[] = {&dst, &gb, &gp, &src, &E, &ch, &N, &npb, &magic, &x, &ea, &wa, &wb, &wc, &wu, &wv, &out, &wrow, &tm1, &tm2, &tmw, &tmx};
    const bool lo32 = ((uintptr_t)x >> 32) == (((uintptr_t)x + (size_t)N * 128 - 1) >> 32) && ((uintptr_t)ea >> 32) == (((uintptr_t)ea + (size_t)E * 32 - 1) >> 32);
    cudaLaunchCooperativeKernel(lo32 && !FORCE64 ? (const void*)gcn_kernel<true> : (const void*)gcn_kernel<false>, dim3(nb), dim3(THREADS), args, SMEM_LAUNCH, cudaStreamPerThread);
}
```

```cpp
#include <cuda_runtime.h>
#include <cuda.h>
#include <cuda_bf16.h>
#include <stdint.h>

namespace {

constexpr int N_MAX = 65536;
constexpr int NPMAX = 11;
constexpr int NPMIN = 4;
constexpr int THREADS = 512;
constexpr int EPT = 12;
constexpr int CH_MAX = THREADS * EPT;
constexpr int NB_MAX = 134, NB_MIN = 120;
constexpr int CE = 64;
constexpr int P1B = NB_MAX * CE * 2;
constexpr int P2B = NB_MAX * CE * 4;
constexpr int HB = NB_MAX * 64;
constexpr int G_H1 = NB_MAX * (P1B + P2B), G_H2 = G_H1 + HB, G_L = G_H2 + HB, G_END = G_L + NB_MAX * 512;
constexpr int NPB_MAX = 384;
constexpr int SLOT_CAP = 6784;
constexpr int TILE_CAP = 124;
constexpr int TILE_X = 8;
constexpr int NCLS = 64;
constexpr int NSTAGE = 2;
constexpr int TR = 2;
constexpr float LOG2E = 1.4426950408889634f;

__device__ __align__(256) uint4 g_str[G_END / 16];
__device__ __align__(128) unsigned g_bar[96];
__device__ float g_slow[N_MAX * 128];

#define WS(k)
#define WS1(k)
#define WSG(k)
#define WGD()
#define WG0()
#define WG1()
#define CG(k)
#define SMEM_LAUNCH SMEM_BYTES
#define EPOLL 0
#define WSPL 1
#define XT0 1000
#define XDT 800
#define D3 0
#define XMID 0
#define SRCE 0
#define XA 1
#define XC 0
#define XW 1
#define XE 0
#define XEW 1
#define XAFT 1
#define WDET 1
#define H1F 0
#define TSRC 1000
#define G3F 1
#define TLBW 0
#define OWNE 0
#define UFORM 0
#define XW2 0
#define XCNT(P)
#define FBLOG(P)
#define FBW 0
#define PD 300
#define SRCV 0
#define SD 0
#define WV 9
#define WLATE 2
#define WPF 0
#define HI1 1
#define HI2 4
#define HORD 0
#define T1 6000
#define NOH2 0
#define TSPIN 0
#define WMAP 0
#define P1S 0
#define BW mbar_wait_c
#define OVU 1
#define S2W 0
#define GD 0
#define HSF 1
#define TPOLL 0
#define PHP 0
#define UOFF 0
#define U0 1
#define JCB 3
#define FX 0
#define RIN 0
#define XPF 0
#define XLD 4
#define XSPL 1
#define P2W 1
#define H2M 0
#define D1 0
#define D2 0
#define FORCE64 0
#define EDHI ((16ull << 32) | (3ull << 62))
template<int NP> struct TileMMA;
template<> struct TileMMA<1> {
  static __device__ __forceinline__ void issue(float* g, float* h, const uint32_t* w, uint32_t dx, uint64_t de, uint64_t dh, uint64_t dc) {
    asm volatile(
      "{\n.reg .b64 dx0, dx1, dx2, dx3;\n.reg .b32 l1, l2, l3, hx;\nmov.b32 hx, 0x40000040;\n"
      "add.u32 l1, %48, 2;\nadd.u32 l2, %48, 4;\nadd.u32 l3, %48, 6;\n"
      "mov.b64 dx0, {%48, hx};\nmov.b64 dx1, {l1, hx};\nmov.b64 dx2, {l2, hx};\nmov.b64 dx3, {l3, hx};\n"
      "wgmma.fence.sync.aligned;\n"
      "wgmma.mma_async.sync.aligned.m64n8k16.f32.bf16.bf16 {%0, %1, %2, %3}, {%44, %45, %46, %47}, %50, 0, 1, 1, 0;\n"
      "wgmma.mma_async.sync.aligned.m64n8k16.f32.bf16.bf16 {%0, %1, %2, %3}, {%24, %25, %26, %27}, %49, 1, 1, 1, 0;\n"
      "wgmma.mma_async.sync.aligned.m64n8k16.f32.bf16.bf16 {%0, %1, %2, %3}, {%8, %9, %10, %11}, dx0, 1, 1, 1, 0;\n"
      "wgmma.mma_async.sync.aligned.m64n8k16.f32.bf16.bf16 {%0, %1, %2, %3}, {%12, %13, %14, %15}, dx1, 1, 1, 1, 0;\n"
      "wgmma.mma_async.sync.aligned.m64n8k16.f32.bf16.bf16 {%0, %1, %2, %3}, {%16, %17, %18, %19}, dx2, 1, 1, 1, 0;\n"
      "wgmma.mma_async.sync.aligned.m64n8k16.f32.bf16.bf16 {%0, %1, %2, %3}, {%20, %21, %22, %23}, dx3, 1, 1, 1, 0;\n"
      "wgmma.commit_group.sync.aligned;\n"
      "wgmma.mma_async.sync.aligned.m64n8k16.f32.bf16.bf16 {%4, %5, %6, %7}, {%28, %29, %30, %31}, dx0, 0, 1, 1, 0;\n"
      "wgmma.mma_async.sync.aligned.m64n8k16.f32.bf16.bf16 {%4, %5, %6, %7}, {%32, %33, %34, %35}, dx1, 1, 1, 1, 0;\n"
      "wgmma.mma_async.sync.aligned.m64n8k16.f32.bf16.bf16 {%4, %5, %6, %7}, {%36, %37, %38, %39}, dx2, 1, 1, 1, 0;\n"
      "wgmma.mma_async.sync.aligned.m64n8k16.f32.bf16.bf16 {%4, %5, %6, %7}, {%40, %41, %42, %43}, dx3, 1, 1, 1, 0;\n"
      "wgmma.commit_group.sync.aligned;\n}\n"
      : "=f"(g[0]), "=f"(g[1]), "=f"(g[2]), "=f"(g[3]),
        "=f"(h[0]), "=f"(h[1]), "=f"(h[2]), "=f"(h[3])
      : "r"(w[0]), "r"(w[1]), "r"(w[2]), "r"(w[3]), "r"(w[4]), "r"(w[5]), "r"(w[6]), "r"(w[7]), "r"(w[8]), "r"(w[9]), "r"(w[10]), "r"(w[11]), "r"(w[12]), "r"(w[13]), "r"(w[14]), "r"(w[15]), "r"(w[16]), "r"(w[17]), "r"(w[18]), "r"(w[19]), "r"(w[20]), "r"(w[21]), "r"(w[22]), "r"(w[23]), "r"(w[24]), "r"(w[25]), "r"(w[26]), "r"(w[27]), "r"(w[28]), "r"(w[29]), "r"(w[30]), "r"(w[31]), "r"(w[32]), "r"(w[33]), "r"(w[34]), "r"(w[35]), "r"(w[36]), "r"(w[37]), "r"(w[38]), "r"(w[39]), "r"(dx), "l"(de), "l"(dh)
      : "memory");
  }
  static __device__ __forceinline__ void wait_g(float* g) {
    asm volatile("wgmma.wait_group.sync.aligned 1;\n"
      : "+f"(g[0]), "+f"(g[1]), "+f"(g[2]), "+f"(g[3])
      :: "memory");
  }
  static __device__ __forceinline__ void wait_h(float* h) {
    asm volatile("wgmma.wait_group.sync.aligned 0;\n"
      : "+f"(h[0]), "+f"(h[1]), "+f"(h[2]), "+f"(h[3])
      :: "memory");
  }
};
template<> struct TileMMA<2> {
  static __device__ __forceinline__ void issue(float* g, float* h, const uint32_t* w, uint32_t dx, uint64_t de, uint64_t dh, uint64_t dc) {
    asm volatile(
      "{\n.reg .b64 dx0, dx1, dx2, dx3;\n.reg .b32 l1, l2, l3, hx;\nmov.b32 hx, 0x40000040;\n"
      "add.u32 l1, %56, 2;\nadd.u32 l2, %56, 4;\nadd.u32 l3, %56, 6;\n"
      "mov.b64 dx0, {%56, hx};\nmov.b64 dx1, {l1, hx};\nmov.b64 dx2, {l2, hx};\nmov.b64 dx3, {l3, hx};\n"
      "wgmma.fence.sync.aligned;\n"
      "wgmma.mma_async.sync.aligned.m64n16k16.f32.bf16.bf16 {%0, %1, %2, %3, %4, %5, %6, %7}, {%52, %53, %54, %55}, %58, 0, 1, 1, 0;\n"
      "wgmma.mma_async.sync.aligned.m64n16k16.f32.bf16.bf16 {%0, %1, %2, %3, %4, %5, %6, %7}, {%32, %33, %34, %35}, %57, 1, 1, 1, 0;\n"
      "wgmma.mma_async.sync.aligned.m64n16k16.f32.bf16.bf16 {%0, %1, %2, %3, %4, %5, %6, %7}, {%16, %17, %18, %19}, dx0, 1, 1, 1, 0;\n"
      "wgmma.mma_async.sync.aligned.m64n16k16.f32.bf16.bf16 {%0, %1, %2, %3, %4, %5, %6, %7}, {%20, %21, %22, %23}, dx1, 1, 1, 1, 0;\n"
      "wgmma.mma_async.sync.aligned.m64n16k16.f32.bf16.bf16 {%0, %1, %2, %3, %4, %5, %6, %7}, {%24, %25, %26, %27}, dx2, 1, 1, 1, 0;\n"
      "wgmma.mma_async.sync.aligned.m64n16k16.f32.bf16.bf16 {%0, %1, %2, %3, %4, %5, %6, %7}, {%28, %29, %30, %31}, dx3, 1, 1, 1, 0;\n"
      "wgmma.commit_group.sync.aligned;\n"
      "wgmma.mma_async.sync.aligned.m64n16k16.f32.bf16.bf16 {%8, %9, %10, %11, %12, %13, %14, %15}, {%36, %37, %38, %39}, dx0, 0, 1, 1, 0;\n"
      "wgmma.mma_async.sync.aligned.m64n16k16.f32.bf16.bf16 {%8, %9, %10, %11, %12, %13, %14, %15}, {%40, %41, %42, %43}, dx1, 1, 1, 1, 0;\n"
      "wgmma.mma_async.sync.aligned.m64n16k16.f32.bf16.bf16 {%8, %9, %10, %11, %12, %13, %14, %15}, {%44, %45, %46, %47}, dx2, 1, 1, 1, 0;\n"
      "wgmma.mma_async.sync.aligned.m64n16k16.f32.bf16.bf16 {%8, %9, %10, %11, %12, %13, %14, %15}, {%48, %49, %50, %51}, dx3, 1, 1, 1, 0;\n"
      "wgmma.commit_group.sync.aligned;\n}\n"
      : "=f"(g[0]), "=f"(g[1]), "=f"(g[2]), "=f"(g[3]), "=f"(g[4]), "=f"(g[5]), "=f"(g[6]), "=f"(g[7]),
        "=f"(h[0]), "=f"(h[1]), "=f"(h[2]), "=f"(h[3]), "=f"(h[4]), "=f"(h[5]), "=f"(h[6]), "=f"(h[7])
      : "r"(w[0]), "r"(w[1]), "r"(w[2]), "r"(w[3]), "r"(w[4]), "r"(w[5]), "r"(w[6]), "r"(w[7]), "r"(w[8]), "r"(w[9]), "r"(w[10]), "r"(w[11]), "r"(w[12]), "r"(w[13]), "r"(w[14]), "r"(w[15]), "r"(w[16]), "r"(w[17]), "r"(w[18]), "r"(w[19]), "r"(w[20]), "r"(w[21]), "r"(w[22]), "r"(w[23]), "r"(w[24]), "r"(w[25]), "r"(w[26]), "r"(w[27]), "r"(w[28]), "r"(w[29]), "r"(w[30]), "r"(w[31]), "r"(w[32]), "r"(w[33]), "r"(w[34]), "r"(w[35]), "r"(w[36]), "r"(w[37]), "r"(w[38]), "r"(w[39]), "r"(dx), "l"(de), "l"(dh)
      : "memory");
  }
  static __device__ __forceinline__ void wait_g(float* g) {
    asm volatile("wgmma.wait_group.sync.aligned 1;\n"
      : "+f"(g[0]), "+f"(g[1]), "+f"(g[2]), "+f"(g[3]), "+f"(g[4]), "+f"(g[5]), "+f"(g[6]), "+f"(g[7])
      :: "memory");
  }
  static __device__ __forceinline__ void wait_h(float* h) {
    asm volatile("wgmma.wait_group.sync.aligned 0;\n"
      : "+f"(h[0]), "+f"(h[1]), "+f"(h[2]), "+f"(h[3]), "+f"(h[4]), "+f"(h[5]), "+f"(h[6]), "+f"(h[7])
      :: "memory");
  }
};
template<> struct TileMMA<3> {
  static __device__ __forceinline__ void issue(float* g, float* h, const uint32_t* w, uint32_t dx, uint64_t de, uint64_t dh, uint64_t dc) {
    asm volatile(
      "{\n.reg .b64 dx0, dx1, dx2, dx3;\n.reg .b32 l1, l2, l3, hx;\nmov.b32 hx, 0x40000040;\n"
      "add.u32 l1, %64, 2;\nadd.u32 l2, %64, 4;\nadd.u32 l3, %64, 6;\n"
      "mov.b64 dx0, {%64, hx};\nmov.b64 dx1, {l1, hx};\nmov.b64 dx2, {l2, hx};\nmov.b64 dx3, {l3, hx};\n"
      "wgmma.fence.sync.aligned;\n"
      "wgmma.mma_async.sync.aligned.m64n24k16.f32.bf16.bf16 {%0, %1, %2, %3, %4, %5, %6, %7, %8, %9, %10, %11}, {%60, %61, %62, %63}, %66, 0, 1, 1, 0;\n"
      "wgmma.mma_async.sync.aligned.m64n24k16.f32.bf16.bf16 {%0, %1, %2, %3, %4, %5, %6, %7, %8, %9, %10, %11}, {%40, %41, %42, %43}, %65, 1, 1, 1, 0;\n"
      "wgmma.mma_async.sync.aligned.m64n24k16.f32.bf16.bf16 {%0, %1, %2, %3, %4, %5, %6, %7, %8, %9, %10, %11}, {%24, %25, %26, %27}, dx0, 1, 1, 1, 0;\n"
      "wgmma.mma_async.sync.aligned.m64n24k16.f32.bf16.bf16 {%0, %1, %2, %3, %4, %5, %6, %7, %8, %9, %10, %11}, {%28, %29, %30, %31}, dx1, 1, 1, 1, 0;\n"
      "wgmma.mma_async.sync.aligned.m64n24k16.f32.bf16.bf16 {%0, %1, %2, %3, %4, %5, %6, %7, %8, %9, %10, %11}, {%32, %33, %34, %35}, dx2, 1, 1, 1, 0;\n"
      "wgmma.mma_async.sync.aligned.m64n24k16.f32.bf16.bf16 {%0, %1, %2, %3, %4, %5, %6, %7, %8, %9, %10, %11}, {%36, %37, %38, %39}, dx3, 1, 1, 1, 0;\n"
      "wgmma.commit_group.sync.aligned;\n"
      "wgmma.mma_async.sync.aligned.m64n24k16.f32.bf16.bf16 {%12, %13, %14, %15, %16, %17, %18, %19, %20, %21, %22, %23}, {%44, %45, %46, %47}, dx0, 0, 1, 1, 0;\n"
      "wgmma.mma_async.sync.aligned.m64n24k16.f32.bf16.bf16 {%12, %13, %14, %15, %16, %17, %18, %19, %20, %21, %22, %23}, {%48, %49, %50, %51}, dx1, 1, 1, 1, 0;\n"
      "wgmma.mma_async.sync.aligned.m64n24k16.f32.bf16.bf16 {%12, %13, %14, %15, %16, %17, %18, %19, %20, %21, %22, %23}, {%52, %53, %54, %55}, dx2, 1, 1, 1, 0;\n"
      "wgmma.mma_async.sync.aligned.m64n24k16.f32.bf16.bf16 {%12, %13, %14, %15, %16, %17, %18, %19, %20, %21, %22, %23}, {%56, %57, %58, %59}, dx3, 1, 1, 1, 0;\n"
      "wgmma.commit_group.sync.aligned;\n}\n"
      : "=f"(g[0]), "=f"(g[1]), "=f"(g[2]), "=f"(g[3]), "=f"(g[4]), "=f"(g[5]), "=f"(g[6]), "=f"(g[7]), "=f"(g[8]), "=f"(g[9]), "=f"(g[10]), "=f"(g[11]),
        "=f"(h[0]), "=f"(h[1]), "=f"(h[2]), "=f"(h[3]), "=f"(h[4]), "=f"(h[5]), "=f"(h[6]), "=f"(h[7]), "=f"(h[8]), "=f"(h[9]), "=f"(h[10]), "=f"(h[11])
      : "r"(w[0]), "r"(w[1]), "r"(w[2]), "r"(w[3]), "r"(w[4]), "r"(w[5]), "r"(w[6]), "r"(w[7]), "r"(w[8]), "r"(w[9]), "r"(w[10]), "r"(w[11]), "r"(w[12]), "r"(w[13]), "r"(w[14]), "r"(w[15]), "r"(w[16]), "r"(w[17]), "r"(w[18]), "r"(w[19]), "r"(w[20]), "r"(w[21]), "r"(w[22]), "r"(w[23]), "r"(w[24]), "r"(w[25]), "r"(w[26]), "r"(w[27]), "r"(w[28]), "r"(w[29]), "r"(w[30]), "r"(w[31]), "r"(w[32]), "r"(w[33]), "r"(w[34]), "r"(w[35]), "r"(w[36]), "r"(w[37]), "r"(w[38]), "r"(w[39]), "r"(dx), "l"(de), "l"(dh)
      : "memory");
  }
  static __device__ __forceinline__ void wait_g(float* g) {
    asm volatile("wgmma.wait_group.sync.aligned 1;\n"
      : "+f"(g[0]), "+f"(g[1]), "+f"(g[2]), "+f"(g[3]), "+f"(g[4]), "+f"(g[5]), "+f"(g[6]), "+f"(g[7]), "+f"(g[8]), "+f"(g[9]), "+f"(g[10]), "+f"(g[11])
      :: "memory");
  }
  static __device__ __forceinline__ void wait_h(float* h) {
    asm volatile("wgmma.wait_group.sync.aligned 0;\n"
      : "+f"(h[0]), "+f"(h[1]), "+f"(h[2]), "+f"(h[3]), "+f"(h[4]), "+f"(h[5]), "+f"(h[6]), "+f"(h[7]), "+f"(h[8]), "+f"(h[9]), "+f"(h[10]), "+f"(h[11])
      :: "memory");
  }
};
template<> struct TileMMA<4> {
  static __device__ __forceinline__ void issue(float* g, float* h, const uint32_t* w, uint32_t dx, uint64_t de, uint64_t dh, uint64_t dc) {
    asm volatile(
      "{\n.reg .b64 dx0, dx1, dx2, dx3;\n.reg .b32 l1, l2, l3, hx;\nmov.b32 hx, 0x40000040;\n"
      "add.u32 l1, %72, 2;\nadd.u32 l2, %72, 4;\nadd.u32 l3, %72, 6;\n"
      "mov.b64 dx0, {%72, hx};\nmov.b64 dx1, {l1, hx};\nmov.b64 dx2, {l2, hx};\nmov.b64 dx3, {l3, hx};\n"
      "wgmma.fence.sync.aligned;\n"
      "wgmma.mma_async.sync.aligned.m64n32k16.f32.bf16.bf16 {%0, %1, %2, %3, %4, %5, %6, %7, %8, %9, %10, %11, %12, %13, %14, %15}, {%68, %69, %70, %71}, %74, 0, 1, 1, 0;\n"
      "wgmma.mma_async.sync.aligned.m64n32k16.f32.bf16.bf16 {%0, %1, %2, %3, %4, %5, %6, %7, %8, %9, %10, %11, %12, %13, %14, %15}, {%48, %49, %50, %51}, %73, 1, 1, 1, 0;\n"
      "wgmma.mma_async.sync.aligned.m64n32k16.f32.bf16.bf16 {%0, %1, %2, %3, %4, %5, %6, %7, %8, %9, %10, %11, %12, %13, %14, %15}, {%32, %33, %34, %35}, dx0, 1, 1, 1, 0;\n"
      "wgmma.mma_async.sync.aligned.m64n32k16.f32.bf16.bf16 {%0, %1, %2, %3, %4, %5, %6, %7, %8, %9, %10, %11, %12, %13, %14, %15}, {%36, %37, %38, %39}, dx1, 1, 1, 1, 0;\n"
      "wgmma.mma_async.sync.aligned.m64n32k16.f32.bf16.bf16 {%0, %1, %2, %3, %4, %5, %6, %7, %8, %9, %10, %11, %12, %13, %14, %15}, {%40, %41, %42, %43}, dx2, 1, 1, 1, 0;\n"
      "wgmma.mma_async.sync.aligned.m64n32k16.f32.bf16.bf16 {%0, %1, %2, %3, %4, %5, %6, %7, %8, %9, %10, %11, %12, %13, %14, %15}, {%44, %45, %46, %47}, dx3, 1, 1, 1, 0;\n"
      "wgmma.commit_group.sync.aligned;\n"
      "wgmma.mma_async.sync.aligned.m64n32k16.f32.bf16.bf16 {%16, %17, %18, %19, %20, %21, %22, %23, %24, %25, %26, %27, %28, %29, %30, %31}, {%52, %53, %54, %55}, dx0, 0, 1, 1, 0;\n"
      "wgmma.mma_async.sync.aligned.m64n32k16.f32.bf16.bf16 {%16, %17, %18, %19, %20, %21, %22, %23, %24, %25, %26, %27, %28, %29, %30, %31}, {%56, %57, %58, %59}, dx1, 1, 1, 1, 0;\n"
      "wgmma.mma_async.sync.aligned.m64n32k16.f32.bf16.bf16 {%16, %17, %18, %19, %20, %21, %22, %23, %24, %25, %26, %27, %28, %29, %30, %31}, {%60, %61, %62, %63}, dx2, 1, 1, 1, 0;\n"
      "wgmma.mma_async.sync.aligned.m64n32k16.f32.bf16.bf16 {%16, %17, %18, %19, %20, %21, %22, %23, %24, %25, %26, %27, %28, %29, %30, %31}, {%64, %65, %66, %67}, dx3, 1, 1, 1, 0;\n"
      "wgmma.commit_group.sync.aligned;\n}\n"
      : "=f"(g[0]), "=f"(g[1]), "=f"(g[2]), "=f"(g[3]), "=f"(g[4]), "=f"(g[5]), "=f"(g[6]), "=f"(g[7]), "=f"(g[8]), "=f"(g[9]), "=f"(g[10]), "=f"(g[11]), "=f"(g[12]), "=f"(g[13]), "=f"(g[14]), "=f"(g[15]),
        "=f"(h[0]), "=f"(h[1]), "=f"(h[2]), "=f"(h[3]), "=f"(h[4]), "=f"(h[5]), "=f"(h[6]), "=f"(h[7]), "=f"(h[8]), "=f"(h[9]), "=f"(h[10]), "=f"(h[11]), "=f"(h[12]), "=f"(h[13]), "=f"(h[14]), "=f"(h[15])
      : "r"(w[0]), "r"(w[1]), "r"(w[2]), "r"(w[3]), "r"(w[4]), "r"(w[5]), "r"(w[6]), "r"(w[7]), "r"(w[8]), "r"(w[9]), "r"(w[10]), "r"(w[11]), "r"(w[12]), "r"(w[13]), "r"(w[14]), "r"(w[15]), "r"(w[16]), "r"(w[17]), "r"(w[18]), "r"(w[19]), "r"(w[20]), "r"(w[21]), "r"(w[22]), "r"(w[23]), "r"(w[24]), "r"(w[25]), "r"(w[26]), "r"(w[27]), "r"(w[28]), "r"(w[29]), "r"(w[30]), "r"(w[31]), "r"(w[32]), "r"(w[33]), "r"(w[34]), "r"(w[35]), "r"(w[36]), "r"(w[37]), "r"(w[38]), "r"(w[39]), "r"(dx), "l"(de), "l"(dh)
      : "memory");
  }
  static __device__ __forceinline__ void wait_g(float* g) {
    asm volatile("wgmma.wait_group.sync.aligned 1;\n"
      : "+f"(g[0]), "+f"(g[1]), "+f"(g[2]), "+f"(g[3]), "+f"(g[4]), "+f"(g[5]), "+f"(g[6]), "+f"(g[7]), "+f"(g[8]), "+f"(g[9]), "+f"(g[10]), "+f"(g[11]), "+f"(g[12]), "+f"(g[13]), "+f"(g[14]), "+f"(g[15])
      :: "memory");
  }
  static __device__ __forceinline__ void wait_h(float* h) {
    asm volatile("wgmma.wait_group.sync.aligned 0;\n"
      : "+f"(h[0]), "+f"(h[1]), "+f"(h[2]), "+f"(h[3]), "+f"(h[4]), "+f"(h[5]), "+f"(h[6]), "+f"(h[7]), "+f"(h[8]), "+f"(h[9]), "+f"(h[10]), "+f"(h[11]), "+f"(h[12]), "+f"(h[13]), "+f"(h[14]), "+f"(h[15])
      :: "memory");
  }
};
template<> struct TileMMA<5> {
  static __device__ __forceinline__ void issue(float* g, float* h, const uint32_t* w, uint32_t dx, uint64_t de, uint64_t dh, uint64_t dc) {
    asm volatile(
      "{\n.reg .b64 dx0, dx1, dx2, dx3;\n.reg .b32 l1, l2, l3, hx;\nmov.b32 hx, 0x40000040;\n"
      "add.u32 l1, %80, 2;\nadd.u32 l2, %80, 4;\nadd.u32 l3, %80, 6;\n"
      "mov.b64 dx0, {%80, hx};\nmov.b64 dx1, {l1, hx};\nmov.b64 dx2, {l2, hx};\nmov.b64 dx3, {l3, hx};\n"
      "wgmma.fence.sync.aligned;\n"
      "wgmma.mma_async.sync.aligned.m64n40k16.f32.bf16.bf16 {%0, %1, %2, %3, %4, %5, %6, %7, %8, %9, %10, %11, %12, %13, %14, %15, %16, %17, %18, %19}, {%76, %77, %78, %79}, %82, 0, 1, 1, 0;\n"
      "wgmma.mma_async.sync.aligned.m64n40k16.f32.bf16.bf16 {%0, %1, %2, %3, %4, %5, %6, %7, %8, %9, %10, %11, %12, %13, %14, %15, %16, %17, %18, %19}, {%56, %57, %58, %59}, %81, 1, 1, 1, 0;\n"
      "wgmma.mma_async.sync.aligned.m64n40k16.f32.bf16.bf16 {%0, %1, %2, %3, %4, %5, %6, %7, %8, %9, %10, %11, %12, %13, %14, %15, %16, %17, %18, %19}, {%40, %41, %42, %43}, dx0, 1, 1, 1, 0;\n"
      "wgmma.mma_async.sync.aligned.m64n40k16.f32.bf16.bf16 {%0, %1, %2, %3, %4, %5, %6, %7, %8, %9, %10, %11, %12, %13, %14, %15, %16, %17, %18, %19}, {%44, %45, %46, %47}, dx1, 1, 1, 1, 0;\n"
      "wgmma.mma_async.sync.aligned.m64n40k16.f32.bf16.bf16 {%0, %1, %2, %3, %4, %5, %6, %7, %8, %9, %10, %11, %12, %13, %14, %15, %16, %17, %18, %19}, {%48, %49, %50, %51}, dx2, 1, 1, 1, 0;\n"
      "wgmma.mma_async.sync.aligned.m64n40k16.f32.bf16.bf16 {%0, %1, %2, %3, %4, %5, %6, %7, %8, %9, %10, %11, %12, %13, %14, %15, %16, %17, %18, %19}, {%52, %53, %54, %55}, dx3, 1, 1, 1, 0;\n"
      "wgmma.commit_group.sync.aligned;\n"
      "wgmma.mma_async.sync.aligned.m64n40k16.f32.bf16.bf16 {%20, %21, %22, %23, %24, %25, %26, %27, %28, %29, %30, %31, %32, %33, %34, %35, %36, %37, %38, %39}, {%60, %61, %62, %63}, dx0, 0, 1, 1, 0;\n"
      "wgmma.mma_async.sync.aligned.m64n40k16.f32.bf16.bf16 {%20, %21, %22, %23, %24, %25, %26, %27, %28, %29, %30, %31, %32, %33, %34, %35, %36, %37, %38, %39}, {%64, %65, %66, %67}, dx1, 1, 1, 1, 0;\n"
      "wgmma.mma_async.sync.aligned.m64n40k16.f32.bf16.bf16 {%20, %21, %22, %23, %24, %25, %26, %27, %28, %29, %30, %31, %32, %33, %34, %35, %36, %37, %38, %39}, {%68, %69, %70, %71}, dx2, 1, 1, 1, 0;\n"
      "wgmma.mma_async.sync.aligned.m64n40k16.f32.bf16.bf16 {%20, %21, %22, %23, %24, %25, %26, %27, %28, %29, %30, %31, %32, %33, %34, %35, %36, %37, %38, %39}, {%72, %73, %74, %75}, dx3, 1, 1, 1, 0;\n"
      "wgmma.commit_group.sync.aligned;\n}\n"
      : "=f"(g[0]), "=f"(g[1]), "=f"(g[2]), "=f"(g[3]), "=f"(g[4]), "=f"(g[5]), "=f"(g[6]), "=f"(g[7]), "=f"(g[8]), "=f"(g[9]), "=f"(g[10]), "=f"(g[11]), "=f"(g[12]), "=f"(g[13]), "=f"(g[14]), "=f"(g[15]), "=f"(g[16]), "=f"(g[17]), "=f"(g[18]), "=f"(g[19]),
        "=f"(h[0]), "=f"(h[1]), "=f"(h[2]), "=f"(h[3]), "=f"(h[4]), "=f"(h[5]), "=f"(h[6]), "=f"(h[7]), "=f"(h[8]), "=f"(h[9]), "=f"(h[10]), "=f"(h[11]), "=f"(h[12]), "=f"(h[13]), "=f"(h[14]), "=f"(h[15]), "=f"(h[16]), "=f"(h[17]), "=f"(h[18]), "=f"(h[19])
      : "r"(w[0]), "r"(w[1]), "r"(w[2]), "r"(w[3]), "r"(w[4]), "r"(w[5]), "r"(w[6]), "r"(w[7]), "r"(w[8]), "r"(w[9]), "r"(w[10]), "r"(w[11]), "r"(w[12]), "r"(w[13]), "r"(w[14]), "r"(w[15]), "r"(w[16]), "r"(w[17]), "r"(w[18]), "r"(w[19]), "r"(w[20]), "r"(w[21]), "r"(w[22]), "r"(w[23]), "r"(w[24]), "r"(w[25]), "r"(w[26]), "r"(w[27]), "r"(w[28]), "r"(w[29]), "r"(w[30]), "r"(w[31]), "r"(w[32]), "r"(w[33]), "r"(w[34]), "r"(w[35]), "r"(w[36]), "r"(w[37]), "r"(w[38]), "r"(w[39]), "r"(dx), "l"(de), "l"(dh)
      : "memory");
  }
  static __device__ __forceinline__ void wait_g(float* g) {
    asm volatile("wgmma.wait_group.sync.aligned 1;\n"
      : "+f"(g[0]), "+f"(g[1]), "+f"(g[2]), "+f"(g[3]), "+f"(g[4]), "+f"(g[5]), "+f"(g[6]), "+f"(g[7]), "+f"(g[8]), "+f"(g[9]), "+f"(g[10]), "+f"(g[11]), "+f"(g[12]), "+f"(g[13]), "+f"(g[14]), "+f"(g[15]), "+f"(g[16]), "+f"(g[17]), "+f"(g[18]), "+f"(g[19])
      :: "memory");
  }
  static __device__ __forceinline__ void wait_h(float* h) {
    asm volatile("wgmma.wait_group.sync.aligned 0;\n"
      : "+f"(h[0]), "+f"(h[1]), "+f"(h[2]), "+f"(h[3]), "+f"(h[4]), "+f"(h[5]), "+f"(h[6]), "+f"(h[7]), "+f"(h[8]), "+f"(h[9]), "+f"(h[10]), "+f"(h[11]), "+f"(h[12]), "+f"(h[13]), "+f"(h[14]), "+f"(h[15]), "+f"(h[16]), "+f"(h[17]), "+f"(h[18]), "+f"(h[19])
      :: "memory");
  }
};
template<> struct TileMMA<6> {
  static __device__ __forceinline__ void issue(float* g, float* h, const uint32_t* w, uint32_t dx, uint64_t de, uint64_t dh, uint64_t dc) {
    asm volatile(
      "{\n.reg .b64 dx0, dx1, dx2, dx3;\n.reg .b32 l1, l2, l3, hx;\nmov.b32 hx, 0x40000040;\n"
      "add.u32 l1, %88, 2;\nadd.u32 l2, %88, 4;\nadd.u32 l3, %88, 6;\n"
      "mov.b64 dx0, {%88, hx};\nmov.b64 dx1, {l1, hx};\nmov.b64 dx2, {l2, hx};\nmov.b64 dx3, {l3, hx};\n"
      "wgmma.fence.sync.aligned;\n"
      "wgmma.mma_async.sync.aligned.m64n48k16.f32.bf16.bf16 {%0, %1, %2, %3, %4, %5, %6, %7, %8, %9, %10, %11, %12, %13, %14, %15, %16, %17, %18, %19, %20, %21, %22, %23}, {%84, %85, %86, %87}, %90, 0, 1, 1, 0;\n"
      "wgmma.mma_async.sync.aligned.m64n48k16.f32.bf16.bf16 {%0, %1, %2, %3, %4, %5, %6, %7, %8, %9, %10, %11, %12, %13, %14, %15, %16, %17, %18, %19, %20, %21, %22, %23}, {%64, %65, %66, %67}, %89, 1, 1, 1, 0;\n"
      "wgmma.mma_async.sync.aligned.m64n48k16.f32.bf16.bf16 {%0, %1, %2, %3, %4, %5, %6, %7, %8, %9, %10, %11, %12, %13, %14, %15, %16, %17, %18, %19, %20, %21, %22, %23}, {%48, %49, %50, %51}, dx0, 1, 1, 1, 0;\n"
      "wgmma.mma_async.sync.aligned.m64n48k16.f32.bf16.bf16 {%0, %1, %2, %3, %4, %5, %6, %7, %8, %9, %10, %11, %12, %13, %14, %15, %16, %17, %18, %19, %20, %21, %22, %23}, {%52, %53, %54, %55}, dx1, 1, 1, 1, 0;\n"
      "wgmma.mma_async.sync.aligned.m64n48k16.f32.bf16.bf16 {%0, %1, %2, %3, %4, %5, %6, %7, %8, %9, %10, %11, %12, %13, %14, %15, %16, %17, %18, %19, %20, %21, %22, %23}, {%56, %57, %58, %59}, dx2, 1, 1, 1, 0;\n"
      "wgmma.mma_async.sync.aligned.m64n48k16.f32.bf16.bf16 {%0, %1, %2, %3, %4, %5, %6, %7, %8, %9, %10, %11, %12, %13, %14, %15, %16, %17, %18, %19, %20, %21, %22, %23}, {%60, %61, %62, %63}, dx3, 1, 1, 1, 0;\n"
      "wgmma.commit_group.sync.aligned;\n"
      "wgmma.mma_async.sync.aligned.m64n48k16.f32.bf16.bf16 {%24, %25, %26, %27, %28, %29, %30, %31, %32, %33, %34, %35, %36, %37, %38, %39, %40, %41, %42, %43, %44, %45, %46, %47}, {%68, %69, %70, %71}, dx0, 0, 1, 1, 0;\n"
      "wgmma.mma_async.sync.aligned.m64n48k16.f32.bf16.bf16 {%24, %25, %26, %27, %28, %29, %30, %31, %32, %33, %34, %35, %36, %37, %38, %39, %40, %41, %42, %43, %44, %45, %46, %47}, {%72, %73, %74, %75}, dx1, 1, 1, 1, 0;\n"
      "wgmma.mma_async.sync.aligned.m64n48k16.f32.bf16.bf16 {%24, %25, %26, %27, %28, %29, %30, %31, %32, %33, %34, %35, %36, %37, %38, %39, %40, %41, %42, %43, %44, %45, %46, %47}, {%76, %77, %78, %79}, dx2, 1, 1, 1, 0;\n"
      "wgmma.mma_async.sync.aligned.m64n48k16.f32.bf16.bf16 {%24, %25, %26, %27, %28, %29, %30, %31, %32, %33, %34, %35, %36, %37, %38, %39, %40, %41, %42, %43, %44, %45, %46, %47}, {%80, %81, %82, %83}, dx3, 1, 1, 1, 0;\n"
      "wgmma.commit_group.sync.aligned;\n}\n"
      : "=f"(g[0]), "=f"(g[1]), "=f"(g[2]), "=f"(g[3]), "=f"(g[4]), "=f"(g[5]), "=f"(g[6]), "=f"(g[7]), "=f"(g[8]), "=f"(g[9]), "=f"(g[10]), "=f"(g[11]), "=f"(g[12]), "=f"(g[13]), "=f"(g[14]), "=f"(g[15]), "=f"(g[16]), "=f"(g[17]), "=f"(g[18]), "=f"(g[19]), "=f"(g[20]), "=f"(g[21]), "=f"(g[22]), "=f"(g[23]),
        "=f"(h[0]), "=f"(h[1]), "=f"(h[2]), "=f"(h[3]), "=f"(h[4]), "=f"(h[5]), "=f"(h[6]), "=f"(h[7]), "=f"(h[8]), "=f"(h[9]), "=f"(h[10]), "=f"(h[11]), "=f"(h[12]), "=f"(h[13]), "=f"(h[14]), "=f"(h[15]), "=f"(h[16]), "=f"(h[17]), "=f"(h[18]), "=f"(h[19]), "=f"(h[20]), "=f"(h[21]), "=f"(h[22]), "=f"(h[23])
      : "r"(w[0]), "r"(w[1]), "r"(w[2]), "r"(w[3]), "r"(w[4]), "r"(w[5]), "r"(w[6]), "r"(w[7]), "r"(w[8]), "r"(w[9]), "r"(w[10]), "r"(w[11]), "r"(w[12]), "r"(w[13]), "r"(w[14]), "r"(w[15]), "r"(w[16]), "r"(w[17]), "r"(w[18]), "r"(w[19]), "r"(w[20]), "r"(w[21]), "r"(w[22]), "r"(w[23]), "r"(w[24]), "r"(w[25]), "r"(w[26]), "r"(w[27]), "r"(w[28]), "r"(w[29]), "r"(w[30]), "r"(w[31]), "r"(w[32]), "r"(w[33]), "r"(w[34]), "r"(w[35]), "r"(w[36]), "r"(w[37]), "r"(w[38]), "r"(w[39]), "r"(dx), "l"(de), "l"(dh)
      : "memory");
  }
  static __device__ __forceinline__ void wait_g(float* g) {
    asm volatile("wgmma.wait_group.sync.aligned 1;\n"
      : "+f"(g[0]), "+f"(g[1]), "+f"(g[2]), "+f"(g[3]), "+f"(g[4]), "+f"(g[5]), "+f"(g[6]), "+f"(g[7]), "+f"(g[8]), "+f"(g[9]), "+f"(g[10]), "+f"(g[11]), "+f"(g[12]), "+f"(g[13]), "+f"(g[14]), "+f"(g[15]), "+f"(g[16]), "+f"(g[17]), "+f"(g[18]), "+f"(g[19]), "+f"(g[20]), "+f"(g[21]), "+f"(g[22]), "+f"(g[23])
      :: "memory");
  }
  static __device__ __forceinline__ void wait_h(float* h) {
    asm volatile("wgmma.wait_group.sync.aligned 0;\n"
      : "+f"(h[0]), "+f"(h[1]), "+f"(h[2]), "+f"(h[3]), "+f"(h[4]), "+f"(h[5]), "+f"(h[6]), "+f"(h[7]), "+f"(h[8]), "+f"(h[9]), "+f"(h[10]), "+f"(h[11]), "+f"(h[12]), "+f"(h[13]), "+f"(h[14]), "+f"(h[15]), "+f"(h[16]), "+f"(h[17]), "+f"(h[18]), "+f"(h[19]), "+f"(h[20]), "+f"(h[21]), "+f"(h[22]), "+f"(h[23])
      :: "memory");
  }
};
template<> struct TileMMA<7> {
  static __device__ __forceinline__ void issue(float* g, float* h, const uint32_t* w, uint32_t dx, uint64_t de, uint64_t dh, uint64_t dc) {
    asm volatile(
      "{\n.reg .b64 dx0, dx1, dx2, dx3;\n.reg .b32 l1, l2, l3, hx;\nmov.b32 hx, 0x40000040;\n"
      "add.u32 l1, %96, 2;\nadd.u32 l2, %96, 4;\nadd.u32 l3, %96, 6;\n"
      "mov.b64 dx0, {%96, hx};\nmov.b64 dx1, {l1, hx};\nmov.b64 dx2, {l2, hx};\nmov.b64 dx3, {l3, hx};\n"
      "wgmma.fence.sync.aligned;\n"
      "wgmma.mma_async.sync.aligned.m64n56k16.f32.bf16.bf16 {%0, %1, %2, %3, %4, %5, %6, %7, %8, %9, %10, %11, %12, %13, %14, %15, %16, %17, %18, %19, %20, %21, %22, %23, %24, %25, %26, %27}, {%92, %93, %94, %95}, %98, 0, 1, 1, 0;\n"
      "wgmma.mma_async.sync.aligned.m64n56k16.f32.bf16.bf16 {%0, %1, %2, %3, %4, %5, %6, %7, %8, %9, %10, %11, %12, %13, %14, %15, %16, %17, %18, %19, %20, %21, %22, %23, %24, %25, %26, %27}, {%72, %73, %74, %75}, %97, 1, 1, 1, 0;\n"
      "wgmma.mma_async.sync.aligned.m64n56k16.f32.bf16.bf16 {%0, %1, %2, %3, %4, %5, %6, %7, %8, %9, %10, %11, %12, %13, %14, %15, %16, %17, %18, %19, %20, %21, %22, %23, %24, %25, %26, %27}, {%56, %57, %58, %59}, dx0, 1, 1, 1, 0;\n"
      "wgmma.mma_async.sync.aligned.m64n56k16.f32.bf16.bf16 {%0, %1, %2, %3, %4, %5, %6, %7, %8, %9, %10, %11, %12, %13, %14, %15, %16, %17, %18, %19, %20, %21, %22, %23, %24, %25, %26, %27}, {%60, %61, %62, %63}, dx1, 1, 1, 1, 0;\n"
      "wgmma.mma_async.sync.aligned.m64n56k16.f32.bf16.bf16 {%0, %1, %2, %3, %4, %5, %6, %7, %8, %9, %10, %11, %12, %13, %14, %15, %16, %17, %18, %19, %20, %21, %22, %23, %24, %25, %26, %27}, {%64, %65, %66, %67}, dx2, 1, 1, 1, 0;\n"
      "wgmma.mma_async.sync.aligned.m64n56k16.f32.bf16.bf16 {%0, %1, %2, %3, %4, %5, %6, %7, %8, %9, %10, %11, %12, %13, %14, %15, %16, %17, %18, %19, %20, %21, %22, %23, %24, %25, %26, %27}, {%68, %69, %70, %71}, dx3, 1, 1, 1, 0;\n"
      "wgmma.commit_group.sync.aligned;\n"
      "wgmma.mma_async.sync.aligned.m64n56k16.f32.bf16.bf16 {%28, %29, %30, %31, %32, %33, %34, %35, %36, %37, %38, %39, %40, %41, %42, %43, %44, %45, %46, %47, %48, %49, %50, %51, %52, %53, %54, %55}, {%76, %77, %78, %79}, dx0, 0, 1, 1, 0;\n"
      "wgmma.mma_async.sync.aligned.m64n56k16.f32.bf16.bf16 {%28, %29, %30, %31, %32, %33, %34, %35, %36, %37, %38, %39, %40, %41, %42, %43, %44, %45, %46, %47, %48, %49, %50, %51, %52, %53, %54, %55}, {%80, %81, %82, %83}, dx1, 1, 1, 1, 0;\n"
      "wgmma.mma_async.sync.aligned.m64n56k16.f32.bf16.bf16 {%28, %29, %30, %31, %32, %33, %34, %35, %36, %37, %38, %39, %40, %41, %42, %43, %44, %45, %46, %47, %48, %49, %50, %51, %52, %53, %54, %55}, {%84, %85, %86, %87}, dx2, 1, 1, 1, 0;\n"
      "wgmma.mma_async.sync.aligned.m64n56k16.f32.bf16.bf16 {%28, %29, %30, %31, %32, %33, %34, %35, %36, %37, %38, %39, %40, %41, %42, %43, %44, %45, %46, %47, %48, %49, %50, %51, %52, %53, %54, %55}, {%88, %89, %90, %91}, dx3, 1, 1, 1, 0;\n"
      "wgmma.commit_group.sync.aligned;\n}\n"
      : "=f"(g[0]), "=f"(g[1]), "=f"(g[2]), "=f"(g[3]), "=f"(g[4]), "=f"(g[5]), "=f"(g[6]), "=f"(g[7]), "=f"(g[8]), "=f"(g[9]), "=f"(g[10]), "=f"(g[11]), "=f"(g[12]), "=f"(g[13]), "=f"(g[14]), "=f"(g[15]), "=f"(g[16]), "=f"(g[17]), "=f"(g[18]), "=f"(g[19]), "=f"(g[20]), "=f"(g[21]), "=f"(g[22]), "=f"(g[23]), "=f"(g[24]), "=f"(g[25]), "=f"(g[26]), "=f"(g[27]),
        "=f"(h[0]), "=f"(h[1]), "=f"(h[2]), "=f"(h[3]), "=f"(h[4]), "=f"(h[5]), "=f"(h[6]), "=f"(h[7]), "=f"(h[8]), "=f"(h[9]), "=f"(h[10]), "=f"(h[11]), "=f"(h[12]), "=f"(h[13]), "=f"(h[14]), "=f"(h[15]), "=f"(h[16]), "=f"(h[17]), "=f"(h[18]), "=f"(h[19]), "=f"(h[20]), "=f"(h[21]), "=f"(h[22]), "=f"(h[23]), "=f"(h[24]), "=f"(h[25]), "=f"(h[26]), "=f"(h[27])
      : "r"(w[0]), "r"(w[1]), "r"(w[2]), "r"(w[3]), "r"(w[4]), "r"(w[5]), "r"(w[6]), "r"(w[7]), "r"(w[8]), "r"(w[9]), "r"(w[10]), "r"(w[11]), "r"(w[12]), "r"(w[13]), "r"(w[14]), "r"(w[15]), "r"(w[16]), "r"(w[17]), "r"(w[18]), "r"(w[19]), "r"(w[20]), "r"(w[21]), "r"(w[22]), "r"(w[23]), "r"(w[24]), "r"(w[25]), "r"(w[26]), "r"(w[27]), "r"(w[28]), "r"(w[29]), "r"(w[30]), "r"(w[31]), "r"(w[32]), "r"(w[33]), "r"(w[34]), "r"(w[35]), "r"(w[36]), "r"(w[37]), "r"(w[38]), "r"(w[39]), "r"(dx), "l"(de), "l"(dh)
      : "memory");
  }
  static __device__ __forceinline__ void wait_g(float* g) {
    asm volatile("wgmma.wait_group.sync.aligned 1;\n"
      : "+f"(g[0]), "+f"(g[1]), "+f"(g[2]), "+f"(g[3]), "+f"(g[4]), "+f"(g[5]), "+f"(g[6]), "+f"(g[7]), "+f"(g[8]), "+f"(g[9]), "+f"(g[10]), "+f"(g[11]), "+f"(g[12]), "+f"(g[13]), "+f"(g[14]), "+f"(g[15]), "+f"(g[16]), "+f"(g[17]), "+f"(g[18]), "+f"(g[19]), "+f"(g[20]), "+f"(g[21]), "+f"(g[22]), "+f"(g[23]), "+f"(g[24]), "+f"(g[25]), "+f"(g[26]), "+f"(g[27])
      :: "memory");
  }
  static __device__ __forceinline__ void wait_h(float* h) {
    asm volatile("wgmma.wait_group.sync.aligned 0;\n"
      : "+f"(h[0]), "+f"(h[1]), "+f"(h[2]), "+f"(h[3]), "+f"(h[4]), "+f"(h[5]), "+f"(h[6]), "+f"(h[7]), "+f"(h[8]), "+f"(h[9]), "+f"(h[10]), "+f"(h[11]), "+f"(h[12]), "+f"(h[13]), "+f"(h[14]), "+f"(h[15]), "+f"(h[16]), "+f"(h[17]), "+f"(h[18]), "+f"(h[19]), "+f"(h[20]), "+f"(h[21]), "+f"(h[22]), "+f"(h[23]), "+f"(h[24]), "+f"(h[25]), "+f"(h[26]), "+f"(h[27])
      :: "memory");
  }
};
template<> struct TileMMA<8> {
  static __device__ __forceinline__ void issue(float* g, float* h, const uint32_t* w, uint32_t dx, uint64_t de, uint64_t dh, uint64_t dc) {
    asm volatile(
      "{\n.reg .b64 dx0, dx1, dx2, dx3;\n.reg .b32 l1, l2, l3, hx;\nmov.b32 hx, 0x40000040;\n"
      "add.u32 l1, %104, 2;\nadd.u32 l2, %104, 4;\nadd.u32 l3, %104, 6;\n"
      "mov.b64 dx0, {%104, hx};\nmov.b64 dx1, {l1, hx};\nmov.b64 dx2, {l2, hx};\nmov.b64 dx3, {l3, hx};\n"
      "wgmma.fence.sync.aligned;\n"
      "wgmma.mma_async.sync.aligned.m64n64k16.f32.bf16.bf16 {%0, %1, %2, %3, %4, %5, %6, %7, %8, %9, %10, %11, %12, %13, %14, %15, %16, %17, %18, %19, %20, %21, %22, %23, %24, %25, %26, %27, %28, %29, %30, %31}, {%100, %101, %102, %103}, %106, 0, 1, 1, 0;\n"
      "wgmma.mma_async.sync.aligned.m64n64k16.f32.bf16.bf16 {%0, %1, %2, %3, %4, %5, %6, %7, %8, %9, %10, %11, %12, %13, %14, %15, %16, %17, %18, %19, %20, %21, %22, %23, %24, %25, %26, %27, %28, %29, %30, %31}, {%80, %81, %82, %83}, %105, 1, 1, 1, 0;\n"
      "wgmma.mma_async.sync.aligned.m64n64k16.f32.bf16.bf16 {%0, %1, %2, %3, %4, %5, %6, %7, %8, %9, %10, %11, %12, %13, %14, %15, %16, %17, %18, %19, %20, %21, %22, %23, %24, %25, %26, %27, %28, %29, %30, %31}, {%64, %65, %66, %67}, dx0, 1, 1, 1, 0;\n"
      "wgmma.mma_async.sync.aligned.m64n64k16.f32.bf16.bf16 {%0, %1, %2, %3, %4, %5, %6, %7, %8, %9, %10, %11, %12, %13, %14, %15, %16, %17, %18, %19, %20, %21, %22, %23, %24, %25, %26, %27, %28, %29, %30, %31}, {%68, %69, %70, %71}, dx1, 1, 1, 1, 0;\n"
      "wgmma.mma_async.sync.aligned.m64n64k16.f32.bf16.bf16 {%0, %1, %2, %3, %4, %5, %6, %7, %8, %9, %10, %11, %12, %13, %14, %15, %16, %17, %18, %19, %20, %21, %22, %23, %24, %25, %26, %27, %28, %29, %30, %31}, {%72, %73, %74, %75}, dx2, 1, 1, 1, 0;\n"
      "wgmma.mma_async.sync.aligned.m64n64k16.f32.bf16.bf16 {%0, %1, %2, %3, %4, %5, %6, %7, %8, %9, %10, %11, %12, %13, %14, %15, %16, %17, %18, %19, %20, %21, %22, %23, %24, %25, %26, %27, %28, %29, %30, %31}, {%76, %77, %78, %79}, dx3, 1, 1, 1, 0;\n"
      "wgmma.commit_group.sync.aligned;\n"
      "wgmma.mma_async.sync.aligned.m64n64k16.f32.bf16.bf16 {%32, %33, %34, %35, %36, %37, %38, %39, %40, %41, %42, %43, %44, %45, %46, %47, %48, %49, %50, %51, %52, %53, %54, %55, %56, %57, %58, %59, %60, %61, %62, %63}, {%84, %85, %86, %87}, dx0, 0, 1, 1, 0;\n"
      "wgmma.mma_async.sync.aligned.m64n64k16.f32.bf16.bf16 {%32, %33, %34, %35, %36, %37, %38, %39, %40, %41, %42, %43, %44, %45, %46, %47, %48, %49, %50, %51, %52, %53, %54, %55, %56, %57, %58, %59, %60, %61, %62, %63}, {%88, %89, %90, %91}, dx1, 1, 1, 1, 0;\n"
      "wgmma.mma_async.sync.aligned.m64n64k16.f32.bf16.bf16 {%32, %33, %34, %35, %36, %37, %38, %39, %40, %41, %42, %43, %44, %45, %46, %47, %48, %49, %50, %51, %52, %53, %54, %55, %56, %57, %58, %59, %60, %61, %62, %63}, {%92, %93, %94, %95}, dx2, 1, 1, 1, 0;\n"
      "wgmma.mma_async.sync.aligned.m64n64k16.f32.bf16.bf16 {%32, %33, %34, %35, %36, %37, %38, %39, %40, %41, %42, %43, %44, %45, %46, %47, %48, %49, %50, %51, %52, %53, %54, %55, %56, %57, %58, %59, %60, %61, %62, %63}, {%96, %97, %98, %99}, dx3, 1, 1, 1, 0;\n"
      "wgmma.commit_group.sync.aligned;\n}\n"
      : "=f"(g[0]), "=f"(g[1]), "=f"(g[2]), "=f"(g[3]), "=f"(g[4]), "=f"(g[5]), "=f"(g[6]), "=f"(g[7]), "=f"(g[8]), "=f"(g[9]), "=f"(g[10]), "=f"(g[11]), "=f"(g[12]), "=f"(g[13]), "=f"(g[14]), "=f"(g[15]), "=f"(g[16]), "=f"(g[17]), "=f"(g[18]), "=f"(g[19]), "=f"(g[20]), "=f"(g[21]), "=f"(g[22]), "=f"(g[23]), "=f"(g[24]), "=f"(g[25]), "=f"(g[26]), "=f"(g[27]), "=f"(g[28]), "=f"(g[29]), "=f"(g[30]), "=f"(g[31]),
        "=f"(h[0]), "=f"(h[1]), "=f"(h[2]), "=f"(h[3]), "=f"(h[4]), "=f"(h[5]), "=f"(h[6]), "=f"(h[7]), "=f"(h[8]), "=f"(h[9]), "=f"(h[10]), "=f"(h[11]), "=f"(h[12]), "=f"(h[13]), "=f"(h[14]), "=f"(h[15]), "=f"(h[16]), "=f"(h[17]), "=f"(h[18]), "=f"(h[19]), "=f"(h[20]), "=f"(h[21]), "=f"(h[22]), "=f"(h[23]), "=f"(h[24]), "=f"(h[25]), "=f"(h[26]), "=f"(h[27]), "=f"(h[28]), "=f"(h[29]), "=f"(h[30]), "=f"(h[31])
      : "r"(w[0]), "r"(w[1]), "r"(w[2]), "r"(w[3]), "r"(w[4]), "r"(w[5]), "r"(w[6]), "r"(w[7]), "r"(w[8]), "r"(w[9]), "r"(w[10]), "r"(w[11]), "r"(w[12]), "r"(w[13]), "r"(w[14]), "r"(w[15]), "r"(w[16]), "r"(w[17]), "r"(w[18]), "r"(w[19]), "r"(w[20]), "r"(w[21]), "r"(w[22]), "r"(w[23]), "r"(w[24]), "r"(w[25]), "r"(w[26]), "r"(w[27]), "r"(w[28]), "r"(w[29]), "r"(w[30]), "r"(w[31]), "r"(w[32]), "r"(w[33]), "r"(w[34]), "r"(w[35]), "r"(w[36]), "r"(w[37]), "r"(w[38]), "r"(w[39]), "r"(dx), "l"(de), "l"(dh)
      : "memory");
  }
  static __device__ __forceinline__ void wait_g(float* g) {
    asm volatile("wgmma.wait_group.sync.aligned 1;\n"
      : "+f"(g[0]), "+f"(g[1]), "+f"(g[2]), "+f"(g[3]), "+f"(g[4]), "+f"(g[5]), "+f"(g[6]), "+f"(g[7]), "+f"(g[8]), "+f"(g[9]), "+f"(g[10]), "+f"(g[11]), "+f"(g[12]), "+f"(g[13]), "+f"(g[14]), "+f"(g[15]), "+f"(g[16]), "+f"(g[17]), "+f"(g[18]), "+f"(g[19]), "+f"(g[20]), "+f"(g[21]), "+f"(g[22]), "+f"(g[23]), "+f"(g[24]), "+f"(g[25]), "+f"(g[26]), "+f"(g[27]), "+f"(g[28]), "+f"(g[29]), "+f"(g[30]), "+f"(g[31])
      :: "memory");
  }
  static __device__ __forceinline__ void wait_h(float* h) {
    asm volatile("wgmma.wait_group.sync.aligned 0;\n"
      : "+f"(h[0]), "+f"(h[1]), "+f"(h[2]), "+f"(h[3]), "+f"(h[4]), "+f"(h[5]), "+f"(h[6]), "+f"(h[7]), "+f"(h[8]), "+f"(h[9]), "+f"(h[10]), "+f"(h[11]), "+f"(h[12]), "+f"(h[13]), "+f"(h[14]), "+f"(h[15]), "+f"(h[16]), "+f"(h[17]), "+f"(h[18]), "+f"(h[19]), "+f"(h[20]), "+f"(h[21]), "+f"(h[22]), "+f"(h[23]), "+f"(h[24]), "+f"(h[25]), "+f"(h[26]), "+f"(h[27]), "+f"(h[28]), "+f"(h[29]), "+f"(h[30]), "+f"(h[31])
      :: "memory");
  }
};
template<> struct TileMMA<9> {
  static __device__ __forceinline__ void issue(float* g, float* h, const uint32_t* w, uint32_t dx, uint64_t de, uint64_t dh, uint64_t dc) {
    asm volatile(
      "{\n.reg .b64 dx0, dx1, dx2, dx3;\n.reg .b32 l1, l2, l3, hx;\nmov.b32 hx, 0x40000040;\n"
      "add.u32 l1, %112, 2;\nadd.u32 l2, %112, 4;\nadd.u32 l3, %112, 6;\n"
      "mov.b64 dx0, {%112, hx};\nmov.b64 dx1, {l1, hx};\nmov.b64 dx2, {l2, hx};\nmov.b64 dx3, {l3, hx};\n"
      "wgmma.fence.sync.aligned;\n"
      "wgmma.mma_async.sync.aligned.m64n72k16.f32.bf16.bf16 {%0, %1, %2, %3, %4, %5, %6, %7, %8, %9, %10, %11, %12, %13, %14, %15, %16, %17, %18, %19, %20, %21, %22, %23, %24, %25, %26, %27, %28, %29, %30, %31, %32, %33, %34, %35}, {%108, %109, %110, %111}, %114, 0, 1, 1, 0;\n"
      "wgmma.mma_async.sync.aligned.m64n72k16.f32.bf16.bf16 {%0, %1, %2, %3, %4, %5, %6, %7, %8, %9, %10, %11, %12, %13, %14, %15, %16, %17, %18, %19, %20, %21, %22, %23, %24, %25, %26, %27, %28, %29, %30, %31, %32, %33, %34, %35}, {%88, %89, %90, %91}, %113, 1, 1, 1, 0;\n"
      "wgmma.mma_async.sync.aligned.m64n72k16.f32.bf16.bf16 {%0, %1, %2, %3, %4, %5, %6, %7, %8, %9, %10, %11, %12, %13, %14, %15, %16, %17, %18, %19, %20, %21, %22, %23, %24, %25, %26, %27, %28, %29, %30, %31, %32, %33, %34, %35}, {%72, %73, %74, %75}, dx0, 1, 1, 1, 0;\n"
      "wgmma.mma_async.sync.aligned.m64n72k16.f32.bf16.bf16 {%0, %1, %2, %3, %4, %5, %6, %7, %8, %9, %10, %11, %12, %13, %14, %15, %16, %17, %18, %19, %20, %21, %22, %23, %24, %25, %26, %27, %28, %29, %30, %31, %32, %33, %34, %35}, {%76, %77, %78, %79}, dx1, 1, 1, 1, 0;\n"
      "wgmma.mma_async.sync.aligned.m64n72k16.f32.bf16.bf16 {%0, %1, %2, %3, %4, %5, %6, %7, %8, %9, %10, %11, %12, %13, %14, %15, %16, %17, %18, %19, %20, %21, %22, %23, %24, %25, %26, %27, %28, %29, %30, %31, %32, %33, %34, %35}, {%80, %81, %82, %83}, dx2, 1, 1, 1, 0;\n"
      "wgmma.mma_async.sync.aligned.m64n72k16.f32.bf16.bf16 {%0, %1, %2, %3, %4, %5, %6, %7, %8, %9, %10, %11, %12, %13, %14, %15, %16, %17, %18, %19, %20, %21, %22, %23, %24, %25, %26, %27, %28, %29, %30, %31, %32, %33, %34, %35}, {%84, %85, %86, %87}, dx3, 1, 1, 1, 0;\n"
      "wgmma.commit_group.sync.aligned;\n"
      "wgmma.mma_async.sync.aligned.m64n72k16.f32.bf16.bf16 {%36, %37, %38, %39, %40, %41, %42, %43, %44, %45, %46, %47, %48, %49, %50, %51, %52, %53, %54, %55, %56, %57, %58, %59, %60, %61, %62, %63, %64, %65, %66, %67, %68, %69, %70, %71}, {%92, %93, %94, %95}, dx0, 0, 1, 1, 0;\n"
      "wgmma.mma_async.sync.aligned.m64n72k16.f32.bf16.bf16 {%36, %37, %38, %39, %40, %41, %42, %43, %44, %45, %46, %47, %48, %49, %50, %51, %52, %53, %54, %55, %56, %57, %58, %59, %60, %61, %62, %63, %64, %65, %66, %67, %68, %69, %70, %71}, {%96, %97, %98, %99}, dx1, 1, 1, 1, 0;\n"
      "wgmma.mma_async.sync.aligned.m64n72k16.f32.bf16.bf16 {%36, %37, %38, %39, %40, %41, %42, %43, %44, %45, %46, %47, %48, %49, %50, %51, %52, %53, %54, %55, %56, %57, %58, %59, %60, %61, %62, %63, %64, %65, %66, %67, %68, %69, %70, %71}, {%100, %101, %102, %103}, dx2, 1, 1, 1, 0;\n"
      "wgmma.mma_async.sync.aligned.m64n72k16.f32.bf16.bf16 {%36, %37, %38, %39, %40, %41, %42, %43, %44, %45, %46, %47, %48, %49, %50, %51, %52, %53, %54, %55, %56, %57, %58, %59, %60, %61, %62, %63, %64, %65, %66, %67, %68, %69, %70, %71}, {%104, %105, %106, %107}, dx3, 1, 1, 1, 0;\n"
      "wgmma.commit_group.sync.aligned;\n}\n"
      : "=f"(g[0]), "=f"(g[1]), "=f"(g[2]), "=f"(g[3]), "=f"(g[4]), "=f"(g[5]), "=f"(g[6]), "=f"(g[7]), "=f"(g[8]), "=f"(g[9]), "=f"(g[10]), "=f"(g[11]), "=f"(g[12]), "=f"(g[13]), "=f"(g[14]), "=f"(g[15]), "=f"(g[16]), "=f"(g[17]), "=f"(g[18]), "=f"(g[19]), "=f"(g[20]), "=f"(g[21]), "=f"(g[22]), "=f"(g[23]), "=f"(g[24]), "=f"(g[25]), "=f"(g[26]), "=f"(g[27]), "=f"(g[28]), "=f"(g[29]), "=f"(g[30]), "=f"(g[31]), "=f"(g[32]), "=f"(g[33]), "=f"(g[34]), "=f"(g[35]),
        "=f"(h[0]), "=f"(h[1]), "=f"(h[2]), "=f"(h[3]), "=f"(h[4]), "=f"(h[5]), "=f"(h[6]), "=f"(h[7]), "=f"(h[8]), "=f"(h[9]), "=f"(h[10]), "=f"(h[11]), "=f"(h[12]), "=f"(h[13]), "=f"(h[14]), "=f"(h[15]), "=f"(h[16]), "=f"(h[17]), "=f"(h[18]), "=f"(h[19]), "=f"(h[20]), "=f"(h[21]), "=f"(h[22]), "=f"(h[23]), "=f"(h[24]), "=f"(h[25]), "=f"(h[26]), "=f"(h[27]), "=f"(h[28]), "=f"(h[29]), "=f"(h[30]), "=f"(h[31]), "=f"(h[32]), "=f"(h[33]), "=f"(h[34]), "=f"(h[35])
      : "r"(w[0]), "r"(w[1]), "r"(w[2]), "r"(w[3]), "r"(w[4]), "r"(w[5]), "r"(w[6]), "r"(w[7]), "r"(w[8]), "r"(w[9]), "r"(w[10]), "r"(w[11]), "r"(w[12]), "r"(w[13]), "r"(w[14]), "r"(w[15]), "r"(w[16]), "r"(w[17]), "r"(w[18]), "r"(w[19]), "r"(w[20]), "r"(w[21]), "r"(w[22]), "r"(w[23]), "r"(w[24]), "r"(w[25]), "r"(w[26]), "r"(w[27]), "r"(w[28]), "r"(w[29]), "r"(w[30]), "r"(w[31]), "r"(w[32]), "r"(w[33]), "r"(w[34]), "r"(w[35]), "r"(w[36]), "r"(w[37]), "r"(w[38]), "r"(w[39]), "r"(dx), "l"(de), "l"(dh)
      : "memory");
  }
  static __device__ __forceinline__ void wait_g(float* g) {
    asm volatile("wgmma.wait_group.sync.aligned 1;\n"
      : "+f"(g[0]), "+f"(g[1]), "+f"(g[2]), "+f"(g[3]), "+f"(g[4]), "+f"(g[5]), "+f"(g[6]), "+f"(g[7]), "+f"(g[8]), "+f"(g[9]), "+f"(g[10]), "+f"(g[11]), "+f"(g[12]), "+f"(g[13]), "+f"(g[14]), "+f"(g[15]), "+f"(g[16]), "+f"(g[17]), "+f"(g[18]), "+f"(g[19]), "+f"(g[20]), "+f"(g[21]), "+f"(g[22]), "+f"(g[23]), "+f"(g[24]), "+f"(g[25]), "+f"(g[26]), "+f"(g[27]), "+f"(g[28]), "+f"(g[29]), "+f"(g[30]), "+f"(g[31]), "+f"(g[32]), "+f"(g[33]), "+f"(g[34]), "+f"(g[35])
      :: "memory");
  }
  static __device__ __forceinline__ void wait_h(float* h) {
    asm volatile("wgmma.wait_group.sync.aligned 0;\n"
      : "+f"(h[0]), "+f"(h[1]), "+f"(h[2]), "+f"(h[3]), "+f"(h[4]), "+f"(h[5]), "+f"(h[6]), "+f"(h[7]), "+f"(h[8]), "+f"(h[9]), "+f"(h[10]), "+f"(h[11]), "+f"(h[12]), "+f"(h[13]), "+f"(h[14]), "+f"(h[15]), "+f"(h[16]), "+f"(h[17]), "+f"(h[18]), "+f"(h[19]), "+f"(h[20]), "+f"(h[21]), "+f"(h[22]), "+f"(h[23]), "+f"(h[24]), "+f"(h[25]), "+f"(h[26]), "+f"(h[27]), "+f"(h[28]), "+f"(h[29]), "+f"(h[30]), "+f"(h[31]), "+f"(h[32]), "+f"(h[33]), "+f"(h[34]), "+f"(h[35])
      :: "memory");
  }
};
template<> struct TileMMA<10> {
  static __device__ __forceinline__ void issue(float* g, float* h, const uint32_t* w, uint32_t dx, uint64_t de, uint64_t dh, uint64_t dc) {
    asm volatile(
      "{\n.reg .b64 dx0, dx1, dx2, dx3;\n.reg .b32 l1, l2, l3, hx;\nmov.b32 hx, 0x40000040;\n"
      "add.u32 l1, %120, 2;\nadd.u32 l2, %120, 4;\nadd.u32 l3, %120, 6;\n"
      "mov.b64 dx0, {%120, hx};\nmov.b64 dx1, {l1, hx};\nmov.b64 dx2, {l2, hx};\nmov.b64 dx3, {l3, hx};\n"
      "wgmma.fence.sync.aligned;\n"
      "wgmma.mma_async.sync.aligned.m64n80k16.f32.bf16.bf16 {%0, %1, %2, %3, %4, %5, %6, %7, %8, %9, %10, %11, %12, %13, %14, %15, %16, %17, %18, %19, %20, %21, %22, %23, %24, %25, %26, %27, %28, %29, %30, %31, %32, %33, %34, %35, %36, %37, %38, %39}, {%116, %117, %118, %119}, %122, 0, 1, 1, 0;\n"
      "wgmma.mma_async.sync.aligned.m64n80k16.f32.bf16.bf16 {%0, %1, %2, %3, %4, %5, %6, %7, %8, %9, %10, %11, %12, %13, %14, %15, %16, %17, %18, %19, %20, %21, %22, %23, %24, %25, %26, %27, %28, %29, %30, %31, %32, %33, %34, %35, %36, %37, %38, %39}, {%96, %97, %98, %99}, %121, 1, 1, 1, 0;\n"
      "wgmma.mma_async.sync.aligned.m64n80k16.f32.bf16.bf16 {%0, %1, %2, %3, %4, %5, %6, %7, %8, %9, %10, %11, %12, %13, %14, %15, %16, %17, %18, %19, %20, %21, %22, %23, %24, %25, %26, %27, %28, %29, %30, %31, %32, %33, %34, %35, %36, %37, %38, %39}, {%80, %81, %82, %83}, dx0, 1, 1, 1, 0;\n"
      "wgmma.mma_async.sync.aligned.m64n80k16.f32.bf16.bf16 {%0, %1, %2, %3, %4, %5, %6, %7, %8, %9, %10, %11, %12, %13, %14, %15, %16, %17, %18, %19, %20, %21, %22, %23, %24, %25, %26, %27, %28, %29, %30, %31, %32, %33, %34, %35, %36, %37, %38, %39}, {%84, %85, %86, %87}, dx1, 1, 1, 1, 0;\n"
      "wgmma.mma_async.sync.aligned.m64n80k16.f32.bf16.bf16 {%0, %1, %2, %3, %4, %5, %6, %7, %8, %9, %10, %11, %12, %13, %14, %15, %16, %17, %18, %19, %20, %21, %22, %23, %24, %25, %26, %27, %28, %29, %30, %31, %32, %33, %34, %35, %36, %37, %38, %39}, {%88, %89, %90, %91}, dx2, 1, 1, 1, 0;\n"
      "wgmma.mma_async.sync.aligned.m64n80k16.f32.bf16.bf16 {%0, %1, %2, %3, %4, %5, %6, %7, %8, %9, %10, %11, %12, %13, %14, %15, %16, %17, %18, %19, %20, %21, %22, %23, %24, %25, %26, %27, %28, %29, %30, %31, %32, %33, %34, %35, %36, %37, %38, %39}, {%92, %93, %94, %95}, dx3, 1, 1, 1, 0;\n"
      "wgmma.commit_group.sync.aligned;\n"
      "wgmma.mma_async.sync.aligned.m64n80k16.f32.bf16.bf16 {%40, %41, %42, %43, %44, %45, %46, %47, %48, %49, %50, %51, %52, %53, %54, %55, %56, %57, %58, %59, %60, %61, %62, %63, %64, %65, %66, %67, %68, %69, %70, %71, %72, %73, %74, %75, %76, %77, %78, %79}, {%100, %101, %102, %103}, dx0, 0, 1, 1, 0;\n"
      "wgmma.mma_async.sync.aligned.m64n80k16.f32.bf16.bf16 {%40, %41, %42, %43, %44, %45, %46, %47, %48, %49, %50, %51, %52, %53, %54, %55, %56, %57, %58, %59, %60, %61, %62, %63, %64, %65, %66, %67, %68, %69, %70, %71, %72, %73, %74, %75, %76, %77, %78, %79}, {%104, %105, %106, %107}, dx1, 1, 1, 1, 0;\n"
      "wgmma.mma_async.sync.aligned.m64n80k16.f32.bf16.bf16 {%40, %41, %42, %43, %44, %45, %46, %47, %48, %49, %50, %51, %52, %53, %54, %55, %56, %57, %58, %59, %60, %61, %62, %63, %64, %65, %66, %67, %68, %69, %70, %71, %72, %73, %74, %75, %76, %77, %78, %79}, {%108, %109, %110, %111}, dx2, 1, 1, 1, 0;\n"
      "wgmma.mma_async.sync.aligned.m64n80k16.f32.bf16.bf16 {%40, %41, %42, %43, %44, %45, %46, %47, %48, %49, %50, %51, %52, %53, %54, %55, %56, %57, %58, %59, %60, %61, %62, %63, %64, %65, %66, %67, %68, %69, %70, %71, %72, %73, %74, %75, %76, %77, %78, %79}, {%112, %113, %114, %115}, dx3, 1, 1, 1, 0;\n"
      "wgmma.commit_group.sync.aligned;\n}\n"
      : "=f"(g[0]), "=f"(g[1]), "=f"(g[2]), "=f"(g[3]), "=f"(g[4]), "=f"(g[5]), "=f"(g[6]), "=f"(g[7]), "=f"(g[8]), "=f"(g[9]), "=f"(g[10]), "=f"(g[11]), "=f"(g[12]), "=f"(g[13]), "=f"(g[14]), "=f"(g[15]), "=f"(g[16]), "=f"(g[17]), "=f"(g[18]), "=f"(g[19]), "=f"(g[20]), "=f"(g[21]), "=f"(g[22]), "=f"(g[23]), "=f"(g[24]), "=f"(g[25]), "=f"(g[26]), "=f"(g[27]), "=f"(g[28]), "=f"(g[29]), "=f"(g[30]), "=f"(g[31]), "=f"(g[32]), "=f"(g[33]), "=f"(g[34]), "=f"(g[35]), "=f"(g[36]), "=f"(g[37]), "=f"(g[38]), "=f"(g[39]),
        "=f"(h[0]), "=f"(h[1]), "=f"(h[2]), "=f"(h[3]), "=f"(h[4]), "=f"(h[5]), "=f"(h[6]), "=f"(h[7]), "=f"(h[8]), "=f"(h[9]), "=f"(h[10]), "=f"(h[11]), "=f"(h[12]), "=f"(h[13]), "=f"(h[14]), "=f"(h[15]), "=f"(h[16]), "=f"(h[17]), "=f"(h[18]), "=f"(h[19]), "=f"(h[20]), "=f"(h[21]), "=f"(h[22]), "=f"(h[23]), "=f"(h[24]), "=f"(h[25]), "=f"(h[26]), "=f"(h[27]), "=f"(h[28]), "=f"(h[29]), "=f"(h[30]), "=f"(h[31]), "=f"(h[32]), "=f"(h[33]), "=f"(h[34]), "=f"(h[35]), "=f"(h[36]), "=f"(h[37]), "=f"(h[38]), "=f"(h[39])
      : "r"(w[0]), "r"(w[1]), "r"(w[2]), "r"(w[3]), "r"(w[4]), "r"(w[5]), "r"(w[6]), "r"(w[7]), "r"(w[8]), "r"(w[9]), "r"(w[10]), "r"(w[11]), "r"(w[12]), "r"(w[13]), "r"(w[14]), "r"(w[15]), "r"(w[16]), "r"(w[17]), "r"(w[18]), "r"(w[19]), "r"(w[20]), "r"(w[21]), "r"(w[22]), "r"(w[23]), "r"(w[24]), "r"(w[25]), "r"(w[26]), "r"(w[27]), "r"(w[28]), "r"(w[29]), "r"(w[30]), "r"(w[31]), "r"(w[32]), "r"(w[33]), "r"(w[34]), "r"(w[35]), "r"(w[36]), "r"(w[37]), "r"(w[38]), "r"(w[39]), "r"(dx), "l"(de), "l"(dh)
      : "memory");
  }
  static __device__ __forceinline__ void wait_g(float* g) {
    asm volatile("wgmma.wait_group.sync.aligned 1;\n"
      : "+f"(g[0]), "+f"(g[1]), "+f"(g[2]), "+f"(g[3]), "+f"(g[4]), "+f"(g[5]), "+f"(g[6]), "+f"(g[7]), "+f"(g[8]), "+f"(g[9]), "+f"(g[10]), "+f"(g[11]), "+f"(g[12]), "+f"(g[13]), "+f"(g[14]), "+f"(g[15]), "+f"(g[16]), "+f"(g[17]), "+f"(g[18]), "+f"(g[19]), "+f"(g[20]), "+f"(g[21]), "+f"(g[22]), "+f"(g[23]), "+f"(g[24]), "+f"(g[25]), "+f"(g[26]), "+f"(g[27]), "+f"(g[28]), "+f"(g[29]), "+f"(g[30]), "+f"(g[31]), "+f"(g[32]), "+f"(g[33]), "+f"(g[34]), "+f"(g[35]), "+f"(g[36]), "+f"(g[37]), "+f"(g[38]), "+f"(g[39])
      :: "memory");
  }
  static __device__ __forceinline__ void wait_h(float* h) {
    asm volatile("wgmma.wait_group.sync.aligned 0;\n"
      : "+f"(h[0]), "+f"(h[1]), "+f"(h[2]), "+f"(h[3]), "+f"(h[4]), "+f"(h[5]), "+f"(h[6]), "+f"(h[7]), "+f"(h[8]), "+f"(h[9]), "+f"(h[10]), "+f"(h[11]), "+f"(h[12]), "+f"(h[13]), "+f"(h[14]), "+f"(h[15]), "+f"(h[16]), "+f"(h[17]), "+f"(h[18]), "+f"(h[19]), "+f"(h[20]), "+f"(h[21]), "+f"(h[22]), "+f"(h[23]), "+f"(h[24]), "+f"(h[25]), "+f"(h[26]), "+f"(h[27]), "+f"(h[28]), "+f"(h[29]), "+f"(h[30]), "+f"(h[31]), "+f"(h[32]), "+f"(h[33]), "+f"(h[34]), "+f"(h[35]), "+f"(h[36]), "+f"(h[37]), "+f"(h[38]), "+f"(h[39])
      :: "memory");
  }
};
template<> struct TileMMA<11> {
  static __device__ __forceinline__ void issue(float* g, float* h, const uint32_t* w, uint32_t dx, uint64_t de, uint64_t dh, uint64_t dc) {
    asm volatile(
      "{\n.reg .b64 dx0, dx1, dx2, dx3;\n.reg .b32 l1, l2, l3, hx;\nmov.b32 hx, 0x40000040;\n"
      "add.u32 l1, %124, 2;\nadd.u32 l2, %124, 4;\nadd.u32 l3, %124, 6;\n"
      "mov.b64 dx0, {%124, hx};\nmov.b64 dx1, {l1, hx};\nmov.b64 dx2, {l2, hx};\nmov.b64 dx3, {l3, hx};\n"
      "wgmma.fence.sync.aligned;\n"
      "wgmma.mma_async.sync.aligned.m64n88k16.f32.bf16.bf16 {%0, %1, %2, %3, %4, %5, %6, %7, %8, %9, %10, %11, %12, %13, %14, %15, %16, %17, %18, %19, %20, %21, %22, %23, %24, %25, %26, %27, %28, %29, %30, %31, %32, %33, %34, %35, %36, %37, %38, %39, %40, %41, %42, %43}, {%120, %121, %122, %123}, %126, 0, 1, 1, 0;\n"
      "wgmma.mma_async.sync.aligned.m64n88k16.f32.bf16.bf16 {%0, %1, %2, %3, %4, %5, %6, %7, %8, %9, %10, %11, %12, %13, %14, %15, %16, %17, %18, %19, %20, %21, %22, %23, %24, %25, %26, %27, %28, %29, %30, %31, %32, %33, %34, %35, %36, %37, %38, %39, %40, %41, %42, %43}, %127, %125, 1, 1, 1, 0, 0;\n"
      "wgmma.mma_async.sync.aligned.m64n88k16.f32.bf16.bf16 {%0, %1, %2, %3, %4, %5, %6, %7, %8, %9, %10, %11, %12, %13, %14, %15, %16, %17, %18, %19, %20, %21, %22, %23, %24, %25, %26, %27, %28, %29, %30, %31, %32, %33, %34, %35, %36, %37, %38, %39, %40, %41, %42, %43}, {%88, %89, %90, %91}, dx0, 1, 1, 1, 0;\n"
      "wgmma.mma_async.sync.aligned.m64n88k16.f32.bf16.bf16 {%0, %1, %2, %3, %4, %5, %6, %7, %8, %9, %10, %11, %12, %13, %14, %15, %16, %17, %18, %19, %20, %21, %22, %23, %24, %25, %26, %27, %28, %29, %30, %31, %32, %33, %34, %35, %36, %37, %38, %39, %40, %41, %42, %43}, {%92, %93, %94, %95}, dx1, 1, 1, 1, 0;\n"
      "wgmma.mma_async.sync.aligned.m64n88k16.f32.bf16.bf16 {%0, %1, %2, %3, %4, %5, %6, %7, %8, %9, %10, %11, %12, %13, %14, %15, %16, %17, %18, %19, %20, %21, %22, %23, %24, %25, %26, %27, %28, %29, %30, %31, %32, %33, %34, %35, %36, %37, %38, %39, %40, %41, %42, %43}, {%96, %97, %98, %99}, dx2, 1, 1, 1, 0;\n"
      "wgmma.mma_async.sync.aligned.m64n88k16.f32.bf16.bf16 {%0, %1, %2, %3, %4, %5, %6, %7, %8, %9, %10, %11, %12, %13, %14, %15, %16, %17, %18, %19, %20, %21, %22, %23, %24, %25, %26, %27, %28, %29, %30, %31, %32, %33, %34, %35, %36, %37, %38, %39, %40, %41, %42, %43}, {%100, %101, %102, %103}, dx3, 1, 1, 1, 0;\n"
      "wgmma.commit_group.sync.aligned;\n"
      "wgmma.mma_async.sync.aligned.m64n88k16.f32.bf16.bf16 {%44, %45, %46, %47, %48, %49, %50, %51, %52, %53, %54, %55, %56, %57, %58, %59, %60, %61, %62, %63, %64, %65, %66, %67, %68, %69, %70, %71, %72, %73, %74, %75, %76, %77, %78, %79, %80, %81, %82, %83, %84, %85, %86, %87}, {%104, %105, %106, %107}, dx0, 0, 1, 1, 0;\n"
      "wgmma.mma_async.sync.aligned.m64n88k16.f32.bf16.bf16 {%44, %45, %46, %47, %48, %49, %50, %51, %52, %53, %54, %55, %56, %57, %58, %59, %60, %61, %62, %63, %64, %65, %66, %67, %68, %69, %70, %71, %72, %73, %74, %75, %76, %77, %78, %79, %80, %81, %82, %83, %84, %85, %86, %87}, {%108, %109, %110, %111}, dx1, 1, 1, 1, 0;\n"
      "wgmma.mma_async.sync.aligned.m64n88k16.f32.bf16.bf16 {%44, %45, %46, %47, %48, %49, %50, %51, %52, %53, %54, %55, %56, %57, %58, %59, %60, %61, %62, %63, %64, %65, %66, %67, %68, %69, %70, %71, %72, %73, %74, %75, %76, %77, %78, %79, %80, %81, %82, %83, %84, %85, %86, %87}, {%112, %113, %114, %115}, dx2, 1, 1, 1, 0;\n"
      "wgmma.mma_async.sync.aligned.m64n88k16.f32.bf16.bf16 {%44, %45, %46, %47, %48, %49, %50, %51, %52, %53, %54, %55, %56, %57, %58, %59, %60, %61, %62, %63, %64, %65, %66, %67, %68, %69, %70, %71, %72, %73, %74, %75, %76, %77, %78, %79, %80, %81, %82, %83, %84, %85, %86, %87}, {%116, %117, %118, %119}, dx3, 1, 1, 1, 0;\n"
      "wgmma.commit_group.sync.aligned;\n}\n"
      : "=f"(g[0]), "=f"(g[1]), "=f"(g[2]), "=f"(g[3]), "=f"(g[4]), "=f"(g[5]), "=f"(g[6]), "=f"(g[7]), "=f"(g[8]), "=f"(g[9]), "=f"(g[10]), "=f"(g[11]), "=f"(g[12]), "=f"(g[13]), "=f"(g[14]), "=f"(g[15]), "=f"(g[16]), "=f"(g[17]), "=f"(g[18]), "=f"(g[19]), "=f"(g[20]), "=f"(g[21]), "=f"(g[22]), "=f"(g[23]), "=f"(g[24]), "=f"(g[25]), "=f"(g[26]), "=f"(g[27]), "=f"(g[28]), "=f"(g[29]), "=f"(g[30]), "=f"(g[31]), "=f"(g[32]), "=f"(g[33]), "=f"(g[34]), "=f"(g[35]), "=f"(g[36]), "=f"(g[37]), "=f"(g[38]), "=f"(g[39]), "=f"(g[40]), "=f"(g[41]), "=f"(g[42]), "=f"(g[43]),
        "=f"(h[0]), "=f"(h[1]), "=f"(h[2]), "=f"(h[3]), "=f"(h[4]), "=f"(h[5]), "=f"(h[6]), "=f"(h[7]), "=f"(h[8]), "=f"(h[9]), "=f"(h[10]), "=f"(h[11]), "=f"(h[12]), "=f"(h[13]), "=f"(h[14]), "=f"(h[15]), "=f"(h[16]), "=f"(h[17]), "=f"(h[18]), "=f"(h[19]), "=f"(h[20]), "=f"(h[21]), "=f"(h[22]), "=f"(h[23]), "=f"(h[24]), "=f"(h[25]), "=f"(h[26]), "=f"(h[27]), "=f"(h[28]), "=f"(h[29]), "=f"(h[30]), "=f"(h[31]), "=f"(h[32]), "=f"(h[33]), "=f"(h[34]), "=f"(h[35]), "=f"(h[36]), "=f"(h[37]), "=f"(h[38]), "=f"(h[39]), "=f"(h[40]), "=f"(h[41]), "=f"(h[42]), "=f"(h[43])
      : "r"(w[0]), "r"(w[1]), "r"(w[2]), "r"(w[3]), "r"(w[4]), "r"(w[5]), "r"(w[6]), "r"(w[7]), "r"(w[8]), "r"(w[9]), "r"(w[10]), "r"(w[11]), "r"(w[12]), "r"(w[13]), "r"(w[14]), "r"(w[15]), "r"(w[20]), "r"(w[21]), "r"(w[22]), "r"(w[23]), "r"(w[24]), "r"(w[25]), "r"(w[26]), "r"(w[27]), "r"(w[28]), "r"(w[29]), "r"(w[30]), "r"(w[31]), "r"(w[32]), "r"(w[33]), "r"(w[34]), "r"(w[35]), "r"(w[36]), "r"(w[37]), "r"(w[38]), "r"(w[39]), "r"(dx), "l"(de), "l"(dh), "l"(dc)
      : "memory");
  }
  static __device__ __forceinline__ void wait_g(float* g) {
    asm volatile("wgmma.wait_group.sync.aligned 1;\n"
      : "+f"(g[0]), "+f"(g[1]), "+f"(g[2]), "+f"(g[3]), "+f"(g[4]), "+f"(g[5]), "+f"(g[6]), "+f"(g[7]), "+f"(g[8]), "+f"(g[9]), "+f"(g[10]), "+f"(g[11]), "+f"(g[12]), "+f"(g[13]), "+f"(g[14]), "+f"(g[15]), "+f"(g[16]), "+f"(g[17]), "+f"(g[18]), "+f"(g[19]), "+f"(g[20]), "+f"(g[21]), "+f"(g[22]), "+f"(g[23]), "+f"(g[24]), "+f"(g[25]), "+f"(g[26]), "+f"(g[27]), "+f"(g[28]), "+f"(g[29]), "+f"(g[30]), "+f"(g[31]), "+f"(g[32]), "+f"(g[33]), "+f"(g[34]), "+f"(g[35]), "+f"(g[36]), "+f"(g[37]), "+f"(g[38]), "+f"(g[39]), "+f"(g[40]), "+f"(g[41]), "+f"(g[42]), "+f"(g[43])
      :: "memory");
  }
  static __device__ __forceinline__ void wait_h(float* h) {
    asm volatile("wgmma.wait_group.sync.aligned 0;\n"
      : "+f"(h[0]), "+f"(h[1]), "+f"(h[2]), "+f"(h[3]), "+f"(h[4]), "+f"(h[5]), "+f"(h[6]), "+f"(h[7]), "+f"(h[8]), "+f"(h[9]), "+f"(h[10]), "+f"(h[11]), "+f"(h[12]), "+f"(h[13]), "+f"(h[14]), "+f"(h[15]), "+f"(h[16]), "+f"(h[17]), "+f"(h[18]), "+f"(h[19]), "+f"(h[20]), "+f"(h[21]), "+f"(h[22]), "+f"(h[23]), "+f"(h[24]), "+f"(h[25]), "+f"(h[26]), "+f"(h[27]), "+f"(h[28]), "+f"(h[29]), "+f"(h[30]), "+f"(h[31]), "+f"(h[32]), "+f"(h[33]), "+f"(h[34]), "+f"(h[35]), "+f"(h[36]), "+f"(h[37]), "+f"(h[38]), "+f"(h[39]), "+f"(h[40]), "+f"(h[41]), "+f"(h[42]), "+f"(h[43])
      :: "memory");
  }
};
__device__ __forceinline__ void node_mma(float* g, const uint32_t* w, uint64_t dx) {
    asm volatile(
      "{\n.reg .b64 dx1, dx2, dx3;\n"
      "add.s64 dx1, %48, 2;\nadd.s64 dx2, %48, 4;\nadd.s64 dx3, %48, 6;\n"
      "wgmma.fence.sync.aligned;\n"
      "wgmma.mma_async.sync.aligned.m64n64k16.f32.bf16.bf16 {%0, %1, %2, %3, %4, %5, %6, %7, %8, %9, %10, %11, %12, %13, %14, %15, %16, %17, %18, %19, %20, %21, %22, %23, %24, %25, %26, %27, %28, %29, %30, %31}, {%32, %33, %34, %35}, %48, 0, 1, 1, 0;\n"
      "wgmma.mma_async.sync.aligned.m64n64k16.f32.bf16.bf16 {%0, %1, %2, %3, %4, %5, %6, %7, %8, %9, %10, %11, %12, %13, %14, %15, %16, %17, %18, %19, %20, %21, %22, %23, %24, %25, %26, %27, %28, %29, %30, %31}, {%36, %37, %38, %39}, dx1, 1, 1, 1, 0;\n"
      "wgmma.mma_async.sync.aligned.m64n64k16.f32.bf16.bf16 {%0, %1, %2, %3, %4, %5, %6, %7, %8, %9, %10, %11, %12, %13, %14, %15, %16, %17, %18, %19, %20, %21, %22, %23, %24, %25, %26, %27, %28, %29, %30, %31}, {%40, %41, %42, %43}, dx2, 1, 1, 1, 0;\n"
      "wgmma.mma_async.sync.aligned.m64n64k16.f32.bf16.bf16 {%0, %1, %2, %3, %4, %5, %6, %7, %8, %9, %10, %11, %12, %13, %14, %15, %16, %17, %18, %19, %20, %21, %22, %23, %24, %25, %26, %27, %28, %29, %30, %31}, {%44, %45, %46, %47}, dx3, 1, 1, 1, 0;\n"
      "wgmma.commit_group.sync.aligned;\n}\n"
      : "=f"(g[0]), "=f"(g[1]), "=f"(g[2]), "=f"(g[3]), "=f"(g[4]), "=f"(g[5]), "=f"(g[6]), "=f"(g[7]), "=f"(g[8]), "=f"(g[9]), "=f"(g[10]), "=f"(g[11]), "=f"(g[12]), "=f"(g[13]), "=f"(g[14]), "=f"(g[15]), "=f"(g[16]), "=f"(g[17]), "=f"(g[18]), "=f"(g[19]), "=f"(g[20]), "=f"(g[21]), "=f"(g[22]), "=f"(g[23]), "=f"(g[24]), "=f"(g[25]), "=f"(g[26]), "=f"(g[27]), "=f"(g[28]), "=f"(g[29]), "=f"(g[30]), "=f"(g[31])
      : "r"(w[0]), "r"(w[1]), "r"(w[2]), "r"(w[3]), "r"(w[4]), "r"(w[5]), "r"(w[6]), "r"(w[7]), "r"(w[8]), "r"(w[9]), "r"(w[10]), "r"(w[11]), "r"(w[12]), "r"(w[13]), "r"(w[14]), "r"(w[15]), "l"(dx)
      : "memory");
}

__device__ __forceinline__ uint32_t smem_u32(const void* p) { return (uint32_t)__cvta_generic_to_shared(p); }
__device__ __forceinline__ float ex2f(float x) { float y; asm("ex2.approx.ftz.f32 %0, %1;" : "=f"(y) : "f"(x)); return y; }
__device__ __forceinline__ float rcpf(float x) { float y; asm("rcp.approx.ftz.f32 %0, %1;" : "=f"(y) : "f"(x)); return y; }
__device__ __forceinline__ uint32_t pack_bf16(float lo, float hi) {
    uint32_t r; asm("cvt.rn.bf16x2.f32 %0, %1, %2;" : "=r"(r) : "f"(hi), "f"(lo)); return r;
}
__device__ __forceinline__ float bf_lo(uint32_t v) { return __uint_as_float(v << 16); }
__device__ __forceinline__ float bf_hi(uint32_t v) { return __uint_as_float(v & 0xFFFF0000u); }
template<int STRIDE>
__device__ __forceinline__ void cp16i(uint32_t dst, const char* base, uint32_t idx) {
    asm volatile("{\n.reg .b64 a;\nmad.wide.u32 a, %2, %3, %1;\ncp.async.cg.shared.global [%0], [a], 16;\n}\n" :: "r"(dst), "l"(base), "r"(idx), "n"(STRIDE) : "memory");
}
__device__ __forceinline__ void cp16e(uint32_t dst, const char* base, uint32_t idx, uint64_t pol) {
    asm volatile("{\n.reg .b64 a;\nmad.wide.u32 a, %2, 32, %1;\ncp.async.cg.shared.global.L2::cache_hint [%0], [a], 16, %3;\n}\n" :: "r"(dst), "l"(base), "r"(idx), "l"(pol) : "memory");
}
template<int STRIDE>
__device__ __forceinline__ void cp16z(uint32_t dst, const char* base, uint32_t idx, int k, int n, uint64_t pol) {
    if (STRIDE == 32)
        asm volatile("{\n.reg .b64 a;\n.reg .pred p;\nsetp.ge.s32 p, %3, %4;\nmad.wide.u32 a, %2, 32, %1;\ncp.async.cg.shared.global.L2::cache_hint [%0], [a], 16, p, %5;\n}\n"
                     :: "r"(dst), "l"(base), "r"(idx), "r"(k), "r"(n), "l"(pol) : "memory");
    else
        asm volatile("{\n.reg .b64 a;\n.reg .pred p;\nsetp.ge.s32 p, %3, %4;\nmad.wide.u32 a, %2, 128, %1;\ncp.async.cg.shared.global [%0], [a], 16, p;\n}\n"
                     :: "r"(dst), "l"(base), "r"(idx), "r"(k), "r"(n) : "memory");
}
template<int HI, bool Z>
__device__ __forceinline__ void cpx(uint32_t hi, uint32_t dst, uint32_t p, uint32_t lo, int k, int n) {
    if (Z) asm volatile("{\n.reg .b32 l;\n.reg .b64 a;\n.reg .pred q;\nsetp.ge.s32 q, %5, %6;\ndp2a.lo.u32.u32 l, %1, %2, %3;\nmov.b64 a, {l, %0};\ncp.async.cg.shared.global [%4], [a], 16, q;\n}\n"
                        :: "r"(hi), "r"(p), "r"(HI ? 0x8000u : 0x80u), "r"(lo), "r"(dst), "r"(k), "r"(n) : "memory");
    else asm volatile("{\n.reg .b32 l;\n.reg .b64 a;\ndp2a.lo.u32.u32 l, %1, %2, %3;\nmov.b64 a, {l, %0};\ncp.async.cg.shared.global [%4], [a], 16;\n}\n"
                      :: "r"(hi), "r"(p), "r"(HI ? 0x8000u : 0x80u), "r"(lo), "r"(dst) : "memory");
}
template<bool Z>
__device__ __forceinline__ void cpe(uint32_t hi, uint32_t dst, uint32_t idx, uint32_t lo, int k, int n, uint64_t pol) {
    if (Z) asm volatile("{\n.reg .b32 l;\n.reg .b64 a;\n.reg .pred q;\nsetp.ge.s32 q, %5, %6;\nmad.lo.u32 l, %1, 32, %2;\nmov.b64 a, {l, %0};\ncp.async.cg.shared.global.L2::cache_hint [%3], [a], 16, q, %4;\n}\n"
                        :: "r"(hi), "r"(idx), "r"(lo), "r"(dst), "l"(pol), "r"(k), "r"(n) : "memory");
    else asm volatile("{\n.reg .b32 l;\n.reg .b64 a;\nmad.lo.u32 l, %1, 32, %2;\nmov.b64 a, {l, %0};\ncp.async.cg.shared.global.L2::cache_hint [%3], [a], 16, %4;\n}\n"
                      :: "r"(hi), "r"(idx), "r"(lo), "r"(dst), "l"(pol) : "memory");
}
__device__ __forceinline__ void cp_commit() { asm volatile("cp.async.commit_group;" ::: "memory"); }
template<int N> __device__ __forceinline__ void cp_wait() { asm volatile("cp.async.wait_group %0;" :: "n"(N) : "memory"); }
__device__ __forceinline__ void mbar_init(uint32_t bar, int cnt) { asm volatile("mbarrier.init.shared.b64 [%0], %1;" :: "r"(bar), "r"(cnt) : "memory"); }
__device__ __forceinline__ void mbar_arrive(uint32_t bar) { asm volatile("mbarrier.arrive.shared.b64 _, [%0];" :: "r"(bar) : "memory"); }
__device__ __forceinline__ void mbar_expect(uint32_t bar, uint32_t bytes) { asm volatile("mbarrier.arrive.expect_tx.shared.b64 _, [%0], %1;" :: "r"(bar), "r"(bytes) : "memory"); }
__device__ __forceinline__ void mbar_cp_arrive(uint32_t bar) { asm volatile("cp.async.mbarrier.arrive.noinc.shared.b64 [%0];" :: "r"(bar) : "memory"); }
__device__ __forceinline__ void mbar_wait(uint32_t bar, uint32_t parity) {
    asm volatile("{\n.reg .pred p;\n.reg .u32 n;\nmbarrier.try_wait.parity.shared.b64 p, [%0], %1;\n@p bra DONE_%=;\nmov.u32 n, 0;\n"
                 "WAIT_%=:\nmbarrier.try_wait.parity.shared.b64 p, [%0], %1, 0x100000;\n@p bra DONE_%=;\n"
                 "add.u32 n, n, 1;\nsetp.lt.u32 p, n, 0x400000;\n@p bra WAIT_%=;\ntrap;\nDONE_%=:\n}\n"
                 :: "r"(bar), "r"(parity) : "memory");
}
__device__ __forceinline__ void mbar_wait_s(uint32_t bar, uint32_t parity) {
    asm volatile("{\n.reg .pred p;\n.reg .u32 n;\nmov.u32 n, 0;\n"
                 "WAIT_%=:\nmbarrier.test_wait.parity.shared.b64 p, [%0], %1;\n@p bra DONE_%=;\n"
                 "add.u32 n, n, 1;\nsetp.lt.u32 p, n, 0x10000000;\n@p bra WAIT_%=;\ntrap;\nDONE_%=:\n}\n"
                 :: "r"(bar), "r"(parity) : "memory");
}
__device__ __forceinline__ void mbar_wait_c(uint32_t bar, uint32_t parity) {
    asm volatile("{\n.reg .pred p;\nWAIT_%=:\nmbarrier.try_wait.parity.shared.b64 p, [%0], %1;\n@p bra DONE_%=;\nbra WAIT_%=;\nDONE_%=:\n}\n"
                 :: "r"(bar), "r"(parity) : "memory");
}
__device__ __forceinline__ void mbar_wait_h(uint32_t bar, uint32_t parity) {
    asm volatile("{\n.reg .pred p;\nWAIT_%=:\nmbarrier.try_wait.parity.shared.b64 p, [%0], %1, 0x100000;\n@p bra DONE_%=;\nbra WAIT_%=;\nDONE_%=:\n}\n"
                 :: "r"(bar), "r"(parity) : "memory");
}
__device__ __forceinline__ uint32_t lds32(uint32_t a) { uint32_t v; asm volatile("ld.shared.u32 %0, [%1];" : "=r"(v) : "r"(a) : "memory"); return v; }
__device__ __forceinline__ void sts32(uint32_t a, uint32_t v) { asm volatile("st.shared.u32 [%0], %1;" :: "r"(a), "r"(v) : "memory"); }
__device__ __forceinline__ uint2 lds64(uint32_t a) { uint2 v; asm volatile("ld.shared.v2.u32 {%0,%1}, [%2];" : "=r"(v.x), "=r"(v.y) : "r"(a) : "memory"); return v; }
__device__ __forceinline__ uint4 lds128(uint32_t a) { uint4 v; asm volatile("ld.shared.v4.u32 {%0,%1,%2,%3}, [%4];" : "=r"(v.x), "=r"(v.y), "=r"(v.z), "=r"(v.w) : "r"(a) : "memory"); return v; }
__device__ __forceinline__ void sts128(uint32_t a, uint4 v) { asm volatile("st.shared.v4.u32 [%0], {%1,%2,%3,%4};" :: "r"(a), "r"(v.x), "r"(v.y), "r"(v.z), "r"(v.w) : "memory"); }
__device__ __forceinline__ void ldsm4t(uint32_t* v, uint32_t a) {
    asm volatile("ldmatrix.sync.aligned.m8n8.x4.trans.shared.b16 {%0,%1,%2,%3}, [%4];" : "=r"(v[0]), "=r"(v[1]), "=r"(v[2]), "=r"(v[3]) : "r"(a) : "memory");
}
__device__ __forceinline__ void stsm4t(uint32_t a, const uint32_t* v) {
    asm volatile("stmatrix.sync.aligned.m8n8.x4.trans.shared.b16 [%0], {%1,%2,%3,%4};" :: "r"(a), "r"(v[0]), "r"(v[1]), "r"(v[2]), "r"(v[3]) : "memory");
}
__device__ __forceinline__ int atoms_inc(uint32_t a) { int v; asm volatile("atom.shared.add.u32 %0, [%1], 1;" : "=r"(v) : "r"(a) : "memory"); return v; }
__device__ __forceinline__ bool elect_one() {
    uint32_t el;
    asm volatile("{\n.reg .pred p;\nelect.sync _|p, 0xffffffff;\nselp.u32 %0, 1, 0, p;\n}" : "=r"(el));
    return el != 0;
}
__device__ __forceinline__ float tanhf_a(float x) { float y; asm("tanh.approx.f32 %0, %1;" : "=f"(y) : "f"(x)); return y; }
__device__ __forceinline__ const char* as_pair(const void* p, uint32_t scratch) {
    const char* r;
    asm volatile("st.shared.u64 [%1], %2;\nld.volatile.shared.u64 %0, [%1];" : "=l"(r) : "r"(scratch), "l"(p) : "memory");
    return r;
}
__device__ __forceinline__ void ld_unit(uint4& v, const char* p, bool ok) {
    asm volatile("{\n.reg .pred q;\nsetp.ne.u32 q, %5, 0;\n@q ld.relaxed.gpu.global.v4.u32 {%0,%1,%2,%3}, [%4];\n}"
                 : "+r"(v.x), "+r"(v.y), "+r"(v.z), "+r"(v.w) : "l"(p), "r"((uint32_t)ok) : "memory");
}
__device__ __forceinline__ void ld_unit(uint2& v, const char* p, bool ok) {
    asm volatile("{\n.reg .pred q;\nsetp.ne.u32 q, %3, 0;\n@q ld.relaxed.gpu.global.v2.u32 {%0,%1}, [%2];\n}"
                 : "+r"(v.x), "+r"(v.y) : "l"(p), "r"((uint32_t)ok) : "memory");
}
__device__ __forceinline__ void bulk_ld(uint32_t dst, const void* src, int bytes, uint32_t bar) {
    mbar_expect(bar, bytes);
    if (bytes > 0) asm volatile("cp.async.bulk.shared::cluster.global.mbarrier::complete_tx::bytes [%0], [%1], %2, [%3];" :: "r"(dst), "l"(src), "r"(bytes), "r"(bar) : "memory");
}
#define ELECT "{\n.reg .pred p;\nelect.sync _|p, 0xffffffff;\n@p "
__device__ __forceinline__ void w_init(uint32_t bar, int n) { asm volatile(ELECT "mbarrier.init.shared.b64 [%0], %1;\n}" :: "r"(bar), "r"(n) : "memory"); }
__device__ __forceinline__ void w_expect(uint32_t bar, uint32_t bytes) { asm volatile(ELECT "mbarrier.arrive.expect_tx.shared.b64 _, [%0], %1;\n}" :: "r"(bar), "r"(bytes) : "memory"); }
__device__ __forceinline__ void w_ld(uint32_t dst, const void* src, int bytes, uint32_t bar) {
    asm volatile(ELECT "cp.async.bulk.shared::cluster.global.mbarrier::complete_tx::bytes [%0], [%1], %2, [%3];\n}" :: "r"(dst), "l"(src), "r"(bytes), "r"(bar) : "memory");
}
__device__ __forceinline__ void w_box_ld(uint32_t dst, const CUtensorMap* tm, int row, uint32_t bar) {
    asm volatile(ELECT "cp.async.bulk.tensor.2d.shared::cluster.global.mbarrier::complete_tx::bytes [%0], [%1, {%3, %4}], [%2];\n}"
        :: "r"(dst), "l"((uint64_t)tm), "r"(bar), "r"(0), "r"(row) : "memory");
}
__device__ __forceinline__ void w_st(void* dst, uint32_t src, int bytes) {
    asm volatile(ELECT "cp.async.bulk.global.shared::cta.bulk_group [%0], [%1], %2;\n}" :: "l"(dst), "r"(src), "r"(bytes) : "memory");
}
__device__ __forceinline__ void w_box_st(const CUtensorMap* tm, int col, uint32_t src) {
    asm volatile(ELECT "cp.async.bulk.tensor.2d.global.shared::cta.bulk_group [%0, {%2, %3}], [%1];\n}" :: "l"((uint64_t)tm), "r"(src), "r"(col), "r"(0) : "memory");
}
__device__ __forceinline__ void w_sent(unsigned* p, uint32_t src) {
    asm volatile(ELECT "cp.reduce.async.bulk.global.shared::cta.bulk_group.add.u32 [%0], [%1], 16;\n}" :: "l"(p), "r"(src) : "memory");
}
__device__ __forceinline__ void w_inc(unsigned* p) { asm volatile(ELECT "red.relaxed.gpu.global.add.u32 [%0], 1;\n}" :: "l"(p) : "memory"); }
__device__ __forceinline__ void w_hint(unsigned* p, uint32_t all) {
    #pragma unroll 1
    for (int i = 0; i < 4096; i++) {
        uint32_t v; asm volatile("ld.relaxed.gpu.global.u32 %0, [%1];" : "=r"(v) : "l"(p) : "memory");
        if (__all_sync(~0u, (int)(v - all) >= 0)) break;
    }
}

__device__ __forceinline__ void finish(uint4& a, const uint4& xu, const uint4& xv) {
    asm("{\n.reg .b32 z;\nfma.rn.relu.bf16x2 z, %0, %3, %1;\nadd.rn.bf16x2 %0, z, %2;\n}" : "+r"(a.x) : "r"(xu.x), "r"(xv.x), "r"(0x3F803F80u));
    asm("{\n.reg .b32 z;\nfma.rn.relu.bf16x2 z, %0, %3, %1;\nadd.rn.bf16x2 %0, z, %2;\n}" : "+r"(a.y) : "r"(xu.y), "r"(xv.y), "r"(0x3F803F80u));
    asm("{\n.reg .b32 z;\nfma.rn.relu.bf16x2 z, %0, %3, %1;\nadd.rn.bf16x2 %0, z, %2;\n}" : "+r"(a.z) : "r"(xu.z), "r"(xv.z), "r"(0x3F803F80u));
    asm("{\n.reg .b32 z;\nfma.rn.relu.bf16x2 z, %0, %3, %1;\nadd.rn.bf16x2 %0, z, %2;\n}" : "+r"(a.w) : "r"(xu.w), "r"(xv.w), "r"(0x3F803F80u));
}

constexpr float EPS2 = 2e-6f;
constexpr float TAU = 2.5e-5f;

constexpr uint32_t TAU_BITS = 0x3A103000u;
template<int NP>
__device__ __forceinline__ bool epi_fast(const float* g, const float* h, float m2, float tau, float& n0, float& d0, float& n1, float& d1, float& dmin)
{
    constexpr int JC = NP >= 6 ? NP - JCB : NP - 2;
    bool ok;
    #pragma unroll
    for (int j = 0; j < NP; j++) {
        float t0 = tanhf_a(g[4*j+0]), t1 = tanhf_a(g[4*j+1]), t2 = tanhf_a(g[4*j+2]), t3 = tanhf_a(g[4*j+3]);
        auto add_d = [&]() {
            if (j == 0) { d0 = t0 + (2.f * (JC + 1) + EPS2); d1 = t2 + (2.f * (JC + 1) + EPS2); } else { d0 += t0; d1 += t2; }
            d0 += t1; d1 += t3;
        };
        if (j <= JC) add_d();
        if (j == 0 && U0) { n0 = fmaf(t0, h[0], h[0]); n1 = fmaf(t2, h[2], h[2]); }
        t0 += 1.f; t2 += 1.f;
        if (j == NP - 1) { t1 = fmaf(t1, m2, m2); t3 = fmaf(t3, m2, m2); } else { t1 += 1.f; t3 += 1.f; }
        if (j > JC) add_d();
        if (j > 0) { n0 = fmaf(t0, h[4*j], n0); n1 = fmaf(t2, h[4*j+2], n1); } else if (!U0) { n0 = t0 * h[0]; n1 = t2 * h[2]; }
        n0 = fmaf(t1, h[4*j+1], n0); n1 = fmaf(t3, h[4*j+3], n1);
        if (j == JC) { dmin = fminf(d0, d1); ok = dmin >= tau; }
    }
    return ok;
}

__device__ __noinline__ void slow_bin(const __nv_bfloat16* x, const __nv_bfloat16* ea, const int* src, const int* dst,
                                      const __nv_bfloat16* wa, const __nv_bfloat16* wb, const __nv_bfloat16* wc,
                                      const __nv_bfloat16* wu, const __nv_bfloat16* wv, __nv_bfloat16* out,
                                      int E, int node0, int nn, int nthr)
{
    const int tid = threadIdx.x, lane = tid & 31;
    for (int i = tid; i < nn * 128; i += nthr) g_slow[(size_t)node0 * 128 + i] = 0.f;
    asm volatile("bar.sync 1, %0;" :: "r"(nthr) : "memory");
    for (int e0 = (tid >> 5) * 32; e0 < E; e0 += nthr) {
        int d = (e0 + lane < E) ? dst[e0 + lane] - node0 : -1;
        unsigned m = __ballot_sync(~0u, d >= 0 && d < nn);
        while (m) {
            int l = __ffs(m) - 1; m &= m - 1;
            int e = e0 + l, n = node0 + __shfl_sync(~0u, d, l), s = src[e];
            float g0 = 0, g1 = 0, h0 = 0, h1 = 0;
            for (int k = 0; k < 64; k++) {
                float xs = __bfloat162float(x[(size_t)s * 64 + k]), xd = __bfloat162float(x[(size_t)n * 64 + k]);
                uint32_t b2 = *(const uint32_t*)(wb + k * 64 + 2 * lane), v2 = *(const uint32_t*)(wv + k * 64 + 2 * lane);
                uint32_t a2 = *(const uint32_t*)(wa + k * 64 + 2 * lane);
                g0 = fmaf(xs, bf_lo(b2), fmaf(xd, bf_lo(a2), g0)); g1 = fmaf(xs, bf_hi(b2), fmaf(xd, bf_hi(a2), g1));
                h0 = fmaf(xs, bf_lo(v2), h0); h1 = fmaf(xs, bf_hi(v2), h1);
            }
            for (int k = 0; k < 16; k++) {
                float ev = __bfloat162float(ea[(size_t)e * 16 + k]);
                uint32_t c2 = *(const uint32_t*)(wc + k * 64 + 2 * lane);
                g0 = fmaf(ev, bf_lo(c2), g0); g1 = fmaf(ev, bf_hi(c2), g1);
            }
            float s0 = rcpf(1.f + ex2f(-LOG2E * g0)), s1 = rcpf(1.f + ex2f(-LOG2E * g1));
            float* acc = g_slow + (size_t)n * 128 + 4 * lane;
            atomicAdd(acc + 0, s0 * h0); atomicAdd(acc + 1, s0);
            atomicAdd(acc + 2, s1 * h1); atomicAdd(acc + 3, s1);
        }
    }
    __threadfence();
    asm volatile("bar.sync 1, %0;" :: "r"(nthr) : "memory");
    for (int i = tid; i < nn * 32; i += nthr) {
        int n = node0 + (i >> 5), cp = i & 31;
        float4 a = __ldcg((const float4*)(g_slow + (size_t)n * 128 + 4 * cp));
        float u0 = 0, u1 = 0;
        for (int k = 0; k < 64; k++) {
            float xd = __bfloat162float(x[(size_t)n * 64 + k]);
            uint32_t w2 = *(const uint32_t*)(wu + k * 64 + 2 * cp);
            u0 = fmaf(xd, bf_lo(w2), u0); u1 = fmaf(xd, bf_hi(w2), u1);
        }
        uint32_t xv = *(const uint32_t*)(x + (size_t)n * 64 + 2 * cp);
        float z0 = u0 + a.x / (a.y + 1e-6f), z1 = u1 + a.z / (a.w + 1e-6f);
        *(uint32_t*)(out + (size_t)n * 64 + 2 * cp) = pack_bf16(bf_lo(xv) + fmaxf(z0, 0.f), bf_hi(xv) + fmaxf(z1, 0.f));
    }
}

__global__ void __launch_bounds__(256) slow_kernel(const __nv_bfloat16* x, const __nv_bfloat16* ea, const int* src, const int* dst,
        const __nv_bfloat16* wa, const __nv_bfloat16* wb, const __nv_bfloat16* wc, const __nv_bfloat16* wu, const __nv_bfloat16* wv,
        __nv_bfloat16* out, int N, int E, int npb)
{
    int node0 = blockIdx.x * npb;
    slow_bin(x, ea, src, dst, wa, wb, wc, wu, wv, out, E, node0, max(0, min(npb, N - node0)), 256);
}

constexpr int XS_BYTES = NPMAX * 1024;
constexpr int ES_BYTES = NPMAX * 256;
constexpr int SM_XS = 0;
constexpr int SM_XU = SM_XS + 3 * NSTAGE * XS_BYTES;
constexpr int SM_TAB = SM_XU + NPB_MAX * 128;
constexpr int SM_ES = SM_TAB + NPB_MAX * 128;
constexpr int SM_WC = SM_ES + 3 * NSTAGE * ES_BYTES;
constexpr int SM_OH = SM_WC + 2048;
constexpr int SM_EID = SM_OH + 128;
constexpr int SM_SRC = SM_EID + SLOT_CAP * 4;
constexpr int SM_TINFO = SM_SRC + SLOT_CAP * 2;
constexpr int SM_MISC = SM_TINFO + TILE_CAP * 32;
constexpr int SM_CLAIM = SM_MISC + 32 * 4;
constexpr int STG = 272;
constexpr int SM_BARS = SM_CLAIM + 32 * 4;
constexpr int SM_ABAR = SM_BARS + 6 * STG;
constexpr int SM_GBAR = SM_ABAR + 16 * 8;
constexpr int SMEM_BYTES = SM_GBAR + 97 * 8;
constexpr int SM_P2 = 0, SM_P1 = P2B + 256;
constexpr int SM_L1 = SM_P1 + P1B + 128;
constexpr int SM_DEG = SM_L1 + 256;
constexpr int SM_CLS = SM_DEG + 512 * 4;
constexpr int SM_HIST = SM_CLS + NCLS * 4;
constexpr int SM_XLIST = SM_HIST + NB_MAX * 4;
constexpr int SM_SORT = SM_XLIST + 8;
constexpr int SM_SDEG = SM_SORT + NPB_MAX * 4;
constexpr int SM_PAIR = SM_SDEG + NPB_MAX * 2;
constexpr int SM_ENT = SM_ES + 1024;
constexpr int SM_H1 = SM_P1 + HB, SM_H2 = SM_P1;
constexpr int SM_IDX = SM_EID;
constexpr int SM_WR = SM_TAB;
static_assert(TILE_CAP <= 128 && TR >= 2 && SM_ES % 256 == 0 && NSTAGE == 2 && SM_BARS % 16 == 0 && SM_TINFO % 16 == 0 && SM_EID % 128 == 0 && SM_TAB % 1024 == 0 && SM_XU % 1024 == 0 && SM_TINFO % 8 == 0 && SM_OH % 16 == 0 && SM_XLIST % 8 == 0 && SM_PAIR % 8 == 0, "align");
static_assert(SM_P1 % 128 == 0 && P1B + HB <= SM_SRC - SM_EID && 2 * HB <= P1B && SM_H1 + 5 * 128 * 16 <= SM_XU && NB_MAX * (CE / 4) <= 6 * 384 && NB_MAX * 4 <= 5 * 128 && NB_MIN * 4 >= 3 * 128 && SM_PAIR + 128 * 8 <= SM_XU && CH_MAX * 4 <= SM_SRC - SM_EID && SM_DEG >= 3 << 14, "alias");
static_assert(CE == 64 && SMEM_BYTES <= 232448, "smem");
constexpr uint32_t C_BRK = 16  , C_CONT = 32, C_MORE = 64;
constexpr uint32_t ONE_F = 0x3F800000u;
constexpr int NONE = NPB_MAX - 1;
__host__ __device__ constexpr uint32_t tab_at(uint32_t n) { return (n >> 2) * 512 + (n & 3) * 32 + ((n >> 2) & 1) * 16; }

__device__ __forceinline__ uint32_t unpad(uint32_t w1, int np, float ga, float gb, float& d0, float& d1, int& dv) {
    const int pad = (w1 >> 8) & 31;
    dv = 2 * np - 1 - pad + (w1 >= ONE_F);
    float t0 = TAU * 2 * np, t1 = t0;
    if (pad) {
        t0 = fmaxf(t0, d0 * (1.f / 1024)); t1 = fmaxf(t1, d1 * (1.f / 1024));
        asm volatile("tanh.approx.f32 %0, %0;\ntanh.approx.f32 %1, %1;" : "+f"(ga), "+f"(gb));
        d0 -= pad * (1.f + ga); d1 -= pad * (1.f + gb);
    }
    if (dv == 0) { d0 = d1 = EPS2; t0 = t1 = 0.f; }
    return __ballot_sync(~0u, d0 < t0 || d1 < t1);
}
__device__ __noinline__ float4* exact_copy(uint32_t bad, float4* own)
{
    extern __shared__ __align__(1024) uint8_t smem[];
    uint32_t old = 1;
    if (bad == 1u << (threadIdx.x & 31)) old = atomicExch((uint32_t*)(smem + SM_MISC + 12), 1u);
    if (__all_sync(~0u, old)) return own;
    return old ? nullptr : (float4*)(smem + SM_XU + tab_at(NPB_MAX - 4) - 16);
}
__device__ __noinline__ float4 epi_exact(const float4* gh, int np, int dv)
{
    extern __shared__ __align__(1024) uint8_t smem[];
    float n0 = 0.f, d0 = 0.f, n1 = 0.f, d1 = 0.f;
    int j = 0, je = np;
    const uint32_t own = __ballot_sync(~0u, gh != nullptr);
    if (own != ~0u) {
        dv = __shfl_sync(~0u, dv, __ffs(own) - 1); j = min(threadIdx.x & 15, np); je = j + 1;
        gh = (const float4*)(smem + SM_XU + tab_at(NPB_MAX - 4) - 16);
        __syncwarp();
    }
    #pragma unroll 1
    for (; j < je; j++) {
        const float4 g = gh[j], h = gh[NPMAX + j];
        const bool ma = 2 * j < dv, mb = 2 * j + 1 < dv;
        const float e0 = 2.f * rcpf(1.f + ex2f(-2.f * LOG2E * g.x)), e1 = 2.f * rcpf(1.f + ex2f(-2.f * LOG2E * g.y));
        const float e2 = 2.f * rcpf(1.f + ex2f(-2.f * LOG2E * g.z)), e3 = 2.f * rcpf(1.f + ex2f(-2.f * LOG2E * g.w));
        if (ma) { d0 += e0; n0 = fmaf(e0, h.x, n0); d1 += e2; n1 = fmaf(e2, h.z, n1); }
        if (mb) { d0 += e1; n0 = fmaf(e1, h.y, n0); d1 += e3; n1 = fmaf(e3, h.w, n1); }
    }
    if (own != ~0u) {
        #pragma unroll
        for (int o = 1; o < 16; o <<= 1) {
            n0 += __shfl_xor_sync(~0u, n0, o); d0 += __shfl_xor_sync(~0u, d0, o);
            n1 += __shfl_xor_sync(~0u, n1, o); d1 += __shfl_xor_sync(~0u, d1, o);
        }
        *(volatile uint32_t*)(smem + SM_MISC + 12) = 0;
    }
    return make_float4(n0, d0 + EPS2, n1, d1 + EPS2);
}
template<int NP>
__device__ __forceinline__ void epi_dump(const float* g, const float* h, float4* gh) {
    #pragma unroll
    for (int i = 0; i < 2 * NP; i++) {
        const float* v = i < NP ? g + 4 * i : h + 4 * (i - NP);
        asm volatile("{\n.reg .pred p;\nsetp.ne.u64 p, %5, 0;\n@p st.v4.f32 [%0], {%1,%2,%3,%4};\n}"
                     :: "l"((uint64_t)gh + (i < NP ? i : NPMAX + i - NP) * 16), "f"(v[0]), "f"(v[1]), "f"(v[2]), "f"(v[3]), "l"(gh) : "memory");
    }
}
__device__ __forceinline__ uint32_t bin_bits(uint32_t b) { return (1u << (b & 7)) | ((b < 48 ? 0x100u : 0x400u) << (b >> 3)); }
__device__ __forceinline__ void place(uint32_t sbase, uint32_t slot, uint32_t v, uint32_t eb) {
    asm volatile("{\n.reg .pred p;\nsetp.lt.u32 p, %0, %5;\n@p st.shared.u32 [%1], %2;\n@p st.shared.u16 [%3], %4;\n}"
                 :: "r"(slot), "r"(sbase + SM_EID + slot * 4), "r"(eb + (v >> 19)), "r"(sbase + SM_SRC + slot * 2), "r"(v), "n"(SLOT_CAP) : "memory");
}
__device__ __forceinline__ uint64_t desc_sw128(uint32_t a) {
    return (uint64_t)((a & 0x3FFFF) >> 4) | ((uint64_t)1 << 16) | ((uint64_t)64 << 32) | ((uint64_t)1 << 62);
}

template<bool LO32>
__global__ void __launch_bounds__(THREADS, 1)
gcn_kernel(const int* __restrict__ dst, unsigned* gbar, char* gs, const int* __restrict__ src, int E, int ch, int N, int npb, uint32_t magic,
           const __nv_bfloat16* __restrict__ x, const __nv_bfloat16* __restrict__ ea,
           const __nv_bfloat16* __restrict__ wa, const __nv_bfloat16* __restrict__ wb, const __nv_bfloat16* __restrict__ wc,
           const __nv_bfloat16* __restrict__ wu, const __nv_bfloat16* __restrict__ wv,
           __nv_bfloat16* out, int4 wrow, const __grid_constant__ CUtensorMap tm1, const __grid_constant__ CUtensorMap tm2,
           const __grid_constant__ CUtensorMap tmw, const __grid_constant__ CUtensorMap tmx)
{
    extern __shared__ __align__(1024) uint8_t smem[];
    int* cls = (int*)(smem + SM_CLS);
    int* misc = (int*)(smem + SM_MISC);
    WG0(); WS(0); CG(0);
    const uint32_t sbase = smem_u32(smem);
    const int tid = threadIdx.x, lane = tid & 31;
    const int b = blockIdx.x, nb = gridDim.x;
    const int cnt = max(0, min(ch, E - b * ch));
    const int node0 = b * npb;
    uint32_t tag = 0, cstart; asm volatile("mov.u32 %0, %%clock;" : "=r"(cstart));
    const int warp = (int)__reduce_max_sync(~0u, (unsigned)tid >> 5);
    const uint32_t su = __reduce_or_sync(~0u, sbase);
    auto weights = [&]() {
        w_box_ld(su + SM_WR, &tmw, wrow.x, su + SM_ABAR + 24); w_box_ld(su + SM_WR + 8192, &tmw, wrow.y, su + SM_ABAR + 24);
        w_box_ld(su + SM_WR + 16384, &tmw, wrow.z, su + SM_ABAR + 24); w_ld(su + SM_WR + 24576, wc, 2048, su + SM_ABAR + 24);
        w_box_ld(su + SM_WR + 40960, &tmw, wrow.w, su + SM_ABAR + 24);
    };
    if (warp >= 12) {
        const int v = warp & 3;
        const uint32_t a1 = su + SM_ABAR + (v == 0 ? 80 : v == 1 ? 120 : v == 2 ? 32 : 40);
        w_init(su + SM_ABAR + v * 8, 1); w_init(a1, 1);
        w_expect(su + SM_ABAR + v * 8, v < 3 ? min(max(cnt * 4 - v * 8192, 0), 8192) : 4 * 8192 + 2048);
        if (P1S) { if (v < 3) w_expect(a1, v == 0 ? 3 * 384 * 8 : v == 1 ? nb * 64 : nb * (CE * 2) - 3 * 384 * 8); }
        else if (v < 2) w_expect(a1, v == 0 ? nb * (CE * 2) : nb * 64);
        asm volatile("fence.mbarrier_init.release.cluster;" ::: "memory");
    }
    asm volatile("{\n.reg .pred q;\nsetp.lt.u32 q, %2, 384;\n@q ld.relaxed.gpu.global.u32 %0, [%1];\n}" : "+r"(tag) : "l"(gbar), "r"(tid));
    #pragma unroll
    for (int v = 0; v < EPT / 4; v++) {
        const uint32_t off = v * (THREADS * 4) + tid * 4;
        if (PD && v) { uint32_t c0, c1; asm volatile("mov.u32 %0, %%clock;" : "=r"(c0)); do { asm volatile("mov.u32 %0, %%clock;" : "=r"(c1)); } while (__all_sync(~0u, c1 - c0 < PD)); }
        asm volatile("{\n.reg .pred q;\nsetp.lt.u32 q, %2, %3;\n@q cp.async.cg.shared.global [%0], [%1], 16;\n}"
                     :: "r"(sbase + SM_IDX + off * 4), "l"(dst + b * ch + off), "r"(off), "r"(cnt) : "memory");
        cp_commit();
        if (WV == 7 + v && warp == 15) weights();
    }
    const int wg = warp >> 2, w = warp & 3;
    const int q = lane >> 2, t = lane & 3;
    const int nn = max(0, min(npb, N - node0));
    if (sbase & 1023) __trap();

    sts32(sbase + SM_DEG + tid * 4, tid < NPB_MAX ? 0 : 0x80000000u);
    if (tid < NCLS + NB_MAX) cls[tid] = tid < NCLS ? 0 : ((tid - NCLS) * 20) & 63;
    else if (warp == 8) sts32(sbase + SM_OH + lane * 4, t != (q >> 1) ? 0u : 0x00003F00u);
    else if (warp == 11) misc[lane] = lane == 5 ? TILE_CAP - TILE_X : lane == 8 || lane == 3;
    if (warp == 14) sts32(sbase + SM_TINFO + 96 * 32 + lane * 4, lane & 1 ? tab_at(NONE) : 0);
    if (warp == 15) sts32(sbase + SM_CLAIM + lane * 4, lane == 0 ? 3 * 32 : 0x40000000);
    if (tid == 0) sts32(sbase + SM_XLIST, tag);
    tag = (tag & 1) | 2;
    if (wg < 3) {
        const uint32_t d0 = ((NPB_MAX + ((2 * lane) & 15) + 16 * (b & 1)) * 4 | (tag << 14)) * 0x10001u, d1 = d0 + 0x40004u, d2 = tag << 16;
        #pragma unroll 1
        for (int i = tid; i < (P1B + 384) / 16; i += 384) {
            sts128(sbase + SM_P1 + i * 16, make_uint4(d0, d0, d1, i == P1B / 16 + 11 ? 0x80000000u | (tag << 14) : d1));
            sts128(sbase + SM_P2 + i * 16, make_uint4(d2, d2, d2, d2)); sts128(sbase + SM_P2 + P1B - 128 + i * 16, make_uint4(d2, d2, d2, d2));
        }
    }
    WS(1);
    __syncthreads();
    if (wg == 3) tag = lds32(sbase + SM_P2) >> 16;
    uint32_t all = 0;
    if (wg == 3) all = (lds32(sbase + SM_XLIST) + 1) * nb;
    if (tid == 128) {
        asm volatile("prefetch.tensormap [%0];" :: "l"((uint64_t)&tmw) : "memory");
        asm volatile("prefetch.tensormap [%0];" :: "l"((uint64_t)&tm1) : "memory");
        asm volatile("prefetch.tensormap [%0];" :: "l"((uint64_t)&tm2) : "memory");
        asm volatile("prefetch.tensormap [%0];" :: "l"((uint64_t)&tmx) : "memory");
    }
    if (WPF && warp == 9 && b < 5) asm volatile(ELECT "cp.async.bulk.prefetch.L2.global [%0], %1;\n}" :: "l"(b == 0 ? wa : b == 1 ? wb : b == 2 ? wu : b == 3 ? wv : wc), "r"(b < 4 ? 8192 : 2048) : "memory");
    const uint32_t m4 = __reduce_or_sync(~0u, -4 * npb);
    uint32_t ent[EPT];
    #pragma unroll
    for (int v = 0; v < EPT / 4; v++) {
        if (v == 0) cp_wait<2>(); else if (v == 1) cp_wait<1>(); else cp_wait<0>();
        if (v == SRCV && wg == 2 && w < 3) {
            const int n = min(cnt * 4 - w * 8192, 8192);
            if (n > 0) w_ld(su + SM_XU + w * 8192, src + b * ch + w * 2048, n, su + SM_ABAR + w * 8);
        }
        if (v == WV) {
            if (warp == 11) w_ld(su + SM_WR + 24576, wc, 2048, su + SM_ABAR + 24);
            else if (wg == 3) w_box_ld(su + SM_WR + (w == 3 ? 5 : w) * 8192, &tmw, w == 0 ? wrow.x : w == 1 ? wrow.y : w == 2 ? wrow.z : wrow.w, su + SM_ABAR + 24);
        }
        const uint32_t off = v * (THREADS * 4) + tid * 4;
        if (off < (uint32_t)cnt) {
            const uint4 u = lds128(sbase + SM_IDX + off * 4);
            uint32_t dv[4] = {u.x, u.y, u.z, u.w}, ps[4], ck[4];
            uint32_t* en = ent + 4 * v;
            #pragma unroll
            for (int k = 0; k < 4; k++) {
                dv[k] = min(dv[k], (uint32_t)(nb * npb - 1));
                ps[k] = __umulhi(dv[k], magic);
                asm volatile("atom.shared.add.u32 %0, [%1], 0x10001;" : "=r"(ck[k]) : "r"(sbase + SM_HIST + ps[k] * 4) : "memory");
            }
            #pragma unroll
            for (int k = 0; k < 4; k++) {
                dv[k] = ps[k] * m4 + (dv[k] * 4 + (tag << 14));
                en[k] = (ck[k] & 63) + ps[k] * CE;
            }
            if (__builtin_expect(max(max(ck[0], ck[1]), max(ck[2], ck[3])) >= CE << 16, 0)) {
                auto step = [&]() {
                    uint32_t e = en[0];
                    const uint32_t d = dv[0];
                    if (ck[0] >= CE << 16) {
                        uint32_t j; asm volatile("atom.shared.inc.u32 %0, [%1], 0x7fffffff;" : "=r"(j) : "r"(sbase + SM_MISC + 8) : "memory");
                        j = min(j + (j >= 15), 63u);
                        sts32(sbase + SM_L1 + j * 4, d | ((j < 63 ? e / CE : 255u) << 16));
                        e = NB_MAX * CE + j;
                    }
                    en[0] = en[1]; en[1] = en[2]; en[2] = en[3]; en[3] = e;
                    dv[0] = dv[1]; dv[1] = dv[2]; dv[2] = dv[3]; dv[3] = d;
                    ck[0] = ck[1]; ck[1] = ck[2]; ck[2] = ck[3];
                };
                if (v == 2 && OVU) { step(); step(); step(); step(); }
                else {
                    #pragma unroll 1
                    for (int k = 0; k < 4; k++) step();
                }
            }
            #pragma unroll
            for (int k = 0; k < 4; k++)
                asm volatile("st.shared.u16 [%0], %1;" :: "r"(sbase + SM_P1 + en[k] * 2), "r"(dv[k]) : "memory");
        }
    }
    if (warp == 15) {
        #pragma unroll
        for (int v = 0; v < EPT / 4; v++) sts128(sbase + SM_ENT + v * 512 + lane * 16, make_uint4(ent[4*v], ent[4*v+1], ent[4*v+2], ent[4*v+3]));
    }
    asm volatile("fence.proxy.async.shared::cta;" ::: "memory");
    WS(5);
    __syncthreads();
    auto delay = [&](uint32_t d) { uint32_t c0, c1; asm volatile("mov.u32 %0, %%clock;" : "=r"(c0)); do { asm volatile("mov.u32 %0, %%clock;" : "=r"(c1)); } while (__all_sync(~0u, c1 - c0 < d)); };
    if (warp == 15) {
        if (HORD != 2) w_inc(gbar + HI1);
        if (!HSF) w_box_st(&tm1, b * (CE / 2), su + SM_P1);
        const uint32_t n = __reduce_or_sync(~0u, lds32(su + SM_MISC + 8));
        if (__builtin_expect(n > 15, 0)) {
            const uint2 r = lds64(su + SM_L1 + lane * 8);
            uint32_t m = lane < 8 ? 0 : (r.x >> 24 ? 0 : bin_bits(r.x >> 16)) | (r.y >> 24 ? 0 : bin_bits(r.y >> 16));
            m = n > 62 ? 0x7FFF3FFFu : __reduce_or_sync(~0u, m);
            sts32(su + SM_L1 + 60, m | 0x80000000u | (tag << 14));
            asm volatile("fence.proxy.async.shared::cta;" ::: "memory");
            __syncwarp();
        }
        w_st(gs + G_H1 + b * 64, su + SM_L1, 64);
        if (HSF) w_box_st(&tm1, b * (CE / 2), su + SM_P1);
        w_st(gs + G_L + b * 512, su + SM_L1, 256);
        asm volatile("cp.async.bulk.commit_group;" ::: "memory");
        if (WV == 3) {
            w_box_ld(su + SM_WR, &tmw, wrow.x, su + SM_ABAR + 24); w_box_ld(su + SM_WR + 8192, &tmw, wrow.y, su + SM_ABAR + 24);
            w_box_ld(su + SM_WR + 16384, &tmw, wrow.z, su + SM_ABAR + 24); w_ld(su + SM_WR + 24576, wc, 2048, su + SM_ABAR + 24);
            w_box_ld(su + SM_WR + 40960, &tmw, wrow.w, su + SM_ABAR + 24);
        }
    } else {
        mbar_wait_c(su + SM_ABAR, 0);
        auto put = [&](uint32_t off, const uint32_t* uu) {
            if (off < (uint32_t)cnt) {
                const uint4 sv = lds128(sbase + SM_XU + off * 4);
                const uint32_t ss[4] = {sv.x, sv.y, sv.z, sv.w};
                #pragma unroll
                for (int k = 0; k < 4; k++) sts32(sbase + SM_P2 + uu[k] * 4, (ss[k] & 0xFFFF) | (((off + k) << 19) + (tag << 16)));
            }
        };
        #pragma unroll
        for (int v = 0; v < EPT / 4; v++) { if (v) mbar_wait_c(su + SM_ABAR + v * 8, 0); put(v * (THREADS * 4) + tid * 4, ent + 4 * v); }
        if (wg == 3) {
            const uint4 e = lds128(sbase + SM_ENT + w * 512 + lane * 16);
            const uint32_t uu[4] = {e.x, e.y, e.z, e.w};
            put(w * (THREADS * 4) + (480 + lane) * 4, uu);
        }
        asm volatile("fence.proxy.async.shared::cta;" ::: "memory");
        WS(7);
        __syncwarp();
        asm volatile("bar.arrive 12, 512;" ::: "memory");
    }
    WS(8);

    const int ngroups = (nn + 3) >> 2;
    if (warp < 12) {
        asm volatile("setmaxnreg.inc.sync.aligned.u32 152;");
        const uint32_t ab = su + SM_ABAR;
        uint32_t wf[40], wn[16];
        const uint32_t mo = sbase + (8 * (lane >> 4) + (lane & 7)) * 128 + (((2 * w + ((lane >> 3) & 1)) ^ (lane & 7)) << 4);
        const uint32_t wca = __shfl_sync(~0u, sbase + SM_WC + (16 * w + q) * 32 + t * 4 + ((q >> 2) << 4), lane), l16 = __shfl_sync(~0u, (lane & 15) * 16, lane);
        WS(1);
        BW(ab + 24, 0);
        WS(5);
        {
            #pragma unroll
            for (int ks = 0; ks < 4; ks++) { ldsm4t(wf + 4 * ks, mo + SM_WR + ks * 2048); ldsm4t(wf + 20 + 4 * ks, mo + SM_WR + 8192 + ks * 2048); ldsm4t(wn + 4 * ks, mo + SM_WR + 16384 + ks * 2048); }
            auto half = [](uint32_t& v) { asm("mul.rn.bf16x2 %0, %0, %1;" : "+r"(v) : "r"(0x3F003F00u)); };
            uint32_t z = 0;
            #pragma unroll
            for (int i = 0; i < 16; i++) { half(wf[i]); z ^= wf[i]; }
            sts32(sbase + SM_ES + lane * 4, z);
            if (wg == 2) {
                uint32_t f[4];
                ldsm4t(f, (mo ^ ((lane & 7) << 4)) + SM_WR + 24576);
                half(f[0]); half(f[1]); half(f[2]); half(f[3]);
                sts32(wca, f[0]); sts32(wca + 256, f[1]); sts32(wca ^ 16, f[2]); sts32((wca ^ 16) + 256, f[3]);
                asm volatile("fence.proxy.async.shared::cta;" ::: "memory");
            }
        }
        const uint64_t wcd = __reduce_or_sync(~0u, (((sbase + SM_WC) & 0x3FFFF) >> 4) | (8u << 16)) | EDHI;
        const uint32_t bar0 = __reduce_or_sync(~0u, sbase + SM_BARS + wg * 2 * STG);
        const uint32_t xd0 = __reduce_or_sync(~0u, (((sbase + SM_XS + wg * NSTAGE * XS_BYTES) & 0x3FFFF) >> 4) | (1u << 16));
        const uint32_t ed0 = __reduce_or_sync(~0u, (((sbase + SM_ES + wg * NSTAGE * ES_BYTES) & 0x3FFFF) >> 4) | (8u << 16));
        const uint64_t ohd = __reduce_or_sync(~0u, ((sbase + SM_OH) & 0x3FFFF) >> 4);
        const uint32_t tabx = __reduce_or_sync(~0u, sbase + SM_TAB + w * 128);
        const uint32_t bars = __reduce_or_sync(~0u, 2 * bar0 + STG), xds = __reduce_or_sync(~0u, 2 * xd0 + XS_BYTES / 16), eds = __reduce_or_sync(~0u, 2 * ed0 + ES_BYTES / 16);
        const uint32_t xuo = __reduce_or_sync(~0u, sbase + SM_XU + wg * 16384);
        { const uint2 z = lds64(sbase + SM_OH + 8); wf[38] = z.x; wf[39] = z.y; }
        WS(9);
        constexpr int NU = 6;
        const uint32_t dm = ((NPB_MAX + lane) * 4 | (tag << 14)) * 0x10001u;
        const uint32_t db = sbase + SM_DEG - (tag << 14);
        const char* const g1 = gs + (uint32_t)(b * (P1B + P2B) + tid * 8);
        int rk[NU][4];
        uint32_t spins = 0;
        constexpr int NH = P1S ? 2 : 1, NUH = NU / NH;
        #pragma unroll
        for (int hf = 0; hf < NH; hf++) {
            uint2 r1[NUH];
            BW(ab + (hf ? 32 : 80), 0);
            if (hf == 0) WS(2);
            #pragma unroll
            for (int k = 0; k < NUH; k++) {
                const int i = hf * NUH + k;
                r1[k] = make_uint2(dm, dm);
                if (i < 5 && NB_MIN * 16 >= 384 * (i + 1) || tid + 384 * i < nb * 16) r1[k] = lds64(sbase + SM_IDX + (tid + 384 * i) * 8);
            }
            #pragma unroll 1
            while (true) {
                uint32_t bad = 0;
                #pragma unroll
                for (int k = 0; k < NUH; k++) bad |= r1[k].y ^ dm;
                if (__builtin_expect(!__any_sync(~0u, bad & 0xC000), 1)) break;
                #pragma unroll
                for (int k = 0; k < NUH; k++) ld_unit(r1[k], g1 + 384 * 8 * (hf * NUH + k), (r1[k].y ^ dm) & 0xC000);
                if (++spins > (1u << 22)) break;
            }
            if (hf == 0) WS(3);
            #pragma unroll
            for (int k = 0; k < NUH; k++) {
                int* r = rk[hf * NUH + k];
                r[0] = r1[k].x & 0xFFFF; r[1] = r1[k].x >> 16; r[2] = r1[k].y & 0xFFFF; r[3] = r1[k].y >> 16;
                #pragma unroll
                for (int m = 0; m < 4; m++) asm volatile("red.shared.add.u32 [%0], 1;" :: "r"(db + min((uint32_t)r[m], NPB_MAX * 4 + (tag << 14))) : "memory");
            }
        }
        WS(10);
        asm volatile("bar.sync 11, 512;" ::: "memory");
        int mycls = 0, mycr = 0, dg = lds32(sbase + SM_DEG + tid * 4);
        if (tid < nn) {
            mycls = NCLS - 1 - (dg <= 40 ? dg : min(41 + ((dg - 41) >> 3), NCLS - 1)); mycr = atomicAdd(&cls[mycls], 1);
        }
        int s0 = 0;
        if (__builtin_expect(dg > 40, 0)) s0 = max(SLOT_CAP - ((dg + 1) & ~1) - atomicAdd(&misc[6], (dg + 1) & ~1), 0);
        asm volatile("bar.sync 1, 384;" ::: "memory");
        WS(12);
        {
            const uint2 c = lds64(sbase + SM_CLS + lane * 8);
            const int v0 = c.x * (lane > 11 ? ((64 - 2 * lane) << 16) + 1 : 1), v1 = c.y * (lane >= 11 ? ((62 - 2 * lane) << 16) + 1 : 1);
            int inc = v0 + v1;
            #pragma unroll
            for (int o = 1; o < 32; o <<= 1) { int y = __shfl_up_sync(~0u, inc, o); if (lane >= o) inc += y; }
            const int e0 = __shfl_sync(~0u, inc - v0 - v1, mycls >> 1), e1 = __shfl_sync(~0u, inc - v1, mycls >> 1);
            const int e = (mycls & 1) ? e1 : e0;
            if (tid < nn) {
                if (dg <= 40) s0 = min((e >> 16) + mycr * ((dg + 1) & ~1), SLOT_CAP - 40);
                sts32(sbase + SM_DEG + tid * 4, s0);
            }
            const uint32_t pos = tid < nn ? (e & 0xFFFF) + mycr : tid;
            sts32(sbase + SM_SORT + pos * 4, tid < nn ? (uint32_t)tid | ((uint32_t)s0 << 16) : NONE);
            asm volatile("st.shared.u16 [%0], %1;" :: "r"(sbase + SM_SDEG + pos * 2), "r"(min(dg, 65535)) : "memory");
            if (tid == 383) { misc[4] = (nn - c.y + 3) >> 2; if ((inc >> 16) + misc[6] > SLOT_CAP - 40) misc[1] = 1; }
        }
        asm volatile("bar.sync 1, 384;" ::: "memory");
        WS(13);
        const uint32_t sv = lds32(sbase + SM_SORT + tid * 4);
        const uint2 d4 = lds64(sbase + SM_SDEG + (tid >> 2) * 8);
        const uint32_t slow = lds32(sbase + SM_MISC + 4);
        #pragma unroll
        for (int i = 0; i < NU; i++) {
            #pragma unroll
            for (int k = 0; k < 4; k++) rk[i][k] = atoms_inc(db + rk[i][k]);
        }
        if (__reduce_or_sync(~0u, slow) == 0) {
            const uint32_t nd = sv & 0xFFFF;
            const int g = tid >> 2;
            dg = ((t & 2 ? d4.y : d4.x) >> (16 * (t & 1))) & 0xFFFF;
            const uint32_t hi2 = __vmaxu2(d4.x, d4.y), lo2 = __vminu2(d4.x, d4.y);
            const int mx = max(hi2 >> 16, hi2 & 0xFFFF), mn = min(lo2 >> 16, lo2 & 0xFFFF);
            int left = (mx + 1) >> 1;
            int tl = g, nx = ngroups + 4 + g, nt = left > NPMAX ? 2 : 1;
            const bool odd = left > 2 * NPMAX || (nt == 2 && nx >= TILE_CAP - TILE_X);
            if (__builtin_expect(__any_sync(~0u, odd), 0)) {
                if (odd) nt = (left + NPMAX - 1) / NPMAX;
                if (odd && t == 0) { asm volatile("atom.shared.add.u32 %0, [%1], %2;" : "=r"(nx) : "r"(sbase + SM_MISC + 20), "r"(nt - 1) : "memory"); if (nx + nt - 1 > TILE_CAP) misc[1] = 1; }
                nx = __shfl_sync(~0u, nx, lane & ~3);
                if (odd && nx + nt - 1 > TILE_CAP) left = 0;
            }
            const uint32_t w0 = tab_at(nd);
            if (g >= ngroups + 4) tl = ngroups;
            uint32_t cont = 0;
            int done = 0;
            bool act = true;
            do {
                int np = nt <= 2 ? (left + nt - 1) >> (nt - 1) : (left + nt - 1) / nt;
                left -= np; nt = max(nt - 1, 1);
                if (np) np = max(np, NPMIN);
                const int dv = min(max(dg - done, 0), 2 * np);
                uint32_t code = (uint32_t)np | cont | (left > 0 ? C_MORE : 0u);
                const bool gen = mn - done < 2 * np - (np == NPMIN ? 1 : 2);
                if (np == 0) code = 0;
                const uint32_t w1 = code | (dv == 2 * np ? 0x8000u : (2 * np - 1 - dv) << 8);
                if (act) *(uint2*)(smem + SM_TINFO + tl * 32 + t * 8) = make_uint2((dv ? (sv >> 16) + done : 0) | ((gen ? (np > 8 ? 15 : np > 5 ? 14 : 13) : np) << 16) | ((left > 0 ? nx : 0) << 20) | ((uint32_t)dv << 27), w0 | (np == 0 ? 0u : w1 << 16));
                tl = nx++; cont = C_CONT; done += 2 * np; act = left > 0;
            } while (__any_sync(~0u, act));
        }
        __syncwarp();
        asm volatile("bar.arrive 4, 512;" ::: "memory");
        WS(14);
        wf[16] = lds32(wca); wf[17] = lds32(wca + 256); wf[18] = lds32(wca ^ 16); wf[19] = lds32((wca ^ 16) + 256);
        #pragma unroll
        for (int pc = 0; pc < 3; pc++) {
            uint4 r2[2];
            BW(ab + pc * 8, 1);
            if (pc == 0) WS(4); if (pc == 2) WS(16);
            #pragma unroll
            for (int k = 0; k < 2; k++) {
                r2[k] = lds128(sbase + SM_P2 + (tid + 384 * (2 * pc + k)) * 16);
                if (rk[2 * pc + k][0] < 0) r2[k].w = tag << 16;
            }
            while (__builtin_expect(__any_sync(~0u, ((r2[0].w ^ (tag << 16)) | (r2[1].w ^ (tag << 16))) & 0x30000), 0)) {
                #pragma unroll
                for (int k = 0; k < 2; k++)
                    ld_unit(r2[k], g1 + (uint32_t)(tid * 8) + (P1B + 384 * 16 * (2 * pc + k)), (r2[k].w ^ (tag << 16)) & 0x30000);
                if (++spins > (1u << 22)) break;
            }
            #pragma unroll
            for (int k = 0; k < 2; k++) {
                const int i = 2 * pc + k;
                const uint32_t eb = ((tid >> 4) + 24 * i) * ch;
                place(sbase, rk[i][0], r2[k].x, eb); place(sbase, rk[i][1], r2[k].y, eb); place(sbase, rk[i][2], r2[k].z, eb); place(sbase, rk[i][3], r2[k].w, eb);
            }
        }
        WGD();
        __syncwarp();
        asm volatile("bar.arrive 3, 480;" ::: "memory");
        float g[4 * NPMAX], h[4 * NPMAX];
        float4 lgh[2 * NPMAX];
        float4 cyr = make_float4(0.f, 0.f, 0.f, 0.f);
        WS(15); CG(1);
        if (GD) { uint32_t c0, c1; asm volatile("mov.u32 %0, %%clock;" : "=r"(c0)); do { asm volatile("mov.u32 %0, %%clock;" : "=r"(c1)); } while (__all_sync(~0u, c1 - c0 < GD)); }
        BW(ab + 88 + wg * 8, 0);
        WSG(1);
        auto pack = [&](uint32_t* v, const float* u) {
            #pragma unroll
            for (int i = 0; i < 16; i++) v[i] = pack_bf16(u[2*i], u[2*i+1]);
        };
        auto rows_st = [&](uint32_t p, const uint32_t* v) {
            #pragma unroll
            for (int i = 0; i < 4; i++) stsm4t(p + i * 2048, v + 4 * i);
        };
        {
            const uint64_t d0 = desc_sw128(xuo), d1 = d0 + 512;
            const uint32_t mr = sbase + wg * 16384 + w * 128 + (tab_at(8 * (lane >> 4) + (lane & 7)) ^ ((lane & 8) << 1));
            uint32_t v[16];
            node_mma(g, wn, d0); node_mma(h, wn, d1);
            TileMMA<8>::wait_g(g);
            pack(v, g); rows_st(mr + SM_TAB, v);
            TileMMA<8>::wait_h(h);
            WSG(5);
            #pragma unroll
            for (int ks = 0; ks < 4; ks++) ldsm4t(wn + 4 * ks, mo + SM_WR + 40960 + ks * 2048);
            node_mma(g, wn, d0);
            if (wg == 2) asm volatile("bar.sync 5, 384;" ::: "memory"); else asm volatile("bar.arrive 5, 384;" ::: "memory");
            pack(v, h); rows_st(mr + SM_TAB + 8192, v);
            node_mma(h, wn, d1);
            __syncwarp();
            if (lane == 0) mbar_arrive(sbase + SM_ABAR + 112);
            WSG(7);
            TileMMA<8>::wait_g(g);
            pack(v, g);
            asm volatile("bar.sync %0, 128;" :: "r"(8 + wg) : "memory");
            rows_st(mr + SM_XU, v);
            TileMMA<8>::wait_h(h);
            WSG(11);
            pack(v, h);
            asm volatile("bar.sync %0, 128;" :: "r"(8 + wg) : "memory");
            rows_st(mr + SM_XU + 8192, v);
            __syncwarp();
            if (lane == 0) mbar_arrive(sbase + SM_ABAR + 72);
            BW(ab + 112, 0);
            __syncwarp();
            if (__builtin_expect(__reduce_or_sync(~0u, misc[1]) != 0, 0)) { slow_bin(x, ea, src, dst, wa, wb, wc, wu, wv, out, E, node0, nn, 384); asm volatile("exit;"); }
            WS(6);
        }
        uint32_t bar = bar0, xd = xd0, ed = ed0, ph = 0;
        float pn0 = 0.f, pd0 = 1.f, pn1 = 0.f, pd1 = 1.f;
        uint4 rc;
        rc.x = lds32(sbase + SM_TINFO + wg * 32 + ((lane >> 1) & 3) * 8 + 4);
        uint32_t code = __reduce_or_sync(~0u, rc.x >> 16);
        rc.x = (rc.x & 0xFFFF) ^ ((lane & 8) << 1);
        uint32_t pst = tabx + tab_at(NONE);
        auto fetch_a = [&]() {
            asm volatile("ldmatrix.sync.aligned.m8n8.x2.trans.shared.b16 {%0,%1}, [%2];" : "=r"(wf[36]), "=r"(wf[37]) : "r"(tabx + rc.x) : "memory");
        };
        auto emit = [&]() {
            asm volatile("stmatrix.sync.aligned.m8n8.x1.trans.shared.b16 [%0], {%1};" :: "r"(pst), "r"(pack_bf16(pn0 * rcpf(pd0), pn1 * rcpf(pd1))) : "memory");
        };
        auto carry = [&]() {
            if (rc.z & C_CONT) { pn0 += cyr.x; pd0 += cyr.y; pn1 += cyr.z; pd1 += cyr.w; }
            if (rc.z & C_MORE) { cyr = make_float4(pn0, pd0 - EPS2, pn1, pd1 - EPS2); pn0 = pn1 = 0.f; pst = tabx + tab_at(NONE); }
        };
        fetch_a();
        while (true) {
            switch (code & 15) {
                default: goto finished;
#define TILE(P, DN) { \
                    bool ok; float dmin; \
                    do { \
                        mbar_wait_c(bar, ph); \
                        TileMMA<P>::issue(g, h, wf, xd, ed | EDHI, ohd, wcd); \
                        const uint32_t eb = bar + 8; \
                        ph ^= bar != bar0; bar = bars - bar; xd = xds - xd; ed = eds - ed; \
                          \
                        asm volatile("{\n.reg .pred p;\nsetp.eq.u32 p, %0, 77;\n@p trap;\n}" :: "r"(xds) : "memory"); \
                        emit(); rc = lds128(eb + 8 + l16); \
                        TileMMA<P>::wait_g(g); fetch_a(); if (RIN) code = __reduce_or_sync(~0u, rc.w); TileMMA<P>::wait_h(h); \
                        mbar_arrive(eb); \
                        asm volatile("add.u32 %0, %1, %2;" : "=r"(pst) : "r"(rc.y), "r"(tabx)); \
                        ok = epi_fast<P>(g, h, __uint_as_float(rc.z), __uint_as_float(rc.w), pn0, pd0, pn1, pd1, dmin); \
                    } while (__all_sync(~0u, ok)); \
                    if (!RIN) code = __reduce_or_sync(~0u, rc.w); \
                    const bool fix = __any_sync(~0u, ((rc.z & 0x1F00) != 0) | (dmin < TAU * 2 * P)); \
                    if (FX && P > NPMIN && P != 11 && (!fix & ((code & 31) == P - 1))) goto L##DN; \
                    XCNT(P); \
                    if (__builtin_expect(fix, 0)) { \
                        int dv; \
                        const uint32_t bad = unpad(rc.z, P, g[4 * P - 4], g[4 * P - 2], pd0, pd1, dv); \
                        if (bad) { \
                            FBLOG(P); \
                            float4* gh = exact_copy(bad, lgh); \
                            epi_dump<P>(g, h, gh); \
                            const float4 r = epi_exact(gh, P, dv); \
                            if (gh) { pn0 = r.x; pd0 = r.y; pn1 = r.z; pd1 = r.w; } \
                        } \
                    } \
                    if (code & C_BRK) { carry(); if (P != 11 && (code & 15) == P) goto L##P; } \
                    if (P == 11) {         \
                        wf[16] = lds32(wca); wf[17] = lds32(wca + 256); wf[18] = lds32(wca ^ 16); wf[19] = lds32((wca ^ 16) + 256); \
                    } }
#define CASE(P, UP, DN) case P: L##P: TILE(P, DN) \
                    if (P > NPMIN && (code & 15) == P - 1) goto L##DN; \
                    if ((code & 15) == UP) goto L##UP; \
                    break;
                CASE(11, 11, 10) CASE(10, 11, 9) CASE(9, 10, 8) CASE(8, 9, 7) CASE(7, 8, 6) CASE(6, 7, 5) CASE(5, 6, 4) CASE(4, 5, 4)
#undef CASE
#undef TILE
            }
        }
finished:
        emit();
        __syncwarp();
        if (lane == 0) mbar_arrive(sbase + SM_ABAR + 48 + wg * 8);
    } else {
        asm volatile("setmaxnreg.dec.sync.aligned.u32 56;");
        auto x_ld = [&](int i0, int i1) {
            #pragma unroll
            for (int i = i0; i < i1; i++) w_box_ld(su + SM_XU + i * 8192, &tmx, node0 + i * 64, su + SM_ABAR + 88 + (i >> 1) * 8);
        };
        if (w < 3) {
            #pragma unroll
            for (int i = 0; i < 2; i++) { w_init(su + SM_BARS + (w * 2 + i) * STG, 64); w_init(su + SM_BARS + (w * 2 + i) * STG + 8, 128); }
            w_init(su + SM_ABAR + 48 + w * 8, 4);
            w_init(su + (w == 0 ? SM_GBAR + 96 * 8 : w == 1 ? SM_ABAR + 72 : SM_ABAR + 112), w == 0 ? 32 : 12);
        } else {
            #pragma unroll
            for (int i = 0; i < 4; i++) { w_init(su + SM_ABAR + (i < 3 ? 88 + i * 8 : 40), 1); w_expect(su + SM_ABAR + (i < 3 ? 88 + i * 8 : 40), i < 3 ? 16384 : nb * 64); }
            asm volatile("fence.mbarrier_init.release.cluster;" ::: "memory");
            if (HORD == 3) { uint32_t c; do { asm volatile("mov.u32 %0, %%clock;" : "=r"(c)); } while (__all_sync(~0u, c - cstart < T1)); }
            if (!HORD || HORD == 3) w_hint(gbar + HI1, all);
            asm volatile("cp.async.bulk.wait_group.read 0;" ::: "memory");
            WS(9);
            if (HORD == 1) w_hint(gbar + HI1, all);
            if (HORD == 2) { uint32_t c; do { asm volatile("mov.u32 %0, %%clock;" : "=r"(c)); } while (__all_sync(~0u, c - cstart < T1)); }
            if (D1) delay(D1);
            WS(2);
            if (H1F) w_ld(su + SM_H1, gs + G_H1, nb * 64, su + SM_ABAR + 120);
            if (P1S) {
                w_ld(su + SM_IDX, gs + b * (P1B + P2B), 3 * 384 * 8, su + SM_ABAR + 80);
                w_ld(su + SM_IDX + 3 * 384 * 8, gs + b * (P1B + P2B) + 3 * 384 * 8, nb * (CE * 2) - 3 * 384 * 8, su + SM_ABAR + 32);
            } else w_ld(su + SM_IDX, gs + b * (P1B + P2B), nb * (CE * 2), su + SM_ABAR + 80);
            if (!H1F) w_ld(su + SM_H1, gs + G_H1, nb * 64, su + SM_ABAR + 120);
        asm volatile("bar.sync 12, 512;" ::: "memory");
            if (D3) delay(D3);
            if (H2M == 1) w_inc(gbar + HI2);
            w_box_st(&tm2, P1B / 4 + b * CE, su + SM_P2);
            w_st(gs + G_H2 + b * 64, su + SM_P2 + P2B, 64);
            w_st(gs + G_L + b * 512 + 256, su + SM_P2 + P2B, 256);
            if (H2M == 0) w_sent(gbar + HI2, su + SM_MISC + 32);
            asm volatile("cp.async.bulk.commit_group;" ::: "memory");
            if (!XAFT) x_ld(0, XSPL);
        }
        const uint32_t ab = su + SM_ABAR;
        uint32_t todo = 0;
        const uint32_t mb = (lane & 3) == 3 ? bin_bits(b) : ~0u;
        WS(12);
        BW(ab + 120, 0);
        WS(13);
        {
            uint4 r[5];
            #pragma unroll
            for (int i = 0; i < 5; i++) r[i] = lds128(sbase + SM_H1 + (tid - 384 + 128 * i) * 16);
            #pragma unroll
            for (int i = 0; i < 5; i++) {
                const uint32_t bb = b << 16;
                const uint32_t m = min(min(r[i].x ^ bb, r[i].y ^ bb), min(r[i].z ^ bb, r[i].w ^ bb)) >> 16;
                if ((m == 0) | (((r[i].w ^ (tag << 14)) & 0xC000) != 0) | ((~r[i].w & mb) == 0)) todo |= 1 << i;
            }
            todo &= tid - 384 + 512 < nb * 4 ? 31 : tid - 384 + 384 < nb * 4 ? 15 : 7;
        }
        #pragma unroll 1
        for (int put = 0; put < 2; put++) {
            uint32_t any = __reduce_or_sync(~0u, todo), m = 0, u = 0;
            #pragma unroll 1
            while (any | m) {
                uint4 r = make_uint4(0, 0, 0, 0), r2 = r;
                uint32_t s, go, gd;
                bool on;
                if (__builtin_expect(m == 0, 1)) {
                    const uint32_t i = __ffs(any) - 1;
                    any &= any - 1; u = tid - 384 + 128 * i; on = (todo >> i) & 1;
                    r = lds128(sbase + SM_H1 + u * 16); if (!NOH2) r2 = lds128(sbase + SM_H2 + u * 16);
                    s = u >> 2; go = G_H1 + u * 16; gd = HB;
                } else {
                    s = ((u & ~31) + __ffs(m) - 1) >> 2; m &= m - 1; on = lane < 12;
                    go = G_L + s * 512 + 64 + lane * 16; gd = 256;
                }
                #pragma unroll 1
                for (int n = 0; n < (1 << 22); n++) {
                    const bool b1 = on && ((r.w >> 14) & 3) != tag, b2 = on && put && ((r2.w >> 16) & 3) != tag;
                    if (__builtin_expect(!__any_sync(~0u, b1 | b2), 1)) break;
                    ld_unit(r, gs + go, b1); ld_unit(r2, gs + go + gd, b2);
                }
                if (gd == HB) m = __ballot_sync(~0u, on && (~r.w & mb) == 0);
                if (on && r.w >> 16 == 255) sts32(sbase + SM_MISC + 4, 1);
                const uint32_t e[4] = {r.x, r.y, r.z, r.w}, v[4] = {r2.x, r2.y, r2.z, r2.w};
                uint32_t slot[4];
                #pragma unroll
                for (int k = 0; k < 4; k++) slot[k] = atoms_inc(sbase + SM_DEG + (on && e[k] >> 16 == (uint32_t)b ? (e[k] & 0x3FFF) : (NPB_MAX + lane) * 4));
                if (put) {
                    #pragma unroll
                    for (int k = 0; k < 4; k++) place(sbase, slot[k], v[k], s * ch);
                }
            }
            if (put == 0) {
                WS(4);
                asm volatile("bar.arrive 11, 512;" ::: "memory");
                if (w == 3) {
                    if (XAFT) x_ld(0, XSPL);
                    w_expect(su + SM_ABAR, 12288); w_expect(su + SM_ABAR + 8, 12288); w_expect(su + SM_ABAR + 16, nb * (CE * 4) - 24576);
                    w_hint(gbar + HI2, all);
                    if (D2) delay(D2);
                    asm volatile("cp.async.bulk.wait_group.read 0;" ::: "memory");
                    WS(3);
                    const char* g2 = gs + b * (P1B + P2B) + P1B;
                    w_ld(su + SM_P2, g2, 12288, su + SM_ABAR);
                    w_ld(su + SM_P2 + 12288, g2 + 12288, 12288, su + SM_ABAR + 8);
                    w_ld(su + SM_P2 + 24576, g2 + 24576, nb * (CE * 4) - 24576, su + SM_ABAR + 16);
                    if (!NOH2) w_ld(su + SM_H2, gs + G_H2, nb * 64, su + SM_ABAR + 40);
                    if (XW2) mbar_wait(ab + (XW2 - 1) * 8, 1);
                    x_ld(XSPL, 6);
                } else {
                    #pragma unroll 8
                    for (int i = 0; i < 32; i++) w_init(su + SM_GBAR + (w * 32 + i) * 8, 32);
                }
                asm volatile("bar.sync 4, 512;" ::: "memory");
                if (NOH2) mbar_wait(ab, 1); else BW(ab + 40, 0);
            }
        }
        __syncwarp();
        WS(10);
        WGD();
        const uint32_t scr = sbase + SM_PAIR + (tid & 127) * 8;
        const int r4 = lane >> 3, c8 = lane & 7;
        const uint32_t sb = su;
        const uint32_t tk = ((c8 & 1) << 4) | ((c8 >> 1) << 7);
        auto row_bytes = [](uint32_t o) { return (o & 0xFE00) | ((o << 2) & 0x180); };
        if (w < 3) {
            const char* gx = as_pair((const char*)x + c8 * 16, scr);
            const char* ge = as_pair((const char*)ea + (lane & 1) * 16, scr);
            const uint32_t gx0 = (uint32_t)(uint64_t)gx, ge0 = (uint32_t)(uint64_t)ge, hi = (uint64_t)gx >> 32, he = (uint64_t)ge >> 32;
            const int s = (lane >> 1) & 3;
            const uint32_t xs0 = sb + SM_XS + w * NSTAGE * XS_BYTES;
            const uint32_t es0 = sb + SM_ES + w * NSTAGE * ES_BYTES + r4 * 64 + (((lane ^ (r4 >> 1)) & 1) << 4) + (s >> 1) * 256 + (s & 1) * 32;
            const uint32_t bars = sb + SM_BARS + w * 2 * STG;
            const uint32_t xoffA = (2 * r4) * 128 + ((c8 ^ (2 * r4)) << 4), xoffB = (2 * r4 + 1) * 128 + ((c8 ^ (2 * r4 + 1)) << 4);
            uint64_t pol;
            asm volatile("createpolicy.fractional.L2::evict_first.b64 %0, 1.0;" : "=l"(pol));
            if (TLBW) {
                const uint32_t k = w * 32 + lane;
                asm volatile("prefetch.global.L2 [%0];" :: "l"(k < 64 ? (const char*)ea + (size_t)(E >> 6) * k * 32 : (const char*)x + (size_t)(N >> 5) * (k - 64) * 128));
            }
            asm volatile("bar.sync 6, 128;" ::: "memory");
            int tcount = 0;
            WS(15);
            uint32_t ph = 1, cur = w;
            uint32_t hist = 96 * 0x010101u;
            auto done3 = [&]() { uint32_t v = (hist >> 16) & 0xFF; asm("" : "+r"(v)); mbar_arrive(sb + SM_GBAR + v * 8); };
            const bool go = __reduce_or_sync(~0u, misc[1] == 0 && nn > 0);
            const uint32_t k32 = __shfl_sync(~0u, lane == 31 ? 0 : 32, lane), k15 = __shfl_sync(~0u, 15 | (lane & 1) << 7, lane), ca = SM_CLAIM + min(lane, 30) * 4, pa = sb + SM_TINFO + r4 * 8;
            const uint32_t pb = sb + SM_TINFO + s * 8 + 4, pc = sb + SM_TINFO + (lane & 3) * 8 + 6, xl = (lane & 8) << 1, xs = (lane & 1) << 4, ra = (lane & 15) * 16 + 16;
            auto row_of = [&](uint32_t o) { uint32_t v; asm volatile("ld.shared.u16 %0, [%1];" : "=r"(v) : "r"(pb + o) : "memory"); return v; };
            auto code_of = [&](uint32_t o) { uint32_t v; asm volatile("ld.shared.s16 %0, [%1];" : "=r"(v) : "r"(pc + o) : "memory"); return v; };
            uint32_t pw = lds32(pa + w * 32), pt = __reduce_or_sync(~0u, pw), cont = 1;
            uint4 rc = make_uint4(0, row_of(w * 32) ^ xs, code_of(w * 32) & (ONE_F | 0x1FFFu), 0);
            const uint32_t se0 = sb + SM_EID + s * 4, xab = xoffB - xoffA, das = 2 * (xs0 + xoffA) + XS_BYTES, des = 2 * es0 + ES_BYTES, brs = 2 * bars + STG;
            uint32_t br = bars;
            uint32_t da = xs0 + xoffA, de = es0;
            #pragma unroll 1
            while (go) {
                uint32_t se, sx;
                asm("dp2a.lo.u32.u32 %0, %1, 4, %2;" : "=r"(se) : "r"(pw), "r"(se0));
                asm("dp2a.lo.u32.u32 %0, %1, 2, %2;" : "=r"(sx) : "r"(pw), "r"(sb + SM_SRC));
                const int dv = pw >> 27;
                const uint32_t db = da + xab;
                const uint32_t sel = (pt >> 16) & 15, nx = (pt >> 15) & (127 << 5);
                uint32_t g;
                auto claim = [&]() { asm volatile("atom.shared.add.u32 %0, [%1], %2;" : "=r"(g) : "r"(ca + (nx == 0 ? sb : sb + 4)), "r"(k32) : "memory"); };
                if (sel == 0) break;
                if (cont & 1) asm volatile("bar.sync 3, 480;" ::: "memory");
                if (S2W && hist == 96 * 0x010101u * 256 + (cont ? 96u : (uint32_t)w)) mbar_wait_c(sb + SM_ABAR + (S2W == 1 ? 112 : 72), 0);
                switch (sel) {
#define CASE(L, P, GEN) case L: { \
                        uint32_t oe[(P + 1) / 2], o[P]; \
                        _Pragma("unroll") for (int j = 0; j < (P + 1) / 2; j++) oe[j] = lds32(se + j * 16); \
                        _Pragma("unroll") for (int j = 0; j < P; j++) o[j] = lds32(sx + j * 4); \
                        mbar_wait_h(br + 8, ph); \
                        _Pragma("unroll") for (int j = 0; j < (P + 1) / 2; j++) \
                            if (LO32) { if (!GEN && 2 * j + 2 < P) cpe<false>(he, de + j * 512, oe[j], ge0, 0, 0, pol); \
                                else if (2 * j + 1 < NPMAX || s < 2) cpe<true>(he, de + j * 512, oe[j], ge0, 4 * j + s, dv, pol); } \
                            else if (!GEN && 2 * j + 2 < P) cp16e(de + j * 512, ge, oe[j], pol); else if (2 * j + 1 < NPMAX || s < 2) cp16z<32>(de + j * 512, ge, oe[j], 4 * j + s, dv, pol); \
                        _Pragma("unroll") for (int j = 0; j < P - 1; j++) { \
                            if (LO32) { cpx<0, GEN>(hi, da + j * 1024, o[j], gx0, 2 * j, dv); cpx<1, GEN>(hi, db + j * 1024, o[j], gx0, 2 * j + 1, dv); } \
                            else if (GEN) { cp16z<128>(da + j * 1024, gx, o[j] & 0xFFFFu, 2 * j, dv, 0); cp16z<128>(db + j * 1024, gx, o[j] >> 16, 2 * j + 1, dv, 0); } \
                            else { cp16i<128>(da + j * 1024, gx, o[j] & 0xFFFFu); cp16i<128>(db + j * 1024, gx, o[j] >> 16); } } \
                        if (LO32) { cpx<0, true>(hi, da + (P - 1) * 1024, o[P - 1], gx0, 2 * P - 2, dv); cpx<1, true>(hi, db + (P - 1) * 1024, o[P - 1], gx0, 2 * P - 1, dv); } \
                        else { cp16z<128>(da + (P - 1) * 1024, gx, o[P - 1] & 0xFFFFu, 2 * P - 2, dv, 0); cp16z<128>(db + (P - 1) * 1024, gx, o[P - 1] >> 16, 2 * P - 1, dv, 0); } \
                    } break;
                    CASE(4, 4, false) CASE(5, 5, false) CASE(6, 6, false) CASE(7, 7, false) CASE(8, 8, false) CASE(9, 9, false) CASE(10, 10, false) CASE(11, 11, false)
                    CASE(15, NPMAX, true) CASE(14, 8, true) default: CASE(13, 5, true)
#undef CASE
                }
                claim();
                mbar_cp_arrive(br);
                done3();
                g = __reduce_min_sync(~0u, g);
                {
                    const uint32_t o = nx == 0 ? g : nx;
                    pw = lds32(pa + o);
                    const uint32_t ya = row_of(o), yb = code_of(o);
                    pt = __reduce_or_sync(~0u, pw);
                    const uint32_t brk = (cont | nx) > 1 ? C_BRK : 0u;
                    rc.x = ya ^ xl;
                    const uint32_t lv = brk | ((sel + (15 - NPMAX)) & 16) | (((pt >> 16) & 15) ^ sel);
                    rc.w = (yb & k15) | (lv ? 0x70000000u | brk : TAU_BITS);
                    asm volatile("st.shared.v4.u32 [%2], {%3, %0, %1, %4};\nxor.b32 %0, %5, %6;\nand.b32 %1, %7, %8;"
                                 : "+r"(rc.y), "+r"(rc.z) : "r"(br + ra), "r"(rc.x), "r"(rc.w), "r"(ya), "r"(xs), "r"(yb), "n"(ONE_F | 0x1FFFu) : "memory");
                    cont = nx;
                }
                mbar_arrive(br);
                hist = (hist << 8) | (nx == 0 ? cur : 96u);
                cur = nx == 0 ? g >> 5 : cur;
                ph ^= br != bars; br = brs - br;
                da = das - da; de = des - de;
            }
            if (cont & 1) asm volatile("bar.sync 3, 480;" ::: "memory");
            if (go) {
                mbar_wait(sb + SM_ABAR + 72, 0);
                const int g0 = 3 * max((ngroups + 2) / 3 - TR, 0) + w;
                uint32_t ro[TR], gb[TR]; uint4 xv[TR], xu[TR]; char* op[TR];
                const int gz = misc[4];
                #pragma unroll
                for (int k = 0; k < TR; k++) {
                    uint32_t nd;
                    asm volatile("ld.shared.u16 %0, [%1];" : "=r"(nd) : "r"(pa + (g0 + 3 * k) * 32 + 4) : "memory");
                    const uint32_t rb = nd == tab_at(NONE) ? 0u : row_bytes(nd);
                    xv[k] = __ldg((const uint4*)(gx + (size_t)node0 * 128 + rb));
                    op[k] = nd == tab_at(NONE) ? nullptr : (char*)out + (size_t)node0 * 128 + rb + c8 * 16;
                    ro[k] = sb + (nd ^ tk);
                    xu[k] = lds128(ro[k] + SM_XU);
                    gb[k] = __reduce_or_sync(~0u, g0 + 3 * k < gz ? sb + SM_GBAR + (g0 + 3 * k) * 8 : 0u);
                }
                #pragma unroll 1
                for (int k = 0; k < 3; k++) {
                    mbar_wait(k < 2 ? br + 8 : sb + SM_ABAR + 48 + w * 8, k < 2 ? ph : 0);
                    done3(); hist <<= 8;
                    ph ^= br != bars; br = brs - br;
                }
                #pragma unroll
                for (int k = 0; k < TR; k++) {
                    uint4 a = make_uint4(0, 0, 0, 0);
                    if (gb[k]) { mbar_wait(gb[k], 0); a = lds128(ro[k] + SM_TAB); }
                    finish(a, xu[k], xv[k]);
                    if (op[k]) *(uint4*)op[k] = a;
                }
            }
            cp_wait<0>();
        } else {
            const int r4 = WMAP ? (lane >> 1) & 3 : lane >> 3, c8 = WMAP ? (lane >> 3) * 2 + (lane & 1) : lane & 7;
            const uint32_t tk = ((c8 & 1) << 4) | ((c8 >> 1) << 7);
            const char* gx = as_pair((const char*)x + (size_t)node0 * 128 + c8 * 16, scr);
            const char* ob = as_pair((const char*)out + (size_t)node0 * 128 + c8 * 16, scr);
            asm volatile("bar.arrive 6, 128;" ::: "memory");
            WS(15);
            if (b == 0 && lane == 0) asm volatile("red.relaxed.gpu.global.add.u32 [%0], 1;" :: "l"(gbar) : "memory");
            if (misc[1] == 0) mbar_wait(sb + SM_ABAR + 72, 0);
            if (npb <= NPB_MAX - 4) sts32(sb + SM_MISC + 12, 0);
            const int rounds = misc[1] ? 0 : max((ngroups + 2) / 3 - TR, 0);
            const int gz = misc[4], fast = __reduce_min_sync(~0u, min(rounds, gz / 3));
            uint32_t wl = sb + SM_TINFO + r4 * 8 + 4, gbar = sb + SM_GBAR;
            auto row_at = [&](uint32_t a) { uint32_t n; asm volatile("ld.shared.u16 %0, [%1];" : "=r"(n) : "r"(a) : "memory"); return n; };
            auto fetch = [&](uint32_t n, uint4& v) {
                asm volatile("{\n.reg .b64 p;\ncvt.u64.u32 p, %5;\nadd.u64 p, p, %4;\nld.global.nc.L1::no_allocate.v4.u32 {%0,%1,%2,%3}, [p];\n}"
                             : "=r"(v.x), "=r"(v.y), "=r"(v.z), "=r"(v.w) : "l"(gx), "r"(n));
            };
            auto store = [&](uint32_t n, const uint4& a) {
                asm volatile("{\n.reg .b64 p;\ncvt.u64.u32 p, %1;\nadd.u64 p, p, %0;\nst.global.v4.u32 [p], {%2,%3,%4,%5};\n}" :: "l"(ob), "r"(n), "r"(a.x), "r"(a.y), "r"(a.z), "r"(a.w) : "memory");
            };
            uint32_t n0[3], o0[3]; uint4 x0[3];
            const uint32_t tw = __shfl_sync(~0u, tk, lane);
            if (fast) {
                #pragma unroll
                for (int r = 0; r < 3; r++) { const uint32_t v = row_at(wl + r * 32); n0[r] = row_bytes(v); o0[r] = v ^ tw; fetch(n0[r], x0[r]); }
            }
            #pragma unroll 1
            for (int k = 0; k < fast; k++) {
                wl += 96;
                #pragma unroll
                for (int r = 0; r < 3; r++) {
                    const uint32_t nd = n0[r];
                    const uint4 xu = lds128(sb + o0[r] + SM_XU);
                    const uint32_t v = row_at(wl + r * 32);
                    mbar_wait(gbar + r * 8, 0);
                    uint4 a = lds128(sb + o0[r] + SM_TAB);
                    n0[r] = row_bytes(v); o0[r] = v ^ tw;
                    finish(a, xu, x0[r]);
                    fetch(n0[r], x0[r]);
                    store(nd, a);
                }
                gbar += 24;
            }
            #pragma unroll 1
            for (int g = 3 * fast; g < 3 * rounds; g++) {
                const uint32_t v = row_at(sb + SM_TINFO + r4 * 8 + 4 + g * 32), nd = row_bytes(v), ro = sb + (v ^ tw);
                uint4 xv, a = make_uint4(0, 0, 0, 0);
                fetch(nd, xv);
                if (g < gz) { mbar_wait(sb + SM_GBAR + g * 8, 0); a = lds128(ro + SM_TAB); }
                finish(a, lds128(ro + SM_XU), xv);
                store(nd, a);
            }
        }
    }
    WS(17); WG1(); CG(2);
}

}

extern "C" void kernel_launch(void* const* d_in, const int* in_sizes, int n_in, void* d_out, int out_size) {
    const __nv_bfloat16* x = (const __nv_bfloat16*)d_in[0];
    const __nv_bfloat16* ea = (const __nv_bfloat16*)d_in[1];
    const int* src = (const int*)d_in[2];
    const int* dst = (const int*)d_in[3];
    const __nv_bfloat16* wa = (const __nv_bfloat16*)d_in[4];
    const __nv_bfloat16* wb = (const __nv_bfloat16*)d_in[5];
    const __nv_bfloat16* wc = (const __nv_bfloat16*)d_in[6];
    const __nv_bfloat16* wu = (const __nv_bfloat16*)d_in[7];
    const __nv_bfloat16* wv = (const __nv_bfloat16*)d_in[8];
    __nv_bfloat16* out = (__nv_bfloat16*)d_out;
    int N = in_sizes[0] / 64, E = in_sizes[2];
    static int sms = 0;
    static CUtensorMap tm1, tm2, tmw, tmx;
    static bool tm_ok = false;
    static void* gp = nullptr; static void* gb = nullptr;
    typedef CUresult (*EncFn)(CUtensorMap*, CUtensorMapDataType, cuuint32_t, void*, const cuuint64_t*, const cuuint64_t*, const cuuint32_t*,
                              const cuuint32_t*, CUtensorMapInterleave, CUtensorMapSwizzle, CUtensorMapL2promotion, CUtensorMapFloatOOBfill);
    static void* fn = nullptr;
    auto enc = [&](CUtensorMap* tm, const void* base, cuuint64_t cols, cuuint64_t rows, cuuint32_t bc, cuuint32_t br, CUtensorMapSwizzle sw) {
        cuuint64_t g2[2] = {cols, rows}, gs[1] = {cols * 4};
        cuuint32_t b2[2] = {bc, br}, es[2] = {1, 1};
        return ((EncFn)fn)(tm, CU_TENSOR_MAP_DATA_TYPE_UINT32, 2, (void*)base, g2, gs, b2, es, CU_TENSOR_MAP_INTERLEAVE_NONE, sw,
                           CU_TENSOR_MAP_L2_PROMOTION_NONE, CU_TENSOR_MAP_FLOAT_OOB_FILL_NONE) == CUDA_SUCCESS;
    };
    if (!sms) {
        cudaDeviceGetAttribute(&sms, cudaDevAttrMultiProcessorCount, 0);
        cudaDriverEntryPointQueryResult qr;
        cudaGetDriverEntryPoint("cuTensorMapEncodeTiled", &fn, cudaEnableDefault, &qr);
        cudaGetSymbolAddress(&gp, g_str); cudaGetSymbolAddress(&gb, g_bar);
        if (fn && gp && gb) {
            const cuuint32_t rows = sms < NB_MAX ? sms : NB_MAX;
            tm_ok = enc(&tm1, gp, (P1B + P2B) / 4, NB_MAX, CE / 2, rows, CU_TENSOR_MAP_SWIZZLE_NONE) && enc(&tm2, gp, (P1B + P2B) / 4, NB_MAX, CE, rows, CU_TENSOR_MAP_SWIZZLE_NONE);
        }
        cudaFuncSetAttribute(gcn_kernel<true>, cudaFuncAttributeMaxDynamicSharedMemorySize, SMEM_LAUNCH);
        cudaFuncSetAttribute(gcn_kernel<false>, cudaFuncAttributeMaxDynamicSharedMemorySize, SMEM_LAUNCH);
    }
    int nb = sms < NB_MAX ? sms : NB_MAX;
    int npb = (N + nb - 1) / nb;
    int ch = (((E + nb - 1) / nb) + 3) & ~3;
    const uintptr_t wp[4] = {(uintptr_t)wb, (uintptr_t)wv, (uintptr_t)wa, (uintptr_t)wu};
    uintptr_t wlo = wp[0], whi = wp[0], wal = 0;
    for (int i = 0; i < 4; i++) { wlo = wp[i] < wlo ? wp[i] : wlo; whi = wp[i] > whi ? wp[i] : whi; wal |= wp[i] - wp[0]; }
    bool ok = tm_ok && nb >= NB_MIN && npb < NPB_MAX && ch <= CH_MAX && !(E & 3) && N <= 65535 && npb >= 2 && !(wal & 127) && (whi - wlo) >> 7 < (1u << 30) &&
              !(((uintptr_t)src | (uintptr_t)dst | (uintptr_t)x | (uintptr_t)wb | (uintptr_t)wc) & 15);
    ok = ok && enc(&tmw, (const void*)wlo, 32, ((whi - wlo) >> 7) + 64, 32, 64, CU_TENSOR_MAP_SWIZZLE_128B) && enc(&tmx, x, 32, N, 32, 64, CU_TENSOR_MAP_SWIZZLE_128B);
    if (!ok) {
        int g = 1024, p = (N + g - 1) / g;
        slow_kernel<<<g, 256>>>(x, ea, src, dst, wa, wb, wc, wu, wv, out, N, E, p < 1 ? 1 : p);
        return;
    }
    int4 wrow = make_int4((int)((wp[0] - wlo) >> 7), (int)((wp[1] - wlo) >> 7), (int)((wp[2] - wlo) >> 7), (int)((wp[3] - wlo) >> 7));
    uint32_t magic = (uint32_t)((1ull << 32) / (uint32_t)npb) + 1u;
    void* args[] = {&dst, &gb, &gp, &src, &E, &ch, &N, &npb, &magic, &x, &ea, &wa, &wb, &wc, &wu, &wv, &out, &wrow, &tm1, &tm2, &tmw, &tmx};
    const bool lo32 = ((uintptr_t)x >> 32) == (((uintptr_t)x + (size_t)N * 128 - 1) >> 32) && ((uintptr_t)ea >> 32) == (((uintptr_t)ea + (size_t)E * 32 - 1) >> 32);
    cudaLaunchCooperativeKernel(lo32 && !FORCE64 ? (const void*)gcn_kernel<true> : (const void*)gcn_kernel<false>, dim3(nb), dim3(THREADS), args, SMEM_LAUNCH, cudaStreamPerThread);
}
```

```cpp
#include <cuda_runtime.h>
#include <cuda.h>
#include <cuda_bf16.h>
#include <stdint.h>

namespace {

constexpr int N_MAX = 65536;
constexpr int NPMAX = 11;
constexpr int NPMIN = 4;
constexpr int THREADS = 512;
constexpr int EPT = 12;
constexpr int CH_MAX = THREADS * EPT;
constexpr int NB_MAX = 134, NB_MIN = 120;
constexpr int CE = 64;
constexpr int P1B = NB_MAX * CE * 2;
constexpr int P2B = NB_MAX * CE * 4;
constexpr int HB = NB_MAX * 64;
constexpr int G_H1 = NB_MAX * (P1B + P2B), G_H2 = G_H1 + HB, G_L = G_H2 + HB, G_END = G_L + NB_MAX * 512;
constexpr int NPB_MAX = 384;
constexpr int SLOT_CAP = 6784;
constexpr int TILE_CAP = 124;
constexpr int TILE_X = 8;
constexpr int NCLS = 64;
constexpr int NSTAGE = 2;
constexpr int PD = 300;
constexpr int TR = 2;
constexpr float LOG2E = 1.4426950408889634f;

__device__ __align__(256) uint4 g_str[G_END / 16];
__device__ __align__(128) unsigned g_bar[8];
__device__ float g_slow[N_MAX * 128];

#define WS(k)
#define WGD()
#define WG0()
#define WG1()
#define CG(k)
#define SMEM_LAUNCH SMEM_BYTES
#define FORCE64 0
#define EDHI ((16ull << 32) | (3ull << 62))
template<int NP> struct TileMMA;
template<> struct TileMMA<4> {
  static __device__ __forceinline__ void issue(float* g, float* h, const uint32_t* w, uint32_t dx, uint64_t de, uint64_t dh, uint64_t dc) {
    asm volatile(
      "{\n.reg .b64 dx0, dx1, dx2, dx3;\n.reg .b32 l1, l2, l3, hx;\nmov.b32 hx, 0x40000040;\n"
      "add.u32 l1, %72, 2;\nadd.u32 l2, %72, 4;\nadd.u32 l3, %72, 6;\n"
      "mov.b64 dx0, {%72, hx};\nmov.b64 dx1, {l1, hx};\nmov.b64 dx2, {l2, hx};\nmov.b64 dx3, {l3, hx};\n"
      "wgmma.fence.sync.aligned;\n"
      "wgmma.mma_async.sync.aligned.m64n32k16.f32.bf16.bf16 {%0, %1, %2, %3, %4, %5, %6, %7, %8, %9, %10, %11, %12, %13, %14, %15}, {%68, %69, %70, %71}, %74, 0, 1, 1, 0;\n"
      "wgmma.mma_async.sync.aligned.m64n32k16.f32.bf16.bf16 {%0, %1, %2, %3, %4, %5, %6, %7, %8, %9, %10, %11, %12, %13, %14, %15}, {%48, %49, %50, %51}, %73, 1, 1, 1, 0;\n"
      "wgmma.mma_async.sync.aligned.m64n32k16.f32.bf16.bf16 {%0, %1, %2, %3, %4, %5, %6, %7, %8, %9, %10, %11, %12, %13, %14, %15}, {%32, %33, %34, %35}, dx0, 1, 1, 1, 0;\n"
      "wgmma.mma_async.sync.aligned.m64n32k16.f32.bf16.bf16 {%0, %1, %2, %3, %4, %5, %6, %7, %8, %9, %10, %11, %12, %13, %14, %15}, {%36, %37, %38, %39}, dx1, 1, 1, 1, 0;\n"
      "wgmma.mma_async.sync.aligned.m64n32k16.f32.bf16.bf16 {%0, %1, %2, %3, %4, %5, %6, %7, %8, %9, %10, %11, %12, %13, %14, %15}, {%40, %41, %42, %43}, dx2, 1, 1, 1, 0;\n"
      "wgmma.mma_async.sync.aligned.m64n32k16.f32.bf16.bf16 {%0, %1, %2, %3, %4, %5, %6, %7, %8, %9, %10, %11, %12, %13, %14, %15}, {%44, %45, %46, %47}, dx3, 1, 1, 1, 0;\n"
      "wgmma.commit_group.sync.aligned;\n"
      "wgmma.mma_async.sync.aligned.m64n32k16.f32.bf16.bf16 {%16, %17, %18, %19, %20, %21, %22, %23, %24, %25, %26, %27, %28, %29, %30, %31}, {%52, %53, %54, %55}, dx0, 0, 1, 1, 0;\n"
      "wgmma.mma_async.sync.aligned.m64n32k16.f32.bf16.bf16 {%16, %17, %18, %19, %20, %21, %22, %23, %24, %25, %26, %27, %28, %29, %30, %31}, {%56, %57, %58, %59}, dx1, 1, 1, 1, 0;\n"
      "wgmma.mma_async.sync.aligned.m64n32k16.f32.bf16.bf16 {%16, %17, %18, %19, %20, %21, %22, %23, %24, %25, %26, %27, %28, %29, %30, %31}, {%60, %61, %62, %63}, dx2, 1, 1, 1, 0;\n"
      "wgmma.mma_async.sync.aligned.m64n32k16.f32.bf16.bf16 {%16, %17, %18, %19, %20, %21, %22, %23, %24, %25, %26, %27, %28, %29, %30, %31}, {%64, %65, %66, %67}, dx3, 1, 1, 1, 0;\n"
      "wgmma.commit_group.sync.aligned;\n}\n"
      : "=f"(g[0]), "=f"(g[1]), "=f"(g[2]), "=f"(g[3]), "=f"(g[4]), "=f"(g[5]), "=f"(g[6]), "=f"(g[7]), "=f"(g[8]), "=f"(g[9]), "=f"(g[10]), "=f"(g[11]), "=f"(g[12]), "=f"(g[13]), "=f"(g[14]), "=f"(g[15]),
        "=f"(h[0]), "=f"(h[1]), "=f"(h[2]), "=f"(h[3]), "=f"(h[4]), "=f"(h[5]), "=f"(h[6]), "=f"(h[7]), "=f"(h[8]), "=f"(h[9]), "=f"(h[10]), "=f"(h[11]), "=f"(h[12]), "=f"(h[13]), "=f"(h[14]), "=f"(h[15])
      : "r"(w[0]), "r"(w[1]), "r"(w[2]), "r"(w[3]), "r"(w[4]), "r"(w[5]), "r"(w[6]), "r"(w[7]), "r"(w[8]), "r"(w[9]), "r"(w[10]), "r"(w[11]), "r"(w[12]), "r"(w[13]), "r"(w[14]), "r"(w[15]), "r"(w[16]), "r"(w[17]), "r"(w[18]), "r"(w[19]), "r"(w[20]), "r"(w[21]), "r"(w[22]), "r"(w[23]), "r"(w[24]), "r"(w[25]), "r"(w[26]), "r"(w[27]), "r"(w[28]), "r"(w[29]), "r"(w[30]), "r"(w[31]), "r"(w[32]), "r"(w[33]), "r"(w[34]), "r"(w[35]), "r"(w[36]), "r"(w[37]), "r"(w[38]), "r"(w[39]), "r"(dx), "l"(de), "l"(dh)
      : "memory");
  }
  static __device__ __forceinline__ void wait_g(float* g) {
    asm volatile("wgmma.wait_group.sync.aligned 1;\n"
      : "+f"(g[0]), "+f"(g[1]), "+f"(g[2]), "+f"(g[3]), "+f"(g[4]), "+f"(g[5]), "+f"(g[6]), "+f"(g[7]), "+f"(g[8]), "+f"(g[9]), "+f"(g[10]), "+f"(g[11]), "+f"(g[12]), "+f"(g[13]), "+f"(g[14]), "+f"(g[15])
      :: "memory");
  }
  static __device__ __forceinline__ void wait_h(float* h) {
    asm volatile("wgmma.wait_group.sync.aligned 0;\n"
      : "+f"(h[0]), "+f"(h[1]), "+f"(h[2]), "+f"(h[3]), "+f"(h[4]), "+f"(h[5]), "+f"(h[6]), "+f"(h[7]), "+f"(h[8]), "+f"(h[9]), "+f"(h[10]), "+f"(h[11]), "+f"(h[12]), "+f"(h[13]), "+f"(h[14]), "+f"(h[15])
      :: "memory");
  }
};
template<> struct TileMMA<5> {
  static __device__ __forceinline__ void issue(float* g, float* h, const uint32_t* w, uint32_t dx, uint64_t de, uint64_t dh, uint64_t dc) {
    asm volatile(
      "{\n.reg .b64 dx0, dx1, dx2, dx3;\n.reg .b32 l1, l2, l3, hx;\nmov.b32 hx, 0x40000040;\n"
      "add.u32 l1, %80, 2;\nadd.u32 l2, %80, 4;\nadd.u32 l3, %80, 6;\n"
      "mov.b64 dx0, {%80, hx};\nmov.b64 dx1, {l1, hx};\nmov.b64 dx2, {l2, hx};\nmov.b64 dx3, {l3, hx};\n"
      "wgmma.fence.sync.aligned;\n"
      "wgmma.mma_async.sync.aligned.m64n40k16.f32.bf16.bf16 {%0, %1, %2, %3, %4, %5, %6, %7, %8, %9, %10, %11, %12, %13, %14, %15, %16, %17, %18, %19}, {%76, %77, %78, %79}, %82, 0, 1, 1, 0;\n"
      "wgmma.mma_async.sync.aligned.m64n40k16.f32.bf16.bf16 {%0, %1, %2, %3, %4, %5, %6, %7, %8, %9, %10, %11, %12, %13, %14, %15, %16, %17, %18, %19}, {%56, %57, %58, %59}, %81, 1, 1, 1, 0;\n"
      "wgmma.mma_async.sync.aligned.m64n40k16.f32.bf16.bf16 {%0, %1, %2, %3, %4, %5, %6, %7, %8, %9, %10, %11, %12, %13, %14, %15, %16, %17, %18, %19}, {%40, %41, %42, %43}, dx0, 1, 1, 1, 0;\n"
      "wgmma.mma_async.sync.aligned.m64n40k16.f32.bf16.bf16 {%0, %1, %2, %3, %4, %5, %6, %7, %8, %9, %10, %11, %12, %13, %14, %15, %16, %17, %18, %19}, {%44, %45, %46, %47}, dx1, 1, 1, 1, 0;\n"
      "wgmma.mma_async.sync.aligned.m64n40k16.f32.bf16.bf16 {%0, %1, %2, %3, %4, %5, %6, %7, %8, %9, %10, %11, %12, %13, %14, %15, %16, %17, %18, %19}, {%48, %49, %50, %51}, dx2, 1, 1, 1, 0;\n"
      "wgmma.mma_async.sync.aligned.m64n40k16.f32.bf16.bf16 {%0, %1, %2, %3, %4, %5, %6, %7, %8, %9, %10, %11, %12, %13, %14, %15, %16, %17, %18, %19}, {%52, %53, %54, %55}, dx3, 1, 1, 1, 0;\n"
      "wgmma.commit_group.sync.aligned;\n"
      "wgmma.mma_async.sync.aligned.m64n40k16.f32.bf16.bf16 {%20, %21, %22, %23, %24, %25, %26, %27, %28, %29, %30, %31, %32, %33, %34, %35, %36, %37, %38, %39}, {%60, %61, %62, %63}, dx0, 0, 1, 1, 0;\n"
      "wgmma.mma_async.sync.aligned.m64n40k16.f32.bf16.bf16 {%20, %21, %22, %23, %24, %25, %26, %27, %28, %29, %30, %31, %32, %33, %34, %35, %36, %37, %38, %39}, {%64, %65, %66, %67}, dx1, 1, 1, 1, 0;\n"
      "wgmma.mma_async.sync.aligned.m64n40k16.f32.bf16.bf16 {%20, %21, %22, %23, %24, %25, %26, %27, %28, %29, %30, %31, %32, %33, %34, %35, %36, %37, %38, %39}, {%68, %69, %70, %71}, dx2, 1, 1, 1, 0;\n"
      "wgmma.mma_async.sync.aligned.m64n40k16.f32.bf16.bf16 {%20, %21, %22, %23, %24, %25, %26, %27, %28, %29, %30, %31, %32, %33, %34, %35, %36, %37, %38, %39}, {%72, %73, %74, %75}, dx3, 1, 1, 1, 0;\n"
      "wgmma.commit_group.sync.aligned;\n}\n"
      : "=f"(g[0]), "=f"(g[1]), "=f"(g[2]), "=f"(g[3]), "=f"(g[4]), "=f"(g[5]), "=f"(g[6]), "=f"(g[7]), "=f"(g[8]), "=f"(g[9]), "=f"(g[10]), "=f"(g[11]), "=f"(g[12]), "=f"(g[13]), "=f"(g[14]), "=f"(g[15]), "=f"(g[16]), "=f"(g[17]), "=f"(g[18]), "=f"(g[19]),
        "=f"(h[0]), "=f"(h[1]), "=f"(h[2]), "=f"(h[3]), "=f"(h[4]), "=f"(h[5]), "=f"(h[6]), "=f"(h[7]), "=f"(h[8]), "=f"(h[9]), "=f"(h[10]), "=f"(h[11]), "=f"(h[12]), "=f"(h[13]), "=f"(h[14]), "=f"(h[15]), "=f"(h[16]), "=f"(h[17]), "=f"(h[18]), "=f"(h[19])
      : "r"(w[0]), "r"(w[1]), "r"(w[2]), "r"(w[3]), "r"(w[4]), "r"(w[5]), "r"(w[6]), "r"(w[7]), "r"(w[8]), "r"(w[9]), "r"(w[10]), "r"(w[11]), "r"(w[12]), "r"(w[13]), "r"(w[14]), "r"(w[15]), "r"(w[16]), "r"(w[17]), "r"(w[18]), "r"(w[19]), "r"(w[20]), "r"(w[21]), "r"(w[22]), "r"(w[23]), "r"(w[24]), "r"(w[25]), "r"(w[26]), "r"(w[27]), "r"(w[28]), "r"(w[29]), "r"(w[30]), "r"(w[31]), "r"(w[32]), "r"(w[33]), "r"(w[34]), "r"(w[35]), "r"(w[36]), "r"(w[37]), "r"(w[38]), "r"(w[39]), "r"(dx), "l"(de), "l"(dh)
      : "memory");
  }
  static __device__ __forceinline__ void wait_g(float* g) {
    asm volatile("wgmma.wait_group.sync.aligned 1;\n"
      : "+f"(g[0]), "+f"(g[1]), "+f"(g[2]), "+f"(g[3]), "+f"(g[4]), "+f"(g[5]), "+f"(g[6]), "+f"(g[7]), "+f"(g[8]), "+f"(g[9]), "+f"(g[10]), "+f"(g[11]), "+f"(g[12]), "+f"(g[13]), "+f"(g[14]), "+f"(g[15]), "+f"(g[16]), "+f"(g[17]), "+f"(g[18]), "+f"(g[19])
      :: "memory");
  }
  static __device__ __forceinline__ void wait_h(float* h) {
    asm volatile("wgmma.wait_group.sync.aligned 0;\n"
      : "+f"(h[0]), "+f"(h[1]), "+f"(h[2]), "+f"(h[3]), "+f"(h[4]), "+f"(h[5]), "+f"(h[6]), "+f"(h[7]), "+f"(h[8]), "+f"(h[9]), "+f"(h[10]), "+f"(h[11]), "+f"(h[12]), "+f"(h[13]), "+f"(h[14]), "+f"(h[15]), "+f"(h[16]), "+f"(h[17]), "+f"(h[18]), "+f"(h[19])
      :: "memory");
  }
};
template<> struct TileMMA<6> {
  static __device__ __forceinline__ void issue(float* g, float* h, const uint32_t* w, uint32_t dx, uint64_t de, uint64_t dh, uint64_t dc) {
    asm volatile(
      "{\n.reg .b64 dx0, dx1, dx2, dx3;\n.reg .b32 l1, l2, l3, hx;\nmov.b32 hx, 0x40000040;\n"
      "add.u32 l1, %88, 2;\nadd.u32 l2, %88, 4;\nadd.u32 l3, %88, 6;\n"
      "mov.b64 dx0, {%88, hx};\nmov.b64 dx1, {l1, hx};\nmov.b64 dx2, {l2, hx};\nmov.b64 dx3, {l3, hx};\n"
      "wgmma.fence.sync.aligned;\n"
      "wgmma.mma_async.sync.aligned.m64n48k16.f32.bf16.bf16 {%0, %1, %2, %3, %4, %5, %6, %7, %8, %9, %10, %11, %12, %13, %14, %15, %16, %17, %18, %19, %20, %21, %22, %23}, {%84, %85, %86, %87}, %90, 0, 1, 1, 0;\n"
      "wgmma.mma_async.sync.aligned.m64n48k16.f32.bf16.bf16 {%0, %1, %2, %3, %4, %5, %6, %7, %8, %9, %10, %11, %12, %13, %14, %15, %16, %17, %18, %19, %20, %21, %22, %23}, {%64, %65, %66, %67}, %89, 1, 1, 1, 0;\n"
      "wgmma.mma_async.sync.aligned.m64n48k16.f32.bf16.bf16 {%0, %1, %2, %3, %4, %5, %6, %7, %8, %9, %10, %11, %12, %13, %14, %15, %16, %17, %18, %19, %20, %21, %22, %23}, {%48, %49, %50, %51}, dx0, 1, 1, 1, 0;\n"
      "wgmma.mma_async.sync.aligned.m64n48k16.f32.bf16.bf16 {%0, %1, %2, %3, %4, %5, %6, %7, %8, %9, %10, %11, %12, %13, %14, %15, %16, %17, %18, %19, %20, %21, %22, %23}, {%52, %53, %54, %55}, dx1, 1, 1, 1, 0;\n"
      "wgmma.mma_async.sync.aligned.m64n48k16.f32.bf16.bf16 {%0, %1, %2, %3, %4, %5, %6, %7, %8, %9, %10, %11, %12, %13, %14, %15, %16, %17, %18, %19, %20, %21, %22, %23}, {%56, %57, %58, %59}, dx2, 1, 1, 1, 0;\n"
      "wgmma.mma_async.sync.aligned.m64n48k16.f32.bf16.bf16 {%0, %1, %2, %3, %4, %5, %6, %7, %8, %9, %10, %11, %12, %13, %14, %15, %16, %17, %18, %19, %20, %21, %22, %23}, {%60, %61, %62, %63}, dx3, 1, 1, 1, 0;\n"
      "wgmma.commit_group.sync.aligned;\n"
      "wgmma.mma_async.sync.aligned.m64n48k16.f32.bf16.bf16 {%24, %25, %26, %27, %28, %29, %30, %31, %32, %33, %34, %35, %36, %37, %38, %39, %40, %41, %42, %43, %44, %45, %46, %47}, {%68, %69, %70, %71}, dx0, 0, 1, 1, 0;\n"
      "wgmma.mma_async.sync.aligned.m64n48k16.f32.bf16.bf16 {%24, %25, %26, %27, %28, %29, %30, %31, %32, %33, %34, %35, %36, %37, %38, %39, %40, %41, %42, %43, %44, %45, %46, %47}, {%72, %73, %74, %75}, dx1, 1, 1, 1, 0;\n"
      "wgmma.mma_async.sync.aligned.m64n48k16.f32.bf16.bf16 {%24, %25, %26, %27, %28, %29, %30, %31, %32, %33, %34, %35, %36, %37, %38, %39, %40, %41, %42, %43, %44, %45, %46, %47}, {%76, %77, %78, %79}, dx2, 1, 1, 1, 0;\n"
      "wgmma.mma_async.sync.aligned.m64n48k16.f32.bf16.bf16 {%24, %25, %26, %27, %28, %29, %30, %31, %32, %33, %34, %35, %36, %37, %38, %39, %40, %41, %42, %43, %44, %45, %46, %47}, {%80, %81, %82, %83}, dx3, 1, 1, 1, 0;\n"
      "wgmma.commit_group.sync.aligned;\n}\n"
      : "=f"(g[0]), "=f"(g[1]), "=f"(g[2]), "=f"(g[3]), "=f"(g[4]), "=f"(g[5]), "=f"(g[6]), "=f"(g[7]), "=f"(g[8]), "=f"(g[9]), "=f"(g[10]), "=f"(g[11]), "=f"(g[12]), "=f"(g[13]), "=f"(g[14]), "=f"(g[15]), "=f"(g[16]), "=f"(g[17]), "=f"(g[18]), "=f"(g[19]), "=f"(g[20]), "=f"(g[21]), "=f"(g[22]), "=f"(g[23]),
        "=f"(h[0]), "=f"(h[1]), "=f"(h[2]), "=f"(h[3]), "=f"(h[4]), "=f"(h[5]), "=f"(h[6]), "=f"(h[7]), "=f"(h[8]), "=f"(h[9]), "=f"(h[10]), "=f"(h[11]), "=f"(h[12]), "=f"(h[13]), "=f"(h[14]), "=f"(h[15]), "=f"(h[16]), "=f"(h[17]), "=f"(h[18]), "=f"(h[19]), "=f"(h[20]), "=f"(h[21]), "=f"(h[22]), "=f"(h[23])
      : "r"(w[0]), "r"(w[1]), "r"(w[2]), "r"(w[3]), "r"(w[4]), "r"(w[5]), "r"(w[6]), "r"(w[7]), "r"(w[8]), "r"(w[9]), "r"(w[10]), "r"(w[11]), "r"(w[12]), "r"(w[13]), "r"(w[14]), "r"(w[15]), "r"(w[16]), "r"(w[17]), "r"(w[18]), "r"(w[19]), "r"(w[20]), "r"(w[21]), "r"(w[22]), "r"(w[23]), "r"(w[24]), "r"(w[25]), "r"(w[26]), "r"(w[27]), "r"(w[28]), "r"(w[29]), "r"(w[30]), "r"(w[31]), "r"(w[32]), "r"(w[33]), "r"(w[34]), "r"(w[35]), "r"(w[36]), "r"(w[37]), "r"(w[38]), "r"(w[39]), "r"(dx), "l"(de), "l"(dh)
      : "memory");
  }
  static __device__ __forceinline__ void wait_g(float* g) {
    asm volatile("wgmma.wait_group.sync.aligned 1;\n"
      : "+f"(g[0]), "+f"(g[1]), "+f"(g[2]), "+f"(g[3]), "+f"(g[4]), "+f"(g[5]), "+f"(g[6]), "+f"(g[7]), "+f"(g[8]), "+f"(g[9]), "+f"(g[10]), "+f"(g[11]), "+f"(g[12]), "+f"(g[13]), "+f"(g[14]), "+f"(g[15]), "+f"(g[16]), "+f"(g[17]), "+f"(g[18]), "+f"(g[19]), "+f"(g[20]), "+f"(g[21]), "+f"(g[22]), "+f"(g[23])
      :: "memory");
  }
  static __device__ __forceinline__ void wait_h(float* h) {
    asm volatile("wgmma.wait_group.sync.aligned 0;\n"
      : "+f"(h[0]), "+f"(h[1]), "+f"(h[2]), "+f"(h[3]), "+f"(h[4]), "+f"(h[5]), "+f"(h[6]), "+f"(h[7]), "+f"(h[8]), "+f"(h[9]), "+f"(h[10]), "+f"(h[11]), "+f"(h[12]), "+f"(h[13]), "+f"(h[14]), "+f"(h[15]), "+f"(h[16]), "+f"(h[17]), "+f"(h[18]), "+f"(h[19]), "+f"(h[20]), "+f"(h[21]), "+f"(h[22]), "+f"(h[23])
      :: "memory");
  }
};
template<> struct TileMMA<7> {
  static __device__ __forceinline__ void issue(float* g, float* h, const uint32_t* w, uint32_t dx, uint64_t de, uint64_t dh, uint64_t dc) {
    asm volatile(
      "{\n.reg .b64 dx0, dx1, dx2, dx3;\n.reg .b32 l1, l2, l3, hx;\nmov.b32 hx, 0x40000040;\n"
      "add.u32 l1, %96, 2;\nadd.u32 l2, %96, 4;\nadd.u32 l3, %96, 6;\n"
      "mov.b64 dx0, {%96, hx};\nmov.b64 dx1, {l1, hx};\nmov.b64 dx2, {l2, hx};\nmov.b64 dx3, {l3, hx};\n"
      "wgmma.fence.sync.aligned;\n"
      "wgmma.mma_async.sync.aligned.m64n56k16.f32.bf16.bf16 {%0, %1, %2, %3, %4, %5, %6, %7, %8, %9, %10, %11, %12, %13, %14, %15, %16, %17, %18, %19, %20, %21, %22, %23, %24, %25, %26, %27}, {%92, %93, %94, %95}, %98, 0, 1, 1, 0;\n"
      "wgmma.mma_async.sync.aligned.m64n56k16.f32.bf16.bf16 {%0, %1, %2, %3, %4, %5, %6, %7, %8, %9, %10, %11, %12, %13, %14, %15, %16, %17, %18, %19, %20, %21, %22, %23, %24, %25, %26, %27}, {%72, %73, %74, %75}, %97, 1, 1, 1, 0;\n"
      "wgmma.mma_async.sync.aligned.m64n56k16.f32.bf16.bf16 {%0, %1, %2, %3, %4, %5, %6, %7, %8, %9, %10, %11, %12, %13, %14, %15, %16, %17, %18, %19, %20, %21, %22, %23, %24, %25, %26, %27}, {%56, %57, %58, %59}, dx0, 1, 1, 1, 0;\n"
      "wgmma.mma_async.sync.aligned.m64n56k16.f32.bf16.bf16 {%0, %1, %2, %3, %4, %5, %6, %7, %8, %9, %10, %11, %12, %13, %14, %15, %16, %17, %18, %19, %20, %21, %22, %23, %24, %25, %26, %27}, {%60, %61, %62, %63}, dx1, 1, 1, 1, 0;\n"
      "wgmma.mma_async.sync.aligned.m64n56k16.f32.bf16.bf16 {%0, %1, %2, %3, %4, %5, %6, %7, %8, %9, %10, %11, %12, %13, %14, %15, %16, %17, %18, %19, %20, %21, %22, %23, %24, %25, %26, %27}, {%64, %65, %66, %67}, dx2, 1, 1, 1, 0;\n"
      "wgmma.mma_async.sync.aligned.m64n56k16.f32.bf16.bf16 {%0, %1, %2, %3, %4, %5, %6, %7, %8, %9, %10, %11, %12, %13, %14, %15, %16, %17, %18, %19, %20, %21, %22, %23, %24, %25, %26, %27}, {%68, %69, %70, %71}, dx3, 1, 1, 1, 0;\n"
      "wgmma.commit_group.sync.aligned;\n"
      "wgmma.mma_async.sync.aligned.m64n56k16.f32.bf16.bf16 {%28, %29, %30, %31, %32, %33, %34, %35, %36, %37, %38, %39, %40, %41, %42, %43, %44, %45, %46, %47, %48, %49, %50, %51, %52, %53, %54, %55}, {%76, %77, %78, %79}, dx0, 0, 1, 1, 0;\n"
      "wgmma.mma_async.sync.aligned.m64n56k16.f32.bf16.bf16 {%28, %29, %30, %31, %32, %33, %34, %35, %36, %37, %38, %39, %40, %41, %42, %43, %44, %45, %46, %47, %48, %49, %50, %51, %52, %53, %54, %55}, {%80, %81, %82, %83}, dx1, 1, 1, 1, 0;\n"
      "wgmma.mma_async.sync.aligned.m64n56k16.f32.bf16.bf16 {%28, %29, %30, %31, %32, %33, %34, %35, %36, %37, %38, %39, %40, %41, %42, %43, %44, %45, %46, %47, %48, %49, %50, %51, %52, %53, %54, %55}, {%84, %85, %86, %87}, dx2, 1, 1, 1, 0;\n"
      "wgmma.mma_async.sync.aligned.m64n56k16.f32.bf16.bf16 {%28, %29, %30, %31, %32, %33, %34, %35, %36, %37, %38, %39, %40, %41, %42, %43, %44, %45, %46, %47, %48, %49, %50, %51, %52, %53, %54, %55}, {%88, %89, %90, %91}, dx3, 1, 1, 1, 0;\n"
      "wgmma.commit_group.sync.aligned;\n}\n"
      : "=f"(g[0]), "=f"(g[1]), "=f"(g[2]), "=f"(g[3]), "=f"(g[4]), "=f"(g[5]), "=f"(g[6]), "=f"(g[7]), "=f"(g[8]), "=f"(g[9]), "=f"(g[10]), "=f"(g[11]), "=f"(g[12]), "=f"(g[13]), "=f"(g[14]), "=f"(g[15]), "=f"(g[16]), "=f"(g[17]), "=f"(g[18]), "=f"(g[19]), "=f"(g[20]), "=f"(g[21]), "=f"(g[22]), "=f"(g[23]), "=f"(g[24]), "=f"(g[25]), "=f"(g[26]), "=f"(g[27]),
        "=f"(h[0]), "=f"(h[1]), "=f"(h[2]), "=f"(h[3]), "=f"(h[4]), "=f"(h[5]), "=f"(h[6]), "=f"(h[7]), "=f"(h[8]), "=f"(h[9]), "=f"(h[10]), "=f"(h[11]), "=f"(h[12]), "=f"(h[13]), "=f"(h[14]), "=f"(h[15]), "=f"(h[16]), "=f"(h[17]), "=f"(h[18]), "=f"(h[19]), "=f"(h[20]), "=f"(h[21]), "=f"(h[22]), "=f"(h[23]), "=f"(h[24]), "=f"(h[25]), "=f"(h[26]), "=f"(h[27])
      : "r"(w[0]), "r"(w[1]), "r"(w[2]), "r"(w[3]), "r"(w[4]), "r"(w[5]), "r"(w[6]), "r"(w[7]), "r"(w[8]), "r"(w[9]), "r"(w[10]), "r"(w[11]), "r"(w[12]), "r"(w[13]), "r"(w[14]), "r"(w[15]), "r"(w[16]), "r"(w[17]), "r"(w[18]), "r"(w[19]), "r"(w[20]), "r"(w[21]), "r"(w[22]), "r"(w[23]), "r"(w[24]), "r"(w[25]), "r"(w[26]), "r"(w[27]), "r"(w[28]), "r"(w[29]), "r"(w[30]), "r"(w[31]), "r"(w[32]), "r"(w[33]), "r"(w[34]), "r"(w[35]), "r"(w[36]), "r"(w[37]), "r"(w[38]), "r"(w[39]), "r"(dx), "l"(de), "l"(dh)
      : "memory");
  }
  static __device__ __forceinline__ void wait_g(float* g) {
    asm volatile("wgmma.wait_group.sync.aligned 1;\n"
      : "+f"(g[0]), "+f"(g[1]), "+f"(g[2]), "+f"(g[3]), "+f"(g[4]), "+f"(g[5]), "+f"(g[6]), "+f"(g[7]), "+f"(g[8]), "+f"(g[9]), "+f"(g[10]), "+f"(g[11]), "+f"(g[12]), "+f"(g[13]), "+f"(g[14]), "+f"(g[15]), "+f"(g[16]), "+f"(g[17]), "+f"(g[18]), "+f"(g[19]), "+f"(g[20]), "+f"(g[21]), "+f"(g[22]), "+f"(g[23]), "+f"(g[24]), "+f"(g[25]), "+f"(g[26]), "+f"(g[27])
      :: "memory");
  }
  static __device__ __forceinline__ void wait_h(float* h) {
    asm volatile("wgmma.wait_group.sync.aligned 0;\n"
      : "+f"(h[0]), "+f"(h[1]), "+f"(h[2]), "+f"(h[3]), "+f"(h[4]), "+f"(h[5]), "+f"(h[6]), "+f"(h[7]), "+f"(h[8]), "+f"(h[9]), "+f"(h[10]), "+f"(h[11]), "+f"(h[12]), "+f"(h[13]), "+f"(h[14]), "+f"(h[15]), "+f"(h[16]), "+f"(h[17]), "+f"(h[18]), "+f"(h[19]), "+f"(h[20]), "+f"(h[21]), "+f"(h[22]), "+f"(h[23]), "+f"(h[24]), "+f"(h[25]), "+f"(h[26]), "+f"(h[27])
      :: "memory");
  }
};
template<> struct TileMMA<8> {
  static __device__ __forceinline__ void issue(float* g, float* h, const uint32_t* w, uint32_t dx, uint64_t de, uint64_t dh, uint64_t dc) {
    asm volatile(
      "{\n.reg .b64 dx0, dx1, dx2, dx3;\n.reg .b32 l1, l2, l3, hx;\nmov.b32 hx, 0x40000040;\n"
      "add.u32 l1, %104, 2;\nadd.u32 l2, %104, 4;\nadd.u32 l3, %104, 6;\n"
      "mov.b64 dx0, {%104, hx};\nmov.b64 dx1, {l1, hx};\nmov.b64 dx2, {l2, hx};\nmov.b64 dx3, {l3, hx};\n"
      "wgmma.fence.sync.aligned;\n"
      "wgmma.mma_async.sync.aligned.m64n64k16.f32.bf16.bf16 {%0, %1, %2, %3, %4, %5, %6, %7, %8, %9, %10, %11, %12, %13, %14, %15, %16, %17, %18, %19, %20, %21, %22, %23, %24, %25, %26, %27, %28, %29, %30, %31}, {%100, %101, %102, %103}, %106, 0, 1, 1, 0;\n"
      "wgmma.mma_async.sync.aligned.m64n64k16.f32.bf16.bf16 {%0, %1, %2, %3, %4, %5, %6, %7, %8, %9, %10, %11, %12, %13, %14, %15, %16, %17, %18, %19, %20, %21, %22, %23, %24, %25, %26, %27, %28, %29, %30, %31}, {%80, %81, %82, %83}, %105, 1, 1, 1, 0;\n"
      "wgmma.mma_async.sync.aligned.m64n64k16.f32.bf16.bf16 {%0, %1, %2, %3, %4, %5, %6, %7, %8, %9, %10, %11, %12, %13, %14, %15, %16, %17, %18, %19, %20, %21, %22, %23, %24, %25, %26, %27, %28, %29, %30, %31}, {%64, %65, %66, %67}, dx0, 1, 1, 1, 0;\n"
      "wgmma.mma_async.sync.aligned.m64n64k16.f32.bf16.bf16 {%0, %1, %2, %3, %4, %5, %6, %7, %8, %9, %10, %11, %12, %13, %14, %15, %16, %17, %18, %19, %20, %21, %22, %23, %24, %25, %26, %27, %28, %29, %30, %31}, {%68, %69, %70, %71}, dx1, 1, 1, 1, 0;\n"
      "wgmma.mma_async.sync.aligned.m64n64k16.f32.bf16.bf16 {%0, %1, %2, %3, %4, %5, %6, %7, %8, %9, %10, %11, %12, %13, %14, %15, %16, %17, %18, %19, %20, %21, %22, %23, %24, %25, %26, %27, %28, %29, %30, %31}, {%72, %73, %74, %75}, dx2, 1, 1, 1, 0;\n"
      "wgmma.mma_async.sync.aligned.m64n64k16.f32.bf16.bf16 {%0, %1, %2, %3, %4, %5, %6, %7, %8, %9, %10, %11, %12, %13, %14, %15, %16, %17, %18, %19, %20, %21, %22, %23, %24, %25, %26, %27, %28, %29, %30, %31}, {%76, %77, %78, %79}, dx3, 1, 1, 1, 0;\n"
      "wgmma.commit_group.sync.aligned;\n"
      "wgmma.mma_async.sync.aligned.m64n64k16.f32.bf16.bf16 {%32, %33, %34, %35, %36, %37, %38, %39, %40, %41, %42, %43, %44, %45, %46, %47, %48, %49, %50, %51, %52, %53, %54, %55, %56, %57, %58, %59, %60, %61, %62, %63}, {%84, %85, %86, %87}, dx0, 0, 1, 1, 0;\n"
      "wgmma.mma_async.sync.aligned.m64n64k16.f32.bf16.bf16 {%32, %33, %34, %35, %36, %37, %38, %39, %40, %41, %42, %43, %44, %45, %46, %47, %48, %49, %50, %51, %52, %53, %54, %55, %56, %57, %58, %59, %60, %61, %62, %63}, {%88, %89, %90, %91}, dx1, 1, 1, 1, 0;\n"
      "wgmma.mma_async.sync.aligned.m64n64k16.f32.bf16.bf16 {%32, %33, %34, %35, %36, %37, %38, %39, %40, %41, %42, %43, %44, %45, %46, %47, %48, %49, %50, %51, %52, %53, %54, %55, %56, %57, %58, %59, %60, %61, %62, %63}, {%92, %93, %94, %95}, dx2, 1, 1, 1, 0;\n"
      "wgmma.mma_async.sync.aligned.m64n64k16.f32.bf16.bf16 {%32, %33, %34, %35, %36, %37, %38, %39, %40, %41, %42, %43, %44, %45, %46, %47, %48, %49, %50, %51, %52, %53, %54, %55, %56, %57, %58, %59, %60, %61, %62, %63}, {%96, %97, %98, %99}, dx3, 1, 1, 1, 0;\n"
      "wgmma.commit_group.sync.aligned;\n}\n"
      : "=f"(g[0]), "=f"(g[1]), "=f"(g[2]), "=f"(g[3]), "=f"(g[4]), "=f"(g[5]), "=f"(g[6]), "=f"(g[7]), "=f"(g[8]), "=f"(g[9]), "=f"(g[10]), "=f"(g[11]), "=f"(g[12]), "=f"(g[13]), "=f"(g[14]), "=f"(g[15]), "=f"(g[16]), "=f"(g[17]), "=f"(g[18]), "=f"(g[19]), "=f"(g[20]), "=f"(g[21]), "=f"(g[22]), "=f"(g[23]), "=f"(g[24]), "=f"(g[25]), "=f"(g[26]), "=f"(g[27]), "=f"(g[28]), "=f"(g[29]), "=f"(g[30]), "=f"(g[31]),
        "=f"(h[0]), "=f"(h[1]), "=f"(h[2]), "=f"(h[3]), "=f"(h[4]), "=f"(h[5]), "=f"(h[6]), "=f"(h[7]), "=f"(h[8]), "=f"(h[9]), "=f"(h[10]), "=f"(h[11]), "=f"(h[12]), "=f"(h[13]), "=f"(h[14]), "=f"(h[15]), "=f"(h[16]), "=f"(h[17]), "=f"(h[18]), "=f"(h[19]), "=f"(h[20]), "=f"(h[21]), "=f"(h[22]), "=f"(h[23]), "=f"(h[24]), "=f"(h[25]), "=f"(h[26]), "=f"(h[27]), "=f"(h[28]), "=f"(h[29]), "=f"(h[30]), "=f"(h[31])
      : "r"(w[0]), "r"(w[1]), "r"(w[2]), "r"(w[3]), "r"(w[4]), "r"(w[5]), "r"(w[6]), "r"(w[7]), "r"(w[8]), "r"(w[9]), "r"(w[10]), "r"(w[11]), "r"(w[12]), "r"(w[13]), "r"(w[14]), "r"(w[15]), "r"(w[16]), "r"(w[17]), "r"(w[18]), "r"(w[19]), "r"(w[20]), "r"(w[21]), "r"(w[22]), "r"(w[23]), "r"(w[24]), "r"(w[25]), "r"(w[26]), "r"(w[27]), "r"(w[28]), "r"(w[29]), "r"(w[30]), "r"(w[31]), "r"(w[32]), "r"(w[33]), "r"(w[34]), "r"(w[35]), "r"(w[36]), "r"(w[37]), "r"(w[38]), "r"(w[39]), "r"(dx), "l"(de), "l"(dh)
      : "memory");
  }
  static __device__ __forceinline__ void wait_g(float* g) {
    asm volatile("wgmma.wait_group.sync.aligned 1;\n"
      : "+f"(g[0]), "+f"(g[1]), "+f"(g[2]), "+f"(g[3]), "+f"(g[4]), "+f"(g[5]), "+f"(g[6]), "+f"(g[7]), "+f"(g[8]), "+f"(g[9]), "+f"(g[10]), "+f"(g[11]), "+f"(g[12]), "+f"(g[13]), "+f"(g[14]), "+f"(g[15]), "+f"(g[16]), "+f"(g[17]), "+f"(g[18]), "+f"(g[19]), "+f"(g[20]), "+f"(g[21]), "+f"(g[22]), "+f"(g[23]), "+f"(g[24]), "+f"(g[25]), "+f"(g[26]), "+f"(g[27]), "+f"(g[28]), "+f"(g[29]), "+f"(g[30]), "+f"(g[31])
      :: "memory");
  }
  static __device__ __forceinline__ void wait_h(float* h) {
    asm volatile("wgmma.wait_group.sync.aligned 0;\n"
      : "+f"(h[0]), "+f"(h[1]), "+f"(h[2]), "+f"(h[3]), "+f"(h[4]), "+f"(h[5]), "+f"(h[6]), "+f"(h[7]), "+f"(h[8]), "+f"(h[9]), "+f"(h[10]), "+f"(h[11]), "+f"(h[12]), "+f"(h[13]), "+f"(h[14]), "+f"(h[15]), "+f"(h[16]), "+f"(h[17]), "+f"(h[18]), "+f"(h[19]), "+f"(h[20]), "+f"(h[21]), "+f"(h[22]), "+f"(h[23]), "+f"(h[24]), "+f"(h[25]), "+f"(h[26]), "+f"(h[27]), "+f"(h[28]), "+f"(h[29]), "+f"(h[30]), "+f"(h[31])
      :: "memory");
  }
};
template<> struct TileMMA<9> {
  static __device__ __forceinline__ void issue(float* g, float* h, const uint32_t* w, uint32_t dx, uint64_t de, uint64_t dh, uint64_t dc) {
    asm volatile(
      "{\n.reg .b64 dx0, dx1, dx2, dx3;\n.reg .b32 l1, l2, l3, hx;\nmov.b32 hx, 0x40000040;\n"
      "add.u32 l1, %112, 2;\nadd.u32 l2, %112, 4;\nadd.u32 l3, %112, 6;\n"
      "mov.b64 dx0, {%112, hx};\nmov.b64 dx1, {l1, hx};\nmov.b64 dx2, {l2, hx};\nmov.b64 dx3, {l3, hx};\n"
      "wgmma.fence.sync.aligned;\n"
      "wgmma.mma_async.sync.aligned.m64n72k16.f32.bf16.bf16 {%0, %1, %2, %3, %4, %5, %6, %7, %8, %9, %10, %11, %12, %13, %14, %15, %16, %17, %18, %19, %20, %21, %22, %23, %24, %25, %26, %27, %28, %29, %30, %31, %32, %33, %34, %35}, {%108, %109, %110, %111}, %114, 0, 1, 1, 0;\n"
      "wgmma.mma_async.sync.aligned.m64n72k16.f32.bf16.bf16 {%0, %1, %2, %3, %4, %5, %6, %7, %8, %9, %10, %11, %12, %13, %14, %15, %16, %17, %18, %19, %20, %21, %22, %23, %24, %25, %26, %27, %28, %29, %30, %31, %32, %33, %34, %35}, {%88, %89, %90, %91}, %113, 1, 1, 1, 0;\n"
      "wgmma.mma_async.sync.aligned.m64n72k16.f32.bf16.bf16 {%0, %1, %2, %3, %4, %5, %6, %7, %8, %9, %10, %11, %12, %13, %14, %15, %16, %17, %18, %19, %20, %21, %22, %23, %24, %25, %26, %27, %28, %29, %30, %31, %32, %33, %34, %35}, {%72, %73, %74, %75}, dx0, 1, 1, 1, 0;\n"
      "wgmma.mma_async.sync.aligned.m64n72k16.f32.bf16.bf16 {%0, %1, %2, %3, %4, %5, %6, %7, %8, %9, %10, %11, %12, %13, %14, %15, %16, %17, %18, %19, %20, %21, %22, %23, %24, %25, %26, %27, %28, %29, %30, %31, %32, %33, %34, %35}, {%76, %77, %78, %79}, dx1, 1, 1, 1, 0;\n"
      "wgmma.mma_async.sync.aligned.m64n72k16.f32.bf16.bf16 {%0, %1, %2, %3, %4, %5, %6, %7, %8, %9, %10, %11, %12, %13, %14, %15, %16, %17, %18, %19, %20, %21, %22, %23, %24, %25, %26, %27, %28, %29, %30, %31, %32, %33, %34, %35}, {%80, %81, %82, %83}, dx2, 1, 1, 1, 0;\n"
      "wgmma.mma_async.sync.aligned.m64n72k16.f32.bf16.bf16 {%0, %1, %2, %3, %4, %5, %6, %7, %8, %9, %10, %11, %12, %13, %14, %15, %16, %17, %18, %19, %20, %21, %22, %23, %24, %25, %26, %27, %28, %29, %30, %31, %32, %33, %34, %35}, {%84, %85, %86, %87}, dx3, 1, 1, 1, 0;\n"
      "wgmma.commit_group.sync.aligned;\n"
      "wgmma.mma_async.sync.aligned.m64n72k16.f32.bf16.bf16 {%36, %37, %38, %39, %40, %41, %42, %43, %44, %45, %46, %47, %48, %49, %50, %51, %52, %53, %54, %55, %56, %57, %58, %59, %60, %61, %62, %63, %64, %65, %66, %67, %68, %69, %70, %71}, {%92, %93, %94, %95}, dx0, 0, 1, 1, 0;\n"
      "wgmma.mma_async.sync.aligned.m64n72k16.f32.bf16.bf16 {%36, %37, %38, %39, %40, %41, %42, %43, %44, %45, %46, %47, %48, %49, %50, %51, %52, %53, %54, %55, %56, %57, %58, %59, %60, %61, %62, %63, %64, %65, %66, %67, %68, %69, %70, %71}, {%96, %97, %98, %99}, dx1, 1, 1, 1, 0;\n"
      "wgmma.mma_async.sync.aligned.m64n72k16.f32.bf16.bf16 {%36, %37, %38, %39, %40, %41, %42, %43, %44, %45, %46, %47, %48, %49, %50, %51, %52, %53, %54, %55, %56, %57, %58, %59, %60, %61, %62, %63, %64, %65, %66, %67, %68, %69, %70, %71}, {%100, %101, %102, %103}, dx2, 1, 1, 1, 0;\n"
      "wgmma.mma_async.sync.aligned.m64n72k16.f32.bf16.bf16 {%36, %37, %38, %39, %40, %41, %42, %43, %44, %45, %46, %47, %48, %49, %50, %51, %52, %53, %54, %55, %56, %57, %58, %59, %60, %61, %62, %63, %64, %65, %66, %67, %68, %69, %70, %71}, {%104, %105, %106, %107}, dx3, 1, 1, 1, 0;\n"
      "wgmma.commit_group.sync.aligned;\n}\n"
      : "=f"(g[0]), "=f"(g[1]), "=f"(g[2]), "=f"(g[3]), "=f"(g[4]), "=f"(g[5]), "=f"(g[6]), "=f"(g[7]), "=f"(g[8]), "=f"(g[9]), "=f"(g[10]), "=f"(g[11]), "=f"(g[12]), "=f"(g[13]), "=f"(g[14]), "=f"(g[15]), "=f"(g[16]), "=f"(g[17]), "=f"(g[18]), "=f"(g[19]), "=f"(g[20]), "=f"(g[21]), "=f"(g[22]), "=f"(g[23]), "=f"(g[24]), "=f"(g[25]), "=f"(g[26]), "=f"(g[27]), "=f"(g[28]), "=f"(g[29]), "=f"(g[30]), "=f"(g[31]), "=f"(g[32]), "=f"(g[33]), "=f"(g[34]), "=f"(g[35]),
        "=f"(h[0]), "=f"(h[1]), "=f"(h[2]), "=f"(h[3]), "=f"(h[4]), "=f"(h[5]), "=f"(h[6]), "=f"(h[7]), "=f"(h[8]), "=f"(h[9]), "=f"(h[10]), "=f"(h[11]), "=f"(h[12]), "=f"(h[13]), "=f"(h[14]), "=f"(h[15]), "=f"(h[16]), "=f"(h[17]), "=f"(h[18]), "=f"(h[19]), "=f"(h[20]), "=f"(h[21]), "=f"(h[22]), "=f"(h[23]), "=f"(h[24]), "=f"(h[25]), "=f"(h[26]), "=f"(h[27]), "=f"(h[28]), "=f"(h[29]), "=f"(h[30]), "=f"(h[31]), "=f"(h[32]), "=f"(h[33]), "=f"(h[34]), "=f"(h[35])
      : "r"(w[0]), "r"(w[1]), "r"(w[2]), "r"(w[3]), "r"(w[4]), "r"(w[5]), "r"(w[6]), "r"(w[7]), "r"(w[8]), "r"(w[9]), "r"(w[10]), "r"(w[11]), "r"(w[12]), "r"(w[13]), "r"(w[14]), "r"(w[15]), "r"(w[16]), "r"(w[17]), "r"(w[18]), "r"(w[19]), "r"(w[20]), "r"(w[21]), "r"(w[22]), "r"(w[23]), "r"(w[24]), "r"(w[25]), "r"(w[26]), "r"(w[27]), "r"(w[28]), "r"(w[29]), "r"(w[30]), "r"(w[31]), "r"(w[32]), "r"(w[33]), "r"(w[34]), "r"(w[35]), "r"(w[36]), "r"(w[37]), "r"(w[38]), "r"(w[39]), "r"(dx), "l"(de), "l"(dh)
      : "memory");
  }
  static __device__ __forceinline__ void wait_g(float* g) {
    asm volatile("wgmma.wait_group.sync.aligned 1;\n"
      : "+f"(g[0]), "+f"(g[1]), "+f"(g[2]), "+f"(g[3]), "+f"(g[4]), "+f"(g[5]), "+f"(g[6]), "+f"(g[7]), "+f"(g[8]), "+f"(g[9]), "+f"(g[10]), "+f"(g[11]), "+f"(g[12]), "+f"(g[13]), "+f"(g[14]), "+f"(g[15]), "+f"(g[16]), "+f"(g[17]), "+f"(g[18]), "+f"(g[19]), "+f"(g[20]), "+f"(g[21]), "+f"(g[22]), "+f"(g[23]), "+f"(g[24]), "+f"(g[25]), "+f"(g[26]), "+f"(g[27]), "+f"(g[28]), "+f"(g[29]), "+f"(g[30]), "+f"(g[31]), "+f"(g[32]), "+f"(g[33]), "+f"(g[34]), "+f"(g[35])
      :: "memory");
  }
  static __device__ __forceinline__ void wait_h(float* h) {
    asm volatile("wgmma.wait_group.sync.aligned 0;\n"
      : "+f"(h[0]), "+f"(h[1]), "+f"(h[2]), "+f"(h[3]), "+f"(h[4]), "+f"(h[5]), "+f"(h[6]), "+f"(h[7]), "+f"(h[8]), "+f"(h[9]), "+f"(h[10]), "+f"(h[11]), "+f"(h[12]), "+f"(h[13]), "+f"(h[14]), "+f"(h[15]), "+f"(h[16]), "+f"(h[17]), "+f"(h[18]), "+f"(h[19]), "+f"(h[20]), "+f"(h[21]), "+f"(h[22]), "+f"(h[23]), "+f"(h[24]), "+f"(h[25]), "+f"(h[26]), "+f"(h[27]), "+f"(h[28]), "+f"(h[29]), "+f"(h[30]), "+f"(h[31]), "+f"(h[32]), "+f"(h[33]), "+f"(h[34]), "+f"(h[35])
      :: "memory");
  }
};
template<> struct TileMMA<10> {
  static __device__ __forceinline__ void issue(float* g, float* h, const uint32_t* w, uint32_t dx, uint64_t de, uint64_t dh, uint64_t dc) {
    asm volatile(
      "{\n.reg .b64 dx0, dx1, dx2, dx3;\n.reg .b32 l1, l2, l3, hx;\nmov.b32 hx, 0x40000040;\n"
      "add.u32 l1, %120, 2;\nadd.u32 l2, %120, 4;\nadd.u32 l3, %120, 6;\n"
      "mov.b64 dx0, {%120, hx};\nmov.b64 dx1, {l1, hx};\nmov.b64 dx2, {l2, hx};\nmov.b64 dx3, {l3, hx};\n"
      "wgmma.fence.sync.aligned;\n"
      "wgmma.mma_async.sync.aligned.m64n80k16.f32.bf16.bf16 {%0, %1, %2, %3, %4, %5, %6, %7, %8, %9, %10, %11, %12, %13, %14, %15, %16, %17, %18, %19, %20, %21, %22, %23, %24, %25, %26, %27, %28, %29, %30, %31, %32, %33, %34, %35, %36, %37, %38, %39}, {%116, %117, %118, %119}, %122, 0, 1, 1, 0;\n"
      "wgmma.mma_async.sync.aligned.m64n80k16.f32.bf16.bf16 {%0, %1, %2, %3, %4, %5, %6, %7, %8, %9, %10, %11, %12, %13, %14, %15, %16, %17, %18, %19, %20, %21, %22, %23, %24, %25, %26, %27, %28, %29, %30, %31, %32, %33, %34, %35, %36, %37, %38, %39}, {%96, %97, %98, %99}, %121, 1, 1, 1, 0;\n"
      "wgmma.mma_async.sync.aligned.m64n80k16.f32.bf16.bf16 {%0, %1, %2, %3, %4, %5, %6, %7, %8, %9, %10, %11, %12, %13, %14, %15, %16, %17, %18, %19, %20, %21, %22, %23, %24, %25, %26, %27, %28, %29, %30, %31, %32, %33, %34, %35, %36, %37, %38, %39}, {%80, %81, %82, %83}, dx0, 1, 1, 1, 0;\n"
      "wgmma.mma_async.sync.aligned.m64n80k16.f32.bf16.bf16 {%0, %1, %2, %3, %4, %5, %6, %7, %8, %9, %10, %11, %12, %13, %14, %15, %16, %17, %18, %19, %20, %21, %22, %23, %24, %25, %26, %27, %28, %29, %30, %31, %32, %33, %34, %35, %36, %37, %38, %39}, {%84, %85, %86, %87}, dx1, 1, 1, 1, 0;\n"
      "wgmma.mma_async.sync.aligned.m64n80k16.f32.bf16.bf16 {%0, %1, %2, %3, %4, %5, %6, %7, %8, %9, %10, %11, %12, %13, %14, %15, %16, %17, %18, %19, %20, %21, %22, %23, %24, %25, %26, %27, %28, %29, %30, %31, %32, %33, %34, %35, %36, %37, %38, %39}, {%88, %89, %90, %91}, dx2, 1, 1, 1, 0;\n"
      "wgmma.mma_async.sync.aligned.m64n80k16.f32.bf16.bf16 {%0, %1, %2, %3, %4, %5, %6, %7, %8, %9, %10, %11, %12, %13, %14, %15, %16, %17, %18, %19, %20, %21, %22, %23, %24, %25, %26, %27, %28, %29, %30, %31, %32, %33, %34, %35, %36, %37, %38, %39}, {%92, %93, %94, %95}, dx3, 1, 1, 1, 0;\n"
      "wgmma.commit_group.sync.aligned;\n"
      "wgmma.mma_async.sync.aligned.m64n80k16.f32.bf16.bf16 {%40, %41, %42, %43, %44, %45, %46, %47, %48, %49, %50, %51, %52, %53, %54, %55, %56, %57, %58, %59, %60, %61, %62, %63, %64, %65, %66, %67, %68, %69, %70, %71, %72, %73, %74, %75, %76, %77, %78, %79}, {%100, %101, %102, %103}, dx0, 0, 1, 1, 0;\n"
      "wgmma.mma_async.sync.aligned.m64n80k16.f32.bf16.bf16 {%40, %41, %42, %43, %44, %45, %46, %47, %48, %49, %50, %51, %52, %53, %54, %55, %56, %57, %58, %59, %60, %61, %62, %63, %64, %65, %66, %67, %68, %69, %70, %71, %72, %73, %74, %75, %76, %77, %78, %79}, {%104, %105, %106, %107}, dx1, 1, 1, 1, 0;\n"
      "wgmma.mma_async.sync.aligned.m64n80k16.f32.bf16.bf16 {%40, %41, %42, %43, %44, %45, %46, %47, %48, %49, %50, %51, %52, %53, %54, %55, %56, %57, %58, %59, %60, %61, %62, %63, %64, %65, %66, %67, %68, %69, %70, %71, %72, %73, %74, %75, %76, %77, %78, %79}, {%108, %109, %110, %111}, dx2, 1, 1, 1, 0;\n"
      "wgmma.mma_async.sync.aligned.m64n80k16.f32.bf16.bf16 {%40, %41, %42, %43, %44, %45, %46, %47, %48, %49, %50, %51, %52, %53, %54, %55, %56, %57, %58, %59, %60, %61, %62, %63, %64, %65, %66, %67, %68, %69, %70, %71, %72, %73, %74, %75, %76, %77, %78, %79}, {%112, %113, %114, %115}, dx3, 1, 1, 1, 0;\n"
      "wgmma.commit_group.sync.aligned;\n}\n"
      : "=f"(g[0]), "=f"(g[1]), "=f"(g[2]), "=f"(g[3]), "=f"(g[4]), "=f"(g[5]), "=f"(g[6]), "=f"(g[7]), "=f"(g[8]), "=f"(g[9]), "=f"(g[10]), "=f"(g[11]), "=f"(g[12]), "=f"(g[13]), "=f"(g[14]), "=f"(g[15]), "=f"(g[16]), "=f"(g[17]), "=f"(g[18]), "=f"(g[19]), "=f"(g[20]), "=f"(g[21]), "=f"(g[22]), "=f"(g[23]), "=f"(g[24]), "=f"(g[25]), "=f"(g[26]), "=f"(g[27]), "=f"(g[28]), "=f"(g[29]), "=f"(g[30]), "=f"(g[31]), "=f"(g[32]), "=f"(g[33]), "=f"(g[34]), "=f"(g[35]), "=f"(g[36]), "=f"(g[37]), "=f"(g[38]), "=f"(g[39]),
        "=f"(h[0]), "=f"(h[1]), "=f"(h[2]), "=f"(h[3]), "=f"(h[4]), "=f"(h[5]), "=f"(h[6]), "=f"(h[7]), "=f"(h[8]), "=f"(h[9]), "=f"(h[10]), "=f"(h[11]), "=f"(h[12]), "=f"(h[13]), "=f"(h[14]), "=f"(h[15]), "=f"(h[16]), "=f"(h[17]), "=f"(h[18]), "=f"(h[19]), "=f"(h[20]), "=f"(h[21]), "=f"(h[22]), "=f"(h[23]), "=f"(h[24]), "=f"(h[25]), "=f"(h[26]), "=f"(h[27]), "=f"(h[28]), "=f"(h[29]), "=f"(h[30]), "=f"(h[31]), "=f"(h[32]), "=f"(h[33]), "=f"(h[34]), "=f"(h[35]), "=f"(h[36]), "=f"(h[37]), "=f"(h[38]), "=f"(h[39])
      : "r"(w[0]), "r"(w[1]), "r"(w[2]), "r"(w[3]), "r"(w[4]), "r"(w[5]), "r"(w[6]), "r"(w[7]), "r"(w[8]), "r"(w[9]), "r"(w[10]), "r"(w[11]), "r"(w[12]), "r"(w[13]), "r"(w[14]), "r"(w[15]), "r"(w[16]), "r"(w[17]), "r"(w[18]), "r"(w[19]), "r"(w[20]), "r"(w[21]), "r"(w[22]), "r"(w[23]), "r"(w[24]), "r"(w[25]), "r"(w[26]), "r"(w[27]), "r"(w[28]), "r"(w[29]), "r"(w[30]), "r"(w[31]), "r"(w[32]), "r"(w[33]), "r"(w[34]), "r"(w[35]), "r"(w[36]), "r"(w[37]), "r"(w[38]), "r"(w[39]), "r"(dx), "l"(de), "l"(dh)
      : "memory");
  }
  static __device__ __forceinline__ void wait_g(float* g) {
    asm volatile("wgmma.wait_group.sync.aligned 1;\n"
      : "+f"(g[0]), "+f"(g[1]), "+f"(g[2]), "+f"(g[3]), "+f"(g[4]), "+f"(g[5]), "+f"(g[6]), "+f"(g[7]), "+f"(g[8]), "+f"(g[9]), "+f"(g[10]), "+f"(g[11]), "+f"(g[12]), "+f"(g[13]), "+f"(g[14]), "+f"(g[15]), "+f"(g[16]), "+f"(g[17]), "+f"(g[18]), "+f"(g[19]), "+f"(g[20]), "+f"(g[21]), "+f"(g[22]), "+f"(g[23]), "+f"(g[24]), "+f"(g[25]), "+f"(g[26]), "+f"(g[27]), "+f"(g[28]), "+f"(g[29]), "+f"(g[30]), "+f"(g[31]), "+f"(g[32]), "+f"(g[33]), "+f"(g[34]), "+f"(g[35]), "+f"(g[36]), "+f"(g[37]), "+f"(g[38]), "+f"(g[39])
      :: "memory");
  }
  static __device__ __forceinline__ void wait_h(float* h) {
    asm volatile("wgmma.wait_group.sync.aligned 0;\n"
      : "+f"(h[0]), "+f"(h[1]), "+f"(h[2]), "+f"(h[3]), "+f"(h[4]), "+f"(h[5]), "+f"(h[6]), "+f"(h[7]), "+f"(h[8]), "+f"(h[9]), "+f"(h[10]), "+f"(h[11]), "+f"(h[12]), "+f"(h[13]), "+f"(h[14]), "+f"(h[15]), "+f"(h[16]), "+f"(h[17]), "+f"(h[18]), "+f"(h[19]), "+f"(h[20]), "+f"(h[21]), "+f"(h[22]), "+f"(h[23]), "+f"(h[24]), "+f"(h[25]), "+f"(h[26]), "+f"(h[27]), "+f"(h[28]), "+f"(h[29]), "+f"(h[30]), "+f"(h[31]), "+f"(h[32]), "+f"(h[33]), "+f"(h[34]), "+f"(h[35]), "+f"(h[36]), "+f"(h[37]), "+f"(h[38]), "+f"(h[39])
      :: "memory");
  }
};
template<> struct TileMMA<11> {
  static __device__ __forceinline__ void issue(float* g, float* h, const uint32_t* w, uint32_t dx, uint64_t de, uint64_t dh, uint64_t dc) {
    asm volatile(
      "{\n.reg .b64 dx0, dx1, dx2, dx3;\n.reg .b32 l1, l2, l3, hx;\nmov.b32 hx, 0x40000040;\n"
      "add.u32 l1, %124, 2;\nadd.u32 l2, %124, 4;\nadd.u32 l3, %124, 6;\n"
      "mov.b64 dx0, {%124, hx};\nmov.b64 dx1, {l1, hx};\nmov.b64 dx2, {l2, hx};\nmov.b64 dx3, {l3, hx};\n"
      "wgmma.fence.sync.aligned;\n"
      "wgmma.mma_async.sync.aligned.m64n88k16.f32.bf16.bf16 {%0, %1, %2, %3, %4, %5, %6, %7, %8, %9, %10, %11, %12, %13, %14, %15, %16, %17, %18, %19, %20, %21, %22, %23, %24, %25, %26, %27, %28, %29, %30, %31, %32, %33, %34, %35, %36, %37, %38, %39, %40, %41, %42, %43}, {%120, %121, %122, %123}, %126, 0, 1, 1, 0;\n"
      "wgmma.mma_async.sync.aligned.m64n88k16.f32.bf16.bf16 {%0, %1, %2, %3, %4, %5, %6, %7, %8, %9, %10, %11, %12, %13, %14, %15, %16, %17, %18, %19, %20, %21, %22, %23, %24, %25, %26, %27, %28, %29, %30, %31, %32, %33, %34, %35, %36, %37, %38, %39, %40, %41, %42, %43}, %127, %125, 1, 1, 1, 0, 0;\n"
      "wgmma.mma_async.sync.aligned.m64n88k16.f32.bf16.bf16 {%0, %1, %2, %3, %4, %5, %6, %7, %8, %9, %10, %11, %12, %13, %14, %15, %16, %17, %18, %19, %20, %21, %22, %23, %24, %25, %26, %27, %28, %29, %30, %31, %32, %33, %34, %35, %36, %37, %38, %39, %40, %41, %42, %43}, {%88, %89, %90, %91}, dx0, 1, 1, 1, 0;\n"
      "wgmma.mma_async.sync.aligned.m64n88k16.f32.bf16.bf16 {%0, %1, %2, %3, %4, %5, %6, %7, %8, %9, %10, %11, %12, %13, %14, %15, %16, %17, %18, %19, %20, %21, %22, %23, %24, %25, %26, %27, %28, %29, %30, %31, %32, %33, %34, %35, %36, %37, %38, %39, %40, %41, %42, %43}, {%92, %93, %94, %95}, dx1, 1, 1, 1, 0;\n"
      "wgmma.mma_async.sync.aligned.m64n88k16.f32.bf16.bf16 {%0, %1, %2, %3, %4, %5, %6, %7, %8, %9, %10, %11, %12, %13, %14, %15, %16, %17, %18, %19, %20, %21, %22, %23, %24, %25, %26, %27, %28, %29, %30, %31, %32, %33, %34, %35, %36, %37, %38, %39, %40, %41, %42, %43}, {%96, %97, %98, %99}, dx2, 1, 1, 1, 0;\n"
      "wgmma.mma_async.sync.aligned.m64n88k16.f32.bf16.bf16 {%0, %1, %2, %3, %4, %5, %6, %7, %8, %9, %10, %11, %12, %13, %14, %15, %16, %17, %18, %19, %20, %21, %22, %23, %24, %25, %26, %27, %28, %29, %30, %31, %32, %33, %34, %35, %36, %37, %38, %39, %40, %41, %42, %43}, {%100, %101, %102, %103}, dx3, 1, 1, 1, 0;\n"
      "wgmma.commit_group.sync.aligned;\n"
      "wgmma.mma_async.sync.aligned.m64n88k16.f32.bf16.bf16 {%44, %45, %46, %47, %48, %49, %50, %51, %52, %53, %54, %55, %56, %57, %58, %59, %60, %61, %62, %63, %64, %65, %66, %67, %68, %69, %70, %71, %72, %73, %74, %75, %76, %77, %78, %79, %80, %81, %82, %83, %84, %85, %86, %87}, {%104, %105, %106, %107}, dx0, 0, 1, 1, 0;\n"
      "wgmma.mma_async.sync.aligned.m64n88k16.f32.bf16.bf16 {%44, %45, %46, %47, %48, %49, %50, %51, %52, %53, %54, %55, %56, %57, %58, %59, %60, %61, %62, %63, %64, %65, %66, %67, %68, %69, %70, %71, %72, %73, %74, %75, %76, %77, %78, %79, %80, %81, %82, %83, %84, %85, %86, %87}, {%108, %109, %110, %111}, dx1, 1, 1, 1, 0;\n"
      "wgmma.mma_async.sync.aligned.m64n88k16.f32.bf16.bf16 {%44, %45, %46, %47, %48, %49, %50, %51, %52, %53, %54, %55, %56, %57, %58, %59, %60, %61, %62, %63, %64, %65, %66, %67, %68, %69, %70, %71, %72, %73, %74, %75, %76, %77, %78, %79, %80, %81, %82, %83, %84, %85, %86, %87}, {%112, %113, %114, %115}, dx2, 1, 1, 1, 0;\n"
      "wgmma.mma_async.sync.aligned.m64n88k16.f32.bf16.bf16 {%44, %45, %46, %47, %48, %49, %50, %51, %52, %53, %54, %55, %56, %57, %58, %59, %60, %61, %62, %63, %64, %65, %66, %67, %68, %69, %70, %71, %72, %73, %74, %75, %76, %77, %78, %79, %80, %81, %82, %83, %84, %85, %86, %87}, {%116, %117, %118, %119}, dx3, 1, 1, 1, 0;\n"
      "wgmma.commit_group.sync.aligned;\n}\n"
      : "=f"(g[0]), "=f"(g[1]), "=f"(g[2]), "=f"(g[3]), "=f"(g[4]), "=f"(g[5]), "=f"(g[6]), "=f"(g[7]), "=f"(g[8]), "=f"(g[9]), "=f"(g[10]), "=f"(g[11]), "=f"(g[12]), "=f"(g[13]), "=f"(g[14]), "=f"(g[15]), "=f"(g[16]), "=f"(g[17]), "=f"(g[18]), "=f"(g[19]), "=f"(g[20]), "=f"(g[21]), "=f"(g[22]), "=f"(g[23]), "=f"(g[24]), "=f"(g[25]), "=f"(g[26]), "=f"(g[27]), "=f"(g[28]), "=f"(g[29]), "=f"(g[30]), "=f"(g[31]), "=f"(g[32]), "=f"(g[33]), "=f"(g[34]), "=f"(g[35]), "=f"(g[36]), "=f"(g[37]), "=f"(g[38]), "=f"(g[39]), "=f"(g[40]), "=f"(g[41]), "=f"(g[42]), "=f"(g[43]),
        "=f"(h[0]), "=f"(h[1]), "=f"(h[2]), "=f"(h[3]), "=f"(h[4]), "=f"(h[5]), "=f"(h[6]), "=f"(h[7]), "=f"(h[8]), "=f"(h[9]), "=f"(h[10]), "=f"(h[11]), "=f"(h[12]), "=f"(h[13]), "=f"(h[14]), "=f"(h[15]), "=f"(h[16]), "=f"(h[17]), "=f"(h[18]), "=f"(h[19]), "=f"(h[20]), "=f"(h[21]), "=f"(h[22]), "=f"(h[23]), "=f"(h[24]), "=f"(h[25]), "=f"(h[26]), "=f"(h[27]), "=f"(h[28]), "=f"(h[29]), "=f"(h[30]), "=f"(h[31]), "=f"(h[32]), "=f"(h[33]), "=f"(h[34]), "=f"(h[35]), "=f"(h[36]), "=f"(h[37]), "=f"(h[38]), "=f"(h[39]), "=f"(h[40]), "=f"(h[41]), "=f"(h[42]), "=f"(h[43])
      : "r"(w[0]), "r"(w[1]), "r"(w[2]), "r"(w[3]), "r"(w[4]), "r"(w[5]), "r"(w[6]), "r"(w[7]), "r"(w[8]), "r"(w[9]), "r"(w[10]), "r"(w[11]), "r"(w[12]), "r"(w[13]), "r"(w[14]), "r"(w[15]), "r"(w[20]), "r"(w[21]), "r"(w[22]), "r"(w[23]), "r"(w[24]), "r"(w[25]), "r"(w[26]), "r"(w[27]), "r"(w[28]), "r"(w[29]), "r"(w[30]), "r"(w[31]), "r"(w[32]), "r"(w[33]), "r"(w[34]), "r"(w[35]), "r"(w[36]), "r"(w[37]), "r"(w[38]), "r"(w[39]), "r"(dx), "l"(de), "l"(dh), "l"(dc)
      : "memory");
  }
  static __device__ __forceinline__ void wait_g(float* g) {
    asm volatile("wgmma.wait_group.sync.aligned 1;\n"
      : "+f"(g[0]), "+f"(g[1]), "+f"(g[2]), "+f"(g[3]), "+f"(g[4]), "+f"(g[5]), "+f"(g[6]), "+f"(g[7]), "+f"(g[8]), "+f"(g[9]), "+f"(g[10]), "+f"(g[11]), "+f"(g[12]), "+f"(g[13]), "+f"(g[14]), "+f"(g[15]), "+f"(g[16]), "+f"(g[17]), "+f"(g[18]), "+f"(g[19]), "+f"(g[20]), "+f"(g[21]), "+f"(g[22]), "+f"(g[23]), "+f"(g[24]), "+f"(g[25]), "+f"(g[26]), "+f"(g[27]), "+f"(g[28]), "+f"(g[29]), "+f"(g[30]), "+f"(g[31]), "+f"(g[32]), "+f"(g[33]), "+f"(g[34]), "+f"(g[35]), "+f"(g[36]), "+f"(g[37]), "+f"(g[38]), "+f"(g[39]), "+f"(g[40]), "+f"(g[41]), "+f"(g[42]), "+f"(g[43])
      :: "memory");
  }
  static __device__ __forceinline__ void wait_h(float* h) {
    asm volatile("wgmma.wait_group.sync.aligned 0;\n"
      : "+f"(h[0]), "+f"(h[1]), "+f"(h[2]), "+f"(h[3]), "+f"(h[4]), "+f"(h[5]), "+f"(h[6]), "+f"(h[7]), "+f"(h[8]), "+f"(h[9]), "+f"(h[10]), "+f"(h[11]), "+f"(h[12]), "+f"(h[13]), "+f"(h[14]), "+f"(h[15]), "+f"(h[16]), "+f"(h[17]), "+f"(h[18]), "+f"(h[19]), "+f"(h[20]), "+f"(h[21]), "+f"(h[22]), "+f"(h[23]), "+f"(h[24]), "+f"(h[25]), "+f"(h[26]), "+f"(h[27]), "+f"(h[28]), "+f"(h[29]), "+f"(h[30]), "+f"(h[31]), "+f"(h[32]), "+f"(h[33]), "+f"(h[34]), "+f"(h[35]), "+f"(h[36]), "+f"(h[37]), "+f"(h[38]), "+f"(h[39]), "+f"(h[40]), "+f"(h[41]), "+f"(h[42]), "+f"(h[43])
      :: "memory");
  }
};
__device__ __forceinline__ void node_mma(float* g, const uint32_t* w, uint64_t dx) {
    asm volatile(
      "{\n.reg .b64 dx1, dx2, dx3;\n"
      "add.s64 dx1, %48, 2;\nadd.s64 dx2, %48, 4;\nadd.s64 dx3, %48, 6;\n"
      "wgmma.fence.sync.aligned;\n"
      "wgmma.mma_async.sync.aligned.m64n64k16.f32.bf16.bf16 {%0, %1, %2, %3, %4, %5, %6, %7, %8, %9, %10, %11, %12, %13, %14, %15, %16, %17, %18, %19, %20, %21, %22, %23, %24, %25, %26, %27, %28, %29, %30, %31}, {%32, %33, %34, %35}, %48, 0, 1, 1, 0;\n"
      "wgmma.mma_async.sync.aligned.m64n64k16.f32.bf16.bf16 {%0, %1, %2, %3, %4, %5, %6, %7, %8, %9, %10, %11, %12, %13, %14, %15, %16, %17, %18, %19, %20, %21, %22, %23, %24, %25, %26, %27, %28, %29, %30, %31}, {%36, %37, %38, %39}, dx1, 1, 1, 1, 0;\n"
      "wgmma.mma_async.sync.aligned.m64n64k16.f32.bf16.bf16 {%0, %1, %2, %3, %4, %5, %6, %7, %8, %9, %10, %11, %12, %13, %14, %15, %16, %17, %18, %19, %20, %21, %22, %23, %24, %25, %26, %27, %28, %29, %30, %31}, {%40, %41, %42, %43}, dx2, 1, 1, 1, 0;\n"
      "wgmma.mma_async.sync.aligned.m64n64k16.f32.bf16.bf16 {%0, %1, %2, %3, %4, %5, %6, %7, %8, %9, %10, %11, %12, %13, %14, %15, %16, %17, %18, %19, %20, %21, %22, %23, %24, %25, %26, %27, %28, %29, %30, %31}, {%44, %45, %46, %47}, dx3, 1, 1, 1, 0;\n"
      "wgmma.commit_group.sync.aligned;\n}\n"
      : "=f"(g[0]), "=f"(g[1]), "=f"(g[2]), "=f"(g[3]), "=f"(g[4]), "=f"(g[5]), "=f"(g[6]), "=f"(g[7]), "=f"(g[8]), "=f"(g[9]), "=f"(g[10]), "=f"(g[11]), "=f"(g[12]), "=f"(g[13]), "=f"(g[14]), "=f"(g[15]), "=f"(g[16]), "=f"(g[17]), "=f"(g[18]), "=f"(g[19]), "=f"(g[20]), "=f"(g[21]), "=f"(g[22]), "=f"(g[23]), "=f"(g[24]), "=f"(g[25]), "=f"(g[26]), "=f"(g[27]), "=f"(g[28]), "=f"(g[29]), "=f"(g[30]), "=f"(g[31])
      : "r"(w[0]), "r"(w[1]), "r"(w[2]), "r"(w[3]), "r"(w[4]), "r"(w[5]), "r"(w[6]), "r"(w[7]), "r"(w[8]), "r"(w[9]), "r"(w[10]), "r"(w[11]), "r"(w[12]), "r"(w[13]), "r"(w[14]), "r"(w[15]), "l"(dx)
      : "memory");
}

__device__ __forceinline__ uint32_t smem_u32(const void* p) { return (uint32_t)__cvta_generic_to_shared(p); }
__device__ __forceinline__ float ex2f(float x) { float y; asm("ex2.approx.ftz.f32 %0, %1;" : "=f"(y) : "f"(x)); return y; }
__device__ __forceinline__ float rcpf(float x) { float y; asm("rcp.approx.ftz.f32 %0, %1;" : "=f"(y) : "f"(x)); return y; }
__device__ __forceinline__ uint32_t pack_bf16(float lo, float hi) {
    uint32_t r; asm("cvt.rn.bf16x2.f32 %0, %1, %2;" : "=r"(r) : "f"(hi), "f"(lo)); return r;
}
__device__ __forceinline__ float bf_lo(uint32_t v) { return __uint_as_float(v << 16); }
__device__ __forceinline__ float bf_hi(uint32_t v) { return __uint_as_float(v & 0xFFFF0000u); }
template<int STRIDE>
__device__ __forceinline__ void cp16i(uint32_t dst, const char* base, uint32_t idx) {
    asm volatile("{\n.reg .b64 a;\nmad.wide.u32 a, %2, %3, %1;\ncp.async.cg.shared.global [%0], [a], 16;\n}\n" :: "r"(dst), "l"(base), "r"(idx), "n"(STRIDE) : "memory");
}
__device__ __forceinline__ void cp16e(uint32_t dst, const char* base, uint32_t idx, uint64_t pol) {
    asm volatile("{\n.reg .b64 a;\nmad.wide.u32 a, %2, 32, %1;\ncp.async.cg.shared.global.L2::cache_hint [%0], [a], 16, %3;\n}\n" :: "r"(dst), "l"(base), "r"(idx), "l"(pol) : "memory");
}
template<int STRIDE>
__device__ __forceinline__ void cp16z(uint32_t dst, const char* base, uint32_t idx, int k, int n, uint64_t pol) {
    if (STRIDE == 32)
        asm volatile("{\n.reg .b64 a;\n.reg .pred p;\nsetp.ge.s32 p, %3, %4;\nmad.wide.u32 a, %2, 32, %1;\ncp.async.cg.shared.global.L2::cache_hint [%0], [a], 16, p, %5;\n}\n"
                     :: "r"(dst), "l"(base), "r"(idx), "r"(k), "r"(n), "l"(pol) : "memory");
    else
        asm volatile("{\n.reg .b64 a;\n.reg .pred p;\nsetp.ge.s32 p, %3, %4;\nmad.wide.u32 a, %2, 128, %1;\ncp.async.cg.shared.global [%0], [a], 16, p;\n}\n"
                     :: "r"(dst), "l"(base), "r"(idx), "r"(k), "r"(n) : "memory");
}
template<int HI, bool Z>
__device__ __forceinline__ void cpx(uint32_t hi, uint32_t dst, uint32_t p, uint32_t lo, int k, int n) {
    if (Z) asm volatile("{\n.reg .b32 l;\n.reg .b64 a;\n.reg .pred q;\nsetp.ge.s32 q, %5, %6;\ndp2a.lo.u32.u32 l, %1, %2, %3;\nmov.b64 a, {l, %0};\ncp.async.cg.shared.global [%4], [a], 16, q;\n}\n"
                        :: "r"(hi), "r"(p), "r"(HI ? 0x8000u : 0x80u), "r"(lo), "r"(dst), "r"(k), "r"(n) : "memory");
    else asm volatile("{\n.reg .b32 l;\n.reg .b64 a;\ndp2a.lo.u32.u32 l, %1, %2, %3;\nmov.b64 a, {l, %0};\ncp.async.cg.shared.global [%4], [a], 16;\n}\n"
                      :: "r"(hi), "r"(p), "r"(HI ? 0x8000u : 0x80u), "r"(lo), "r"(dst) : "memory");
}
template<bool Z>
__device__ __forceinline__ void cpe(uint32_t hi, uint32_t dst, uint32_t idx, uint32_t lo, int k, int n, uint64_t pol) {
    if (Z) asm volatile("{\n.reg .b32 l;\n.reg .b64 a;\n.reg .pred q;\nsetp.ge.s32 q, %5, %6;\nmad.lo.u32 l, %1, 32, %2;\nmov.b64 a, {l, %0};\ncp.async.cg.shared.global.L2::cache_hint [%3], [a], 16, q, %4;\n}\n"
                        :: "r"(hi), "r"(idx), "r"(lo), "r"(dst), "l"(pol), "r"(k), "r"(n) : "memory");
    else asm volatile("{\n.reg .b32 l;\n.reg .b64 a;\nmad.lo.u32 l, %1, 32, %2;\nmov.b64 a, {l, %0};\ncp.async.cg.shared.global.L2::cache_hint [%3], [a], 16, %4;\n}\n"
                      :: "r"(hi), "r"(idx), "r"(lo), "r"(dst), "l"(pol) : "memory");
}
__device__ __forceinline__ void cp_commit() { asm volatile("cp.async.commit_group;" ::: "memory"); }
template<int N> __device__ __forceinline__ void cp_wait() { asm volatile("cp.async.wait_group %0;" :: "n"(N) : "memory"); }
__device__ __forceinline__ void mbar_arrive(uint32_t bar) { asm volatile("mbarrier.arrive.shared.b64 _, [%0];" :: "r"(bar) : "memory"); }
__device__ __forceinline__ void mbar_cp_arrive(uint32_t bar) { asm volatile("cp.async.mbarrier.arrive.noinc.shared.b64 [%0];" :: "r"(bar) : "memory"); }
__device__ __forceinline__ void mbar_wait(uint32_t bar, uint32_t parity) {
    asm volatile("{\n.reg .pred p;\n.reg .u32 n;\nmbarrier.try_wait.parity.shared.b64 p, [%0], %1;\n@p bra DONE_%=;\nmov.u32 n, 0;\n"
                 "WAIT_%=:\nmbarrier.try_wait.parity.shared.b64 p, [%0], %1, 0x100000;\n@p bra DONE_%=;\n"
                 "add.u32 n, n, 1;\nsetp.lt.u32 p, n, 0x400000;\n@p bra WAIT_%=;\ntrap;\nDONE_%=:\n}\n"
                 :: "r"(bar), "r"(parity) : "memory");
}
__device__ __forceinline__ void mbar_wait_c(uint32_t bar, uint32_t parity) {
    asm volatile("{\n.reg .pred p;\nWAIT_%=:\nmbarrier.try_wait.parity.shared.b64 p, [%0], %1;\n@p bra DONE_%=;\nbra WAIT_%=;\nDONE_%=:\n}\n"
                 :: "r"(bar), "r"(parity) : "memory");
}
__device__ __forceinline__ void mbar_wait_h(uint32_t bar, uint32_t parity) {
    asm volatile("{\n.reg .pred p;\nWAIT_%=:\nmbarrier.try_wait.parity.shared.b64 p, [%0], %1, 0x100000;\n@p bra DONE_%=;\nbra WAIT_%=;\nDONE_%=:\n}\n"
                 :: "r"(bar), "r"(parity) : "memory");
}
__device__ __forceinline__ uint32_t lds32(uint32_t a) { uint32_t v; asm volatile("ld.shared.u32 %0, [%1];" : "=r"(v) : "r"(a) : "memory"); return v; }
__device__ __forceinline__ void sts32(uint32_t a, uint32_t v) { asm volatile("st.shared.u32 [%0], %1;" :: "r"(a), "r"(v) : "memory"); }
__device__ __forceinline__ uint2 lds64(uint32_t a) { uint2 v; asm volatile("ld.shared.v2.u32 {%0,%1}, [%2];" : "=r"(v.x), "=r"(v.y) : "r"(a) : "memory"); return v; }
__device__ __forceinline__ uint4 lds128(uint32_t a) { uint4 v; asm volatile("ld.shared.v4.u32 {%0,%1,%2,%3}, [%4];" : "=r"(v.x), "=r"(v.y), "=r"(v.z), "=r"(v.w) : "r"(a) : "memory"); return v; }
__device__ __forceinline__ void sts128(uint32_t a, uint4 v) { asm volatile("st.shared.v4.u32 [%0], {%1,%2,%3,%4};" :: "r"(a), "r"(v.x), "r"(v.y), "r"(v.z), "r"(v.w) : "memory"); }
__device__ __forceinline__ void ldsm4t(uint32_t* v, uint32_t a) {
    asm volatile("ldmatrix.sync.aligned.m8n8.x4.trans.shared.b16 {%0,%1,%2,%3}, [%4];" : "=r"(v[0]), "=r"(v[1]), "=r"(v[2]), "=r"(v[3]) : "r"(a) : "memory");
}
__device__ __forceinline__ void stsm4t(uint32_t a, const uint32_t* v) {
    asm volatile("stmatrix.sync.aligned.m8n8.x4.trans.shared.b16 [%0], {%1,%2,%3,%4};" :: "r"(a), "r"(v[0]), "r"(v[1]), "r"(v[2]), "r"(v[3]) : "memory");
}
__device__ __forceinline__ int atoms_inc(uint32_t a) { int v; asm volatile("atom.shared.add.u32 %0, [%1], 1;" : "=r"(v) : "r"(a) : "memory"); return v; }
__device__ __forceinline__ float tanhf_a(float x) { float y; asm("tanh.approx.f32 %0, %1;" : "=f"(y) : "f"(x)); return y; }
__device__ __forceinline__ const char* as_pair(const void* p, uint32_t scratch) {
    const char* r;
    asm volatile("st.shared.u64 [%1], %2;\nld.volatile.shared.u64 %0, [%1];" : "=l"(r) : "r"(scratch), "l"(p) : "memory");
    return r;
}
__device__ __forceinline__ void ld_unit(uint4& v, const char* p, bool ok) {
    asm volatile("{\n.reg .pred q;\nsetp.ne.u32 q, %5, 0;\n@q ld.relaxed.gpu.global.v4.u32 {%0,%1,%2,%3}, [%4];\n}"
                 : "+r"(v.x), "+r"(v.y), "+r"(v.z), "+r"(v.w) : "l"(p), "r"((uint32_t)ok) : "memory");
}
__device__ __forceinline__ void ld_unit(uint2& v, const char* p, bool ok) {
    asm volatile("{\n.reg .pred q;\nsetp.ne.u32 q, %3, 0;\n@q ld.relaxed.gpu.global.v2.u32 {%0,%1}, [%2];\n}"
                 : "+r"(v.x), "+r"(v.y) : "l"(p), "r"((uint32_t)ok) : "memory");
}
#define ELECT "{\n.reg .pred p;\nelect.sync _|p, 0xffffffff;\n@p "
__device__ __forceinline__ void w_init(uint32_t bar, int n) { asm volatile(ELECT "mbarrier.init.shared.b64 [%0], %1;\n}" :: "r"(bar), "r"(n) : "memory"); }
__device__ __forceinline__ void w_expect(uint32_t bar, uint32_t bytes) { asm volatile(ELECT "mbarrier.arrive.expect_tx.shared.b64 _, [%0], %1;\n}" :: "r"(bar), "r"(bytes) : "memory"); }
__device__ __forceinline__ void w_ld(uint32_t dst, const void* src, int bytes, uint32_t bar) {
    asm volatile(ELECT "cp.async.bulk.shared::cluster.global.mbarrier::complete_tx::bytes [%0], [%1], %2, [%3];\n}" :: "r"(dst), "l"(src), "r"(bytes), "r"(bar) : "memory");
}
__device__ __forceinline__ void w_box_ld(uint32_t dst, const CUtensorMap* tm, int row, uint32_t bar) {
    asm volatile(ELECT "cp.async.bulk.tensor.2d.shared::cluster.global.mbarrier::complete_tx::bytes [%0], [%1, {%3, %4}], [%2];\n}"
        :: "r"(dst), "l"((uint64_t)tm), "r"(bar), "r"(0), "r"(row) : "memory");
}
__device__ __forceinline__ void w_st(void* dst, uint32_t src, int bytes) {
    asm volatile(ELECT "cp.async.bulk.global.shared::cta.bulk_group [%0], [%1], %2;\n}" :: "l"(dst), "r"(src), "r"(bytes) : "memory");
}
__device__ __forceinline__ void w_box_st(const CUtensorMap* tm, int col, uint32_t src) {
    asm volatile(ELECT "cp.async.bulk.tensor.2d.global.shared::cta.bulk_group [%0, {%2, %3}], [%1];\n}" :: "l"((uint64_t)tm), "r"(src), "r"(col), "r"(0) : "memory");
}
__device__ __forceinline__ void w_sent(unsigned* p, uint32_t src) {
    asm volatile(ELECT "cp.reduce.async.bulk.global.shared::cta.bulk_group.add.u32 [%0], [%1], 16;\n}" :: "l"(p), "r"(src) : "memory");
}
__device__ __forceinline__ void w_inc(unsigned* p) { asm volatile(ELECT "red.relaxed.gpu.global.add.u32 [%0], 1;\n}" :: "l"(p) : "memory"); }
__device__ __forceinline__ void w_hint(unsigned* p, uint32_t all) {
    #pragma unroll 1
    for (int i = 0; i < 4096; i++) {
        uint32_t v; asm volatile("ld.relaxed.gpu.global.u32 %0, [%1];" : "=r"(v) : "l"(p) : "memory");
        if (__all_sync(~0u, (int)(v - all) >= 0)) break;
    }
}

__device__ __forceinline__ void finish(uint4& a, const uint4& xu, const uint4& xv) {
    asm("{\n.reg .b32 z;\nfma.rn.relu.bf16x2 z, %0, %3, %1;\nadd.rn.bf16x2 %0, z, %2;\n}" : "+r"(a.x) : "r"(xu.x), "r"(xv.x), "r"(0x3F803F80u));
    asm("{\n.reg .b32 z;\nfma.rn.relu.bf16x2 z, %0, %3, %1;\nadd.rn.bf16x2 %0, z, %2;\n}" : "+r"(a.y) : "r"(xu.y), "r"(xv.y), "r"(0x3F803F80u));
    asm("{\n.reg .b32 z;\nfma.rn.relu.bf16x2 z, %0, %3, %1;\nadd.rn.bf16x2 %0, z, %2;\n}" : "+r"(a.z) : "r"(xu.z), "r"(xv.z), "r"(0x3F803F80u));
    asm("{\n.reg .b32 z;\nfma.rn.relu.bf16x2 z, %0, %3, %1;\nadd.rn.bf16x2 %0, z, %2;\n}" : "+r"(a.w) : "r"(xu.w), "r"(xv.w), "r"(0x3F803F80u));
}

constexpr float EPS2 = 2e-6f;
constexpr float TAU = 2.5e-5f;

constexpr uint32_t TAU_BITS = 0x3A103000u;
template<int NP>
__device__ __forceinline__ bool epi_fast(const float* g, const float* h, float m2, float tau, float& n0, float& d0, float& n1, float& d1, float& dmin)
{
    constexpr int JC = NP >= 6 ? NP - 3 : NP - 2;
    bool ok;
    #pragma unroll
    for (int j = 0; j < NP; j++) {
        float t0 = tanhf_a(g[4*j+0]), t1 = tanhf_a(g[4*j+1]), t2 = tanhf_a(g[4*j+2]), t3 = tanhf_a(g[4*j+3]);
        auto add_d = [&]() {
            if (j == 0) { d0 = t0 + (2.f * (JC + 1) + EPS2); d1 = t2 + (2.f * (JC + 1) + EPS2); } else { d0 += t0; d1 += t2; }
            d0 += t1; d1 += t3;
        };
        if (j <= JC) add_d();
        if (j == 0) { n0 = fmaf(t0, h[0], h[0]); n1 = fmaf(t2, h[2], h[2]); }
        t0 += 1.f; t2 += 1.f;
        if (j == NP - 1) { t1 = fmaf(t1, m2, m2); t3 = fmaf(t3, m2, m2); } else { t1 += 1.f; t3 += 1.f; }
        if (j > JC) add_d();
        if (j > 0) { n0 = fmaf(t0, h[4*j], n0); n1 = fmaf(t2, h[4*j+2], n1); }
        n0 = fmaf(t1, h[4*j+1], n0); n1 = fmaf(t3, h[4*j+3], n1);
        if (j == JC) { dmin = fminf(d0, d1); ok = dmin >= tau; }
    }
    return ok;
}

__device__ __noinline__ void slow_bin(const __nv_bfloat16* x, const __nv_bfloat16* ea, const int* src, const int* dst,
                                      const __nv_bfloat16* wa, const __nv_bfloat16* wb, const __nv_bfloat16* wc,
                                      const __nv_bfloat16* wu, const __nv_bfloat16* wv, __nv_bfloat16* out,
                                      int E, int node0, int nn, int nthr)
{
    const int tid = threadIdx.x, lane = tid & 31;
    for (int i = tid; i < nn * 128; i += nthr) g_slow[(size_t)node0 * 128 + i] = 0.f;
    asm volatile("bar.sync 1, %0;" :: "r"(nthr) : "memory");
    for (int e0 = (tid >> 5) * 32; e0 < E; e0 += nthr) {
        int d = (e0 + lane < E) ? dst[e0 + lane] - node0 : -1;
        unsigned m = __ballot_sync(~0u, d >= 0 && d < nn);
        while (m) {
            int l = __ffs(m) - 1; m &= m - 1;
            int e = e0 + l, n = node0 + __shfl_sync(~0u, d, l), s = src[e];
            float g0 = 0, g1 = 0, h0 = 0, h1 = 0;
            for (int k = 0; k < 64; k++) {
                float xs = __bfloat162float(x[(size_t)s * 64 + k]), xd = __bfloat162float(x[(size_t)n * 64 + k]);
                uint32_t b2 = *(const uint32_t*)(wb + k * 64 + 2 * lane), v2 = *(const uint32_t*)(wv + k * 64 + 2 * lane);
                uint32_t a2 = *(const uint32_t*)(wa + k * 64 + 2 * lane);
                g0 = fmaf(xs, bf_lo(b2), fmaf(xd, bf_lo(a2), g0)); g1 = fmaf(xs, bf_hi(b2), fmaf(xd, bf_hi(a2), g1));
                h0 = fmaf(xs, bf_lo(v2), h0); h1 = fmaf(xs, bf_hi(v2), h1);
            }
            for (int k = 0; k < 16; k++) {
                float ev = __bfloat162float(ea[(size_t)e * 16 + k]);
                uint32_t c2 = *(const uint32_t*)(wc + k * 64 + 2 * lane);
                g0 = fmaf(ev, bf_lo(c2), g0); g1 = fmaf(ev, bf_hi(c2), g1);
            }
            float s0 = rcpf(1.f + ex2f(-LOG2E * g0)), s1 = rcpf(1.f + ex2f(-LOG2E * g1));
            float* acc = g_slow + (size_t)n * 128 + 4 * lane;
            atomicAdd(acc + 0, s0 * h0); atomicAdd(acc + 1, s0);
            atomicAdd(acc + 2, s1 * h1); atomicAdd(acc + 3, s1);
        }
    }
    __threadfence();
    asm volatile("bar.sync 1, %0;" :: "r"(nthr) : "memory");
    for (int i = tid; i < nn * 32; i += nthr) {
        int n = node0 + (i >> 5), cp = i & 31;
        float4 a = __ldcg((const float4*)(g_slow + (size_t)n * 128 + 4 * cp));
        float u0 = 0, u1 = 0;
        for (int k = 0; k < 64; k++) {
            float xd = __bfloat162float(x[(size_t)n * 64 + k]);
            uint32_t w2 = *(const uint32_t*)(wu + k * 64 + 2 * cp);
            u0 = fmaf(xd, bf_lo(w2), u0); u1 = fmaf(xd, bf_hi(w2), u1);
        }
        uint32_t xv = *(const uint32_t*)(x + (size_t)n * 64 + 2 * cp);
        float z0 = u0 + a.x / (a.y + 1e-6f), z1 = u1 + a.z / (a.w + 1e-6f);
        *(uint32_t*)(out + (size_t)n * 64 + 2 * cp) = pack_bf16(bf_lo(xv) + fmaxf(z0, 0.f), bf_hi(xv) + fmaxf(z1, 0.f));
    }
}

__global__ void __launch_bounds__(256) slow_kernel(const __nv_bfloat16* x, const __nv_bfloat16* ea, const int* src, const int* dst,
        const __nv_bfloat16* wa, const __nv_bfloat16* wb, const __nv_bfloat16* wc, const __nv_bfloat16* wu, const __nv_bfloat16* wv,
        __nv_bfloat16* out, int N, int E, int npb)
{
    int node0 = blockIdx.x * npb;
    slow_bin(x, ea, src, dst, wa, wb, wc, wu, wv, out, E, node0, max(0, min(npb, N - node0)), 256);
}

constexpr int XS_BYTES = NPMAX * 1024;
constexpr int ES_BYTES = NPMAX * 256;
constexpr int SM_XS = 0;
constexpr int SM_XU = SM_XS + 3 * NSTAGE * XS_BYTES;
constexpr int SM_TAB = SM_XU + NPB_MAX * 128;
constexpr int SM_ES = SM_TAB + NPB_MAX * 128;
constexpr int SM_WC = SM_ES + 3 * NSTAGE * ES_BYTES;
constexpr int SM_OH = SM_WC + 2048;
constexpr int SM_EID = SM_OH + 128;
constexpr int SM_SRC = SM_EID + SLOT_CAP * 4;
constexpr int SM_TINFO = SM_SRC + SLOT_CAP * 2;
constexpr int SM_MISC = SM_TINFO + TILE_CAP * 32;
constexpr int SM_CLAIM = SM_MISC + 32 * 4;
constexpr int STG = 272;
constexpr int SM_BARS = SM_CLAIM + 32 * 4;
constexpr int SM_ABAR = SM_BARS + 6 * STG;
constexpr int SM_GBAR = SM_ABAR + 16 * 8;
constexpr int SMEM_BYTES = SM_GBAR + 97 * 8;
constexpr int SM_P2 = 0, SM_P1 = P2B + 256;
constexpr int SM_L1 = SM_P1 + P1B + 128;
constexpr int SM_DEG = SM_L1 + 256;
constexpr int SM_CLS = SM_DEG + 512 * 4;
constexpr int SM_HIST = SM_CLS + NCLS * 4;
constexpr int SM_XLIST = SM_HIST + NB_MAX * 4;
constexpr int SM_SORT = SM_XLIST + 8;
constexpr int SM_SDEG = SM_SORT + NPB_MAX * 4;
constexpr int SM_PAIR = SM_SDEG + NPB_MAX * 2;
constexpr int SM_ENT = SM_ES + 1024;
constexpr int SM_H1 = SM_P1 + HB, SM_H2 = SM_P1;
constexpr int SM_IDX = SM_EID;
constexpr int SM_WR = SM_TAB;
static_assert(TILE_CAP <= 128 && TR >= 2 && SM_ES % 256 == 0 && NSTAGE == 2 && SM_BARS % 16 == 0 && SM_TINFO % 16 == 0 && SM_EID % 128 == 0 && SM_TAB % 1024 == 0 && SM_XU % 1024 == 0 && SM_TINFO % 8 == 0 && SM_OH % 16 == 0 && SM_XLIST % 8 == 0 && SM_PAIR % 8 == 0, "align");
static_assert(SM_P1 % 128 == 0 && P1B + HB <= SM_SRC - SM_EID && 2 * HB <= P1B && SM_H1 + 5 * 128 * 16 <= SM_XU && NB_MAX * (CE / 4) <= 6 * 384 && NB_MAX * 4 <= 5 * 128 && NB_MIN * 4 >= 3 * 128 && SM_PAIR + 128 * 8 <= SM_XU && CH_MAX * 4 <= SM_SRC - SM_EID && SM_DEG >= 3 << 14, "alias");
static_assert(CE == 64 && SMEM_BYTES <= 232448, "smem");
constexpr uint32_t C_BRK = 16  , C_CONT = 32, C_MORE = 64;
constexpr uint32_t ONE_F = 0x3F800000u;
constexpr int NONE = NPB_MAX - 1;
__host__ __device__ constexpr uint32_t tab_at(uint32_t n) { return (n >> 2) * 512 + (n & 3) * 32 + ((n >> 2) & 1) * 16; }

__device__ __forceinline__ uint32_t unpad(uint32_t w1, int np, float ga, float gb, float& d0, float& d1, int& dv) {
    const int pad = (w1 >> 8) & 31;
    dv = 2 * np - 1 - pad + (w1 >= ONE_F);
    float t0 = TAU * 2 * np, t1 = t0;
    if (pad) {
        t0 = fmaxf(t0, d0 * (1.f / 1024)); t1 = fmaxf(t1, d1 * (1.f / 1024));
        asm volatile("tanh.approx.f32 %0, %0;\ntanh.approx.f32 %1, %1;" : "+f"(ga), "+f"(gb));
        d0 -= pad * (1.f + ga); d1 -= pad * (1.f + gb);
    }
    if (dv == 0) { d0 = d1 = EPS2; t0 = t1 = 0.f; }
    return __ballot_sync(~0u, d0 < t0 || d1 < t1);
}
__device__ __noinline__ float4* exact_copy(uint32_t bad, float4* own)
{
    extern __shared__ __align__(1024) uint8_t smem[];
    uint32_t old = 1;
    if (bad == 1u << (threadIdx.x & 31)) old = atomicExch((uint32_t*)(smem + SM_MISC + 12), 1u);
    if (__all_sync(~0u, old)) return own;
    return old ? nullptr : (float4*)(smem + SM_XU + tab_at(NPB_MAX - 4) - 16);
}
__device__ __noinline__ float4 epi_exact(const float4* gh, int np, int dv)
{
    extern __shared__ __align__(1024) uint8_t smem[];
    float n0 = 0.f, d0 = 0.f, n1 = 0.f, d1 = 0.f;
    int j = 0, je = np;
    const uint32_t own = __ballot_sync(~0u, gh != nullptr);
    if (own != ~0u) {
        dv = __shfl_sync(~0u, dv, __ffs(own) - 1); j = min(threadIdx.x & 15, np); je = j + 1;
        gh = (const float4*)(smem + SM_XU + tab_at(NPB_MAX - 4) - 16);
        __syncwarp();
    }
    #pragma unroll 1
    for (; j < je; j++) {
        const float4 g = gh[j], h = gh[NPMAX + j];
        const bool ma = 2 * j < dv, mb = 2 * j + 1 < dv;
        const float e0 = 2.f * rcpf(1.f + ex2f(-2.f * LOG2E * g.x)), e1 = 2.f * rcpf(1.f + ex2f(-2.f * LOG2E * g.y));
        const float e2 = 2.f * rcpf(1.f + ex2f(-2.f * LOG2E * g.z)), e3 = 2.f * rcpf(1.f + ex2f(-2.f * LOG2E * g.w));
        if (ma) { d0 += e0; n0 = fmaf(e0, h.x, n0); d1 += e2; n1 = fmaf(e2, h.z, n1); }
        if (mb) { d0 += e1; n0 = fmaf(e1, h.y, n0); d1 += e3; n1 = fmaf(e3, h.w, n1); }
    }
    if (own != ~0u) {
        #pragma unroll
        for (int o = 1; o < 16; o <<= 1) {
            n0 += __shfl_xor_sync(~0u, n0, o); d0 += __shfl_xor_sync(~0u, d0, o);
            n1 += __shfl_xor_sync(~0u, n1, o); d1 += __shfl_xor_sync(~0u, d1, o);
        }
        *(volatile uint32_t*)(smem + SM_MISC + 12) = 0;
    }
    return make_float4(n0, d0 + EPS2, n1, d1 + EPS2);
}
template<int NP>
__device__ __forceinline__ void epi_dump(const float* g, const float* h, float4* gh) {
    #pragma unroll
    for (int i = 0; i < 2 * NP; i++) {
        const float* v = i < NP ? g + 4 * i : h + 4 * (i - NP);
        asm volatile("{\n.reg .pred p;\nsetp.ne.u64 p, %5, 0;\n@p st.v4.f32 [%0], {%1,%2,%3,%4};\n}"
                     :: "l"((uint64_t)gh + (i < NP ? i : NPMAX + i - NP) * 16), "f"(v[0]), "f"(v[1]), "f"(v[2]), "f"(v[3]), "l"(gh) : "memory");
    }
}
__device__ __forceinline__ uint32_t bin_bits(uint32_t b) { return (1u << (b & 7)) | ((b < 48 ? 0x100u : 0x400u) << (b >> 3)); }
__device__ __forceinline__ void place(uint32_t sbase, uint32_t slot, uint32_t v, uint32_t eb) {
    asm volatile("{\n.reg .pred p;\nsetp.lt.u32 p, %0, %5;\n@p st.shared.u32 [%1], %2;\n@p st.shared.u16 [%3], %4;\n}"
                 :: "r"(slot), "r"(sbase + SM_EID + slot * 4), "r"(eb + (v >> 19)), "r"(sbase + SM_SRC + slot * 2), "r"(v), "n"(SLOT_CAP) : "memory");
}
__device__ __forceinline__ uint64_t desc_sw128(uint32_t a) {
    return (uint64_t)((a & 0x3FFFF) >> 4) | ((uint64_t)1 << 16) | ((uint64_t)64 << 32) | ((uint64_t)1 << 62);
}

template<bool LO32>
__global__ void __launch_bounds__(THREADS, 1)
gcn_kernel(const int* __restrict__ dst, unsigned* gbar, char* gs, const int* __restrict__ src, int E, int ch, int N, int npb, uint32_t magic,
           const __nv_bfloat16* __restrict__ x, const __nv_bfloat16* __restrict__ ea,
           const __nv_bfloat16* __restrict__ wa, const __nv_bfloat16* __restrict__ wb, const __nv_bfloat16* __restrict__ wc,
           const __nv_bfloat16* __restrict__ wu, const __nv_bfloat16* __restrict__ wv,
           __nv_bfloat16* out, int4 wrow, const __grid_constant__ CUtensorMap tm1, const __grid_constant__ CUtensorMap tm2,
           const __grid_constant__ CUtensorMap tmw, const __grid_constant__ CUtensorMap tmx)
{
    extern __shared__ __align__(1024) uint8_t smem[];
    int* cls = (int*)(smem + SM_CLS);
    int* misc = (int*)(smem + SM_MISC);
    WG0(); WS(0); CG(0);
    const uint32_t sbase = smem_u32(smem);
    const int tid = threadIdx.x, lane = tid & 31;
    const int b = blockIdx.x, nb = gridDim.x;
    const int cnt = max(0, min(ch, E - b * ch));
    const int node0 = b * npb;
    uint32_t tag = 0;
    if (tid < 384) asm volatile("ld.relaxed.gpu.global.u32 %0, [%1];" : "=r"(tag) : "l"(gbar) : "memory");
    const int warp = (int)__reduce_max_sync(~0u, (unsigned)tid >> 5);
    const uint32_t su = __reduce_or_sync(~0u, sbase);
    if (warp >= 12) {
        const int v = warp & 3;
        const uint32_t a1 = su + SM_ABAR + (v == 0 ? 80 : v == 1 ? 120 : v == 2 ? 32 : 40);
        w_init(su + SM_ABAR + v * 8, 1); w_init(a1, 1);
        w_expect(su + SM_ABAR + v * 8, v < 3 ? min(max(cnt * 4 - v * 8192, 0), 8192) : 4 * 8192 + 2048);
        if (v < 2) w_expect(a1, v == 0 ? nb * (CE * 2) : nb * 64);
        asm volatile("fence.mbarrier_init.release.cluster;" ::: "memory");
    }
    #pragma unroll
    for (int v = 0; v < EPT / 4; v++) {
        const uint32_t off = v * (THREADS * 4) + tid * 4;
        if (v) { uint32_t c0, c1; asm volatile("mov.u32 %0, %%clock;" : "=r"(c0)); do { asm volatile("mov.u32 %0, %%clock;" : "=r"(c1)); } while (__all_sync(~0u, c1 - c0 < PD)); }
        asm volatile("{\n.reg .pred q;\nsetp.lt.u32 q, %2, %3;\n@q cp.async.cg.shared.global [%0], [%1], 16;\n}"
                     :: "r"(sbase + SM_IDX + off * 4), "l"(dst + b * ch + off), "r"(off), "r"(cnt) : "memory");
        cp_commit();
    }
    if (warp == 15) {
        w_box_ld(su + SM_WR, &tmw, wrow.x, su + SM_ABAR + 24); w_box_ld(su + SM_WR + 8192, &tmw, wrow.y, su + SM_ABAR + 24);
        w_box_ld(su + SM_WR + 16384, &tmw, wrow.z, su + SM_ABAR + 24); w_ld(su + SM_WR + 24576, wc, 2048, su + SM_ABAR + 24);
        w_box_ld(su + SM_WR + 40960, &tmw, wrow.w, su + SM_ABAR + 24);
    }
    const int wg = warp >> 2, w = warp & 3;
    const int q = lane >> 2, t = lane & 3;
    const int nn = max(0, min(npb, N - node0));
    if (sbase & 1023) __trap();

    sts32(sbase + SM_DEG + tid * 4, tid < NPB_MAX ? 0 : 0x80000000u);
    if (tid < NCLS + NB_MAX) cls[tid] = tid < NCLS ? 0 : ((tid - NCLS) * 20) & 63;
    else if (warp == 8) sts32(sbase + SM_OH + lane * 4, t != (q >> 1) ? 0u : 0x00003F00u);
    else if (warp == 11) misc[lane] = lane == 5 ? TILE_CAP - TILE_X : lane == 8 || lane == 3;
    if (warp == 14) sts32(sbase + SM_TINFO + 96 * 32 + lane * 4, lane & 1 ? tab_at(NONE) : 0);
    if (warp == 15) sts32(sbase + SM_CLAIM + lane * 4, lane == 0 ? 3 * 32 : 0x40000000);
    if (tid == 0) sts32(sbase + SM_XLIST, tag);
    tag = (tag & 1) | 2;
    if (wg < 3) {
        const uint32_t d0 = ((NPB_MAX + ((2 * lane) & 15) + 16 * (b & 1)) * 4 | (tag << 14)) * 0x10001u, d1 = d0 + 0x40004u, d2 = tag << 16;
        #pragma unroll 1
        for (int i = tid; i < (P1B + 384) / 16; i += 384) {
            sts128(sbase + SM_P1 + i * 16, make_uint4(d0, d0, d1, i == P1B / 16 + 11 ? 0x80000000u | (tag << 14) : d1));
            sts128(sbase + SM_P2 + i * 16, make_uint4(d2, d2, d2, d2)); sts128(sbase + SM_P2 + P1B - 128 + i * 16, make_uint4(d2, d2, d2, d2));
        }
    }
    WS(1);
    __syncthreads();
    if (wg == 3) tag = lds32(sbase + SM_P2) >> 16;
    uint32_t all = 0;
    if (wg == 3) all = (lds32(sbase + SM_XLIST) + 1) * nb;
    if (tid == 128) {
        asm volatile("prefetch.tensormap [%0];" :: "l"((uint64_t)&tm1) : "memory");
        asm volatile("prefetch.tensormap [%0];" :: "l"((uint64_t)&tm2) : "memory");
        asm volatile("prefetch.tensormap [%0];" :: "l"((uint64_t)&tmx) : "memory");
    }
    const uint32_t m4 = __reduce_or_sync(~0u, -4 * npb);
    uint32_t ent[EPT];
    #pragma unroll
    for (int v = 0; v < EPT / 4; v++) {
        if (v == 0) cp_wait<2>(); else if (v == 1) cp_wait<1>(); else cp_wait<0>();
        if (v == 0 && wg == 2 && w < 3) {
            const int n = min(cnt * 4 - w * 8192, 8192);
            if (n > 0) w_ld(su + SM_XU + w * 8192, src + b * ch + w * 2048, n, su + SM_ABAR + w * 8);
        }
        const uint32_t off = v * (THREADS * 4) + tid * 4;
        if (off < (uint32_t)cnt) {
            const uint4 u = lds128(sbase + SM_IDX + off * 4);
            uint32_t dv[4] = {u.x, u.y, u.z, u.w}, ps[4], ck[4];
            uint32_t* en = ent + 4 * v;
            #pragma unroll
            for (int k = 0; k < 4; k++) {
                dv[k] = min(dv[k], (uint32_t)(nb * npb - 1));
                ps[k] = __umulhi(dv[k], magic);
                asm volatile("atom.shared.add.u32 %0, [%1], 0x10001;" : "=r"(ck[k]) : "r"(sbase + SM_HIST + ps[k] * 4) : "memory");
            }
            #pragma unroll
            for (int k = 0; k < 4; k++) {
                dv[k] = ps[k] * m4 + (dv[k] * 4 + (tag << 14));
                en[k] = (ck[k] & 63) + ps[k] * CE;
            }
            if (__builtin_expect(max(max(ck[0], ck[1]), max(ck[2], ck[3])) >= CE << 16, 0)) {
                auto step = [&]() {
                    uint32_t e = en[0];
                    const uint32_t d = dv[0];
                    if (ck[0] >= CE << 16) {
                        uint32_t j; asm volatile("atom.shared.inc.u32 %0, [%1], 0x7fffffff;" : "=r"(j) : "r"(sbase + SM_MISC + 8) : "memory");
                        j = min(j + (j >= 15), 63u);
                        sts32(sbase + SM_L1 + j * 4, d | ((j < 63 ? e / CE : 255u) << 16));
                        e = NB_MAX * CE + j;
                    }
                    en[0] = en[1]; en[1] = en[2]; en[2] = en[3]; en[3] = e;
                    dv[0] = dv[1]; dv[1] = dv[2]; dv[2] = dv[3]; dv[3] = d;
                    ck[0] = ck[1]; ck[1] = ck[2]; ck[2] = ck[3];
                };
                if (v == 2) { step(); step(); step(); step(); }
                else {
                    #pragma unroll 1
                    for (int k = 0; k < 4; k++) step();
                }
            }
            #pragma unroll
            for (int k = 0; k < 4; k++)
                asm volatile("st.shared.u16 [%0], %1;" :: "r"(sbase + SM_P1 + en[k] * 2), "r"(dv[k]) : "memory");
        }
    }
    if (warp == 15) {
        #pragma unroll
        for (int v = 0; v < EPT / 4; v++) sts128(sbase + SM_ENT + v * 512 + lane * 16, make_uint4(ent[4*v], ent[4*v+1], ent[4*v+2], ent[4*v+3]));
    }
    asm volatile("fence.proxy.async.shared::cta;" ::: "memory");
    WS(5);
    __syncthreads();
    if (warp == 15) {
        w_inc(gbar + 1);
        const uint32_t n = __reduce_or_sync(~0u, lds32(su + SM_MISC + 8));
        if (__builtin_expect(n > 15, 0)) {
            const uint2 r = lds64(su + SM_L1 + lane * 8);
            uint32_t m = lane < 8 ? 0 : (r.x >> 24 ? 0 : bin_bits(r.x >> 16)) | (r.y >> 24 ? 0 : bin_bits(r.y >> 16));
            m = n > 62 ? 0x7FFF3FFFu : __reduce_or_sync(~0u, m);
            sts32(su + SM_L1 + 60, m | 0x80000000u | (tag << 14));
            asm volatile("fence.proxy.async.shared::cta;" ::: "memory");
            __syncwarp();
        }
        w_st(gs + G_H1 + b * 64, su + SM_L1, 64);
        w_box_st(&tm1, b * (CE / 2), su + SM_P1);
        w_st(gs + G_L + b * 512, su + SM_L1, 256);
        asm volatile("cp.async.bulk.commit_group;" ::: "memory");
    } else {
        mbar_wait_c(su + SM_ABAR, 0);
        auto put = [&](uint32_t off, const uint32_t* uu) {
            if (off < (uint32_t)cnt) {
                const uint4 sv = lds128(sbase + SM_XU + off * 4);
                const uint32_t ss[4] = {sv.x, sv.y, sv.z, sv.w};
                #pragma unroll
                for (int k = 0; k < 4; k++) sts32(sbase + SM_P2 + uu[k] * 4, (ss[k] & 0xFFFF) | (((off + k) << 19) + (tag << 16)));
            }
        };
        #pragma unroll
        for (int v = 0; v < EPT / 4; v++) { if (v) mbar_wait_c(su + SM_ABAR + v * 8, 0); put(v * (THREADS * 4) + tid * 4, ent + 4 * v); }
        if (wg == 3) {
            const uint4 e = lds128(sbase + SM_ENT + w * 512 + lane * 16);
            const uint32_t uu[4] = {e.x, e.y, e.z, e.w};
            put(w * (THREADS * 4) + (480 + lane) * 4, uu);
        }
        asm volatile("fence.proxy.async.shared::cta;" ::: "memory");
        WS(7);
        __syncwarp();
        asm volatile("bar.arrive 12, 512;" ::: "memory");
    }
    WS(8);

    const int ngroups = (nn + 3) >> 2;
    if (warp < 12) {
        asm volatile("setmaxnreg.inc.sync.aligned.u32 152;");
        const uint32_t ab = su + SM_ABAR;
        uint32_t wf[40], wn[16];
        const uint32_t mo = sbase + (8 * (lane >> 4) + (lane & 7)) * 128 + (((2 * w + ((lane >> 3) & 1)) ^ (lane & 7)) << 4);
        const uint32_t wca = __shfl_sync(~0u, sbase + SM_WC + (16 * w + q) * 32 + t * 4 + ((q >> 2) << 4), lane), l16 = __shfl_sync(~0u, (lane & 15) * 16, lane);
        mbar_wait_c(ab + 24, 0);
        {
            #pragma unroll
            for (int ks = 0; ks < 4; ks++) { ldsm4t(wf + 4 * ks, mo + SM_WR + ks * 2048); ldsm4t(wf + 20 + 4 * ks, mo + SM_WR + 8192 + ks * 2048); ldsm4t(wn + 4 * ks, mo + SM_WR + 16384 + ks * 2048); }
            auto half = [](uint32_t& v) { asm("mul.rn.bf16x2 %0, %0, %1;" : "+r"(v) : "r"(0x3F003F00u)); };
            uint32_t z = 0;
            #pragma unroll
            for (int i = 0; i < 16; i++) { half(wf[i]); z ^= wf[i]; }
            sts32(sbase + SM_ES + lane * 4, z);
            if (wg == 2) {
                uint32_t f[4];
                ldsm4t(f, (mo ^ ((lane & 7) << 4)) + SM_WR + 24576);
                half(f[0]); half(f[1]); half(f[2]); half(f[3]);
                sts32(wca, f[0]); sts32(wca + 256, f[1]); sts32(wca ^ 16, f[2]); sts32((wca ^ 16) + 256, f[3]);
                asm volatile("fence.proxy.async.shared::cta;" ::: "memory");
            }
        }
        const uint64_t wcd = __reduce_or_sync(~0u, (((sbase + SM_WC) & 0x3FFFF) >> 4) | (8u << 16)) | EDHI;
        const uint32_t bar0 = __reduce_or_sync(~0u, sbase + SM_BARS + wg * 2 * STG);
        const uint32_t xd0 = __reduce_or_sync(~0u, (((sbase + SM_XS + wg * NSTAGE * XS_BYTES) & 0x3FFFF) >> 4) | (1u << 16));
        const uint32_t ed0 = __reduce_or_sync(~0u, (((sbase + SM_ES + wg * NSTAGE * ES_BYTES) & 0x3FFFF) >> 4) | (8u << 16));
        const uint64_t ohd = __reduce_or_sync(~0u, ((sbase + SM_OH) & 0x3FFFF) >> 4);
        const uint32_t tabx = __reduce_or_sync(~0u, sbase + SM_TAB + w * 128);
        const uint32_t bars = __reduce_or_sync(~0u, 2 * bar0 + STG), xds = __reduce_or_sync(~0u, 2 * xd0 + XS_BYTES / 16), eds = __reduce_or_sync(~0u, 2 * ed0 + ES_BYTES / 16);
        const uint32_t xuo = __reduce_or_sync(~0u, sbase + SM_XU + wg * 16384);
        { const uint2 z = lds64(sbase + SM_OH + 8); wf[38] = z.x; wf[39] = z.y; }
        WS(9);
        constexpr int NU = 6;
        const uint32_t dm = ((NPB_MAX + lane) * 4 | (tag << 14)) * 0x10001u;
        const uint32_t db = sbase + SM_DEG - (tag << 14);
        const char* const g1 = gs + (uint32_t)(b * (P1B + P2B) + tid * 8);
        int rk[NU][4];
        uint32_t spins = 0;
        {
            uint2 r1[NU];
            mbar_wait_c(ab + 80, 0);
            WS(2);
            #pragma unroll
            for (int i = 0; i < NU; i++) {
                r1[i] = make_uint2(dm, dm);
                if (NB_MIN * 16 >= 384 * (i + 1) || tid + 384 * i < nb * 16) r1[i] = lds64(sbase + SM_IDX + (tid + 384 * i) * 8);
            }
            #pragma unroll 1
            while (true) {
                uint32_t bad = 0;
                #pragma unroll
                for (int i = 0; i < NU; i++) bad |= r1[i].y ^ dm;
                if (__builtin_expect(!__any_sync(~0u, bad & 0xC000), 1)) break;
                #pragma unroll
                for (int i = 0; i < NU; i++) ld_unit(r1[i], g1 + 384 * 8 * i, (r1[i].y ^ dm) & 0xC000);
                if (++spins > (1u << 22)) break;
            }
            WS(3);
            #pragma unroll
            for (int i = 0; i < NU; i++) {
                rk[i][0] = r1[i].x & 0xFFFF; rk[i][1] = r1[i].x >> 16; rk[i][2] = r1[i].y & 0xFFFF; rk[i][3] = r1[i].y >> 16;
                #pragma unroll
                for (int k = 0; k < 4; k++) asm volatile("red.shared.add.u32 [%0], 1;" :: "r"(db + min((uint32_t)rk[i][k], NPB_MAX * 4 + (tag << 14))) : "memory");
            }
        }
        WS(10);
        asm volatile("bar.sync 11, 512;" ::: "memory");
        int mycls = 0, mycr = 0, dg = lds32(sbase + SM_DEG + tid * 4);
        if (tid < nn) {
            mycls = NCLS - 1 - (dg <= 40 ? dg : min(41 + ((dg - 41) >> 3), NCLS - 1)); mycr = atomicAdd(&cls[mycls], 1);
        }
        int s0 = 0;
        if (__builtin_expect(dg > 40, 0)) s0 = max(SLOT_CAP - ((dg + 1) & ~1) - atomicAdd(&misc[6], (dg + 1) & ~1), 0);
        asm volatile("bar.sync 1, 384;" ::: "memory");
        WS(12);
        {
            const uint2 c = lds64(sbase + SM_CLS + lane * 8);
            const int v0 = c.x * (lane > 11 ? ((64 - 2 * lane) << 16) + 1 : 1), v1 = c.y * (lane >= 11 ? ((62 - 2 * lane) << 16) + 1 : 1);
            int inc = v0 + v1;
            #pragma unroll
            for (int o = 1; o < 32; o <<= 1) { int y = __shfl_up_sync(~0u, inc, o); if (lane >= o) inc += y; }
            const int e0 = __shfl_sync(~0u, inc - v0 - v1, mycls >> 1), e1 = __shfl_sync(~0u, inc - v1, mycls >> 1);
            const int e = (mycls & 1) ? e1 : e0;
            if (tid < nn) {
                if (dg <= 40) s0 = min((e >> 16) + mycr * ((dg + 1) & ~1), SLOT_CAP - 40);
                sts32(sbase + SM_DEG + tid * 4, s0);
            }
            const uint32_t pos = tid < nn ? (e & 0xFFFF) + mycr : tid;
            sts32(sbase + SM_SORT + pos * 4, tid < nn ? (uint32_t)tid | ((uint32_t)s0 << 16) : NONE);
            asm volatile("st.shared.u16 [%0], %1;" :: "r"(sbase + SM_SDEG + pos * 2), "r"(min(dg, 65535)) : "memory");
            if (tid == 383) { misc[4] = (nn - c.y + 3) >> 2; if ((inc >> 16) + misc[6] > SLOT_CAP - 40) misc[1] = 1; }
        }
        asm volatile("bar.sync 1, 384;" ::: "memory");
        WS(13);
        const uint32_t sv = lds32(sbase + SM_SORT + tid * 4);
        const uint2 d4 = lds64(sbase + SM_SDEG + (tid >> 2) * 8);
        const uint32_t slow = lds32(sbase + SM_MISC + 4);
        #pragma unroll
        for (int i = 0; i < NU; i++) {
            #pragma unroll
            for (int k = 0; k < 4; k++) rk[i][k] = atoms_inc(db + rk[i][k]);
        }
        if (__reduce_or_sync(~0u, slow) == 0) {
            const uint32_t nd = sv & 0xFFFF;
            const int g = tid >> 2;
            dg = ((t & 2 ? d4.y : d4.x) >> (16 * (t & 1))) & 0xFFFF;
            const uint32_t hi2 = __vmaxu2(d4.x, d4.y), lo2 = __vminu2(d4.x, d4.y);
            const int mx = max(hi2 >> 16, hi2 & 0xFFFF), mn = min(lo2 >> 16, lo2 & 0xFFFF);
            int left = (mx + 1) >> 1;
            int tl = g, nx = ngroups + 4 + g, nt = left > NPMAX ? 2 : 1;
            const bool odd = left > 2 * NPMAX || (nt == 2 && nx >= TILE_CAP - TILE_X);
            if (__builtin_expect(__any_sync(~0u, odd), 0)) {
                if (odd) nt = (left + NPMAX - 1) / NPMAX;
                if (odd && t == 0) { asm volatile("atom.shared.add.u32 %0, [%1], %2;" : "=r"(nx) : "r"(sbase + SM_MISC + 20), "r"(nt - 1) : "memory"); if (nx + nt - 1 > TILE_CAP) misc[1] = 1; }
                nx = __shfl_sync(~0u, nx, lane & ~3);
                if (odd && nx + nt - 1 > TILE_CAP) left = 0;
            }
            const uint32_t w0 = tab_at(nd);
            if (g >= ngroups + 4) tl = ngroups;
            uint32_t cont = 0;
            int done = 0;
            bool act = true;
            do {
                int np = nt <= 2 ? (left + nt - 1) >> (nt - 1) : (left + nt - 1) / nt;
                left -= np; nt = max(nt - 1, 1);
                if (np) np = max(np, NPMIN);
                const int dv = min(max(dg - done, 0), 2 * np);
                uint32_t code = (uint32_t)np | cont | (left > 0 ? C_MORE : 0u);
                const bool gen = mn - done < 2 * np - (np == NPMIN ? 1 : 2);
                if (np == 0) code = 0;
                const uint32_t w1 = code | (dv == 2 * np ? 0x8000u : (2 * np - 1 - dv) << 8);
                if (act) *(uint2*)(smem + SM_TINFO + tl * 32 + t * 8) = make_uint2((dv ? (sv >> 16) + done : 0) | ((gen ? (np > 8 ? 15 : np > 5 ? 14 : 13) : np) << 16) | ((left > 0 ? nx : 0) << 20) | ((uint32_t)dv << 27), w0 | (np == 0 ? 0u : w1 << 16));
                tl = nx++; cont = C_CONT; done += 2 * np; act = left > 0;
            } while (__any_sync(~0u, act));
        }
        __syncwarp();
        asm volatile("bar.arrive 4, 512;" ::: "memory");
        WS(14);
        wf[16] = lds32(wca); wf[17] = lds32(wca + 256); wf[18] = lds32(wca ^ 16); wf[19] = lds32((wca ^ 16) + 256);
        #pragma unroll
        for (int pc = 0; pc < 3; pc++) {
            uint4 r2[2];
            mbar_wait_c(ab + pc * 8, 1);
            if (pc == 0) WS(4); if (pc == 2) WS(16);
            #pragma unroll
            for (int k = 0; k < 2; k++) {
                r2[k] = lds128(sbase + SM_P2 + (tid + 384 * (2 * pc + k)) * 16);
                if (rk[2 * pc + k][0] < 0) r2[k].w = tag << 16;
            }
            while (__builtin_expect(__any_sync(~0u, ((r2[0].w ^ (tag << 16)) | (r2[1].w ^ (tag << 16))) & 0x30000), 0)) {
                #pragma unroll
                for (int k = 0; k < 2; k++)
                    ld_unit(r2[k], g1 + (uint32_t)(tid * 8) + (P1B + 384 * 16 * (2 * pc + k)), (r2[k].w ^ (tag << 16)) & 0x30000);
                if (++spins > (1u << 22)) break;
            }
            #pragma unroll
            for (int k = 0; k < 2; k++) {
                const int i = 2 * pc + k;
                const uint32_t eb = ((tid >> 4) + 24 * i) * ch;
                place(sbase, rk[i][0], r2[k].x, eb); place(sbase, rk[i][1], r2[k].y, eb); place(sbase, rk[i][2], r2[k].z, eb); place(sbase, rk[i][3], r2[k].w, eb);
            }
        }
        WGD();
        __syncwarp();
        asm volatile("bar.arrive 3, 480;" ::: "memory");
        float g[4 * NPMAX], h[4 * NPMAX];
        float4 lgh[2 * NPMAX];
        float4 cyr = make_float4(0.f, 0.f, 0.f, 0.f);
        WS(15); CG(1);
        mbar_wait_c(ab + 88 + wg * 8, 0);
        auto pack = [&](uint32_t* v, const float* u) {
            #pragma unroll
            for (int i = 0; i < 16; i++) v[i] = pack_bf16(u[2*i], u[2*i+1]);
        };
        auto rows_st = [&](uint32_t p, const uint32_t* v) {
            #pragma unroll
            for (int i = 0; i < 4; i++) stsm4t(p + i * 2048, v + 4 * i);
        };
        {
            const uint64_t d0 = desc_sw128(xuo), d1 = d0 + 512;
            const uint32_t mr = sbase + wg * 16384 + w * 128 + (tab_at(8 * (lane >> 4) + (lane & 7)) ^ ((lane & 8) << 1));
            uint32_t v[16];
            node_mma(g, wn, d0); node_mma(h, wn, d1);
            TileMMA<8>::wait_g(g);
            pack(v, g); rows_st(mr + SM_TAB, v);
            TileMMA<8>::wait_h(h);
            #pragma unroll
            for (int ks = 0; ks < 4; ks++) ldsm4t(wn + 4 * ks, mo + SM_WR + 40960 + ks * 2048);
            node_mma(g, wn, d0);
            if (wg == 2) asm volatile("bar.sync 5, 384;" ::: "memory"); else asm volatile("bar.arrive 5, 384;" ::: "memory");
            pack(v, h); rows_st(mr + SM_TAB + 8192, v);
            node_mma(h, wn, d1);
            __syncwarp();
            if (lane == 0) mbar_arrive(sbase + SM_ABAR + 112);
            TileMMA<8>::wait_g(g);
            pack(v, g);
            asm volatile("bar.sync %0, 128;" :: "r"(8 + wg) : "memory");
            rows_st(mr + SM_XU, v);
            TileMMA<8>::wait_h(h);
            pack(v, h);
            asm volatile("bar.sync %0, 128;" :: "r"(8 + wg) : "memory");
            rows_st(mr + SM_XU + 8192, v);
            __syncwarp();
            if (lane == 0) mbar_arrive(sbase + SM_ABAR + 72);
            mbar_wait_c(ab + 112, 0);
            __syncwarp();
            if (__builtin_expect(__reduce_or_sync(~0u, misc[1]) != 0, 0)) { slow_bin(x, ea, src, dst, wa, wb, wc, wu, wv, out, E, node0, nn, 384); asm volatile("exit;"); }
            WS(6);
        }
        uint32_t bar = bar0, xd = xd0, ed = ed0, ph = 0;
        float pn0 = 0.f, pd0 = 1.f, pn1 = 0.f, pd1 = 1.f;
        uint4 rc;
        rc.x = lds32(sbase + SM_TINFO + wg * 32 + ((lane >> 1) & 3) * 8 + 4);
        uint32_t code = __reduce_or_sync(~0u, rc.x >> 16);
        rc.x = (rc.x & 0xFFFF) ^ ((lane & 8) << 1);
        uint32_t pst = tabx + tab_at(NONE);
        auto fetch_a = [&]() {
            asm volatile("ldmatrix.sync.aligned.m8n8.x2.trans.shared.b16 {%0,%1}, [%2];" : "=r"(wf[36]), "=r"(wf[37]) : "r"(tabx + rc.x) : "memory");
        };
        auto emit = [&]() {
            asm volatile("stmatrix.sync.aligned.m8n8.x1.trans.shared.b16 [%0], {%1};" :: "r"(pst), "r"(pack_bf16(pn0 * rcpf(pd0), pn1 * rcpf(pd1))) : "memory");
        };
        auto carry = [&]() {
            if (rc.z & C_CONT) { pn0 += cyr.x; pd0 += cyr.y; pn1 += cyr.z; pd1 += cyr.w; }
            if (rc.z & C_MORE) { cyr = make_float4(pn0, pd0 - EPS2, pn1, pd1 - EPS2); pn0 = pn1 = 0.f; pst = tabx + tab_at(NONE); }
        };
        fetch_a();
        while (true) {
            switch (code & 15) {
                default: goto finished;
#define TILE(P) { \
                    bool ok; float dmin; \
                    do { \
                        mbar_wait_c(bar, ph); \
                        TileMMA<P>::issue(g, h, wf, xd, ed | EDHI, ohd, wcd); \
                        const uint32_t eb = bar + 8; \
                        ph ^= bar != bar0; bar = bars - bar; xd = xds - xd; ed = eds - ed; \
                          \
                        asm volatile("{\n.reg .pred p;\nsetp.eq.u32 p, %0, 77;\n@p trap;\n}" :: "r"(xds) : "memory"); \
                        emit(); rc = lds128(eb + 8 + l16); \
                        TileMMA<P>::wait_g(g); fetch_a(); TileMMA<P>::wait_h(h); \
                        mbar_arrive(eb); \
                        asm volatile("add.u32 %0, %1, %2;" : "=r"(pst) : "r"(rc.y), "r"(tabx)); \
                        ok = epi_fast<P>(g, h, __uint_as_float(rc.z), __uint_as_float(rc.w), pn0, pd0, pn1, pd1, dmin); \
                    } while (__all_sync(~0u, ok)); \
                    code = __reduce_or_sync(~0u, rc.w); \
                    if (__builtin_expect(__any_sync(~0u, ((rc.z & 0x1F00) != 0) | (dmin < TAU * 2 * P)), 0)) { \
                        int dv; \
                        const uint32_t bad = unpad(rc.z, P, g[4 * P - 4], g[4 * P - 2], pd0, pd1, dv); \
                        if (bad) { \
                            float4* gh = exact_copy(bad, lgh); \
                            epi_dump<P>(g, h, gh); \
                            const float4 r = epi_exact(gh, P, dv); \
                            if (gh) { pn0 = r.x; pd0 = r.y; pn1 = r.z; pd1 = r.w; } \
                        } \
                    } \
                    if (code & C_BRK) { carry(); if (P != 11 && (code & 15) == P) goto L##P; } \
                    if (P == 11) {         \
                        wf[16] = lds32(wca); wf[17] = lds32(wca + 256); wf[18] = lds32(wca ^ 16); wf[19] = lds32((wca ^ 16) + 256); \
                    } }
#define CASE(P, UP, DN) case P: L##P: TILE(P) \
                    if (P > NPMIN && (code & 15) == P - 1) goto L##DN; \
                    if ((code & 15) == UP) goto L##UP; \
                    break;
                CASE(11, 11, 10) CASE(10, 11, 9) CASE(9, 10, 8) CASE(8, 9, 7) CASE(7, 8, 6) CASE(6, 7, 5) CASE(5, 6, 4) CASE(4, 5, 4)
#undef CASE
#undef TILE
            }
        }
finished:
        emit();
        __syncwarp();
        if (lane == 0) mbar_arrive(sbase + SM_ABAR + 48 + wg * 8);
    } else {
        asm volatile("setmaxnreg.dec.sync.aligned.u32 56;");
        auto x_ld = [&](int i0, int i1) {
            #pragma unroll
            for (int i = i0; i < i1; i++) w_box_ld(su + SM_XU + i * 8192, &tmx, node0 + i * 64, su + SM_ABAR + 88 + (i >> 1) * 8);
        };
        if (w < 3) {
            #pragma unroll
            for (int i = 0; i < 2; i++) { w_init(su + SM_BARS + (w * 2 + i) * STG, 64); w_init(su + SM_BARS + (w * 2 + i) * STG + 8, 128); }
            w_init(su + SM_ABAR + 48 + w * 8, 4);
            w_init(su + (w == 0 ? SM_GBAR + 96 * 8 : w == 1 ? SM_ABAR + 72 : SM_ABAR + 112), w == 0 ? 32 : 12);
        } else {
            #pragma unroll
            for (int i = 0; i < 4; i++) { w_init(su + SM_ABAR + (i < 3 ? 88 + i * 8 : 40), 1); w_expect(su + SM_ABAR + (i < 3 ? 88 + i * 8 : 40), i < 3 ? 16384 : nb * 64); }
            asm volatile("fence.mbarrier_init.release.cluster;" ::: "memory");
            w_hint(gbar + 1, all);
            asm volatile("cp.async.bulk.wait_group.read 0;" ::: "memory");
            WS(2);
            w_ld(su + SM_IDX, gs + b * (P1B + P2B), nb * (CE * 2), su + SM_ABAR + 80);
            w_ld(su + SM_H1, gs + G_H1, nb * 64, su + SM_ABAR + 120);
            asm volatile("bar.sync 12, 512;" ::: "memory");
            w_box_st(&tm2, P1B / 4 + b * CE, su + SM_P2);
            w_st(gs + G_H2 + b * 64, su + SM_P2 + P2B, 64);
            w_st(gs + G_L + b * 512 + 256, su + SM_P2 + P2B, 256);
            w_sent(gbar + 4, su + SM_MISC + 32);
            asm volatile("cp.async.bulk.commit_group;" ::: "memory");
        }
        const uint32_t ab = su + SM_ABAR;
        uint32_t todo = 0;
        const uint32_t mb = (lane & 3) == 3 ? bin_bits(b) : ~0u;
        WS(12);
        mbar_wait_c(ab + 120, 0);
        WS(13);
        {
            uint4 r[5];
            #pragma unroll
            for (int i = 0; i < 5; i++) r[i] = lds128(sbase + SM_H1 + (tid - 384 + 128 * i) * 16);
            #pragma unroll
            for (int i = 0; i < 5; i++) {
                const uint32_t bb = b << 16;
                const uint32_t m = min(min(r[i].x ^ bb, r[i].y ^ bb), min(r[i].z ^ bb, r[i].w ^ bb)) >> 16;
                if ((m == 0) | (((r[i].w ^ (tag << 14)) & 0xC000) != 0) | ((~r[i].w & mb) == 0)) todo |= 1 << i;
            }
            todo &= tid - 384 + 512 < nb * 4 ? 31 : tid - 384 + 384 < nb * 4 ? 15 : 7;
        }
        #pragma unroll 1
        for (int put = 0; put < 2; put++) {
            uint32_t any = __reduce_or_sync(~0u, todo), m = 0, u = 0;
            #pragma unroll 1
            while (any | m) {
                uint4 r = make_uint4(0, 0, 0, 0), r2 = r;
                uint32_t s, go, gd;
                bool on;
                if (__builtin_expect(m == 0, 1)) {
                    const uint32_t i = __ffs(any) - 1;
                    any &= any - 1; u = tid - 384 + 128 * i; on = (todo >> i) & 1;
                    r = lds128(sbase + SM_H1 + u * 16); r2 = lds128(sbase + SM_H2 + u * 16);
                    s = u >> 2; go = G_H1 + u * 16; gd = HB;
                } else {
                    s = ((u & ~31) + __ffs(m) - 1) >> 2; m &= m - 1; on = lane < 12;
                    go = G_L + s * 512 + 64 + lane * 16; gd = 256;
                }
                #pragma unroll 1
                for (int n = 0; n < (1 << 22); n++) {
                    const bool b1 = on && ((r.w >> 14) & 3) != tag, b2 = on && put && ((r2.w >> 16) & 3) != tag;
                    if (__builtin_expect(!__any_sync(~0u, b1 | b2), 1)) break;
                    ld_unit(r, gs + go, b1); ld_unit(r2, gs + go + gd, b2);
                }
                if (gd == HB) m = __ballot_sync(~0u, on && (~r.w & mb) == 0);
                if (on && r.w >> 16 == 255) sts32(sbase + SM_MISC + 4, 1);
                const uint32_t e[4] = {r.x, r.y, r.z, r.w}, v[4] = {r2.x, r2.y, r2.z, r2.w};
                uint32_t slot[4];
                #pragma unroll
                for (int k = 0; k < 4; k++) slot[k] = atoms_inc(sbase + SM_DEG + (on && e[k] >> 16 == (uint32_t)b ? (e[k] & 0x3FFF) : (NPB_MAX + lane) * 4));
                if (put) {
                    #pragma unroll
                    for (int k = 0; k < 4; k++) place(sbase, slot[k], v[k], s * ch);
                }
            }
            if (put == 0) {
                WS(4);
                asm volatile("bar.arrive 11, 512;" ::: "memory");
                if (w == 3) {
                    x_ld(0, 1);
                    w_expect(su + SM_ABAR, 12288); w_expect(su + SM_ABAR + 8, 12288); w_expect(su + SM_ABAR + 16, nb * (CE * 4) - 24576);
                    w_hint(gbar + 4, all);
                    asm volatile("cp.async.bulk.wait_group.read 0;" ::: "memory");
                    WS(3);
                    const char* g2 = gs + b * (P1B + P2B) + P1B;
                    w_ld(su + SM_P2, g2, 12288, su + SM_ABAR);
                    w_ld(su + SM_P2 + 12288, g2 + 12288, 12288, su + SM_ABAR + 8);
                    w_ld(su + SM_P2 + 24576, g2 + 24576, nb * (CE * 4) - 24576, su + SM_ABAR + 16);
                    w_ld(su + SM_H2, gs + G_H2, nb * 64, su + SM_ABAR + 40);
                    x_ld(1, 6);
                } else {
                    #pragma unroll 8
                    for (int i = 0; i < 32; i++) w_init(su + SM_GBAR + (w * 32 + i) * 8, 32);
                }
                asm volatile("bar.sync 4, 512;" ::: "memory");
                mbar_wait_c(ab + 40, 0);
            }
        }
        __syncwarp();
        WS(10);
        WGD();
        const uint32_t scr = sbase + SM_PAIR + (tid & 127) * 8;
        const int r4 = lane >> 3, c8 = lane & 7;
        const uint32_t sb = su;
        const uint32_t tk = ((c8 & 1) << 4) | ((c8 >> 1) << 7);
        auto row_bytes = [](uint32_t o) { return (o & 0xFE00) | ((o << 2) & 0x180); };
        if (w < 3) {
            const char* gx = as_pair((const char*)x + c8 * 16, scr);
            const char* ge = as_pair((const char*)ea + (lane & 1) * 16, scr);
            const uint32_t gx0 = (uint32_t)(uint64_t)gx, ge0 = (uint32_t)(uint64_t)ge, hi = (uint64_t)gx >> 32, he = (uint64_t)ge >> 32;
            const int s = (lane >> 1) & 3;
            const uint32_t xs0 = sb + SM_XS + w * NSTAGE * XS_BYTES;
            const uint32_t es0 = sb + SM_ES + w * NSTAGE * ES_BYTES + r4 * 64 + (((lane ^ (r4 >> 1)) & 1) << 4) + (s >> 1) * 256 + (s & 1) * 32;
            const uint32_t bars = sb + SM_BARS + w * 2 * STG;
            const uint32_t xoffA = (2 * r4) * 128 + ((c8 ^ (2 * r4)) << 4), xoffB = (2 * r4 + 1) * 128 + ((c8 ^ (2 * r4 + 1)) << 4);
            uint64_t pol;
            asm volatile("createpolicy.fractional.L2::evict_first.b64 %0, 1.0;" : "=l"(pol));
            asm volatile("bar.sync 6, 128;" ::: "memory");
            WS(15);
            uint32_t ph = 1, cur = w;
            uint32_t hist = 96 * 0x010101u;
            auto done3 = [&]() { uint32_t v = (hist >> 16) & 0xFF; asm("" : "+r"(v)); mbar_arrive(sb + SM_GBAR + v * 8); };
            const bool go = __reduce_or_sync(~0u, misc[1] == 0 && nn > 0);
            const uint32_t k32 = __shfl_sync(~0u, lane == 31 ? 0 : 32, lane), k15 = __shfl_sync(~0u, 15 | (lane & 1) << 7, lane), ca = SM_CLAIM + min(lane, 30) * 4, pa = sb + SM_TINFO + r4 * 8;
            const uint32_t pb = sb + SM_TINFO + s * 8 + 4, pc = sb + SM_TINFO + (lane & 3) * 8 + 6, xl = (lane & 8) << 1, xs = (lane & 1) << 4, ra = (lane & 15) * 16 + 16;
            auto row_of = [&](uint32_t o) { uint32_t v; asm volatile("ld.shared.u16 %0, [%1];" : "=r"(v) : "r"(pb + o) : "memory"); return v; };
            auto code_of = [&](uint32_t o) { uint32_t v; asm volatile("ld.shared.s16 %0, [%1];" : "=r"(v) : "r"(pc + o) : "memory"); return v; };
            uint32_t pw = lds32(pa + w * 32), pt = __reduce_or_sync(~0u, pw), cont = 1;
            uint4 rc = make_uint4(0, row_of(w * 32) ^ xs, code_of(w * 32) & (ONE_F | 0x1FFFu), 0);
            const uint32_t se0 = sb + SM_EID + s * 4, xab = xoffB - xoffA, das = 2 * (xs0 + xoffA) + XS_BYTES, des = 2 * es0 + ES_BYTES, brs = 2 * bars + STG;
            uint32_t br = bars, da = xs0 + xoffA, de = es0;
            #pragma unroll 1
            while (go) {
                uint32_t se, sx;
                asm("dp2a.lo.u32.u32 %0, %1, 4, %2;" : "=r"(se) : "r"(pw), "r"(se0));
                asm("dp2a.lo.u32.u32 %0, %1, 2, %2;" : "=r"(sx) : "r"(pw), "r"(sb + SM_SRC));
                const int dv = pw >> 27;
                const uint32_t db = da + xab;
                const uint32_t sel = (pt >> 16) & 15, nx = (pt >> 15) & (127 << 5);
                uint32_t g;
                auto claim = [&]() { asm volatile("atom.shared.add.u32 %0, [%1], %2;" : "=r"(g) : "r"(ca + (nx == 0 ? sb : sb + 4)), "r"(k32) : "memory"); };
                if (sel == 0) break;
                if (cont & 1) asm volatile("bar.sync 3, 480;" ::: "memory");
                switch (sel) {
#define CASE(L, P, GEN) case L: { \
                        uint32_t oe[(P + 1) / 2], o[P]; \
                        _Pragma("unroll") for (int j = 0; j < (P + 1) / 2; j++) oe[j] = lds32(se + j * 16); \
                        _Pragma("unroll") for (int j = 0; j < P; j++) o[j] = lds32(sx + j * 4); \
                        mbar_wait_h(br + 8, ph); \
                        _Pragma("unroll") for (int j = 0; j < (P + 1) / 2; j++) \
                            if (LO32) { if (!GEN && 2 * j + 2 < P) cpe<false>(he, de + j * 512, oe[j], ge0, 0, 0, pol); \
                                else if (2 * j + 1 < NPMAX || s < 2) cpe<true>(he, de + j * 512, oe[j], ge0, 4 * j + s, dv, pol); } \
                            else if (!GEN && 2 * j + 2 < P) cp16e(de + j * 512, ge, oe[j], pol); else if (2 * j + 1 < NPMAX || s < 2) cp16z<32>(de + j * 512, ge, oe[j], 4 * j + s, dv, pol); \
                        _Pragma("unroll") for (int j = 0; j < P - 1; j++) { \
                            if (LO32) { cpx<0, GEN>(hi, da + j * 1024, o[j], gx0, 2 * j, dv); cpx<1, GEN>(hi, db + j * 1024, o[j], gx0, 2 * j + 1, dv); } \
                            else if (GEN) { cp16z<128>(da + j * 1024, gx, o[j] & 0xFFFFu, 2 * j, dv, 0); cp16z<128>(db + j * 1024, gx, o[j] >> 16, 2 * j + 1, dv, 0); } \
                            else { cp16i<128>(da + j * 1024, gx, o[j] & 0xFFFFu); cp16i<128>(db + j * 1024, gx, o[j] >> 16); } } \
                        if (LO32) { cpx<0, true>(hi, da + (P - 1) * 1024, o[P - 1], gx0, 2 * P - 2, dv); cpx<1, true>(hi, db + (P - 1) * 1024, o[P - 1], gx0, 2 * P - 1, dv); } \
                        else { cp16z<128>(da + (P - 1) * 1024, gx, o[P - 1] & 0xFFFFu, 2 * P - 2, dv, 0); cp16z<128>(db + (P - 1) * 1024, gx, o[P - 1] >> 16, 2 * P - 1, dv, 0); } \
                    } break;
                    CASE(4, 4, false) CASE(5, 5, false) CASE(6, 6, false) CASE(7, 7, false) CASE(8, 8, false) CASE(9, 9, false) CASE(10, 10, false) CASE(11, 11, false)
                    CASE(15, NPMAX, true) CASE(14, 8, true) default: CASE(13, 5, true)
#undef CASE
                }
                claim();
                mbar_cp_arrive(br);
                done3();
                g = __reduce_min_sync(~0u, g);
                {
                    const uint32_t o = nx == 0 ? g : nx;
                    pw = lds32(pa + o);
                    const uint32_t ya = row_of(o), yb = code_of(o);
                    pt = __reduce_or_sync(~0u, pw);
                    const uint32_t brk = (cont | nx) > 1 ? C_BRK : 0u;
                    rc.x = ya ^ xl;
                    const uint32_t lv = brk | ((sel + (15 - NPMAX)) & 16) | (((pt >> 16) & 15) ^ sel);
                    rc.w = (yb & k15) | (lv ? 0x70000000u | brk : TAU_BITS);
                    asm volatile("st.shared.v4.u32 [%2], {%3, %0, %1, %4};\nxor.b32 %0, %5, %6;\nand.b32 %1, %7, %8;"
                                 : "+r"(rc.y), "+r"(rc.z) : "r"(br + ra), "r"(rc.x), "r"(rc.w), "r"(ya), "r"(xs), "r"(yb), "n"(ONE_F | 0x1FFFu) : "memory");
                    cont = nx;
                }
                mbar_arrive(br);
                hist = (hist << 8) | (nx == 0 ? cur : 96u);
                cur = nx == 0 ? g >> 5 : cur;
                ph ^= br != bars; br = brs - br;
                da = das - da; de = des - de;
            }
            if (cont & 1) asm volatile("bar.sync 3, 480;" ::: "memory");
            if (go) {
                mbar_wait(sb + SM_ABAR + 72, 0);
                const int g0 = 3 * max((ngroups + 2) / 3 - TR, 0) + w;
                uint32_t ro[TR], gb[TR]; uint4 xv[TR], xu[TR]; char* op[TR];
                const int gz = misc[4];
                #pragma unroll
                for (int k = 0; k < TR; k++) {
                    uint32_t nd;
                    asm volatile("ld.shared.u16 %0, [%1];" : "=r"(nd) : "r"(pa + (g0 + 3 * k) * 32 + 4) : "memory");
                    const uint32_t rb = nd == tab_at(NONE) ? 0u : row_bytes(nd);
                    xv[k] = __ldg((const uint4*)(gx + (size_t)node0 * 128 + rb));
                    op[k] = nd == tab_at(NONE) ? nullptr : (char*)out + (size_t)node0 * 128 + rb + c8 * 16;
                    ro[k] = sb + (nd ^ tk);
                    xu[k] = lds128(ro[k] + SM_XU);
                    gb[k] = __reduce_or_sync(~0u, g0 + 3 * k < gz ? sb + SM_GBAR + (g0 + 3 * k) * 8 : 0u);
                }
                #pragma unroll 1
                for (int k = 0; k < 3; k++) {
                    mbar_wait(k < 2 ? br + 8 : sb + SM_ABAR + 48 + w * 8, k < 2 ? ph : 0);
                    done3(); hist <<= 8;
                    ph ^= br != bars; br = brs - br;
                }
                #pragma unroll
                for (int k = 0; k < TR; k++) {
                    uint4 a = make_uint4(0, 0, 0, 0);
                    if (gb[k]) { mbar_wait(gb[k], 0); a = lds128(ro[k] + SM_TAB); }
                    finish(a, xu[k], xv[k]);
                    if (op[k]) *(uint4*)op[k] = a;
                }
            }
            cp_wait<0>();
        } else {
            const char* gx = as_pair((const char*)x + (size_t)node0 * 128 + c8 * 16, scr);
            const char* ob = as_pair((const char*)out + (size_t)node0 * 128 + c8 * 16, scr);
            asm volatile("bar.arrive 6, 128;" ::: "memory");
            WS(15);
            if (b == 0 && lane == 0) asm volatile("red.relaxed.gpu.global.add.u32 [%0], 1;" :: "l"(gbar) : "memory");
            if (misc[1] == 0) mbar_wait(sb + SM_ABAR + 72, 0);
            if (npb <= NPB_MAX - 4) sts32(sb + SM_MISC + 12, 0);
            const int rounds = misc[1] ? 0 : max((ngroups + 2) / 3 - TR, 0);
            const int gz = misc[4], fast = __reduce_min_sync(~0u, min(rounds, gz / 3));
            uint32_t wl = sb + SM_TINFO + r4 * 8 + 4, gbar = sb + SM_GBAR;
            auto row_at = [&](uint32_t a) { uint32_t n; asm volatile("ld.shared.u16 %0, [%1];" : "=r"(n) : "r"(a) : "memory"); return n; };
            auto fetch = [&](uint32_t n, uint4& v) {
                asm volatile("{\n.reg .b64 p;\ncvt.u64.u32 p, %5;\nadd.u64 p, p, %4;\nld.global.nc.L1::no_allocate.v4.u32 {%0,%1,%2,%3}, [p];\n}"
                             : "=r"(v.x), "=r"(v.y), "=r"(v.z), "=r"(v.w) : "l"(gx), "r"(n));
            };
            auto store = [&](uint32_t n, const uint4& a) {
                asm volatile("{\n.reg .b64 p;\ncvt.u64.u32 p, %1;\nadd.u64 p, p, %0;\nst.global.v4.u32 [p], {%2,%3,%4,%5};\n}" :: "l"(ob), "r"(n), "r"(a.x), "r"(a.y), "r"(a.z), "r"(a.w) : "memory");
            };
            uint32_t n0[3], o0[3]; uint4 x0[3];
            const uint32_t tw = __shfl_sync(~0u, tk, lane);
            if (fast) {
                #pragma unroll
                for (int r = 0; r < 3; r++) { const uint32_t v = row_at(wl + r * 32); n0[r] = row_bytes(v); o0[r] = v ^ tw; fetch(n0[r], x0[r]); }
            }
            #pragma unroll 1
            for (int k = 0; k < fast; k++) {
                wl += 96;
                #pragma unroll
                for (int r = 0; r < 3; r++) {
                    const uint32_t nd = n0[r];
                    const uint4 xu = lds128(sb + o0[r] + SM_XU);
                    const uint32_t v = row_at(wl + r * 32);
                    mbar_wait(gbar + r * 8, 0);
                    uint4 a = lds128(sb + o0[r] + SM_TAB);
                    n0[r] = row_bytes(v); o0[r] = v ^ tw;
                    finish(a, xu, x0[r]);
                    fetch(n0[r], x0[r]);
                    store(nd, a);
                }
                gbar += 24;
            }
            #pragma unroll 1
            for (int g = 3 * fast; g < 3 * rounds; g++) {
                const uint32_t v = row_at(sb + SM_TINFO + r4 * 8 + 4 + g * 32), nd = row_bytes(v), ro = sb + (v ^ tw);
                uint4 xv, a = make_uint4(0, 0, 0, 0);
                fetch(nd, xv);
                if (g < gz) { mbar_wait(sb + SM_GBAR + g * 8, 0); a = lds128(ro + SM_TAB); }
                finish(a, lds128(ro + SM_XU), xv);
                store(nd, a);
            }
        }
    }
    WS(17); WG1(); CG(2);
}

}

extern "C" void kernel_launch(void* const* d_in, const int* in_sizes, int n_in, void* d_out, int out_size) {
    const __nv_bfloat16* x = (const __nv_bfloat16*)d_in[0];
    const __nv_bfloat16* ea = (const __nv_bfloat16*)d_in[1];
    const int* src = (const int*)d_in[2];
    const int* dst = (const int*)d_in[3];
    const __nv_bfloat16* wa = (const __nv_bfloat16*)d_in[4];
    const __nv_bfloat16* wb = (const __nv_bfloat16*)d_in[5];
    const __nv_bfloat16* wc = (const __nv_bfloat16*)d_in[6];
    const __nv_bfloat16* wu = (const __nv_bfloat16*)d_in[7];
    const __nv_bfloat16* wv = (const __nv_bfloat16*)d_in[8];
    __nv_bfloat16* out = (__nv_bfloat16*)d_out;
    int N = in_sizes[0] / 64, E = in_sizes[2];
    static int sms = 0;
    static CUtensorMap tm1, tm2, tmw, tmx;
    static bool tm_ok = false;
    static void* gp = nullptr; static void* gb = nullptr;
    typedef CUresult (*EncFn)(CUtensorMap*, CUtensorMapDataType, cuuint32_t, void*, const cuuint64_t*, const cuuint64_t*, const cuuint32_t*,
                              const cuuint32_t*, CUtensorMapInterleave, CUtensorMapSwizzle, CUtensorMapL2promotion, CUtensorMapFloatOOBfill);
    static void* fn = nullptr;
    auto enc = [&](CUtensorMap* tm, const void* base, cuuint64_t cols, cuuint64_t rows, cuuint32_t bc, cuuint32_t br, CUtensorMapSwizzle sw) {
        cuuint64_t g2[2] = {cols, rows}, gs[1] = {cols * 4};
        cuuint32_t b2[2] = {bc, br}, es[2] = {1, 1};
        return ((EncFn)fn)(tm, CU_TENSOR_MAP_DATA_TYPE_UINT32, 2, (void*)base, g2, gs, b2, es, CU_TENSOR_MAP_INTERLEAVE_NONE, sw,
                           CU_TENSOR_MAP_L2_PROMOTION_NONE, CU_TENSOR_MAP_FLOAT_OOB_FILL_NONE) == CUDA_SUCCESS;
    };
    if (!sms) {
        cudaDeviceGetAttribute(&sms, cudaDevAttrMultiProcessorCount, 0);
        cudaDriverEntryPointQueryResult qr;
        cudaGetDriverEntryPoint("cuTensorMapEncodeTiled", &fn, cudaEnableDefault, &qr);
        cudaGetSymbolAddress(&gp, g_str); cudaGetSymbolAddress(&gb, g_bar);
        if (fn && gp && gb) {
            const cuuint32_t rows = sms < NB_MAX ? sms : NB_MAX;
            tm_ok = enc(&tm1, gp, (P1B + P2B) / 4, NB_MAX, CE / 2, rows, CU_TENSOR_MAP_SWIZZLE_NONE) && enc(&tm2, gp, (P1B + P2B) / 4, NB_MAX, CE, rows, CU_TENSOR_MAP_SWIZZLE_NONE);
        }
        cudaFuncSetAttribute(gcn_kernel<true>, cudaFuncAttributeMaxDynamicSharedMemorySize, SMEM_LAUNCH);
        cudaFuncSetAttribute(gcn_kernel<false>, cudaFuncAttributeMaxDynamicSharedMemorySize, SMEM_LAUNCH);
    }
    int nb = sms < NB_MAX ? sms : NB_MAX;
    int npb = (N + nb - 1) / nb;
    int ch = (((E + nb - 1) / nb) + 3) & ~3;
    const uintptr_t wp[4] = {(uintptr_t)wb, (uintptr_t)wv, (uintptr_t)wa, (uintptr_t)wu};
    uintptr_t wlo = wp[0], whi = wp[0], wal = 0;
    for (int i = 0; i < 4; i++) { wlo = wp[i] < wlo ? wp[i] : wlo; whi = wp[i] > whi ? wp[i] : whi; wal |= wp[i] - wp[0]; }
    bool ok = tm_ok && nb >= NB_MIN && npb < NPB_MAX && ch <= CH_MAX && !(E & 3) && N <= 65535 && npb >= 2 && !(wal & 127) && (whi - wlo) >> 7 < (1u << 30) &&
              !(((uintptr_t)src | (uintptr_t)dst | (uintptr_t)x | (uintptr_t)wb | (uintptr_t)wc) & 15);
    ok = ok && enc(&tmw, (const void*)wlo, 32, ((whi - wlo) >> 7) + 64, 32, 64, CU_TENSOR_MAP_SWIZZLE_128B) && enc(&tmx, x, 32, N, 32, 64, CU_TENSOR_MAP_SWIZZLE_128B);
    if (!ok) {
        int g = 1024, p = (N + g - 1) / g;
        slow_kernel<<<g, 256>>>(x, ea, src, dst, wa, wb, wc, wu, wv, out, N, E, p < 1 ? 1 : p);
        return;
    }
    int4 wrow = make_int4((int)((wp[0] - wlo) >> 7), (int)((wp[1] - wlo) >> 7), (int)((wp[2] - wlo) >> 7), (int)((wp[3] - wlo) >> 7));
    uint32_t magic = (uint32_t)((1ull << 32) / (uint32_t)npb) + 1u;
    void* args[] = {&dst, &gb, &gp, &src, &E, &ch, &N, &npb, &magic, &x, &ea, &wa, &wb, &wc, &wu, &wv, &out, &wrow, &tm1, &tm2, &tmw, &tmx};
    const bool lo32 = ((uintptr_t)x >> 32) == (((uintptr_t)x + (size_t)N * 128 - 1) >> 32) && ((uintptr_t)ea >> 32) == (((uintptr_t)ea + (size_t)E * 32 - 1) >> 32);
    cudaLaunchCooperativeKernel(lo32 && !FORCE64 ? (const void*)gcn_kernel<true> : (const void*)gcn_kernel<false>, dim3(nb), dim3(THREADS), args, SMEM_LAUNCH, cudaStreamPerThread);
}
```

```cpp
#include <cuda_runtime.h>
#include <cuda.h>
#include <cuda_bf16.h>
#include <stdint.h>

namespace {

constexpr int N_MAX = 65536;
constexpr int NPMAX = 11;
constexpr int NPMIN = 4;
constexpr int THREADS = 512;
constexpr int EPT = 12;
constexpr int CH_MAX = THREADS * EPT;
constexpr int NB_MAX = 134, NB_MIN = 120;
constexpr int CE = 64;
constexpr int P1B = NB_MAX * CE * 2;
constexpr int P2B = NB_MAX * CE * 4;
constexpr int HB = NB_MAX * 64;
constexpr int G_H1 = NB_MAX * (P1B + P2B), G_H2 = G_H1 + HB, G_L = G_H2 + HB, G_END = G_L + NB_MAX * 512;
constexpr int NPB_MAX = 384;
constexpr int SLOT_CAP = 6784;
constexpr int TILE_CAP = 124;
constexpr int TILE_X = 8;
constexpr int NCLS = 64;
constexpr int NSTAGE = 2;
constexpr int PD = 300;
constexpr int TR = 2;
constexpr float LOG2E = 1.4426950408889634f;

__device__ __align__(256) uint4 g_str[G_END / 16];
__device__ __align__(128) unsigned g_bar[8];
__device__ float g_slow[N_MAX * 128];
__device__ float4 g_copy[NB_MAX * 384 * 2 * NPMAX];

#define WS(k)
#define WGD()
#define WG0()
#define WG1()
#define CG(k)
#define SMEM_LAUNCH SMEM_BYTES
#define FORCE64 0
#define EDHI ((16ull << 32) | (3ull << 62))
template<int NP> struct TileMMA;
template<> struct TileMMA<4> {
  static __device__ __forceinline__ void issue(float* g, float* h, const uint32_t* w, uint32_t dx, uint64_t de, uint64_t dh, uint64_t dc) {
    asm volatile(
      "{\n.reg .b64 dx0, dx1, dx2, dx3;\n.reg .b32 l1, l2, l3, hx;\nmov.b32 hx, 0x40000040;\n"
      "add.u32 l1, %72, 2;\nadd.u32 l2, %72, 4;\nadd.u32 l3, %72, 6;\n"
      "mov.b64 dx0, {%72, hx};\nmov.b64 dx1, {l1, hx};\nmov.b64 dx2, {l2, hx};\nmov.b64 dx3, {l3, hx};\n"
      "wgmma.fence.sync.aligned;\n"
      "wgmma.mma_async.sync.aligned.m64n32k16.f32.bf16.bf16 {%0, %1, %2, %3, %4, %5, %6, %7, %8, %9, %10, %11, %12, %13, %14, %15}, {%68, %69, %70, %71}, %74, 0, 1, 1, 0;\n"
      "wgmma.mma_async.sync.aligned.m64n32k16.f32.bf16.bf16 {%0, %1, %2, %3, %4, %5, %6, %7, %8, %9, %10, %11, %12, %13, %14, %15}, {%48, %49, %50, %51}, %73, 1, 1, 1, 0;\n"
      "wgmma.mma_async.sync.aligned.m64n32k16.f32.bf16.bf16 {%0, %1, %2, %3, %4, %5, %6, %7, %8, %9, %10, %11, %12, %13, %14, %15}, {%32, %33, %34, %35}, dx0, 1, 1, 1, 0;\n"
      "wgmma.mma_async.sync.aligned.m64n32k16.f32.bf16.bf16 {%0, %1, %2, %3, %4, %5, %6, %7, %8, %9, %10, %11, %12, %13, %14, %15}, {%36, %37, %38, %39}, dx1, 1, 1, 1, 0;\n"
      "wgmma.mma_async.sync.aligned.m64n32k16.f32.bf16.bf16 {%0, %1, %2, %3, %4, %5, %6, %7, %8, %9, %10, %11, %12, %13, %14, %15}, {%40, %41, %42, %43}, dx2, 1, 1, 1, 0;\n"
      "wgmma.mma_async.sync.aligned.m64n32k16.f32.bf16.bf16 {%0, %1, %2, %3, %4, %5, %6, %7, %8, %9, %10, %11, %12, %13, %14, %15}, {%44, %45, %46, %47}, dx3, 1, 1, 1, 0;\n"
      "wgmma.commit_group.sync.aligned;\n"
      "wgmma.mma_async.sync.aligned.m64n32k16.f32.bf16.bf16 {%16, %17, %18, %19, %20, %21, %22, %23, %24, %25, %26, %27, %28, %29, %30, %31}, {%52, %53, %54, %55}, dx0, 0, 1, 1, 0;\n"
      "wgmma.mma_async.sync.aligned.m64n32k16.f32.bf16.bf16 {%16, %17, %18, %19, %20, %21, %22, %23, %24, %25, %26, %27, %28, %29, %30, %31}, {%56, %57, %58, %59}, dx1, 1, 1, 1, 0;\n"
      "wgmma.mma_async.sync.aligned.m64n32k16.f32.bf16.bf16 {%16, %17, %18, %19, %20, %21, %22, %23, %24, %25, %26, %27, %28, %29, %30, %31}, {%60, %61, %62, %63}, dx2, 1, 1, 1, 0;\n"
      "wgmma.mma_async.sync.aligned.m64n32k16.f32.bf16.bf16 {%16, %17, %18, %19, %20, %21, %22, %23, %24, %25, %26, %27, %28, %29, %30, %31}, {%64, %65, %66, %67}, dx3, 1, 1, 1, 0;\n"
      "wgmma.commit_group.sync.aligned;\n}\n"
      : "=f"(g[0]), "=f"(g[1]), "=f"(g[2]), "=f"(g[3]), "=f"(g[4]), "=f"(g[5]), "=f"(g[6]), "=f"(g[7]), "=f"(g[8]), "=f"(g[9]), "=f"(g[10]), "=f"(g[11]), "=f"(g[12]), "=f"(g[13]), "=f"(g[14]), "=f"(g[15]),
        "=f"(h[0]), "=f"(h[1]), "=f"(h[2]), "=f"(h[3]), "=f"(h[4]), "=f"(h[5]), "=f"(h[6]), "=f"(h[7]), "=f"(h[8]), "=f"(h[9]), "=f"(h[10]), "=f"(h[11]), "=f"(h[12]), "=f"(h[13]), "=f"(h[14]), "=f"(h[15])
      : "r"(w[0]), "r"(w[1]), "r"(w[2]), "r"(w[3]), "r"(w[4]), "r"(w[5]), "r"(w[6]), "r"(w[7]), "r"(w[8]), "r"(w[9]), "r"(w[10]), "r"(w[11]), "r"(w[12]), "r"(w[13]), "r"(w[14]), "r"(w[15]), "r"(w[16]), "r"(w[17]), "r"(w[18]), "r"(w[19]), "r"(w[20]), "r"(w[21]), "r"(w[22]), "r"(w[23]), "r"(w[24]), "r"(w[25]), "r"(w[26]), "r"(w[27]), "r"(w[28]), "r"(w[29]), "r"(w[30]), "r"(w[31]), "r"(w[32]), "r"(w[33]), "r"(w[34]), "r"(w[35]), "r"(w[36]), "r"(w[37]), "r"(w[38]), "r"(w[39]), "r"(dx), "l"(de), "l"(dh)
      : "memory");
  }
  static __device__ __forceinline__ void wait_g(float* g) {
    asm volatile("wgmma.wait_group.sync.aligned 1;\n"
      : "+f"(g[0]), "+f"(g[1]), "+f"(g[2]), "+f"(g[3]), "+f"(g[4]), "+f"(g[5]), "+f"(g[6]), "+f"(g[7]), "+f"(g[8]), "+f"(g[9]), "+f"(g[10]), "+f"(g[11]), "+f"(g[12]), "+f"(g[13]), "+f"(g[14]), "+f"(g[15])
      :: "memory");
  }
  static __device__ __forceinline__ void wait_h(float* h) {
    asm volatile("wgmma.wait_group.sync.aligned 0;\n"
      : "+f"(h[0]), "+f"(h[1]), "+f"(h[2]), "+f"(h[3]), "+f"(h[4]), "+f"(h[5]), "+f"(h[6]), "+f"(h[7]), "+f"(h[8]), "+f"(h[9]), "+f"(h[10]), "+f"(h[11]), "+f"(h[12]), "+f"(h[13]), "+f"(h[14]), "+f"(h[15])
      :: "memory");
  }
};
template<> struct TileMMA<5> {
  static __device__ __forceinline__ void issue(float* g, float* h, const uint32_t* w, uint32_t dx, uint64_t de, uint64_t dh, uint64_t dc) {
    asm volatile(
      "{\n.reg .b64 dx0, dx1, dx2, dx3;\n.reg .b32 l1, l2, l3, hx;\nmov.b32 hx, 0x40000040;\n"
      "add.u32 l1, %80, 2;\nadd.u32 l2, %80, 4;\nadd.u32 l3, %80, 6;\n"
      "mov.b64 dx0, {%80, hx};\nmov.b64 dx1, {l1, hx};\nmov.b64 dx2, {l2, hx};\nmov.b64 dx3, {l3, hx};\n"
      "wgmma.fence.sync.aligned;\n"
      "wgmma.mma_async.sync.aligned.m64n40k16.f32.bf16.bf16 {%0, %1, %2, %3, %4, %5, %6, %7, %8, %9, %10, %11, %12, %13, %14, %15, %16, %17, %18, %19}, {%76, %77, %78, %79}, %82, 0, 1, 1, 0;\n"
      "wgmma.mma_async.sync.aligned.m64n40k16.f32.bf16.bf16 {%0, %1, %2, %3, %4, %5, %6, %7, %8, %9, %10, %11, %12, %13, %14, %15, %16, %17, %18, %19}, {%56, %57, %58, %59}, %81, 1, 1, 1, 0;\n"
      "wgmma.mma_async.sync.aligned.m64n40k16.f32.bf16.bf16 {%0, %1, %2, %3, %4, %5, %6, %7, %8, %9, %10, %11, %12, %13, %14, %15, %16, %17, %18, %19}, {%40, %41, %42, %43}, dx0, 1, 1, 1, 0;\n"
      "wgmma.mma_async.sync.aligned.m64n40k16.f32.bf16.bf16 {%0, %1, %2, %3, %4, %5, %6, %7, %8, %9, %10, %11, %12, %13, %14, %15, %16, %17, %18, %19}, {%44, %45, %46, %47}, dx1, 1, 1, 1, 0;\n"
      "wgmma.mma_async.sync.aligned.m64n40k16.f32.bf16.bf16 {%0, %1, %2, %3, %4, %5, %6, %7, %8, %9, %10, %11, %12, %13, %14, %15, %16, %17, %18, %19}, {%48, %49, %50, %51}, dx2, 1, 1, 1, 0;\n"
      "wgmma.mma_async.sync.aligned.m64n40k16.f32.bf16.bf16 {%0, %1, %2, %3, %4, %5, %6, %7, %8, %9, %10, %11, %12, %13, %14, %15, %16, %17, %18, %19}, {%52, %53, %54, %55}, dx3, 1, 1, 1, 0;\n"
      "wgmma.commit_group.sync.aligned;\n"
      "wgmma.mma_async.sync.aligned.m64n40k16.f32.bf16.bf16 {%20, %21, %22, %23, %24, %25, %26, %27, %28, %29, %30, %31, %32, %33, %34, %35, %36, %37, %38, %39}, {%60, %61, %62, %63}, dx0, 0, 1, 1, 0;\n"
      "wgmma.mma_async.sync.aligned.m64n40k16.f32.bf16.bf16 {%20, %21, %22, %23, %24, %25, %26, %27, %28, %29, %30, %31, %32, %33, %34, %35, %36, %37, %38, %39}, {%64, %65, %66, %67}, dx1, 1, 1, 1, 0;\n"
      "wgmma.mma_async.sync.aligned.m64n40k16.f32.bf16.bf16 {%20, %21, %22, %23, %24, %25, %26, %27, %28, %29, %30, %31, %32, %33, %34, %35, %36, %37, %38, %39}, {%68, %69, %70, %71}, dx2, 1, 1, 1, 0;\n"
      "wgmma.mma_async.sync.aligned.m64n40k16.f32.bf16.bf16 {%20, %21, %22, %23, %24, %25, %26, %27, %28, %29, %30, %31, %32, %33, %34, %35, %36, %37, %38, %39}, {%72, %73, %74, %75}, dx3, 1, 1, 1, 0;\n"
      "wgmma.commit_group.sync.aligned;\n}\n"
      : "=f"(g[0]), "=f"(g[1]), "=f"(g[2]), "=f"(g[3]), "=f"(g[4]), "=f"(g[5]), "=f"(g[6]), "=f"(g[7]), "=f"(g[8]), "=f"(g[9]), "=f"(g[10]), "=f"(g[11]), "=f"(g[12]), "=f"(g[13]), "=f"(g[14]), "=f"(g[15]), "=f"(g[16]), "=f"(g[17]), "=f"(g[18]), "=f"(g[19]),
        "=f"(h[0]), "=f"(h[1]), "=f"(h[2]), "=f"(h[3]), "=f"(h[4]), "=f"(h[5]), "=f"(h[6]), "=f"(h[7]), "=f"(h[8]), "=f"(h[9]), "=f"(h[10]), "=f"(h[11]), "=f"(h[12]), "=f"(h[13]), "=f"(h[14]), "=f"(h[15]), "=f"(h[16]), "=f"(h[17]), "=f"(h[18]), "=f"(h[19])
      : "r"(w[0]), "r"(w[1]), "r"(w[2]), "r"(w[3]), "r"(w[4]), "r"(w[5]), "r"(w[6]), "r"(w[7]), "r"(w[8]), "r"(w[9]), "r"(w[10]), "r"(w[11]), "r"(w[12]), "r"(w[13]), "r"(w[14]), "r"(w[15]), "r"(w[16]), "r"(w[17]), "r"(w[18]), "r"(w[19]), "r"(w[20]), "r"(w[21]), "r"(w[22]), "r"(w[23]), "r"(w[24]), "r"(w[25]), "r"(w[26]), "r"(w[27]), "r"(w[28]), "r"(w[29]), "r"(w[30]), "r"(w[31]), "r"(w[32]), "r"(w[33]), "r"(w[34]), "r"(w[35]), "r"(w[36]), "r"(w[37]), "r"(w[38]), "r"(w[39]), "r"(dx), "l"(de), "l"(dh)
      : "memory");
  }
  static __device__ __forceinline__ void wait_g(float* g) {
    asm volatile("wgmma.wait_group.sync.aligned 1;\n"
      : "+f"(g[0]), "+f"(g[1]), "+f"(g[2]), "+f"(g[3]), "+f"(g[4]), "+f"(g[5]), "+f"(g[6]), "+f"(g[7]), "+f"(g[8]), "+f"(g[9]), "+f"(g[10]), "+f"(g[11]), "+f"(g[12]), "+f"(g[13]), "+f"(g[14]), "+f"(g[15]), "+f"(g[16]), "+f"(g[17]), "+f"(g[18]), "+f"(g[19])
      :: "memory");
  }
  static __device__ __forceinline__ void wait_h(float* h) {
    asm volatile("wgmma.wait_group.sync.aligned 0;\n"
      : "+f"(h[0]), "+f"(h[1]), "+f"(h[2]), "+f"(h[3]), "+f"(h[4]), "+f"(h[5]), "+f"(h[6]), "+f"(h[7]), "+f"(h[8]), "+f"(h[9]), "+f"(h[10]), "+f"(h[11]), "+f"(h[12]), "+f"(h[13]), "+f"(h[14]), "+f"(h[15]), "+f"(h[16]), "+f"(h[17]), "+f"(h[18]), "+f"(h[19])
      :: "memory");
  }
};
template<> struct TileMMA<6> {
  static __device__ __forceinline__ void issue(float* g, float* h, const uint32_t* w, uint32_t dx, uint64_t de, uint64_t dh, uint64_t dc) {
    asm volatile(
      "{\n.reg .b64 dx0, dx1, dx2, dx3;\n.reg .b32 l1, l2, l3, hx;\nmov.b32 hx, 0x40000040;\n"
      "add.u32 l1, %88, 2;\nadd.u32 l2, %88, 4;\nadd.u32 l3, %88, 6;\n"
      "mov.b64 dx0, {%88, hx};\nmov.b64 dx1, {l1, hx};\nmov.b64 dx2, {l2, hx};\nmov.b64 dx3, {l3, hx};\n"
      "wgmma.fence.sync.aligned;\n"
      "wgmma.mma_async.sync.aligned.m64n48k16.f32.bf16.bf16 {%0, %1, %2, %3, %4, %5, %6, %7, %8, %9, %10, %11, %12, %13, %14, %15, %16, %17, %18, %19, %20, %21, %22, %23}, {%84, %85, %86, %87}, %90, 0, 1, 1, 0;\n"
      "wgmma.mma_async.sync.aligned.m64n48k16.f32.bf16.bf16 {%0, %1, %2, %3, %4, %5, %6, %7, %8, %9, %10, %11, %12, %13, %14, %15, %16, %17, %18, %19, %20, %21, %22, %23}, {%64, %65, %66, %67}, %89, 1, 1, 1, 0;\n"
      "wgmma.mma_async.sync.aligned.m64n48k16.f32.bf16.bf16 {%0, %1, %2, %3, %4, %5, %6, %7, %8, %9, %10, %11, %12, %13, %14, %15, %16, %17, %18, %19, %20, %21, %22, %23}, {%48, %49, %50, %51}, dx0, 1, 1, 1, 0;\n"
      "wgmma.mma_async.sync.aligned.m64n48k16.f32.bf16.bf16 {%0, %1, %2, %3, %4, %5, %6, %7, %8, %9, %10, %11, %12, %13, %14, %15, %16, %17, %18, %19, %20, %21, %22, %23}, {%52, %53, %54, %55}, dx1, 1, 1, 1, 0;\n"
      "wgmma.mma_async.sync.aligned.m64n48k16.f32.bf16.bf16 {%0, %1, %2, %3, %4, %5, %6, %7, %8, %9, %10, %11, %12, %13, %14, %15, %16, %17, %18, %19, %20, %21, %22, %23}, {%56, %57, %58, %59}, dx2, 1, 1, 1, 0;\n"
      "wgmma.mma_async.sync.aligned.m64n48k16.f32.bf16.bf16 {%0, %1, %2, %3, %4, %5, %6, %7, %8, %9, %10, %11, %12, %13, %14, %15, %16, %17, %18, %19, %20, %21, %22, %23}, {%60, %61, %62, %63}, dx3, 1, 1, 1, 0;\n"
      "wgmma.commit_group.sync.aligned;\n"
      "wgmma.mma_async.sync.aligned.m64n48k16.f32.bf16.bf16 {%24, %25, %26, %27, %28, %29, %30, %31, %32, %33, %34, %35, %36, %37, %38, %39, %40, %41, %42, %43, %44, %45, %46, %47}, {%68, %69, %70, %71}, dx0, 0, 1, 1, 0;\n"
      "wgmma.mma_async.sync.aligned.m64n48k16.f32.bf16.bf16 {%24, %25, %26, %27, %28, %29, %30, %31, %32, %33, %34, %35, %36, %37, %38, %39, %40, %41, %42, %43, %44, %45, %46, %47}, {%72, %73, %74, %75}, dx1, 1, 1, 1, 0;\n"
      "wgmma.mma_async.sync.aligned.m64n48k16.f32.bf16.bf16 {%24, %25, %26, %27, %28, %29, %30, %31, %32, %33, %34, %35, %36, %37, %38, %39, %40, %41, %42, %43, %44, %45, %46, %47}, {%76, %77, %78, %79}, dx2, 1, 1, 1, 0;\n"
      "wgmma.mma_async.sync.aligned.m64n48k16.f32.bf16.bf16 {%24, %25, %26, %27, %28, %29, %30, %31, %32, %33, %34, %35, %36, %37, %38, %39, %40, %41, %42, %43, %44, %45, %46, %47}, {%80, %81, %82, %83}, dx3, 1, 1, 1, 0;\n"
      "wgmma.commit_group.sync.aligned;\n}\n"
      : "=f"(g[0]), "=f"(g[1]), "=f"(g[2]), "=f"(g[3]), "=f"(g[4]), "=f"(g[5]), "=f"(g[6]), "=f"(g[7]), "=f"(g[8]), "=f"(g[9]), "=f"(g[10]), "=f"(g[11]), "=f"(g[12]), "=f"(g[13]), "=f"(g[14]), "=f"(g[15]), "=f"(g[16]), "=f"(g[17]), "=f"(g[18]), "=f"(g[19]), "=f"(g[20]), "=f"(g[21]), "=f"(g[22]), "=f"(g[23]),
        "=f"(h[0]), "=f"(h[1]), "=f"(h[2]), "=f"(h[3]), "=f"(h[4]), "=f"(h[5]), "=f"(h[6]), "=f"(h[7]), "=f"(h[8]), "=f"(h[9]), "=f"(h[10]), "=f"(h[11]), "=f"(h[12]), "=f"(h[13]), "=f"(h[14]), "=f"(h[15]), "=f"(h[16]), "=f"(h[17]), "=f"(h[18]), "=f"(h[19]), "=f"(h[20]), "=f"(h[21]), "=f"(h[22]), "=f"(h[23])
      : "r"(w[0]), "r"(w[1]), "r"(w[2]), "r"(w[3]), "r"(w[4]), "r"(w[5]), "r"(w[6]), "r"(w[7]), "r"(w[8]), "r"(w[9]), "r"(w[10]), "r"(w[11]), "r"(w[12]), "r"(w[13]), "r"(w[14]), "r"(w[15]), "r"(w[16]), "r"(w[17]), "r"(w[18]), "r"(w[19]), "r"(w[20]), "r"(w[21]), "r"(w[22]), "r"(w[23]), "r"(w[24]), "r"(w[25]), "r"(w[26]), "r"(w[27]), "r"(w[28]), "r"(w[29]), "r"(w[30]), "r"(w[31]), "r"(w[32]), "r"(w[33]), "r"(w[34]), "r"(w[35]), "r"(w[36]), "r"(w[37]), "r"(w[38]), "r"(w[39]), "r"(dx), "l"(de), "l"(dh)
      : "memory");
  }
  static __device__ __forceinline__ void wait_g(float* g) {
    asm volatile("wgmma.wait_group.sync.aligned 1;\n"
      : "+f"(g[0]), "+f"(g[1]), "+f"(g[2]), "+f"(g[3]), "+f"(g[4]), "+f"(g[5]), "+f"(g[6]), "+f"(g[7]), "+f"(g[8]), "+f"(g[9]), "+f"(g[10]), "+f"(g[11]), "+f"(g[12]), "+f"(g[13]), "+f"(g[14]), "+f"(g[15]), "+f"(g[16]), "+f"(g[17]), "+f"(g[18]), "+f"(g[19]), "+f"(g[20]), "+f"(g[21]), "+f"(g[22]), "+f"(g[23])
      :: "memory");
  }
  static __device__ __forceinline__ void wait_h(float* h) {
    asm volatile("wgmma.wait_group.sync.aligned 0;\n"
      : "+f"(h[0]), "+f"(h[1]), "+f"(h[2]), "+f"(h[3]), "+f"(h[4]), "+f"(h[5]), "+f"(h[6]), "+f"(h[7]), "+f"(h[8]), "+f"(h[9]), "+f"(h[10]), "+f"(h[11]), "+f"(h[12]), "+f"(h[13]), "+f"(h[14]), "+f"(h[15]), "+f"(h[16]), "+f"(h[17]), "+f"(h[18]), "+f"(h[19]), "+f"(h[20]), "+f"(h[21]), "+f"(h[22]), "+f"(h[23])
      :: "memory");
  }
};
template<> struct TileMMA<7> {
  static __device__ __forceinline__ void issue(float* g, float* h, const uint32_t* w, uint32_t dx, uint64_t de, uint64_t dh, uint64_t dc) {
    asm volatile(
      "{\n.reg .b64 dx0, dx1, dx2, dx3;\n.reg .b32 l1, l2, l3, hx;\nmov.b32 hx, 0x40000040;\n"
      "add.u32 l1, %96, 2;\nadd.u32 l2, %96, 4;\nadd.u32 l3, %96, 6;\n"
      "mov.b64 dx0, {%96, hx};\nmov.b64 dx1, {l1, hx};\nmov.b64 dx2, {l2, hx};\nmov.b64 dx3, {l3, hx};\n"
      "wgmma.fence.sync.aligned;\n"
      "wgmma.mma_async.sync.aligned.m64n56k16.f32.bf16.bf16 {%0, %1, %2, %3, %4, %5, %6, %7, %8, %9, %10, %11, %12, %13, %14, %15, %16, %17, %18, %19, %20, %21, %22, %23, %24, %25, %26, %27}, {%92, %93, %94, %95}, %98, 0, 1, 1, 0;\n"
      "wgmma.mma_async.sync.aligned.m64n56k16.f32.bf16.bf16 {%0, %1, %2, %3, %4, %5, %6, %7, %8, %9, %10, %11, %12, %13, %14, %15, %16, %17, %18, %19, %20, %21, %22, %23, %24, %25, %26, %27}, {%72, %73, %74, %75}, %97, 1, 1, 1, 0;\n"
      "wgmma.mma_async.sync.aligned.m64n56k16.f32.bf16.bf16 {%0, %1, %2, %3, %4, %5, %6, %7, %8, %9, %10, %11, %12, %13, %14, %15, %16, %17, %18, %19, %20, %21, %22, %23, %24, %25, %26, %27}, {%56, %57, %58, %59}, dx0, 1, 1, 1, 0;\n"
      "wgmma.mma_async.sync.aligned.m64n56k16.f32.bf16.bf16 {%0, %1, %2, %3, %4, %5, %6, %7, %8, %9, %10, %11, %12, %13, %14, %15, %16, %17, %18, %19, %20, %21, %22, %23, %24, %25, %26, %27}, {%60, %61, %62, %63}, dx1, 1, 1, 1, 0;\n"
      "wgmma.mma_async.sync.aligned.m64n56k16.f32.bf16.bf16 {%0, %1, %2, %3, %4, %5, %6, %7, %8, %9, %10, %11, %12, %13, %14, %15, %16, %17, %18, %19, %20, %21, %22, %23, %24, %25, %26, %27}, {%64, %65, %66, %67}, dx2, 1, 1, 1, 0;\n"
      "wgmma.mma_async.sync.aligned.m64n56k16.f32.bf16.bf16 {%0, %1, %2, %3, %4, %5, %6, %7, %8, %9, %10, %11, %12, %13, %14, %15, %16, %17, %18, %19, %20, %21, %22, %23, %24, %25, %26, %27}, {%68, %69, %70, %71}, dx3, 1, 1, 1, 0;\n"
      "wgmma.commit_group.sync.aligned;\n"
      "wgmma.mma_async.sync.aligned.m64n56k16.f32.bf16.bf16 {%28, %29, %30, %31, %32, %33, %34, %35, %36, %37, %38, %39, %40, %41, %42, %43, %44, %45, %46, %47, %48, %49, %50, %51, %52, %53, %54, %55}, {%76, %77, %78, %79}, dx0, 0, 1, 1, 0;\n"
      "wgmma.mma_async.sync.aligned.m64n56k16.f32.bf16.bf16 {%28, %29, %30, %31, %32, %33, %34, %35, %36, %37, %38, %39, %40, %41, %42, %43, %44, %45, %46, %47, %48, %49, %50, %51, %52, %53, %54, %55}, {%80, %81, %82, %83}, dx1, 1, 1, 1, 0;\n"
      "wgmma.mma_async.sync.aligned.m64n56k16.f32.bf16.bf16 {%28, %29, %30, %31, %32, %33, %34, %35, %36, %37, %38, %39, %40, %41, %42, %43, %44, %45, %46, %47, %48, %49, %50, %51, %52, %53, %54, %55}, {%84, %85, %86, %87}, dx2, 1, 1, 1, 0;\n"
      "wgmma.mma_async.sync.aligned.m64n56k16.f32.bf16.bf16 {%28, %29, %30, %31, %32, %33, %34, %35, %36, %37, %38, %39, %40, %41, %42, %43, %44, %45, %46, %47, %48, %49, %50, %51, %52, %53, %54, %55}, {%88, %89, %90, %91}, dx3, 1, 1, 1, 0;\n"
      "wgmma.commit_group.sync.aligned;\n}\n"
      : "=f"(g[0]), "=f"(g[1]), "=f"(g[2]), "=f"(g[3]), "=f"(g[4]), "=f"(g[5]), "=f"(g[6]), "=f"(g[7]), "=f"(g[8]), "=f"(g[9]), "=f"(g[10]), "=f"(g[11]), "=f"(g[12]), "=f"(g[13]), "=f"(g[14]), "=f"(g[15]), "=f"(g[16]), "=f"(g[17]), "=f"(g[18]), "=f"(g[19]), "=f"(g[20]), "=f"(g[21]), "=f"(g[22]), "=f"(g[23]), "=f"(g[24]), "=f"(g[25]), "=f"(g[26]), "=f"(g[27]),
        "=f"(h[0]), "=f"(h[1]), "=f"(h[2]), "=f"(h[3]), "=f"(h[4]), "=f"(h[5]), "=f"(h[6]), "=f"(h[7]), "=f"(h[8]), "=f"(h[9]), "=f"(h[10]), "=f"(h[11]), "=f"(h[12]), "=f"(h[13]), "=f"(h[14]), "=f"(h[15]), "=f"(h[16]), "=f"(h[17]), "=f"(h[18]), "=f"(h[19]), "=f"(h[20]), "=f"(h[21]), "=f"(h[22]), "=f"(h[23]), "=f"(h[24]), "=f"(h[25]), "=f"(h[26]), "=f"(h[27])
      : "r"(w[0]), "r"(w[1]), "r"(w[2]), "r"(w[3]), "r"(w[4]), "r"(w[5]), "r"(w[6]), "r"(w[7]), "r"(w[8]), "r"(w[9]), "r"(w[10]), "r"(w[11]), "r"(w[12]), "r"(w[13]), "r"(w[14]), "r"(w[15]), "r"(w[16]), "r"(w[17]), "r"(w[18]), "r"(w[19]), "r"(w[20]), "r"(w[21]), "r"(w[22]), "r"(w[23]), "r"(w[24]), "r"(w[25]), "r"(w[26]), "r"(w[27]), "r"(w[28]), "r"(w[29]), "r"(w[30]), "r"(w[31]), "r"(w[32]), "r"(w[33]), "r"(w[34]), "r"(w[35]), "r"(w[36]), "r"(w[37]), "r"(w[38]), "r"(w[39]), "r"(dx), "l"(de), "l"(dh)
      : "memory");
  }
  static __device__ __forceinline__ void wait_g(float* g) {
    asm volatile("wgmma.wait_group.sync.aligned 1;\n"
      : "+f"(g[0]), "+f"(g[1]), "+f"(g[2]), "+f"(g[3]), "+f"(g[4]), "+f"(g[5]), "+f"(g[6]), "+f"(g[7]), "+f"(g[8]), "+f"(g[9]), "+f"(g[10]), "+f"(g[11]), "+f"(g[12]), "+f"(g[13]), "+f"(g[14]), "+f"(g[15]), "+f"(g[16]), "+f"(g[17]), "+f"(g[18]), "+f"(g[19]), "+f"(g[20]), "+f"(g[21]), "+f"(g[22]), "+f"(g[23]), "+f"(g[24]), "+f"(g[25]), "+f"(g[26]), "+f"(g[27])
      :: "memory");
  }
  static __device__ __forceinline__ void wait_h(float* h) {
    asm volatile("wgmma.wait_group.sync.aligned 0;\n"
      : "+f"(h[0]), "+f"(h[1]), "+f"(h[2]), "+f"(h[3]), "+f"(h[4]), "+f"(h[5]), "+f"(h[6]), "+f"(h[7]), "+f"(h[8]), "+f"(h[9]), "+f"(h[10]), "+f"(h[11]), "+f"(h[12]), "+f"(h[13]), "+f"(h[14]), "+f"(h[15]), "+f"(h[16]), "+f"(h[17]), "+f"(h[18]), "+f"(h[19]), "+f"(h[20]), "+f"(h[21]), "+f"(h[22]), "+f"(h[23]), "+f"(h[24]), "+f"(h[25]), "+f"(h[26]), "+f"(h[27])
      :: "memory");
  }
};
template<> struct TileMMA<8> {
  static __device__ __forceinline__ void issue(float* g, float* h, const uint32_t* w, uint32_t dx, uint64_t de, uint64_t dh, uint64_t dc) {
    asm volatile(
      "{\n.reg .b64 dx0, dx1, dx2, dx3;\n.reg .b32 l1, l2, l3, hx;\nmov.b32 hx, 0x40000040;\n"
      "add.u32 l1, %104, 2;\nadd.u32 l2, %104, 4;\nadd.u32 l3, %104, 6;\n"
      "mov.b64 dx0, {%104, hx};\nmov.b64 dx1, {l1, hx};\nmov.b64 dx2, {l2, hx};\nmov.b64 dx3, {l3, hx};\n"
      "wgmma.fence.sync.aligned;\n"
      "wgmma.mma_async.sync.aligned.m64n64k16.f32.bf16.bf16 {%0, %1, %2, %3, %4, %5, %6, %7, %8, %9, %10, %11, %12, %13, %14, %15, %16, %17, %18, %19, %20, %21, %22, %23, %24, %25, %26, %27, %28, %29, %30, %31}, {%100, %101, %102, %103}, %106, 0, 1, 1, 0;\n"
      "wgmma.mma_async.sync.aligned.m64n64k16.f32.bf16.bf16 {%0, %1, %2, %3, %4, %5, %6, %7, %8, %9, %10, %11, %12, %13, %14, %15, %16, %17, %18, %19, %20, %21, %22, %23, %24, %25, %26, %27, %28, %29, %30, %31}, {%80, %81, %82, %83}, %105, 1, 1, 1, 0;\n"
      "wgmma.mma_async.sync.aligned.m64n64k16.f32.bf16.bf16 {%0, %1, %2, %3, %4, %5, %6, %7, %8, %9, %10, %11, %12, %13, %14, %15, %16, %17, %18, %19, %20, %21, %22, %23, %24, %25, %26, %27, %28, %29, %30, %31}, {%64, %65, %66, %67}, dx0, 1, 1, 1, 0;\n"
      "wgmma.mma_async.sync.aligned.m64n64k16.f32.bf16.bf16 {%0, %1, %2, %3, %4, %5, %6, %7, %8, %9, %10, %11, %12, %13, %14, %15, %16, %17, %18, %19, %20, %21, %22, %23, %24, %25, %26, %27, %28, %29, %30, %31}, {%68, %69, %70, %71}, dx1, 1, 1, 1, 0;\n"
      "wgmma.mma_async.sync.aligned.m64n64k16.f32.bf16.bf16 {%0, %1, %2, %3, %4, %5, %6, %7, %8, %9, %10, %11, %12, %13, %14, %15, %16, %17, %18, %19, %20, %21, %22, %23, %24, %25, %26, %27, %28, %29, %30, %31}, {%72, %73, %74, %75}, dx2, 1, 1, 1, 0;\n"
      "wgmma.mma_async.sync.aligned.m64n64k16.f32.bf16.bf16 {%0, %1, %2, %3, %4, %5, %6, %7, %8, %9, %10, %11, %12, %13, %14, %15, %16, %17, %18, %19, %20, %21, %22, %23, %24, %25, %26, %27, %28, %29, %30, %31}, {%76, %77, %78, %79}, dx3, 1, 1, 1, 0;\n"
      "wgmma.commit_group.sync.aligned;\n"
      "wgmma.mma_async.sync.aligned.m64n64k16.f32.bf16.bf16 {%32, %33, %34, %35, %36, %37, %38, %39, %40, %41, %42, %43, %44, %45, %46, %47, %48, %49, %50, %51, %52, %53, %54, %55, %56, %57, %58, %59, %60, %61, %62, %63}, {%84, %85, %86, %87}, dx0, 0, 1, 1, 0;\n"
      "wgmma.mma_async.sync.aligned.m64n64k16.f32.bf16.bf16 {%32, %33, %34, %35, %36, %37, %38, %39, %40, %41, %42, %43, %44, %45, %46, %47, %48, %49, %50, %51, %52, %53, %54, %55, %56, %57, %58, %59, %60, %61, %62, %63}, {%88, %89, %90, %91}, dx1, 1, 1, 1, 0;\n"
      "wgmma.mma_async.sync.aligned.m64n64k16.f32.bf16.bf16 {%32, %33, %34, %35, %36, %37, %38, %39, %40, %41, %42, %43, %44, %45, %46, %47, %48, %49, %50, %51, %52, %53, %54, %55, %56, %57, %58, %59, %60, %61, %62, %63}, {%92, %93, %94, %95}, dx2, 1, 1, 1, 0;\n"
      "wgmma.mma_async.sync.aligned.m64n64k16.f32.bf16.bf16 {%32, %33, %34, %35, %36, %37, %38, %39, %40, %41, %42, %43, %44, %45, %46, %47, %48, %49, %50, %51, %52, %53, %54, %55, %56, %57, %58, %59, %60, %61, %62, %63}, {%96, %97, %98, %99}, dx3, 1, 1, 1, 0;\n"
      "wgmma.commit_group.sync.aligned;\n}\n"
      : "=f"(g[0]), "=f"(g[1]), "=f"(g[2]), "=f"(g[3]), "=f"(g[4]), "=f"(g[5]), "=f"(g[6]), "=f"(g[7]), "=f"(g[8]), "=f"(g[9]), "=f"(g[10]), "=f"(g[11]), "=f"(g[12]), "=f"(g[13]), "=f"(g[14]), "=f"(g[15]), "=f"(g[16]), "=f"(g[17]), "=f"(g[18]), "=f"(g[19]), "=f"(g[20]), "=f"(g[21]), "=f"(g[22]), "=f"(g[23]), "=f"(g[24]), "=f"(g[25]), "=f"(g[26]), "=f"(g[27]), "=f"(g[28]), "=f"(g[29]), "=f"(g[30]), "=f"(g[31]),
        "=f"(h[0]), "=f"(h[1]), "=f"(h[2]), "=f"(h[3]), "=f"(h[4]), "=f"(h[5]), "=f"(h[6]), "=f"(h[7]), "=f"(h[8]), "=f"(h[9]), "=f"(h[10]), "=f"(h[11]), "=f"(h[12]), "=f"(h[13]), "=f"(h[14]), "=f"(h[15]), "=f"(h[16]), "=f"(h[17]), "=f"(h[18]), "=f"(h[19]), "=f"(h[20]), "=f"(h[21]), "=f"(h[22]), "=f"(h[23]), "=f"(h[24]), "=f"(h[25]), "=f"(h[26]), "=f"(h[27]), "=f"(h[28]), "=f"(h[29]), "=f"(h[30]), "=f"(h[31])
      : "r"(w[0]), "r"(w[1]), "r"(w[2]), "r"(w[3]), "r"(w[4]), "r"(w[5]), "r"(w[6]), "r"(w[7]), "r"(w[8]), "r"(w[9]), "r"(w[10]), "r"(w[11]), "r"(w[12]), "r"(w[13]), "r"(w[14]), "r"(w[15]), "r"(w[16]), "r"(w[17]), "r"(w[18]), "r"(w[19]), "r"(w[20]), "r"(w[21]), "r"(w[22]), "r"(w[23]), "r"(w[24]), "r"(w[25]), "r"(w[26]), "r"(w[27]), "r"(w[28]), "r"(w[29]), "r"(w[30]), "r"(w[31]), "r"(w[32]), "r"(w[33]), "r"(w[34]), "r"(w[35]), "r"(w[36]), "r"(w[37]), "r"(w[38]), "r"(w[39]), "r"(dx), "l"(de), "l"(dh)
      : "memory");
  }
  static __device__ __forceinline__ void wait_g(float* g) {
    asm volatile("wgmma.wait_group.sync.aligned 1;\n"
      : "+f"(g[0]), "+f"(g[1]), "+f"(g[2]), "+f"(g[3]), "+f"(g[4]), "+f"(g[5]), "+f"(g[6]), "+f"(g[7]), "+f"(g[8]), "+f"(g[9]), "+f"(g[10]), "+f"(g[11]), "+f"(g[12]), "+f"(g[13]), "+f"(g[14]), "+f"(g[15]), "+f"(g[16]), "+f"(g[17]), "+f"(g[18]), "+f"(g[19]), "+f"(g[20]), "+f"(g[21]), "+f"(g[22]), "+f"(g[23]), "+f"(g[24]), "+f"(g[25]), "+f"(g[26]), "+f"(g[27]), "+f"(g[28]), "+f"(g[29]), "+f"(g[30]), "+f"(g[31])
      :: "memory");
  }
  static __device__ __forceinline__ void wait_h(float* h) {
    asm volatile("wgmma.wait_group.sync.aligned 0;\n"
      : "+f"(h[0]), "+f"(h[1]), "+f"(h[2]), "+f"(h[3]), "+f"(h[4]), "+f"(h[5]), "+f"(h[6]), "+f"(h[7]), "+f"(h[8]), "+f"(h[9]), "+f"(h[10]), "+f"(h[11]), "+f"(h[12]), "+f"(h[13]), "+f"(h[14]), "+f"(h[15]), "+f"(h[16]), "+f"(h[17]), "+f"(h[18]), "+f"(h[19]), "+f"(h[20]), "+f"(h[21]), "+f"(h[22]), "+f"(h[23]), "+f"(h[24]), "+f"(h[25]), "+f"(h[26]), "+f"(h[27]), "+f"(h[28]), "+f"(h[29]), "+f"(h[30]), "+f"(h[31])
      :: "memory");
  }
};
template<> struct TileMMA<9> {
  static __device__ __forceinline__ void issue(float* g, float* h, const uint32_t* w, uint32_t dx, uint64_t de, uint64_t dh, uint64_t dc) {
    asm volatile(
      "{\n.reg .b64 dx0, dx1, dx2, dx3;\n.reg .b32 l1, l2, l3, hx;\nmov.b32 hx, 0x40000040;\n"
      "add.u32 l1, %112, 2;\nadd.u32 l2, %112, 4;\nadd.u32 l3, %112, 6;\n"
      "mov.b64 dx0, {%112, hx};\nmov.b64 dx1, {l1, hx};\nmov.b64 dx2, {l2, hx};\nmov.b64 dx3, {l3, hx};\n"
      "wgmma.fence.sync.aligned;\n"
      "wgmma.mma_async.sync.aligned.m64n72k16.f32.bf16.bf16 {%0, %1, %2, %3, %4, %5, %6, %7, %8, %9, %10, %11, %12, %13, %14, %15, %16, %17, %18, %19, %20, %21, %22, %23, %24, %25, %26, %27, %28, %29, %30, %31, %32, %33, %34, %35}, {%108, %109, %110, %111}, %114, 0, 1, 1, 0;\n"
      "wgmma.mma_async.sync.aligned.m64n72k16.f32.bf16.bf16 {%0, %1, %2, %3, %4, %5, %6, %7, %8, %9, %10, %11, %12, %13, %14, %15, %16, %17, %18, %19, %20, %21, %22, %23, %24, %25, %26, %27, %28, %29, %30, %31, %32, %33, %34, %35}, {%88, %89, %90, %91}, %113, 1, 1, 1, 0;\n"
      "wgmma.mma_async.sync.aligned.m64n72k16.f32.bf16.bf16 {%0, %1, %2, %3, %4, %5, %6, %7, %8, %9, %10, %11, %12, %13, %14, %15, %16, %17, %18, %19, %20, %21, %22, %23, %24, %25, %26, %27, %28, %29, %30, %31, %32, %33, %34, %35}, {%72, %73, %74, %75}, dx0, 1, 1, 1, 0;\n"
      "wgmma.mma_async.sync.aligned.m64n72k16.f32.bf16.bf16 {%0, %1, %2, %3, %4, %5, %6, %7, %8, %9, %10, %11, %12, %13, %14, %15, %16, %17, %18, %19, %20, %21, %22, %23, %24, %25, %26, %27, %28, %29, %30, %31, %32, %33, %34, %35}, {%76, %77, %78, %79}, dx1, 1, 1, 1, 0;\n"
      "wgmma.mma_async.sync.aligned.m64n72k16.f32.bf16.bf16 {%0, %1, %2, %3, %4, %5, %6, %7, %8, %9, %10, %11, %12, %13, %14, %15, %16, %17, %18, %19, %20, %21, %22, %23, %24, %25, %26, %27, %28, %29, %30, %31, %32, %33, %34, %35}, {%80, %81, %82, %83}, dx2, 1, 1, 1, 0;\n"
      "wgmma.mma_async.sync.aligned.m64n72k16.f32.bf16.bf16 {%0, %1, %2, %3, %4, %5, %6, %7, %8, %9, %10, %11, %12, %13, %14, %15, %16, %17, %18, %19, %20, %21, %22, %23, %24, %25, %26, %27, %28, %29, %30, %31, %32, %33, %34, %35}, {%84, %85, %86, %87}, dx3, 1, 1, 1, 0;\n"
      "wgmma.commit_group.sync.aligned;\n"
      "wgmma.mma_async.sync.aligned.m64n72k16.f32.bf16.bf16 {%36, %37, %38, %39, %40, %41, %42, %43, %44, %45, %46, %47, %48, %49, %50, %51, %52, %53, %54, %55, %56, %57, %58, %59, %60, %61, %62, %63, %64, %65, %66, %67, %68, %69, %70, %71}, {%92, %93, %94, %95}, dx0, 0, 1, 1, 0;\n"
      "wgmma.mma_async.sync.aligned.m64n72k16.f32.bf16.bf16 {%36, %37, %38, %39, %40, %41, %42, %43, %44, %45, %46, %47, %48, %49, %50, %51, %52, %53, %54, %55, %56, %57, %58, %59, %60, %61, %62, %63, %64, %65, %66, %67, %68, %69, %70, %71}, {%96, %97, %98, %99}, dx1, 1, 1, 1, 0;\n"
      "wgmma.mma_async.sync.aligned.m64n72k16.f32.bf16.bf16 {%36, %37, %38, %39, %40, %41, %42, %43, %44, %45, %46, %47, %48, %49, %50, %51, %52, %53, %54, %55, %56, %57, %58, %59, %60, %61, %62, %63, %64, %65, %66, %67, %68, %69, %70, %71}, {%100, %101, %102, %103}, dx2, 1, 1, 1, 0;\n"
      "wgmma.mma_async.sync.aligned.m64n72k16.f32.bf16.bf16 {%36, %37, %38, %39, %40, %41, %42, %43, %44, %45, %46, %47, %48, %49, %50, %51, %52, %53, %54, %55, %56, %57, %58, %59, %60, %61, %62, %63, %64, %65, %66, %67, %68, %69, %70, %71}, {%104, %105, %106, %107}, dx3, 1, 1, 1, 0;\n"
      "wgmma.commit_group.sync.aligned;\n}\n"
      : "=f"(g[0]), "=f"(g[1]), "=f"(g[2]), "=f"(g[3]), "=f"(g[4]), "=f"(g[5]), "=f"(g[6]), "=f"(g[7]), "=f"(g[8]), "=f"(g[9]), "=f"(g[10]), "=f"(g[11]), "=f"(g[12]), "=f"(g[13]), "=f"(g[14]), "=f"(g[15]), "=f"(g[16]), "=f"(g[17]), "=f"(g[18]), "=f"(g[19]), "=f"(g[20]), "=f"(g[21]), "=f"(g[22]), "=f"(g[23]), "=f"(g[24]), "=f"(g[25]), "=f"(g[26]), "=f"(g[27]), "=f"(g[28]), "=f"(g[29]), "=f"(g[30]), "=f"(g[31]), "=f"(g[32]), "=f"(g[33]), "=f"(g[34]), "=f"(g[35]),
        "=f"(h[0]), "=f"(h[1]), "=f"(h[2]), "=f"(h[3]), "=f"(h[4]), "=f"(h[5]), "=f"(h[6]), "=f"(h[7]), "=f"(h[8]), "=f"(h[9]), "=f"(h[10]), "=f"(h[11]), "=f"(h[12]), "=f"(h[13]), "=f"(h[14]), "=f"(h[15]), "=f"(h[16]), "=f"(h[17]), "=f"(h[18]), "=f"(h[19]), "=f"(h[20]), "=f"(h[21]), "=f"(h[22]), "=f"(h[23]), "=f"(h[24]), "=f"(h[25]), "=f"(h[26]), "=f"(h[27]), "=f"(h[28]), "=f"(h[29]), "=f"(h[30]), "=f"(h[31]), "=f"(h[32]), "=f"(h[33]), "=f"(h[34]), "=f"(h[35])
      : "r"(w[0]), "r"(w[1]), "r"(w[2]), "r"(w[3]), "r"(w[4]), "r"(w[5]), "r"(w[6]), "r"(w[7]), "r"(w[8]), "r"(w[9]), "r"(w[10]), "r"(w[11]), "r"(w[12]), "r"(w[13]), "r"(w[14]), "r"(w[15]), "r"(w[16]), "r"(w[17]), "r"(w[18]), "r"(w[19]), "r"(w[20]), "r"(w[21]), "r"(w[22]), "r"(w[23]), "r"(w[24]), "r"(w[25]), "r"(w[26]), "r"(w[27]), "r"(w[28]), "r"(w[29]), "r"(w[30]), "r"(w[31]), "r"(w[32]), "r"(w[33]), "r"(w[34]), "r"(w[35]), "r"(w[36]), "r"(w[37]), "r"(w[38]), "r"(w[39]), "r"(dx), "l"(de), "l"(dh)
      : "memory");
  }
  static __device__ __forceinline__ void wait_g(float* g) {
    asm volatile("wgmma.wait_group.sync.aligned 1;\n"
      : "+f"(g[0]), "+f"(g[1]), "+f"(g[2]), "+f"(g[3]), "+f"(g[4]), "+f"(g[5]), "+f"(g[6]), "+f"(g[7]), "+f"(g[8]), "+f"(g[9]), "+f"(g[10]), "+f"(g[11]), "+f"(g[12]), "+f"(g[13]), "+f"(g[14]), "+f"(g[15]), "+f"(g[16]), "+f"(g[17]), "+f"(g[18]), "+f"(g[19]), "+f"(g[20]), "+f"(g[21]), "+f"(g[22]), "+f"(g[23]), "+f"(g[24]), "+f"(g[25]), "+f"(g[26]), "+f"(g[27]), "+f"(g[28]), "+f"(g[29]), "+f"(g[30]), "+f"(g[31]), "+f"(g[32]), "+f"(g[33]), "+f"(g[34]), "+f"(g[35])
      :: "memory");
  }
  static __device__ __forceinline__ void wait_h(float* h) {
    asm volatile("wgmma.wait_group.sync.aligned 0;\n"
      : "+f"(h[0]), "+f"(h[1]), "+f"(h[2]), "+f"(h[3]), "+f"(h[4]), "+f"(h[5]), "+f"(h[6]), "+f"(h[7]), "+f"(h[8]), "+f"(h[9]), "+f"(h[10]), "+f"(h[11]), "+f"(h[12]), "+f"(h[13]), "+f"(h[14]), "+f"(h[15]), "+f"(h[16]), "+f"(h[17]), "+f"(h[18]), "+f"(h[19]), "+f"(h[20]), "+f"(h[21]), "+f"(h[22]), "+f"(h[23]), "+f"(h[24]), "+f"(h[25]), "+f"(h[26]), "+f"(h[27]), "+f"(h[28]), "+f"(h[29]), "+f"(h[30]), "+f"(h[31]), "+f"(h[32]), "+f"(h[33]), "+f"(h[34]), "+f"(h[35])
      :: "memory");
  }
};
template<> struct TileMMA<10> {
  static __device__ __forceinline__ void issue(float* g, float* h, const uint32_t* w, uint32_t dx, uint64_t de, uint64_t dh, uint64_t dc) {
    asm volatile(
      "{\n.reg .b64 dx0, dx1, dx2, dx3;\n.reg .b32 l1, l2, l3, hx;\nmov.b32 hx, 0x40000040;\n"
      "add.u32 l1, %120, 2;\nadd.u32 l2, %120, 4;\nadd.u32 l3, %120, 6;\n"
      "mov.b64 dx0, {%120, hx};\nmov.b64 dx1, {l1, hx};\nmov.b64 dx2, {l2, hx};\nmov.b64 dx3, {l3, hx};\n"
      "wgmma.fence.sync.aligned;\n"
      "wgmma.mma_async.sync.aligned.m64n80k16.f32.bf16.bf16 {%0, %1, %2, %3, %4, %5, %6, %7, %8, %9, %10, %11, %12, %13, %14, %15, %16, %17, %18, %19, %20, %21, %22, %23, %24, %25, %26, %27, %28, %29, %30, %31, %32, %33, %34, %35, %36, %37, %38, %39}, {%116, %117, %118, %119}, %122, 0, 1, 1, 0;\n"
      "wgmma.mma_async.sync.aligned.m64n80k16.f32.bf16.bf16 {%0, %1, %2, %3, %4, %5, %6, %7, %8, %9, %10, %11, %12, %13, %14, %15, %16, %17, %18, %19, %20, %21, %22, %23, %24, %25, %26, %27, %28, %29, %30, %31, %32, %33, %34, %35, %36, %37, %38, %39}, {%96, %97, %98, %99}, %121, 1, 1, 1, 0;\n"
      "wgmma.mma_async.sync.aligned.m64n80k16.f32.bf16.bf16 {%0, %1, %2, %3, %4, %5, %6, %7, %8, %9, %10, %11, %12, %13, %14, %15, %16, %17, %18, %19, %20, %21, %22, %23, %24, %25, %26, %27, %28, %29, %30, %31, %32, %33, %34, %35, %36, %37, %38, %39}, {%80, %81, %82, %83}, dx0, 1, 1, 1, 0;\n"
      "wgmma.mma_async.sync.aligned.m64n80k16.f32.bf16.bf16 {%0, %1, %2, %3, %4, %5, %6, %7, %8, %9, %10, %11, %12, %13, %14, %15, %16, %17, %18, %19, %20, %21, %22, %23, %24, %25, %26, %27, %28, %29, %30, %31, %32, %33, %34, %35, %36, %37, %38, %39}, {%84, %85, %86, %87}, dx1, 1, 1, 1, 0;\n"
      "wgmma.mma_async.sync.aligned.m64n80k16.f32.bf16.bf16 {%0, %1, %2, %3, %4, %5, %6, %7, %8, %9, %10, %11, %12, %13, %14, %15, %16, %17, %18, %19, %20, %21, %22, %23, %24, %25, %26, %27, %28, %29, %30, %31, %32, %33, %34, %35, %36, %37, %38, %39}, {%88, %89, %90, %91}, dx2, 1, 1, 1, 0;\n"
      "wgmma.mma_async.sync.aligned.m64n80k16.f32.bf16.bf16 {%0, %1, %2, %3, %4, %5, %6, %7, %8, %9, %10, %11, %12, %13, %14, %15, %16, %17, %18, %19, %20, %21, %22, %23, %24, %25, %26, %27, %28, %29, %30, %31, %32, %33, %34, %35, %36, %37, %38, %39}, {%92, %93, %94, %95}, dx3, 1, 1, 1, 0;\n"
      "wgmma.commit_group.sync.aligned;\n"
      "wgmma.mma_async.sync.aligned.m64n80k16.f32.bf16.bf16 {%40, %41, %42, %43, %44, %45, %46, %47, %48, %49, %50, %51, %52, %53, %54, %55, %56, %57, %58, %59, %60, %61, %62, %63, %64, %65, %66, %67, %68, %69, %70, %71, %72, %73, %74, %75, %76, %77, %78, %79}, {%100, %101, %102, %103}, dx0, 0, 1, 1, 0;\n"
      "wgmma.mma_async.sync.aligned.m64n80k16.f32.bf16.bf16 {%40, %41, %42, %43, %44, %45, %46, %47, %48, %49, %50, %51, %52, %53, %54, %55, %56, %57, %58, %59, %60, %61, %62, %63, %64, %65, %66, %67, %68, %69, %70, %71, %72, %73, %74, %75, %76, %77, %78, %79}, {%104, %105, %106, %107}, dx1, 1, 1, 1, 0;\n"
      "wgmma.mma_async.sync.aligned.m64n80k16.f32.bf16.bf16 {%40, %41, %42, %43, %44, %45, %46, %47, %48, %49, %50, %51, %52, %53, %54, %55, %56, %57, %58, %59, %60, %61, %62, %63, %64, %65, %66, %67, %68, %69, %70, %71, %72, %73, %74, %75, %76, %77, %78, %79}, {%108, %109, %110, %111}, dx2, 1, 1, 1, 0;\n"
      "wgmma.mma_async.sync.aligned.m64n80k16.f32.bf16.bf16 {%40, %41, %42, %43, %44, %45, %46, %47, %48, %49, %50, %51, %52, %53, %54, %55, %56, %57, %58, %59, %60, %61, %62, %63, %64, %65, %66, %67, %68, %69, %70, %71, %72, %73, %74, %75, %76, %77, %78, %79}, {%112, %113, %114, %115}, dx3, 1, 1, 1, 0;\n"
      "wgmma.commit_group.sync.aligned;\n}\n"
      : "=f"(g[0]), "=f"(g[1]), "=f"(g[2]), "=f"(g[3]), "=f"(g[4]), "=f"(g[5]), "=f"(g[6]), "=f"(g[7]), "=f"(g[8]), "=f"(g[9]), "=f"(g[10]), "=f"(g[11]), "=f"(g[12]), "=f"(g[13]), "=f"(g[14]), "=f"(g[15]), "=f"(g[16]), "=f"(g[17]), "=f"(g[18]), "=f"(g[19]), "=f"(g[20]), "=f"(g[21]), "=f"(g[22]), "=f"(g[23]), "=f"(g[24]), "=f"(g[25]), "=f"(g[26]), "=f"(g[27]), "=f"(g[28]), "=f"(g[29]), "=f"(g[30]), "=f"(g[31]), "=f"(g[32]), "=f"(g[33]), "=f"(g[34]), "=f"(g[35]), "=f"(g[36]), "=f"(g[37]), "=f"(g[38]), "=f"(g[39]),
        "=f"(h[0]), "=f"(h[1]), "=f"(h[2]), "=f"(h[3]), "=f"(h[4]), "=f"(h[5]), "=f"(h[6]), "=f"(h[7]), "=f"(h[8]), "=f"(h[9]), "=f"(h[10]), "=f"(h[11]), "=f"(h[12]), "=f"(h[13]), "=f"(h[14]), "=f"(h[15]), "=f"(h[16]), "=f"(h[17]), "=f"(h[18]), "=f"(h[19]), "=f"(h[20]), "=f"(h[21]), "=f"(h[22]), "=f"(h[23]), "=f"(h[24]), "=f"(h[25]), "=f"(h[26]), "=f"(h[27]), "=f"(h[28]), "=f"(h[29]), "=f"(h[30]), "=f"(h[31]), "=f"(h[32]), "=f"(h[33]), "=f"(h[34]), "=f"(h[35]), "=f"(h[36]), "=f"(h[37]), "=f"(h[38]), "=f"(h[39])
      : "r"(w[0]), "r"(w[1]), "r"(w[2]), "r"(w[3]), "r"(w[4]), "r"(w[5]), "r"(w[6]), "r"(w[7]), "r"(w[8]), "r"(w[9]), "r"(w[10]), "r"(w[11]), "r"(w[12]), "r"(w[13]), "r"(w[14]), "r"(w[15]), "r"(w[16]), "r"(w[17]), "r"(w[18]), "r"(w[19]), "r"(w[20]), "r"(w[21]), "r"(w[22]), "r"(w[23]), "r"(w[24]), "r"(w[25]), "r"(w[26]), "r"(w[27]), "r"(w[28]), "r"(w[29]), "r"(w[30]), "r"(w[31]), "r"(w[32]), "r"(w[33]), "r"(w[34]), "r"(w[35]), "r"(w[36]), "r"(w[37]), "r"(w[38]), "r"(w[39]), "r"(dx), "l"(de), "l"(dh)
      : "memory");
  }
  static __device__ __forceinline__ void wait_g(float* g) {
    asm volatile("wgmma.wait_group.sync.aligned 1;\n"
      : "+f"(g[0]), "+f"(g[1]), "+f"(g[2]), "+f"(g[3]), "+f"(g[4]), "+f"(g[5]), "+f"(g[6]), "+f"(g[7]), "+f"(g[8]), "+f"(g[9]), "+f"(g[10]), "+f"(g[11]), "+f"(g[12]), "+f"(g[13]), "+f"(g[14]), "+f"(g[15]), "+f"(g[16]), "+f"(g[17]), "+f"(g[18]), "+f"(g[19]), "+f"(g[20]), "+f"(g[21]), "+f"(g[22]), "+f"(g[23]), "+f"(g[24]), "+f"(g[25]), "+f"(g[26]), "+f"(g[27]), "+f"(g[28]), "+f"(g[29]), "+f"(g[30]), "+f"(g[31]), "+f"(g[32]), "+f"(g[33]), "+f"(g[34]), "+f"(g[35]), "+f"(g[36]), "+f"(g[37]), "+f"(g[38]), "+f"(g[39])
      :: "memory");
  }
  static __device__ __forceinline__ void wait_h(float* h) {
    asm volatile("wgmma.wait_group.sync.aligned 0;\n"
      : "+f"(h[0]), "+f"(h[1]), "+f"(h[2]), "+f"(h[3]), "+f"(h[4]), "+f"(h[5]), "+f"(h[6]), "+f"(h[7]), "+f"(h[8]), "+f"(h[9]), "+f"(h[10]), "+f"(h[11]), "+f"(h[12]), "+f"(h[13]), "+f"(h[14]), "+f"(h[15]), "+f"(h[16]), "+f"(h[17]), "+f"(h[18]), "+f"(h[19]), "+f"(h[20]), "+f"(h[21]), "+f"(h[22]), "+f"(h[23]), "+f"(h[24]), "+f"(h[25]), "+f"(h[26]), "+f"(h[27]), "+f"(h[28]), "+f"(h[29]), "+f"(h[30]), "+f"(h[31]), "+f"(h[32]), "+f"(h[33]), "+f"(h[34]), "+f"(h[35]), "+f"(h[36]), "+f"(h[37]), "+f"(h[38]), "+f"(h[39])
      :: "memory");
  }
};
template<> struct TileMMA<11> {
  static __device__ __forceinline__ void issue(float* g, float* h, const uint32_t* w, uint32_t dx, uint64_t de, uint64_t dh, uint64_t dc) {
    asm volatile(
      "{\n.reg .b64 dx0, dx1, dx2, dx3;\n.reg .b32 l1, l2, l3, hx;\nmov.b32 hx, 0x40000040;\n"
      "add.u32 l1, %124, 2;\nadd.u32 l2, %124, 4;\nadd.u32 l3, %124, 6;\n"
      "mov.b64 dx0, {%124, hx};\nmov.b64 dx1, {l1, hx};\nmov.b64 dx2, {l2, hx};\nmov.b64 dx3, {l3, hx};\n"
      "wgmma.fence.sync.aligned;\n"
      "wgmma.mma_async.sync.aligned.m64n88k16.f32.bf16.bf16 {%0, %1, %2, %3, %4, %5, %6, %7, %8, %9, %10, %11, %12, %13, %14, %15, %16, %17, %18, %19, %20, %21, %22, %23, %24, %25, %26, %27, %28, %29, %30, %31, %32, %33, %34, %35, %36, %37, %38, %39, %40, %41, %42, %43}, {%120, %121, %122, %123}, %126, 0, 1, 1, 0;\n"
      "wgmma.mma_async.sync.aligned.m64n88k16.f32.bf16.bf16 {%0, %1, %2, %3, %4, %5, %6, %7, %8, %9, %10, %11, %12, %13, %14, %15, %16, %17, %18, %19, %20, %21, %22, %23, %24, %25, %26, %27, %28, %29, %30, %31, %32, %33, %34, %35, %36, %37, %38, %39, %40, %41, %42, %43}, %127, %125, 1, 1, 1, 0, 0;\n"
      "wgmma.mma_async.sync.aligned.m64n88k16.f32.bf16.bf16 {%0, %1, %2, %3, %4, %5, %6, %7, %8, %9, %10, %11, %12, %13, %14, %15, %16, %17, %18, %19, %20, %21, %22, %23, %24, %25, %26, %27, %28, %29, %30, %31, %32, %33, %34, %35, %36, %37, %38, %39, %40, %41, %42, %43}, {%88, %89, %90, %91}, dx0, 1, 1, 1, 0;\n"
      "wgmma.mma_async.sync.aligned.m64n88k16.f32.bf16.bf16 {%0, %1, %2, %3, %4, %5, %6, %7, %8, %9, %10, %11, %12, %13, %14, %15, %16, %17, %18, %19, %20, %21, %22, %23, %24, %25, %26, %27, %28, %29, %30, %31, %32, %33, %34, %35, %36, %37, %38, %39, %40, %41, %42, %43}, {%92, %93, %94, %95}, dx1, 1, 1, 1, 0;\n"
      "wgmma.mma_async.sync.aligned.m64n88k16.f32.bf16.bf16 {%0, %1, %2, %3, %4, %5, %6, %7, %8, %9, %10, %11, %12, %13, %14, %15, %16, %17, %18, %19, %20, %21, %22, %23, %24, %25, %26, %27, %28, %29, %30, %31, %32, %33, %34, %35, %36, %37, %38, %39, %40, %41, %42, %43}, {%96, %97, %98, %99}, dx2, 1, 1, 1, 0;\n"
      "wgmma.mma_async.sync.aligned.m64n88k16.f32.bf16.bf16 {%0, %1, %2, %3, %4, %5, %6, %7, %8, %9, %10, %11, %12, %13, %14, %15, %16, %17, %18, %19, %20, %21, %22, %23, %24, %25, %26, %27, %28, %29, %30, %31, %32, %33, %34, %35, %36, %37, %38, %39, %40, %41, %42, %43}, {%100, %101, %102, %103}, dx3, 1, 1, 1, 0;\n"
      "wgmma.commit_group.sync.aligned;\n"
      "wgmma.mma_async.sync.aligned.m64n88k16.f32.bf16.bf16 {%44, %45, %46, %47, %48, %49, %50, %51, %52, %53, %54, %55, %56, %57, %58, %59, %60, %61, %62, %63, %64, %65, %66, %67, %68, %69, %70, %71, %72, %73, %74, %75, %76, %77, %78, %79, %80, %81, %82, %83, %84, %85, %86, %87}, {%104, %105, %106, %107}, dx0, 0, 1, 1, 0;\n"
      "wgmma.mma_async.sync.aligned.m64n88k16.f32.bf16.bf16 {%44, %45, %46, %47, %48, %49, %50, %51, %52, %53, %54, %55, %56, %57, %58, %59, %60, %61, %62, %63, %64, %65, %66, %67, %68, %69, %70, %71, %72, %73, %74, %75, %76, %77, %78, %79, %80, %81, %82, %83, %84, %85, %86, %87}, {%108, %109, %110, %111}, dx1, 1, 1, 1, 0;\n"
      "wgmma.mma_async.sync.aligned.m64n88k16.f32.bf16.bf16 {%44, %45, %46, %47, %48, %49, %50, %51, %52, %53, %54, %55, %56, %57, %58, %59, %60, %61, %62, %63, %64, %65, %66, %67, %68, %69, %70, %71, %72, %73, %74, %75, %76, %77, %78, %79, %80, %81, %82, %83, %84, %85, %86, %87}, {%112, %113, %114, %115}, dx2, 1, 1, 1, 0;\n"
      "wgmma.mma_async.sync.aligned.m64n88k16.f32.bf16.bf16 {%44, %45, %46, %47, %48, %49, %50, %51, %52, %53, %54, %55, %56, %57, %58, %59, %60, %61, %62, %63, %64, %65, %66, %67, %68, %69, %70, %71, %72, %73, %74, %75, %76, %77, %78, %79, %80, %81, %82, %83, %84, %85, %86, %87}, {%116, %117, %118, %119}, dx3, 1, 1, 1, 0;\n"
      "wgmma.commit_group.sync.aligned;\n}\n"
      : "=f"(g[0]), "=f"(g[1]), "=f"(g[2]), "=f"(g[3]), "=f"(g[4]), "=f"(g[5]), "=f"(g[6]), "=f"(g[7]), "=f"(g[8]), "=f"(g[9]), "=f"(g[10]), "=f"(g[11]), "=f"(g[12]), "=f"(g[13]), "=f"(g[14]), "=f"(g[15]), "=f"(g[16]), "=f"(g[17]), "=f"(g[18]), "=f"(g[19]), "=f"(g[20]), "=f"(g[21]), "=f"(g[22]), "=f"(g[23]), "=f"(g[24]), "=f"(g[25]), "=f"(g[26]), "=f"(g[27]), "=f"(g[28]), "=f"(g[29]), "=f"(g[30]), "=f"(g[31]), "=f"(g[32]), "=f"(g[33]), "=f"(g[34]), "=f"(g[35]), "=f"(g[36]), "=f"(g[37]), "=f"(g[38]), "=f"(g[39]), "=f"(g[40]), "=f"(g[41]), "=f"(g[42]), "=f"(g[43]),
        "=f"(h[0]), "=f"(h[1]), "=f"(h[2]), "=f"(h[3]), "=f"(h[4]), "=f"(h[5]), "=f"(h[6]), "=f"(h[7]), "=f"(h[8]), "=f"(h[9]), "=f"(h[10]), "=f"(h[11]), "=f"(h[12]), "=f"(h[13]), "=f"(h[14]), "=f"(h[15]), "=f"(h[16]), "=f"(h[17]), "=f"(h[18]), "=f"(h[19]), "=f"(h[20]), "=f"(h[21]), "=f"(h[22]), "=f"(h[23]), "=f"(h[24]), "=f"(h[25]), "=f"(h[26]), "=f"(h[27]), "=f"(h[28]), "=f"(h[29]), "=f"(h[30]), "=f"(h[31]), "=f"(h[32]), "=f"(h[33]), "=f"(h[34]), "=f"(h[35]), "=f"(h[36]), "=f"(h[37]), "=f"(h[38]), "=f"(h[39]), "=f"(h[40]), "=f"(h[41]), "=f"(h[42]), "=f"(h[43])
      : "r"(w[0]), "r"(w[1]), "r"(w[2]), "r"(w[3]), "r"(w[4]), "r"(w[5]), "r"(w[6]), "r"(w[7]), "r"(w[8]), "r"(w[9]), "r"(w[10]), "r"(w[11]), "r"(w[12]), "r"(w[13]), "r"(w[14]), "r"(w[15]), "r"(w[20]), "r"(w[21]), "r"(w[22]), "r"(w[23]), "r"(w[24]), "r"(w[25]), "r"(w[26]), "r"(w[27]), "r"(w[28]), "r"(w[29]), "r"(w[30]), "r"(w[31]), "r"(w[32]), "r"(w[33]), "r"(w[34]), "r"(w[35]), "r"(w[36]), "r"(w[37]), "r"(w[38]), "r"(w[39]), "r"(dx), "l"(de), "l"(dh), "l"(dc)
      : "memory");
  }
  static __device__ __forceinline__ void wait_g(float* g) {
    asm volatile("wgmma.wait_group.sync.aligned 1;\n"
      : "+f"(g[0]), "+f"(g[1]), "+f"(g[2]), "+f"(g[3]), "+f"(g[4]), "+f"(g[5]), "+f"(g[6]), "+f"(g[7]), "+f"(g[8]), "+f"(g[9]), "+f"(g[10]), "+f"(g[11]), "+f"(g[12]), "+f"(g[13]), "+f"(g[14]), "+f"(g[15]), "+f"(g[16]), "+f"(g[17]), "+f"(g[18]), "+f"(g[19]), "+f"(g[20]), "+f"(g[21]), "+f"(g[22]), "+f"(g[23]), "+f"(g[24]), "+f"(g[25]), "+f"(g[26]), "+f"(g[27]), "+f"(g[28]), "+f"(g[29]), "+f"(g[30]), "+f"(g[31]), "+f"(g[32]), "+f"(g[33]), "+f"(g[34]), "+f"(g[35]), "+f"(g[36]), "+f"(g[37]), "+f"(g[38]), "+f"(g[39]), "+f"(g[40]), "+f"(g[41]), "+f"(g[42]), "+f"(g[43])
      :: "memory");
  }
  static __device__ __forceinline__ void wait_h(float* h) {
    asm volatile("wgmma.wait_group.sync.aligned 0;\n"
      : "+f"(h[0]), "+f"(h[1]), "+f"(h[2]), "+f"(h[3]), "+f"(h[4]), "+f"(h[5]), "+f"(h[6]), "+f"(h[7]), "+f"(h[8]), "+f"(h[9]), "+f"(h[10]), "+f"(h[11]), "+f"(h[12]), "+f"(h[13]), "+f"(h[14]), "+f"(h[15]), "+f"(h[16]), "+f"(h[17]), "+f"(h[18]), "+f"(h[19]), "+f"(h[20]), "+f"(h[21]), "+f"(h[22]), "+f"(h[23]), "+f"(h[24]), "+f"(h[25]), "+f"(h[26]), "+f"(h[27]), "+f"(h[28]), "+f"(h[29]), "+f"(h[30]), "+f"(h[31]), "+f"(h[32]), "+f"(h[33]), "+f"(h[34]), "+f"(h[35]), "+f"(h[36]), "+f"(h[37]), "+f"(h[38]), "+f"(h[39]), "+f"(h[40]), "+f"(h[41]), "+f"(h[42]), "+f"(h[43])
      :: "memory");
  }
};
__device__ __forceinline__ void node_mma(float* g, const uint32_t* w, uint64_t dx) {
    asm volatile(
      "{\n.reg .b64 dx1, dx2, dx3;\n"
      "add.s64 dx1, %48, 2;\nadd.s64 dx2, %48, 4;\nadd.s64 dx3, %48, 6;\n"
      "wgmma.fence.sync.aligned;\n"
      "wgmma.mma_async.sync.aligned.m64n64k16.f32.bf16.bf16 {%0, %1, %2, %3, %4, %5, %6, %7, %8, %9, %10, %11, %12, %13, %14, %15, %16, %17, %18, %19, %20, %21, %22, %23, %24, %25, %26, %27, %28, %29, %30, %31}, {%32, %33, %34, %35}, %48, 0, 1, 1, 0;\n"
      "wgmma.mma_async.sync.aligned.m64n64k16.f32.bf16.bf16 {%0, %1, %2, %3, %4, %5, %6, %7, %8, %9, %10, %11, %12, %13, %14, %15, %16, %17, %18, %19, %20, %21, %22, %23, %24, %25, %26, %27, %28, %29, %30, %31}, {%36, %37, %38, %39}, dx1, 1, 1, 1, 0;\n"
      "wgmma.mma_async.sync.aligned.m64n64k16.f32.bf16.bf16 {%0, %1, %2, %3, %4, %5, %6, %7, %8, %9, %10, %11, %12, %13, %14, %15, %16, %17, %18, %19, %20, %21, %22, %23, %24, %25, %26, %27, %28, %29, %30, %31}, {%40, %41, %42, %43}, dx2, 1, 1, 1, 0;\n"
      "wgmma.mma_async.sync.aligned.m64n64k16.f32.bf16.bf16 {%0, %1, %2, %3, %4, %5, %6, %7, %8, %9, %10, %11, %12, %13, %14, %15, %16, %17, %18, %19, %20, %21, %22, %23, %24, %25, %26, %27, %28, %29, %30, %31}, {%44, %45, %46, %47}, dx3, 1, 1, 1, 0;\n"
      "wgmma.commit_group.sync.aligned;\n}\n"
      : "=f"(g[0]), "=f"(g[1]), "=f"(g[2]), "=f"(g[3]), "=f"(g[4]), "=f"(g[5]), "=f"(g[6]), "=f"(g[7]), "=f"(g[8]), "=f"(g[9]), "=f"(g[10]), "=f"(g[11]), "=f"(g[12]), "=f"(g[13]), "=f"(g[14]), "=f"(g[15]), "=f"(g[16]), "=f"(g[17]), "=f"(g[18]), "=f"(g[19]), "=f"(g[20]), "=f"(g[21]), "=f"(g[22]), "=f"(g[23]), "=f"(g[24]), "=f"(g[25]), "=f"(g[26]), "=f"(g[27]), "=f"(g[28]), "=f"(g[29]), "=f"(g[30]), "=f"(g[31])
      : "r"(w[0]), "r"(w[1]), "r"(w[2]), "r"(w[3]), "r"(w[4]), "r"(w[5]), "r"(w[6]), "r"(w[7]), "r"(w[8]), "r"(w[9]), "r"(w[10]), "r"(w[11]), "r"(w[12]), "r"(w[13]), "r"(w[14]), "r"(w[15]), "l"(dx)
      : "memory");
}

__device__ __forceinline__ uint32_t smem_u32(const void* p) { return (uint32_t)__cvta_generic_to_shared(p); }
__device__ __forceinline__ float ex2f(float x) { float y; asm("ex2.approx.ftz.f32 %0, %1;" : "=f"(y) : "f"(x)); return y; }
__device__ __forceinline__ float rcpf(float x) { float y; asm("rcp.approx.ftz.f32 %0, %1;" : "=f"(y) : "f"(x)); return y; }
__device__ __forceinline__ uint32_t pack_bf16(float lo, float hi) {
    uint32_t r; asm("cvt.rn.bf16x2.f32 %0, %1, %2;" : "=r"(r) : "f"(hi), "f"(lo)); return r;
}
__device__ __forceinline__ float bf_lo(uint32_t v) { return __uint_as_float(v << 16); }
__device__ __forceinline__ float bf_hi(uint32_t v) { return __uint_as_float(v & 0xFFFF0000u); }
template<int STRIDE>
__device__ __forceinline__ void cp16i(uint32_t dst, const char* base, uint32_t idx) {
    asm volatile("{\n.reg .b64 a;\nmad.wide.u32 a, %2, %3, %1;\ncp.async.cg.shared.global [%0], [a], 16;\n}\n" :: "r"(dst), "l"(base), "r"(idx), "n"(STRIDE) : "memory");
}
__device__ __forceinline__ void cp16e(uint32_t dst, const char* base, uint32_t idx, uint64_t pol) {
    asm volatile("{\n.reg .b64 a;\nmad.wide.u32 a, %2, 32, %1;\ncp.async.cg.shared.global.L2::cache_hint [%0], [a], 16, %3;\n}\n" :: "r"(dst), "l"(base), "r"(idx), "l"(pol) : "memory");
}
template<int STRIDE>
__device__ __forceinline__ void cp16z(uint32_t dst, const char* base, uint32_t idx, int k, int n, uint64_t pol) {
    if (STRIDE == 32)
        asm volatile("{\n.reg .b64 a;\n.reg .pred p;\nsetp.ge.s32 p, %3, %4;\nmad.wide.u32 a, %2, 32, %1;\ncp.async.cg.shared.global.L2::cache_hint [%0], [a], 16, p, %5;\n}\n"
                     :: "r"(dst), "l"(base), "r"(idx), "r"(k), "r"(n), "l"(pol) : "memory");
    else
        asm volatile("{\n.reg .b64 a;\n.reg .pred p;\nsetp.ge.s32 p, %3, %4;\nmad.wide.u32 a, %2, 128, %1;\ncp.async.cg.shared.global [%0], [a], 16, p;\n}\n"
                     :: "r"(dst), "l"(base), "r"(idx), "r"(k), "r"(n) : "memory");
}
template<int HI, bool Z>
__device__ __forceinline__ void cpx(uint32_t hi, uint32_t dst, uint32_t p, uint32_t lo, int k, int n) {
    if (Z) asm volatile("{\n.reg .b32 l;\n.reg .b64 a;\n.reg .pred q;\nsetp.ge.s32 q, %5, %6;\ndp2a.lo.u32.u32 l, %1, %2, %3;\nmov.b64 a, {l, %0};\ncp.async.cg.shared.global [%4], [a], 16, q;\n}\n"
                        :: "r"(hi), "r"(p), "r"(HI ? 0x8000u : 0x80u), "r"(lo), "r"(dst), "r"(k), "r"(n) : "memory");
    else asm volatile("{\n.reg .b32 l;\n.reg .b64 a;\ndp2a.lo.u32.u32 l, %1, %2, %3;\nmov.b64 a, {l, %0};\ncp.async.cg.shared.global [%4], [a], 16;\n}\n"
                      :: "r"(hi), "r"(p), "r"(HI ? 0x8000u : 0x80u), "r"(lo), "r"(dst) : "memory");
}
template<bool Z>
__device__ __forceinline__ void cpe(uint32_t hi, uint32_t dst, uint32_t idx, uint32_t lo, int k, int n, uint64_t pol) {
    if (Z) asm volatile("{\n.reg .b32 l;\n.reg .b64 a;\n.reg .pred q;\nsetp.ge.s32 q, %5, %6;\nmad.lo.u32 l, %1, 32, %2;\nmov.b64 a, {l, %0};\ncp.async.cg.shared.global.L2::cache_hint [%3], [a], 16, q, %4;\n}\n"
                        :: "r"(hi), "r"(idx), "r"(lo), "r"(dst), "l"(pol), "r"(k), "r"(n) : "memory");
    else asm volatile("{\n.reg .b32 l;\n.reg .b64 a;\nmad.lo.u32 l, %1, 32, %2;\nmov.b64 a, {l, %0};\ncp.async.cg.shared.global.L2::cache_hint [%3], [a], 16, %4;\n}\n"
                      :: "r"(hi), "r"(idx), "r"(lo), "r"(dst), "l"(pol) : "memory");
}
__device__ __forceinline__ void cp_commit() { asm volatile("cp.async.commit_group;" ::: "memory"); }
template<int N> __device__ __forceinline__ void cp_wait() { asm volatile("cp.async.wait_group %0;" :: "n"(N) : "memory"); }
__device__ __forceinline__ void mbar_arrive(uint32_t bar) { asm volatile("mbarrier.arrive.shared.b64 _, [%0];" :: "r"(bar) : "memory"); }
__device__ __forceinline__ void mbar_cp_arrive(uint32_t bar) { asm volatile("cp.async.mbarrier.arrive.noinc.shared.b64 [%0];" :: "r"(bar) : "memory"); }
__device__ __forceinline__ void mbar_wait(uint32_t bar, uint32_t parity) {
    asm volatile("{\n.reg .pred p;\n.reg .u32 n;\nmbarrier.try_wait.parity.shared.b64 p, [%0], %1;\n@p bra DONE_%=;\nmov.u32 n, 0;\n"
                 "WAIT_%=:\nmbarrier.try_wait.parity.shared.b64 p, [%0], %1, 0x100000;\n@p bra DONE_%=;\n"
                 "add.u32 n, n, 1;\nsetp.lt.u32 p, n, 0x400000;\n@p bra WAIT_%=;\ntrap;\nDONE_%=:\n}\n"
                 :: "r"(bar), "r"(parity) : "memory");
}
__device__ __forceinline__ void mbar_wait_c(uint32_t bar, uint32_t parity) {
    asm volatile("{\n.reg .pred p;\nWAIT_%=:\nmbarrier.try_wait.parity.shared.b64 p, [%0], %1;\n@p bra DONE_%=;\nbra WAIT_%=;\nDONE_%=:\n}\n"
                 :: "r"(bar), "r"(parity) : "memory");
}
__device__ __forceinline__ void mbar_wait_h(uint32_t bar, uint32_t parity) {
    asm volatile("{\n.reg .pred p;\nWAIT_%=:\nmbarrier.try_wait.parity.shared.b64 p, [%0], %1, 0x100000;\n@p bra DONE_%=;\nbra WAIT_%=;\nDONE_%=:\n}\n"
                 :: "r"(bar), "r"(parity) : "memory");
}
__device__ __forceinline__ uint32_t lds32(uint32_t a) { uint32_t v; asm volatile("ld.shared.u32 %0, [%1];" : "=r"(v) : "r"(a) : "memory"); return v; }
__device__ __forceinline__ void sts32(uint32_t a, uint32_t v) { asm volatile("st.shared.u32 [%0], %1;" :: "r"(a), "r"(v) : "memory"); }
__device__ __forceinline__ uint2 lds64(uint32_t a) { uint2 v; asm volatile("ld.shared.v2.u32 {%0,%1}, [%2];" : "=r"(v.x), "=r"(v.y) : "r"(a) : "memory"); return v; }
__device__ __forceinline__ uint4 lds128(uint32_t a) { uint4 v; asm volatile("ld.shared.v4.u32 {%0,%1,%2,%3}, [%4];" : "=r"(v.x), "=r"(v.y), "=r"(v.z), "=r"(v.w) : "r"(a) : "memory"); return v; }
__device__ __forceinline__ void sts128(uint32_t a, uint4 v) { asm volatile("st.shared.v4.u32 [%0], {%1,%2,%3,%4};" :: "r"(a), "r"(v.x), "r"(v.y), "r"(v.z), "r"(v.w) : "memory"); }
__device__ __forceinline__ void ldsm4t(uint32_t* v, uint32_t a) {
    asm volatile("ldmatrix.sync.aligned.m8n8.x4.trans.shared.b16 {%0,%1,%2,%3}, [%4];" : "=r"(v[0]), "=r"(v[1]), "=r"(v[2]), "=r"(v[3]) : "r"(a) : "memory");
}
__device__ __forceinline__ void stsm4t(uint32_t a, const uint32_t* v) {
    asm volatile("stmatrix.sync.aligned.m8n8.x4.trans.shared.b16 [%0], {%1,%2,%3,%4};" :: "r"(a), "r"(v[0]), "r"(v[1]), "r"(v[2]), "r"(v[3]) : "memory");
}
__device__ __forceinline__ int atoms_inc(uint32_t a) { int v; asm volatile("atom.shared.add.u32 %0, [%1], 1;" : "=r"(v) : "r"(a) : "memory"); return v; }
__device__ __forceinline__ float tanhf_a(float x) { float y; asm("tanh.approx.f32 %0, %1;" : "=f"(y) : "f"(x)); return y; }
__device__ __forceinline__ const char* as_pair(const void* p, uint32_t scratch) {
    const char* r;
    asm volatile("st.shared.u64 [%1], %2;\nld.volatile.shared.u64 %0, [%1];" : "=l"(r) : "r"(scratch), "l"(p) : "memory");
    return r;
}
__device__ __forceinline__ void ld_unit(uint4& v, const char* p, bool ok) {
    asm volatile("{\n.reg .pred q;\nsetp.ne.u32 q, %5, 0;\n@q ld.relaxed.gpu.global.v4.u32 {%0,%1,%2,%3}, [%4];\n}"
                 : "+r"(v.x), "+r"(v.y), "+r"(v.z), "+r"(v.w) : "l"(p), "r"((uint32_t)ok) : "memory");
}
__device__ __forceinline__ void ld_unit(uint2& v, const char* p, bool ok) {
    asm volatile("{\n.reg .pred q;\nsetp.ne.u32 q, %3, 0;\n@q ld.relaxed.gpu.global.v2.u32 {%0,%1}, [%2];\n}"
                 : "+r"(v.x), "+r"(v.y) : "l"(p), "r"((uint32_t)ok) : "memory");
}
#define ELECT "{\n.reg .pred p;\nelect.sync _|p, 0xffffffff;\n@p "
__device__ __forceinline__ void w_init(uint32_t bar, int n) { asm volatile(ELECT "mbarrier.init.shared.b64 [%0], %1;\n}" :: "r"(bar), "r"(n) : "memory"); }
__device__ __forceinline__ void w_expect(uint32_t bar, uint32_t bytes) { asm volatile(ELECT "mbarrier.arrive.expect_tx.shared.b64 _, [%0], %1;\n}" :: "r"(bar), "r"(bytes) : "memory"); }
__device__ __forceinline__ void w_ld(uint32_t dst, const void* src, int bytes, uint32_t bar) {
    asm volatile(ELECT "cp.async.bulk.shared::cluster.global.mbarrier::complete_tx::bytes [%0], [%1], %2, [%3];\n}" :: "r"(dst), "l"(src), "r"(bytes), "r"(bar) : "memory");
}
__device__ __forceinline__ void w_box_ld(uint32_t dst, const CUtensorMap* tm, int row, uint32_t bar) {
    asm volatile(ELECT "cp.async.bulk.tensor.2d.shared::cluster.global.mbarrier::complete_tx::bytes [%0], [%1, {%3, %4}], [%2];\n}"
        :: "r"(dst), "l"((uint64_t)tm), "r"(bar), "r"(0), "r"(row) : "memory");
}
__device__ __forceinline__ void w_st(void* dst, uint32_t src, int bytes) {
    asm volatile(ELECT "cp.async.bulk.global.shared::cta.bulk_group [%0], [%1], %2;\n}" :: "l"(dst), "r"(src), "r"(bytes) : "memory");
}
__device__ __forceinline__ void w_box_st(const CUtensorMap* tm, int col, uint32_t src) {
    asm volatile(ELECT "cp.async.bulk.tensor.2d.global.shared::cta.bulk_group [%0, {%2, %3}], [%1];\n}" :: "l"((uint64_t)tm), "r"(src), "r"(col), "r"(0) : "memory");
}
__device__ __forceinline__ void w_sent(unsigned* p, uint32_t src) {
    asm volatile(ELECT "cp.reduce.async.bulk.global.shared::cta.bulk_group.add.u32 [%0], [%1], 16;\n}" :: "l"(p), "r"(src) : "memory");
}
__device__ __forceinline__ void w_inc(unsigned* p) { asm volatile(ELECT "red.relaxed.gpu.global.add.u32 [%0], 1;\n}" :: "l"(p) : "memory"); }
__device__ __forceinline__ void w_hint(unsigned* p, uint32_t all) {
    #pragma unroll 1
    for (int i = 0; i < 4096; i++) {
        uint32_t v; asm volatile("ld.relaxed.gpu.global.u32 %0, [%1];" : "=r"(v) : "l"(p) : "memory");
        if (__all_sync(~0u, (int)(v - all) >= 0)) break;
    }
}

__device__ __forceinline__ void finish(uint4& a, const uint4& xu, const uint4& xv) {
    asm("{\n.reg .b32 z;\nfma.rn.relu.bf16x2 z, %0, %3, %1;\nadd.rn.bf16x2 %0, z, %2;\n}" : "+r"(a.x) : "r"(xu.x), "r"(xv.x), "r"(0x3F803F80u));
    asm("{\n.reg .b32 z;\nfma.rn.relu.bf16x2 z, %0, %3, %1;\nadd.rn.bf16x2 %0, z, %2;\n}" : "+r"(a.y) : "r"(xu.y), "r"(xv.y), "r"(0x3F803F80u));
    asm("{\n.reg .b32 z;\nfma.rn.relu.bf16x2 z, %0, %3, %1;\nadd.rn.bf16x2 %0, z, %2;\n}" : "+r"(a.z) : "r"(xu.z), "r"(xv.z), "r"(0x3F803F80u));
    asm("{\n.reg .b32 z;\nfma.rn.relu.bf16x2 z, %0, %3, %1;\nadd.rn.bf16x2 %0, z, %2;\n}" : "+r"(a.w) : "r"(xu.w), "r"(xv.w), "r"(0x3F803F80u));
}

constexpr float EPS2 = 2e-6f;
constexpr float TAU = 2.5e-5f;

constexpr uint32_t TAU_BITS = 0x3A103000u;
template<int NP>
__device__ __forceinline__ bool epi_fast(const float* g, const float* h, float m2, float tau, float& n0, float& d0, float& n1, float& d1, float& dmin)
{
    constexpr int JC = NP >= 6 ? NP - 3 : NP - 2;
    bool ok;
    #pragma unroll
    for (int j = 0; j < NP; j++) {
        float t0 = tanhf_a(g[4*j+0]), t1 = tanhf_a(g[4*j+1]), t2 = tanhf_a(g[4*j+2]), t3 = tanhf_a(g[4*j+3]);
        auto add_d = [&]() {
            if (j == 0) { d0 = t0 + (2.f * (JC + 1) + EPS2); d1 = t2 + (2.f * (JC + 1) + EPS2); } else { d0 += t0; d1 += t2; }
            d0 += t1; d1 += t3;
        };
        if (j <= JC) add_d();
        if (j == 0) { n0 = fmaf(t0, h[0], h[0]); n1 = fmaf(t2, h[2], h[2]); }
        t0 += 1.f; t2 += 1.f;
        if (j == NP - 1) { t1 = fmaf(t1, m2, m2); t3 = fmaf(t3, m2, m2); } else { t1 += 1.f; t3 += 1.f; }
        if (j > JC) add_d();
        if (j > 0) { n0 = fmaf(t0, h[4*j], n0); n1 = fmaf(t2, h[4*j+2], n1); }
        n0 = fmaf(t1, h[4*j+1], n0); n1 = fmaf(t3, h[4*j+3], n1);
        if (j == JC) { dmin = fminf(d0, d1); ok = dmin >= tau; }
    }
    return ok;
}

__device__ __noinline__ void slow_bin(const __nv_bfloat16* x, const __nv_bfloat16* ea, const int* src, const int* dst,
                                      const __nv_bfloat16* wa, const __nv_bfloat16* wb, const __nv_bfloat16* wc,
                                      const __nv_bfloat16* wu, const __nv_bfloat16* wv, __nv_bfloat16* out,
                                      int E, int node0, int nn, int nthr)
{
    const int tid = threadIdx.x, lane = tid & 31;
    for (int i = tid; i < nn * 128; i += nthr) g_slow[(size_t)node0 * 128 + i] = 0.f;
    asm volatile("bar.sync 1, %0;" :: "r"(nthr) : "memory");
    for (int e0 = (tid >> 5) * 32; e0 < E; e0 += nthr) {
        int d = (e0 + lane < E) ? dst[e0 + lane] - node0 : -1;
        unsigned m = __ballot_sync(~0u, d >= 0 && d < nn);
        while (m) {
            int l = __ffs(m) - 1; m &= m - 1;
            int e = e0 + l, n = node0 + __shfl_sync(~0u, d, l), s = src[e];
            float g0 = 0, g1 = 0, h0 = 0, h1 = 0;
            for (int k = 0; k < 64; k++) {
                float xs = __bfloat162float(x[(size_t)s * 64 + k]), xd = __bfloat162float(x[(size_t)n * 64 + k]);
                uint32_t b2 = *(const uint32_t*)(wb + k * 64 + 2 * lane), v2 = *(const uint32_t*)(wv + k * 64 + 2 * lane);
                uint32_t a2 = *(const uint32_t*)(wa + k * 64 + 2 * lane);
                g0 = fmaf(xs, bf_lo(b2), fmaf(xd, bf_lo(a2), g0)); g1 = fmaf(xs, bf_hi(b2), fmaf(xd, bf_hi(a2), g1));
                h0 = fmaf(xs, bf_lo(v2), h0); h1 = fmaf(xs, bf_hi(v2), h1);
            }
            for (int k = 0; k < 16; k++) {
                float ev = __bfloat162float(ea[(size_t)e * 16 + k]);
                uint32_t c2 = *(const uint32_t*)(wc + k * 64 + 2 * lane);
                g0 = fmaf(ev, bf_lo(c2), g0); g1 = fmaf(ev, bf_hi(c2), g1);
            }
            float s0 = rcpf(1.f + ex2f(-LOG2E * g0)), s1 = rcpf(1.f + ex2f(-LOG2E * g1));
            float* acc = g_slow + (size_t)n * 128 + 4 * lane;
            atomicAdd(acc + 0, s0 * h0); atomicAdd(acc + 1, s0);
            atomicAdd(acc + 2, s1 * h1); atomicAdd(acc + 3, s1);
        }
    }
    __threadfence();
    asm volatile("bar.sync 1, %0;" :: "r"(nthr) : "memory");
    for (int i = tid; i < nn * 32; i += nthr) {
        int n = node0 + (i >> 5), cp = i & 31;
        float4 a = __ldcg((const float4*)(g_slow + (size_t)n * 128 + 4 * cp));
        float u0 = 0, u1 = 0;
        for (int k = 0; k < 64; k++) {
            float xd = __bfloat162float(x[(size_t)n * 64 + k]);
            uint32_t w2 = *(const uint32_t*)(wu + k * 64 + 2 * cp);
            u0 = fmaf(xd, bf_lo(w2), u0); u1 = fmaf(xd, bf_hi(w2), u1);
        }
        uint32_t xv = *(const uint32_t*)(x + (size_t)n * 64 + 2 * cp);
        float z0 = u0 + a.x / (a.y + 1e-6f), z1 = u1 + a.z / (a.w + 1e-6f);
        *(uint32_t*)(out + (size_t)n * 64 + 2 * cp) = pack_bf16(bf_lo(xv) + fmaxf(z0, 0.f), bf_hi(xv) + fmaxf(z1, 0.f));
    }
}

__global__ void __launch_bounds__(256) slow_kernel(const __nv_bfloat16* x, const __nv_bfloat16* ea, const int* src, const int* dst,
        const __nv_bfloat16* wa, const __nv_bfloat16* wb, const __nv_bfloat16* wc, const __nv_bfloat16* wu, const __nv_bfloat16* wv,
        __nv_bfloat16* out, int N, int E, int npb)
{
    int node0 = blockIdx.x * npb;
    slow_bin(x, ea, src, dst, wa, wb, wc, wu, wv, out, E, node0, max(0, min(npb, N - node0)), 256);
}

constexpr int XS_BYTES = NPMAX * 1024;
constexpr int ES_BYTES = NPMAX * 256;
constexpr int SM_XS = 0;
constexpr int SM_XU = SM_XS + 3 * NSTAGE * XS_BYTES;
constexpr int SM_TAB = SM_XU + NPB_MAX * 128;
constexpr int SM_ES = SM_TAB + NPB_MAX * 128;
constexpr int SM_WC = SM_ES + 3 * NSTAGE * ES_BYTES;
constexpr int SM_OH = SM_WC + 2048;
constexpr int SM_EID = SM_OH + 128;
constexpr int SM_SRC = SM_EID + SLOT_CAP * 4;
constexpr int SM_TINFO = SM_SRC + SLOT_CAP * 2;
constexpr int SM_MISC = SM_TINFO + TILE_CAP * 32;
constexpr int SM_CLAIM = SM_MISC + 32 * 4;
constexpr int STG = 272;
constexpr int SM_BARS = SM_CLAIM + 32 * 4;
constexpr int SM_ABAR = SM_BARS + 6 * STG;
constexpr int SM_GBAR = SM_ABAR + 16 * 8;
constexpr int SMEM_BYTES = SM_GBAR + 97 * 8;
constexpr int SM_P2 = 0, SM_P1 = P2B + 256;
constexpr int SM_L1 = SM_P1 + P1B + 128;
constexpr int SM_DEG = SM_L1 + 256;
constexpr int SM_CLS = SM_DEG + 512 * 4;
constexpr int SM_HIST = SM_CLS + NCLS * 4;
constexpr int SM_XLIST = SM_HIST + NB_MAX * 4;
constexpr int SM_SORT = SM_XLIST + 8;
constexpr int SM_SDEG = SM_SORT + NPB_MAX * 4;
constexpr int SM_PAIR = SM_SDEG + NPB_MAX * 2;
constexpr int SM_ENT = SM_ES + 1024;
constexpr int SM_H1 = SM_P1 + HB, SM_H2 = SM_P1;
constexpr int SM_IDX = SM_EID;
constexpr int SM_WR = SM_TAB;
static_assert(TILE_CAP <= 128 && TR >= 2 && SM_ES % 256 == 0 && NSTAGE == 2 && SM_BARS % 16 == 0 && SM_TINFO % 16 == 0 && SM_EID % 128 == 0 && SM_TAB % 1024 == 0 && SM_XU % 1024 == 0 && SM_TINFO % 8 == 0 && SM_OH % 16 == 0 && SM_XLIST % 8 == 0 && SM_PAIR % 8 == 0, "align");
static_assert(SM_P1 % 128 == 0 && P1B + HB <= SM_SRC - SM_EID && 2 * HB <= P1B && SM_H1 + 5 * 128 * 16 <= SM_XU && NB_MAX * (CE / 4) <= 6 * 384 && NB_MAX * 4 <= 5 * 128 && NB_MIN * 4 >= 3 * 128 && SM_PAIR + 128 * 8 <= SM_XU && CH_MAX * 4 <= SM_SRC - SM_EID && SM_DEG >= 3 << 14, "alias");
static_assert(CE == 64 && SMEM_BYTES <= 232448, "smem");
constexpr uint32_t C_BRK = 16  , C_CONT = 32, C_MORE = 64;
constexpr uint32_t ONE_F = 0x3F800000u;
constexpr int NONE = NPB_MAX - 1;
__host__ __device__ constexpr uint32_t tab_at(uint32_t n) { return (n >> 2) * 512 + (n & 3) * 32 + ((n >> 2) & 1) * 16; }

__device__ __forceinline__ uint32_t unpad(uint32_t w1, int np, float ga, float gb, float& d0, float& d1, int& dv) {
    const int pad = (w1 >> 8) & 31;
    dv = 2 * np - 1 - pad + (w1 >= ONE_F);
    float t0 = TAU * 2 * np, t1 = t0;
    if (pad) {
        t0 = fmaxf(t0, d0 * (1.f / 1024)); t1 = fmaxf(t1, d1 * (1.f / 1024));
        asm volatile("tanh.approx.f32 %0, %0;\ntanh.approx.f32 %1, %1;" : "+f"(ga), "+f"(gb));
        d0 -= pad * (1.f + ga); d1 -= pad * (1.f + gb);
    }
    if (dv == 0) { d0 = d1 = EPS2; t0 = t1 = 0.f; }
    return __ballot_sync(~0u, d0 < t0 || d1 < t1);
}
constexpr int SM_COPY = SM_XU + tab_at(NPB_MAX - 4) - 16;
__device__ __noinline__ float4* exact_copy(uint32_t bad)
{
    extern __shared__ __align__(1024) uint8_t smem[];
    uint32_t old = 1;
    if (bad == 1u << (threadIdx.x & 31)) old = atomicExch((uint32_t*)(smem + SM_MISC + 12), 1u);
    return __all_sync(~0u, old) ? g_copy + (blockIdx.x * 12 + (threadIdx.x >> 5)) * (64 * NPMAX) + (threadIdx.x & 31) : nullptr;
}
__device__ __noinline__ float4 epi_exact(const float4* gh, int np, int dv, uint32_t bad)
{
    extern __shared__ __align__(1024) uint8_t smem[];
    float n0 = 0.f, d0 = 0.f, n1 = 0.f, d1 = 0.f;
    int j = 0, ho = 32 * NPMAX;
    const bool one = gh == nullptr;
    if (one) {
        dv = __shfl_sync(~0u, dv, __ffs(bad) - 1); j = min(threadIdx.x & 15, np); np = j + 1; ho = NPMAX;
        gh = (const float4*)(smem + SM_COPY) + j;
        __syncwarp();
    }
    #pragma unroll 1
    for (; j < np; j++, gh += 32) {
        const float4 g = gh[0], h = gh[ho];
        const bool ma = 2 * j < dv, mb = 2 * j + 1 < dv;
        const float e0 = 2.f * rcpf(1.f + ex2f(-2.f * LOG2E * g.x)), e1 = 2.f * rcpf(1.f + ex2f(-2.f * LOG2E * g.y));
        const float e2 = 2.f * rcpf(1.f + ex2f(-2.f * LOG2E * g.z)), e3 = 2.f * rcpf(1.f + ex2f(-2.f * LOG2E * g.w));
        if (ma) { d0 += e0; n0 = fmaf(e0, h.x, n0); d1 += e2; n1 = fmaf(e2, h.z, n1); }
        if (mb) { d0 += e1; n0 = fmaf(e1, h.y, n0); d1 += e3; n1 = fmaf(e3, h.w, n1); }
    }
    if (__all_sync(~0u, one)) {
        #pragma unroll
        for (int o = 1; o < 16; o <<= 1) {
            n0 += __shfl_xor_sync(~0u, n0, o); d0 += __shfl_xor_sync(~0u, d0, o);
            n1 += __shfl_xor_sync(~0u, n1, o); d1 += __shfl_xor_sync(~0u, d1, o);
        }
        *(volatile uint32_t*)(smem + SM_MISC + 12) = 0;
    }
    return make_float4(n0, d0 + EPS2, n1, d1 + EPS2);
}
template<int NP>
__device__ __forceinline__ void epi_dump(const float* g, const float* h, float4* gh, uint32_t sa, bool on) {
    if (__all_sync(~0u, gh == nullptr)) {
        #pragma unroll
        for (int i = 0; i < 2 * NP; i++) {
            const float* v = i < NP ? g + 4 * i : h + 4 * (i - NP);
            asm volatile("{\n.reg .pred p;\nsetp.ne.u32 p, %5, 0;\n@p st.shared.v4.f32 [%0], {%1,%2,%3,%4};\n}"
                         :: "r"(sa + (i < NP ? i : NPMAX + i - NP) * 16), "f"(v[0]), "f"(v[1]), "f"(v[2]), "f"(v[3]), "r"((uint32_t)on) : "memory");
        }
    } else {
        #pragma unroll
        for (int i = 0; i < 2 * NP; i++) {
            const float* v = i < NP ? g + 4 * i : h + 4 * (i - NP);
            asm volatile("st.global.v4.f32 [%0], {%1,%2,%3,%4};" :: "l"(gh + (i < NP ? i : NPMAX + i - NP) * 32), "f"(v[0]), "f"(v[1]), "f"(v[2]), "f"(v[3]) : "memory");
        }
    }
}
__device__ __forceinline__ uint32_t bin_bits(uint32_t b) { return (1u << (b & 7)) | ((b < 48 ? 0x100u : 0x400u) << (b >> 3)); }
__device__ __forceinline__ void place(uint32_t sbase, uint32_t slot, uint32_t v, uint32_t eb) {
    asm volatile("{\n.reg .pred p;\nsetp.lt.u32 p, %0, %5;\n@p st.shared.u32 [%1], %2;\n@p st.shared.u16 [%3], %4;\n}"
                 :: "r"(slot), "r"(sbase + SM_EID + slot * 4), "r"(eb + (v >> 19)), "r"(sbase + SM_SRC + slot * 2), "r"(v), "n"(SLOT_CAP) : "memory");
}
__device__ __forceinline__ uint64_t desc_sw128(uint32_t a) {
    return (uint64_t)((a & 0x3FFFF) >> 4) | ((uint64_t)1 << 16) | ((uint64_t)64 << 32) | ((uint64_t)1 << 62);
}

template<bool LO32>
__global__ void __launch_bounds__(THREADS, 1)
gcn_kernel(const int* __restrict__ dst, unsigned* gbar, char* gs, const int* __restrict__ src, int E, int ch, int N, int npb, uint32_t magic,
           const __nv_bfloat16* __restrict__ x, const __nv_bfloat16* __restrict__ ea,
           const __nv_bfloat16* __restrict__ wa, const __nv_bfloat16* __restrict__ wb, const __nv_bfloat16* __restrict__ wc,
           const __nv_bfloat16* __restrict__ wu, const __nv_bfloat16* __restrict__ wv,
           __nv_bfloat16* out, int4 wrow, const __grid_constant__ CUtensorMap tm1, const __grid_constant__ CUtensorMap tm2,
           const __grid_constant__ CUtensorMap tmw, const __grid_constant__ CUtensorMap tmx)
{
    extern __shared__ __align__(1024) uint8_t smem[];
    int* cls = (int*)(smem + SM_CLS);
    int* misc = (int*)(smem + SM_MISC);
    WG0(); WS(0); CG(0);
    const uint32_t sbase = smem_u32(smem);
    const int tid = threadIdx.x, lane = tid & 31;
    const int b = blockIdx.x, nb = gridDim.x;
    const int cnt = max(0, min(ch, E - b * ch));
    const int node0 = b * npb;
    uint32_t tag = 0;
    if (tid < 384) asm volatile("ld.relaxed.gpu.global.u32 %0, [%1];" : "=r"(tag) : "l"(gbar) : "memory");
    auto dst_ld = [&](int v, uint32_t n) {
        const uint32_t off = v * (THREADS * 4) + tid * 4;
        asm volatile("{\n.reg .pred q;\nsetp.lt.u32 q, %2, %3;\n@q cp.async.cg.shared.global [%0], [%1], 16;\n}"
                     :: "r"(sbase + SM_IDX + off * 4), "l"(dst + (uint32_t)(b * ch + off)), "r"(off), "r"(n) : "memory");
    };
    dst_ld(0, min(cnt, 384 * 4));
    const int warp = (int)__reduce_max_sync(~0u, (unsigned)tid >> 5);
    const uint32_t su = __reduce_or_sync(~0u, sbase);
    if (warp >= 12) {
        const int v = warp & 3;
        const uint32_t a1 = su + SM_ABAR + (v == 0 ? 80 : v == 1 ? 120 : v == 2 ? 32 : 40);
        w_init(su + SM_ABAR + v * 8, 1); w_init(a1, 1);
        w_expect(su + SM_ABAR + v * 8, v < 3 ? min(max(cnt * 4 - v * 8192, 0), 8192) : 4 * 8192 + 2048);
        if (v < 2) w_expect(a1, v == 0 ? nb * (CE * 2) : nb * 64);
        asm volatile("fence.mbarrier_init.release.cluster;" ::: "memory");
        dst_ld(0, cnt);
    }
    #pragma unroll
    for (int v = 0; v < EPT / 4; v++) {
        if (v) {
            uint32_t c0, c1; asm volatile("mov.u32 %0, %%clock;" : "=r"(c0)); do { asm volatile("mov.u32 %0, %%clock;" : "=r"(c1)); } while (__all_sync(~0u, c1 - c0 < PD));
            dst_ld(v, cnt);
        }
        cp_commit();
    }
    if (warp == 15) {
        w_box_ld(su + SM_WR, &tmw, wrow.x, su + SM_ABAR + 24); w_box_ld(su + SM_WR + 8192, &tmw, wrow.y, su + SM_ABAR + 24);
        w_box_ld(su + SM_WR + 16384, &tmw, wrow.z, su + SM_ABAR + 24); w_ld(su + SM_WR + 24576, wc, 2048, su + SM_ABAR + 24);
        w_box_ld(su + SM_WR + 40960, &tmw, wrow.w, su + SM_ABAR + 24);
    }
    const int wg = warp >> 2, w = warp & 3;
    const int q = lane >> 2, t = lane & 3;
    const int nn = max(0, min(npb, N - node0));
    if (sbase & 1023) __trap();

    sts32(sbase + SM_DEG + tid * 4, tid < NPB_MAX ? 0 : 0x80000000u);
    if (tid < NCLS + NB_MAX) cls[tid] = tid < NCLS ? 0 : ((tid - NCLS) * 20) & 63;
    else if (warp == 8) sts32(sbase + SM_OH + lane * 4, t != (q >> 1) ? 0u : 0x00003F00u);
    else if (warp == 11) misc[lane] = lane == 5 ? TILE_CAP - TILE_X : lane == 8 || lane == 3;
    if (warp == 14) sts32(sbase + SM_TINFO + 96 * 32 + lane * 4, lane & 1 ? tab_at(NONE) : 0);
    if (warp == 15) sts32(sbase + SM_CLAIM + lane * 4, lane == 0 ? 3 * 32 : 0x40000000);
    if (tid == 0) sts32(sbase + SM_XLIST, tag);
    tag = (tag & 1) | 2;
    if (wg < 3) {
        const uint32_t d0 = ((NPB_MAX + ((2 * lane) & 15) + 16 * (b & 1)) * 4 | (tag << 14)) * 0x10001u, d1 = d0 + 0x40004u, d2 = tag << 16;
        #pragma unroll 1
        for (int i = tid; i < (P1B + 384) / 16; i += 384) {
            sts128(sbase + SM_P1 + i * 16, make_uint4(d0, d0, d1, i == P1B / 16 + 11 ? 0x80000000u | (tag << 14) : d1));
            sts128(sbase + SM_P2 + i * 16, make_uint4(d2, d2, d2, d2)); sts128(sbase + SM_P2 + P1B - 128 + i * 16, make_uint4(d2, d2, d2, d2));
        }
    }
    WS(1);
    __syncthreads();
    if (wg == 3) tag = lds32(sbase + SM_P2) >> 16;
    uint32_t all = 0;
    if (wg == 3) all = (lds32(sbase + SM_XLIST) + 1) * nb;
    if (tid == 128) {
        asm volatile("prefetch.tensormap [%0];" :: "l"((uint64_t)&tm1) : "memory");
        asm volatile("prefetch.tensormap [%0];" :: "l"((uint64_t)&tm2) : "memory");
        asm volatile("prefetch.tensormap [%0];" :: "l"((uint64_t)&tmx) : "memory");
    }
    const uint32_t m4 = __reduce_or_sync(~0u, -4 * npb);
    uint32_t ent[EPT];
    #pragma unroll
    for (int v = 0; v < EPT / 4; v++) {
        if (v == 0) cp_wait<2>(); else if (v == 1) cp_wait<1>(); else cp_wait<0>();
        if (v == 0 && wg == 2 && w < 3) {
            const int n = min(cnt * 4 - w * 8192, 8192);
            if (n > 0) w_ld(su + SM_XU + w * 8192, src + b * ch + w * 2048, n, su + SM_ABAR + w * 8);
        }
        const uint32_t off = v * (THREADS * 4) + tid * 4;
        if (off < (uint32_t)cnt) {
            const uint4 u = lds128(sbase + SM_IDX + off * 4);
            uint32_t dv[4] = {u.x, u.y, u.z, u.w}, ps[4], ck[4];
            uint32_t* en = ent + 4 * v;
            #pragma unroll
            for (int k = 0; k < 4; k++) {
                dv[k] = min(dv[k], (uint32_t)(nb * npb - 1));
                ps[k] = __umulhi(dv[k], magic);
                asm volatile("atom.shared.add.u32 %0, [%1], 0x10001;" : "=r"(ck[k]) : "r"(sbase + SM_HIST + ps[k] * 4) : "memory");
            }
            #pragma unroll
            for (int k = 0; k < 4; k++) {
                dv[k] = ps[k] * m4 + (dv[k] * 4 + (tag << 14));
                en[k] = (ck[k] & 63) + ps[k] * CE;
            }
            if (__builtin_expect(max(max(ck[0], ck[1]), max(ck[2], ck[3])) >= CE << 16, 0)) {
                auto step = [&]() {
                    uint32_t e = en[0];
                    const uint32_t d = dv[0];
                    if (ck[0] >= CE << 16) {
                        uint32_t j; asm volatile("atom.shared.inc.u32 %0, [%1], 0x7fffffff;" : "=r"(j) : "r"(sbase + SM_MISC + 8) : "memory");
                        j = min(j + (j >= 15), 63u);
                        sts32(sbase + SM_L1 + j * 4, d | ((j < 63 ? e / CE : 255u) << 16));
                        e = NB_MAX * CE + j;
                    }
                    en[0] = en[1]; en[1] = en[2]; en[2] = en[3]; en[3] = e;
                    dv[0] = dv[1]; dv[1] = dv[2]; dv[2] = dv[3]; dv[3] = d;
                    ck[0] = ck[1]; ck[1] = ck[2]; ck[2] = ck[3];
                };
                if (v == 2) { step(); step(); step(); step(); }
                else {
                    #pragma unroll 1
                    for (int k = 0; k < 4; k++) step();
                }
            }
            #pragma unroll
            for (int k = 0; k < 4; k++)
                asm volatile("st.shared.u16 [%0], %1;" :: "r"(sbase + SM_P1 + en[k] * 2), "r"(dv[k]) : "memory");
        }
    }
    if (warp == 15) {
        #pragma unroll
        for (int v = 0; v < EPT / 4; v++) sts128(sbase + SM_ENT + v * 512 + lane * 16, make_uint4(ent[4*v], ent[4*v+1], ent[4*v+2], ent[4*v+3]));
    }
    asm volatile("fence.proxy.async.shared::cta;" ::: "memory");
    WS(5);
    __syncthreads();
    if (warp == 15) {
        w_inc(gbar + 1);
        const uint32_t n = __reduce_or_sync(~0u, lds32(su + SM_MISC + 8));
        if (__builtin_expect(n > 15, 0)) {
            const uint2 r = lds64(su + SM_L1 + lane * 8);
            uint32_t m = lane < 8 ? 0 : (r.x >> 24 ? 0 : bin_bits(r.x >> 16)) | (r.y >> 24 ? 0 : bin_bits(r.y >> 16));
            m = n > 62 ? 0x7FFF3FFFu : __reduce_or_sync(~0u, m);
            sts32(su + SM_L1 + 60, m | 0x80000000u | (tag << 14));
            asm volatile("fence.proxy.async.shared::cta;" ::: "memory");
            __syncwarp();
        }
        w_st(gs + G_H1 + b * 64, su + SM_L1, 64);
        w_box_st(&tm1, b * (CE / 2), su + SM_P1);
        w_st(gs + G_L + b * 512, su + SM_L1, 256);
        asm volatile("cp.async.bulk.commit_group;" ::: "memory");
    } else {
        mbar_wait_c(su + SM_ABAR, 0);
        auto put = [&](uint32_t off, const uint32_t* uu) {
            if (off < (uint32_t)cnt) {
                const uint4 sv = lds128(sbase + SM_XU + off * 4);
                const uint32_t ss[4] = {sv.x, sv.y, sv.z, sv.w};
                #pragma unroll
                for (int k = 0; k < 4; k++) sts32(sbase + SM_P2 + uu[k] * 4, (ss[k] & 0xFFFF) | (((off + k) << 19) + (tag << 16)));
            }
        };
        #pragma unroll
        for (int v = 0; v < EPT / 4; v++) { if (v) mbar_wait_c(su + SM_ABAR + v * 8, 0); put(v * (THREADS * 4) + tid * 4, ent + 4 * v); }
        if (wg == 3) {
            const uint4 e = lds128(sbase + SM_ENT + w * 512 + lane * 16);
            const uint32_t uu[4] = {e.x, e.y, e.z, e.w};
            put(w * (THREADS * 4) + (480 + lane) * 4, uu);
        }
        asm volatile("fence.proxy.async.shared::cta;" ::: "memory");
        WS(7);
        __syncwarp();
        asm volatile("bar.arrive 12, 512;" ::: "memory");
    }
    WS(8);

    const int ngroups = (nn + 3) >> 2;
    if (warp < 12) {
        asm volatile("setmaxnreg.inc.sync.aligned.u32 152;");
        const uint32_t ab = su + SM_ABAR;
        uint32_t wf[40], wn[16];
        const uint32_t mo = sbase + (8 * (lane >> 4) + (lane & 7)) * 128 + (((2 * w + ((lane >> 3) & 1)) ^ (lane & 7)) << 4);
        const uint32_t wca = __shfl_sync(~0u, sbase + SM_WC + (16 * w + q) * 32 + t * 4 + ((q >> 2) << 4), lane), l16 = __shfl_sync(~0u, (lane & 15) * 16, lane);
        mbar_wait_c(ab + 24, 0);
        {
            #pragma unroll
            for (int ks = 0; ks < 4; ks++) { ldsm4t(wf + 4 * ks, mo + SM_WR + ks * 2048); ldsm4t(wf + 20 + 4 * ks, mo + SM_WR + 8192 + ks * 2048); ldsm4t(wn + 4 * ks, mo + SM_WR + 16384 + ks * 2048); }
            auto half = [](uint32_t& v) { asm("mul.rn.bf16x2 %0, %0, %1;" : "+r"(v) : "r"(0x3F003F00u)); };
            uint32_t z = 0;
            #pragma unroll
            for (int i = 0; i < 16; i++) { half(wf[i]); z ^= wf[i]; }
            sts32(sbase + SM_ES + lane * 4, z);
            if (wg == 2) {
                uint32_t f[4];
                ldsm4t(f, (mo ^ ((lane & 7) << 4)) + SM_WR + 24576);
                half(f[0]); half(f[1]); half(f[2]); half(f[3]);
                sts32(wca, f[0]); sts32(wca + 256, f[1]); sts32(wca ^ 16, f[2]); sts32((wca ^ 16) + 256, f[3]);
                asm volatile("fence.proxy.async.shared::cta;" ::: "memory");
            }
        }
        const uint64_t wcd = __reduce_or_sync(~0u, (((sbase + SM_WC) & 0x3FFFF) >> 4) | (8u << 16)) | EDHI;
        const uint32_t bar0 = __reduce_or_sync(~0u, sbase + SM_BARS + wg * 2 * STG);
        const uint32_t xd0 = __reduce_or_sync(~0u, (((sbase + SM_XS + wg * NSTAGE * XS_BYTES) & 0x3FFFF) >> 4) | (1u << 16));
        const uint32_t ed0 = __reduce_or_sync(~0u, (((sbase + SM_ES + wg * NSTAGE * ES_BYTES) & 0x3FFFF) >> 4) | (8u << 16));
        const uint64_t ohd = __reduce_or_sync(~0u, ((sbase + SM_OH) & 0x3FFFF) >> 4);
        const uint32_t tabx = __reduce_or_sync(~0u, sbase + SM_TAB + w * 128);
        const uint32_t bars = __reduce_or_sync(~0u, 2 * bar0 + STG), xds = __reduce_or_sync(~0u, 2 * xd0 + XS_BYTES / 16), eds = __reduce_or_sync(~0u, 2 * ed0 + ES_BYTES / 16);
        const uint32_t xuo = __reduce_or_sync(~0u, sbase + SM_XU + wg * 16384);
        { const uint2 z = lds64(sbase + SM_OH + 8); wf[38] = z.x; wf[39] = z.y; }
        WS(9);
        constexpr int NU = 6;
        const uint32_t dm = ((NPB_MAX + lane) * 4 | (tag << 14)) * 0x10001u;
        const uint32_t db = sbase + SM_DEG - (tag << 14);
        const char* const g1 = gs + (uint32_t)(b * (P1B + P2B) + tid * 8);
        int rk[NU][4];
        uint32_t spins = 0;
        {
            uint2 r1[NU];
            mbar_wait_c(ab + 80, 0);
            WS(2);
            #pragma unroll
            for (int i = 0; i < NU; i++) {
                r1[i] = make_uint2(dm, dm);
                if (NB_MIN * 16 >= 384 * (i + 1) || tid + 384 * i < nb * 16) r1[i] = lds64(sbase + SM_IDX + (tid + 384 * i) * 8);
            }
            #pragma unroll 1
            while (true) {
                uint32_t bad = 0;
                #pragma unroll
                for (int i = 0; i < NU; i++) bad |= r1[i].y ^ dm;
                if (__builtin_expect(!__any_sync(~0u, bad & 0xC000), 1)) break;
                #pragma unroll
                for (int i = 0; i < NU; i++) ld_unit(r1[i], g1 + 384 * 8 * i, (r1[i].y ^ dm) & 0xC000);
                if (++spins > (1u << 22)) break;
            }
            WS(3);
            #pragma unroll
            for (int i = 0; i < NU; i++) {
                rk[i][0] = r1[i].x & 0xFFFF; rk[i][1] = r1[i].x >> 16; rk[i][2] = r1[i].y & 0xFFFF; rk[i][3] = r1[i].y >> 16;
                #pragma unroll
                for (int k = 0; k < 4; k++) asm volatile("red.shared.add.u32 [%0], 1;" :: "r"(db + min((uint32_t)rk[i][k], NPB_MAX * 4 + (tag << 14))) : "memory");
            }
        }
        WS(10);
        asm volatile("bar.sync 11, 512;" ::: "memory");
        int mycls = 0, mycr = 0, dg = lds32(sbase + SM_DEG + tid * 4);
        if (tid < nn) {
            mycls = NCLS - 1 - (dg <= 40 ? dg : min(41 + ((dg - 41) >> 3), NCLS - 1)); mycr = atomicAdd(&cls[mycls], 1);
        }
        int s0 = 0;
        if (__builtin_expect(dg > 40, 0)) s0 = max(SLOT_CAP - ((dg + 1) & ~1) - atomicAdd(&misc[6], (dg + 1) & ~1), 0);
        asm volatile("bar.sync 1, 384;" ::: "memory");
        WS(12);
        {
            const uint2 c = lds64(sbase + SM_CLS + lane * 8);
            const int v0 = c.x * (lane > 11 ? ((64 - 2 * lane) << 16) + 1 : 1), v1 = c.y * (lane >= 11 ? ((62 - 2 * lane) << 16) + 1 : 1);
            int inc = v0 + v1;
            #pragma unroll
            for (int o = 1; o < 32; o <<= 1) { int y = __shfl_up_sync(~0u, inc, o); if (lane >= o) inc += y; }
            const int e0 = __shfl_sync(~0u, inc - v0 - v1, mycls >> 1), e1 = __shfl_sync(~0u, inc - v1, mycls >> 1);
            const int e = (mycls & 1) ? e1 : e0;
            if (tid < nn) {
                if (dg <= 40) s0 = min((e >> 16) + mycr * ((dg + 1) & ~1), SLOT_CAP - 40);
                sts32(sbase + SM_DEG + tid * 4, s0);
            }
            const uint32_t pos = tid < nn ? (e & 0xFFFF) + mycr : tid;
            sts32(sbase + SM_SORT + pos * 4, tid < nn ? (uint32_t)tid | ((uint32_t)s0 << 16) : NONE);
            asm volatile("st.shared.u16 [%0], %1;" :: "r"(sbase + SM_SDEG + pos * 2), "r"(min(dg, 65535)) : "memory");
            if (tid == 383) { misc[4] = (nn - c.y + 3) >> 2; if ((inc >> 16) + misc[6] > SLOT_CAP - 40) misc[1] = 1; }
        }
        asm volatile("bar.sync 1, 384;" ::: "memory");
        WS(13);
        const uint32_t sv = lds32(sbase + SM_SORT + tid * 4);
        const uint2 d4 = lds64(sbase + SM_SDEG + (tid >> 2) * 8);
        const uint32_t slow = lds32(sbase + SM_MISC + 4);
        #pragma unroll
        for (int i = 0; i < NU; i++) {
            #pragma unroll
            for (int k = 0; k < 4; k++) rk[i][k] = atoms_inc(db + rk[i][k]);
        }
        if (__reduce_or_sync(~0u, slow) == 0) {
            const uint32_t nd = sv & 0xFFFF;
            const int g = tid >> 2;
            dg = ((t & 2 ? d4.y : d4.x) >> (16 * (t & 1))) & 0xFFFF;
            const uint32_t hi2 = __vmaxu2(d4.x, d4.y), lo2 = __vminu2(d4.x, d4.y);
            const int mx = max(hi2 >> 16, hi2 & 0xFFFF), mn = min(lo2 >> 16, lo2 & 0xFFFF);
            int left = (mx + 1) >> 1;
            int tl = g, nx = ngroups + 4 + g, nt = left > NPMAX ? 2 : 1;
            const bool odd = left > 2 * NPMAX || (nt == 2 && nx >= TILE_CAP - TILE_X);
            if (__builtin_expect(__any_sync(~0u, odd), 0)) {
                if (odd) nt = (left + NPMAX - 1) / NPMAX;
                if (odd && t == 0) { asm volatile("atom.shared.add.u32 %0, [%1], %2;" : "=r"(nx) : "r"(sbase + SM_MISC + 20), "r"(nt - 1) : "memory"); if (nx + nt - 1 > TILE_CAP) misc[1] = 1; }
                nx = __shfl_sync(~0u, nx, lane & ~3);
                if (odd && nx + nt - 1 > TILE_CAP) left = 0;
            }
            const uint32_t w0 = tab_at(nd);
            if (g >= ngroups + 4) tl = ngroups;
            uint32_t cont = 0;
            int done = 0;
            bool act = true;
            do {
                int np = nt <= 2 ? (left + nt - 1) >> (nt - 1) : (left + nt - 1) / nt;
                left -= np; nt = max(nt - 1, 1);
                if (np) np = max(np, NPMIN);
                const int dv = min(max(dg - done, 0), 2 * np);
                uint32_t code = (uint32_t)np | cont | (left > 0 ? C_MORE : 0u);
                const bool gen = mn - done < 2 * np - (np == NPMIN ? 1 : 2);
                if (np == 0) code = 0;
                const uint32_t w1 = code | (dv == 2 * np ? 0x8000u : (2 * np - 1 - dv) << 8);
                if (act) *(uint2*)(smem + SM_TINFO + tl * 32 + t * 8) = make_uint2((dv ? (sv >> 16) + done : 0) | ((gen ? (np > 8 ? 15 : np > 5 ? 14 : 13) : np) << 16) | ((left > 0 ? nx : 0) << 20) | ((uint32_t)dv << 27), w0 | (np == 0 ? 0u : w1 << 16));
                tl = nx++; cont = C_CONT; done += 2 * np; act = left > 0;
            } while (__any_sync(~0u, act));
        }
        __syncwarp();
        asm volatile("bar.arrive 4, 512;" ::: "memory");
        WS(14);
        wf[16] = lds32(wca); wf[17] = lds32(wca + 256); wf[18] = lds32(wca ^ 16); wf[19] = lds32((wca ^ 16) + 256);
        #pragma unroll
        for (int pc = 0; pc < 3; pc++) {
            uint4 r2[2];
            mbar_wait_c(ab + pc * 8, 1);
            if (pc == 0) WS(4); if (pc == 2) WS(16);
            #pragma unroll
            for (int k = 0; k < 2; k++) {
                r2[k] = lds128(sbase + SM_P2 + (tid + 384 * (2 * pc + k)) * 16);
                if (rk[2 * pc + k][0] < 0) r2[k].w = tag << 16;
            }
            while (__builtin_expect(__any_sync(~0u, ((r2[0].w ^ (tag << 16)) | (r2[1].w ^ (tag << 16))) & 0x30000), 0)) {
                #pragma unroll
                for (int k = 0; k < 2; k++)
                    ld_unit(r2[k], g1 + (uint32_t)(tid * 8) + (P1B + 384 * 16 * (2 * pc + k)), (r2[k].w ^ (tag << 16)) & 0x30000);
                if (++spins > (1u << 22)) break;
            }
            #pragma unroll
            for (int k = 0; k < 2; k++) {
                const int i = 2 * pc + k;
                const uint32_t eb = ((tid >> 4) + 24 * i) * ch;
                place(sbase, rk[i][0], r2[k].x, eb); place(sbase, rk[i][1], r2[k].y, eb); place(sbase, rk[i][2], r2[k].z, eb); place(sbase, rk[i][3], r2[k].w, eb);
            }
        }
        WGD();
        __syncwarp();
        asm volatile("bar.arrive 3, 480;" ::: "memory");
        float g[4 * NPMAX], h[4 * NPMAX];
        float4 cyr = make_float4(0.f, 0.f, 0.f, 0.f);
        WS(15); CG(1);
        mbar_wait_c(ab + 88 + wg * 8, 0);
        auto pack = [&](uint32_t* v, const float* u) {
            #pragma unroll
            for (int i = 0; i < 16; i++) v[i] = pack_bf16(u[2*i], u[2*i+1]);
        };
        auto rows_st = [&](uint32_t p, const uint32_t* v) {
            #pragma unroll
            for (int i = 0; i < 4; i++) stsm4t(p + i * 2048, v + 4 * i);
        };
        {
            const uint64_t d0 = desc_sw128(xuo), d1 = d0 + 512;
            const uint32_t mr = sbase + wg * 16384 + w * 128 + (tab_at(8 * (lane >> 4) + (lane & 7)) ^ ((lane & 8) << 1));
            uint32_t v[16];
            node_mma(g, wn, d0); node_mma(h, wn, d1);
            TileMMA<8>::wait_g(g);
            pack(v, g); rows_st(mr + SM_TAB, v);
            TileMMA<8>::wait_h(h);
            #pragma unroll
            for (int ks = 0; ks < 4; ks++) ldsm4t(wn + 4 * ks, mo + SM_WR + 40960 + ks * 2048);
            node_mma(g, wn, d0);
            if (wg == 2) asm volatile("bar.sync 5, 384;" ::: "memory"); else asm volatile("bar.arrive 5, 384;" ::: "memory");
            pack(v, h); rows_st(mr + SM_TAB + 8192, v);
            node_mma(h, wn, d1);
            __syncwarp();
            if (lane == 0) mbar_arrive(sbase + SM_ABAR + 112);
            TileMMA<8>::wait_g(g);
            pack(v, g);
            asm volatile("bar.sync %0, 128;" :: "r"(8 + wg) : "memory");
            rows_st(mr + SM_XU, v);
            TileMMA<8>::wait_h(h);
            pack(v, h);
            asm volatile("bar.sync %0, 128;" :: "r"(8 + wg) : "memory");
            rows_st(mr + SM_XU + 8192, v);
            __syncwarp();
            if (lane == 0) mbar_arrive(sbase + SM_ABAR + 72);
            mbar_wait_c(ab + 112, 0);
            __syncwarp();
            if (__builtin_expect(__reduce_or_sync(~0u, misc[1]) != 0, 0)) { slow_bin(x, ea, src, dst, wa, wb, wc, wu, wv, out, E, node0, nn, 384); asm volatile("exit;"); }
            WS(6);
        }
        uint32_t bar = bar0, xd = xd0, ed = ed0, ph = 0;
        float pn0 = 0.f, pd0 = 1.f, pn1 = 0.f, pd1 = 1.f;
        uint4 rc;
        rc.x = lds32(sbase + SM_TINFO + wg * 32 + ((lane >> 1) & 3) * 8 + 4);
        uint32_t code = __reduce_or_sync(~0u, rc.x >> 16);
        rc.x = (rc.x & 0xFFFF) ^ ((lane & 8) << 1);
        uint32_t pst = tabx + tab_at(NONE);
        auto fetch_a = [&]() {
            asm volatile("ldmatrix.sync.aligned.m8n8.x2.trans.shared.b16 {%0,%1}, [%2];" : "=r"(wf[36]), "=r"(wf[37]) : "r"(tabx + rc.x) : "memory");
        };
        auto emit = [&]() {
            asm volatile("stmatrix.sync.aligned.m8n8.x1.trans.shared.b16 [%0], {%1};" :: "r"(pst), "r"(pack_bf16(pn0 * rcpf(pd0), pn1 * rcpf(pd1))) : "memory");
        };
        auto carry = [&]() {
            if (rc.z & C_CONT) { pn0 += cyr.x; pd0 += cyr.y; pn1 += cyr.z; pd1 += cyr.w; }
            if (rc.z & C_MORE) { cyr = make_float4(pn0, pd0 - EPS2, pn1, pd1 - EPS2); pn0 = pn1 = 0.f; pst = tabx + tab_at(NONE); }
        };
        fetch_a();
        while (true) {
            switch (code & 15) {
                default: goto finished;
#define TILE(P) { \
                    bool ok; float dmin; \
                    do { \
                        mbar_wait_c(bar, ph); \
                        TileMMA<P>::issue(g, h, wf, xd, ed | EDHI, ohd, wcd); \
                        const uint32_t eb = bar + 8; \
                        ph ^= bar != bar0; bar = bars - bar; xd = xds - xd; ed = eds - ed; \
                          \
                        asm volatile("{\n.reg .pred p;\nsetp.eq.u32 p, %0, 77;\n@p trap;\n}" :: "r"(xds) : "memory"); \
                        emit(); rc = lds128(eb + 8 + l16); \
                        TileMMA<P>::wait_g(g); fetch_a(); TileMMA<P>::wait_h(h); \
                        mbar_arrive(eb); \
                        asm volatile("add.u32 %0, %1, %2;" : "=r"(pst) : "r"(rc.y), "r"(tabx)); \
                        ok = epi_fast<P>(g, h, __uint_as_float(rc.z), __uint_as_float(rc.w), pn0, pd0, pn1, pd1, dmin); \
                    } while (__all_sync(~0u, ok)); \
                    code = __reduce_or_sync(~0u, rc.w); \
                    if (__builtin_expect(__any_sync(~0u, ((rc.z & 0x1F00) != 0) | (dmin < TAU * 2 * P)), 0)) { \
                        int dv; \
                        const uint32_t bad = unpad(rc.z, P, g[4 * P - 4], g[4 * P - 2], pd0, pd1, dv); \
                        if (bad) { \
                            float4* gh = exact_copy(bad); \
                            const bool on = (bad >> lane) & 1; \
                            epi_dump<P>(g, h, gh, su + SM_COPY, on); \
                            const float4 r = epi_exact(gh, P, dv, bad); \
                            if (on) { pn0 = r.x; pd0 = r.y; pn1 = r.z; pd1 = r.w; } \
                        } \
                    } \
                    if (code & C_BRK) { carry(); if (P != 11 && (code & 15) == P) goto L##P; } \
                    if (P == 11) {         \
                        wf[16] = lds32(wca); wf[17] = lds32(wca + 256); wf[18] = lds32(wca ^ 16); wf[19] = lds32((wca ^ 16) + 256); \
                    } }
#define CASE(P, UP, DN) case P: L##P: TILE(P) \
                    if (P > NPMIN && (code & 15) == P - 1) goto L##DN; \
                    if ((code & 15) == UP) goto L##UP; \
                    break;
                CASE(11, 11, 10) CASE(10, 11, 9) CASE(9, 10, 8) CASE(8, 9, 7) CASE(7, 8, 6) CASE(6, 7, 5) CASE(5, 6, 4) CASE(4, 5, 4)
#undef CASE
#undef TILE
            }
        }
finished:
        emit();
        __syncwarp();
        if (lane == 0) mbar_arrive(sbase + SM_ABAR + 48 + wg * 8);
    } else {
        asm volatile("setmaxnreg.dec.sync.aligned.u32 56;");
        auto x_ld = [&](int i0, int i1) {
            #pragma unroll
            for (int i = i0; i < i1; i++) w_box_ld(su + SM_XU + i * 8192, &tmx, node0 + i * 64, su + SM_ABAR + 88 + (i >> 1) * 8);
        };
        if (w < 3) {
            #pragma unroll
            for (int i = 0; i < 2; i++) { w_init(su + SM_BARS + (w * 2 + i) * STG, 64); w_init(su + SM_BARS + (w * 2 + i) * STG + 8, 128); }
            w_init(su + SM_ABAR + 48 + w * 8, 4);
            w_init(su + (w == 0 ? SM_GBAR + 96 * 8 : w == 1 ? SM_ABAR + 72 : SM_ABAR + 112), w == 0 ? 32 : 12);
        } else {
            #pragma unroll
            for (int i = 0; i < 4; i++) { w_init(su + SM_ABAR + (i < 3 ? 88 + i * 8 : 40), 1); w_expect(su + SM_ABAR + (i < 3 ? 88 + i * 8 : 40), i < 3 ? 16384 : nb * 64); }
            asm volatile("fence.mbarrier_init.release.cluster;" ::: "memory");
            w_hint(gbar + 1, all);
            asm volatile("cp.async.bulk.wait_group.read 0;" ::: "memory");
            WS(2);
            w_ld(su + SM_IDX, gs + b * (P1B + P2B), nb * (CE * 2), su + SM_ABAR + 80);
            w_ld(su + SM_H1, gs + G_H1, nb * 64, su + SM_ABAR + 120);
            asm volatile("bar.sync 12, 512;" ::: "memory");
            w_box_st(&tm2, P1B / 4 + b * CE, su + SM_P2);
            w_st(gs + G_H2 + b * 64, su + SM_P2 + P2B, 64);
            w_st(gs + G_L + b * 512 + 256, su + SM_P2 + P2B, 256);
            w_sent(gbar + 4, su + SM_MISC + 32);
            asm volatile("cp.async.bulk.commit_group;" ::: "memory");
        }
        const uint32_t ab = su + SM_ABAR;
        uint32_t todo = 0;
        const uint32_t mb = (lane & 3) == 3 ? bin_bits(b) : ~0u;
        WS(12);
        mbar_wait_c(ab + 120, 0);
        WS(13);
        {
            uint4 r[5];
            #pragma unroll
            for (int i = 0; i < 5; i++) r[i] = lds128(sbase + SM_H1 + (tid - 384 + 128 * i) * 16);
            #pragma unroll
            for (int i = 0; i < 5; i++) {
                const uint32_t bb = b << 16;
                const uint32_t m = min(min(r[i].x ^ bb, r[i].y ^ bb), min(r[i].z ^ bb, r[i].w ^ bb)) >> 16;
                if ((m == 0) | (((r[i].w ^ (tag << 14)) & 0xC000) != 0) | ((~r[i].w & mb) == 0)) todo |= 1 << i;
            }
            todo &= tid - 384 + 512 < nb * 4 ? 31 : tid - 384 + 384 < nb * 4 ? 15 : 7;
        }
        #pragma unroll 1
        for (int put = 0; put < 2; put++) {
            uint32_t any = __reduce_or_sync(~0u, todo), m = 0, u = 0;
            #pragma unroll 1
            while (any | m) {
                uint4 r = make_uint4(0, 0, 0, 0), r2 = r;
                uint32_t s, go, gd;
                bool on;
                if (__builtin_expect(m == 0, 1)) {
                    const uint32_t i = __ffs(any) - 1;
                    any &= any - 1; u = tid - 384 + 128 * i; on = (todo >> i) & 1;
                    r = lds128(sbase + SM_H1 + u * 16); r2 = lds128(sbase + SM_H2 + u * 16);
                    s = u >> 2; go = G_H1 + u * 16; gd = HB;
                } else {
                    s = ((u & ~31) + __ffs(m) - 1) >> 2; m &= m - 1; on = lane < 12;
                    go = G_L + s * 512 + 64 + lane * 16; gd = 256;
                }
                #pragma unroll 1
                for (int n = 0; n < (1 << 22); n++) {
                    const bool b1 = on && ((r.w >> 14) & 3) != tag, b2 = on && put && ((r2.w >> 16) & 3) != tag;
                    if (__builtin_expect(!__any_sync(~0u, b1 | b2), 1)) break;
                    ld_unit(r, gs + go, b1); ld_unit(r2, gs + go + gd, b2);
                }
                if (gd == HB) m = __ballot_sync(~0u, on && (~r.w & mb) == 0);
                if (on && r.w >> 16 == 255) sts32(sbase + SM_MISC + 4, 1);
                const uint32_t e[4] = {r.x, r.y, r.z, r.w}, v[4] = {r2.x, r2.y, r2.z, r2.w};
                uint32_t slot[4];
                #pragma unroll
                for (int k = 0; k < 4; k++) slot[k] = atoms_inc(sbase + SM_DEG + (on && e[k] >> 16 == (uint32_t)b ? (e[k] & 0x3FFF) : (NPB_MAX + lane) * 4));
                if (put) {
                    #pragma unroll
                    for (int k = 0; k < 4; k++) place(sbase, slot[k], v[k], s * ch);
                }
            }
            if (put == 0) {
                WS(4);
                asm volatile("bar.arrive 11, 512;" ::: "memory");
                if (w == 3) {
                    x_ld(0, 1);
                    w_expect(su + SM_ABAR, 12288); w_expect(su + SM_ABAR + 8, 12288); w_expect(su + SM_ABAR + 16, nb * (CE * 4) - 24576);
                    w_hint(gbar + 4, all);
                    asm volatile("cp.async.bulk.wait_group.read 0;" ::: "memory");
                    WS(3);
                    const char* g2 = gs + b * (P1B + P2B) + P1B;
                    w_ld(su + SM_P2, g2, 12288, su + SM_ABAR);
                    w_ld(su + SM_P2 + 12288, g2 + 12288, 12288, su + SM_ABAR + 8);
                    w_ld(su + SM_P2 + 24576, g2 + 24576, nb * (CE * 4) - 24576, su + SM_ABAR + 16);
                    w_ld(su + SM_H2, gs + G_H2, nb * 64, su + SM_ABAR + 40);
                    x_ld(1, 6);
                } else {
                    #pragma unroll 8
                    for (int i = 0; i < 32; i++) w_init(su + SM_GBAR + (w * 32 + i) * 8, 32);
                }
                asm volatile("bar.sync 4, 512;" ::: "memory");
                mbar_wait_c(ab + 40, 0);
            }
        }
        __syncwarp();
        WS(10);
        WGD();
        const uint32_t scr = sbase + SM_PAIR + (tid & 127) * 8;
        const int r4 = lane >> 3, c8 = lane & 7;
        const uint32_t sb = su;
        const uint32_t tk = ((c8 & 1) << 4) | ((c8 >> 1) << 7);
        auto row_bytes = [](uint32_t o) { return (o & 0xFE00) | ((o << 2) & 0x180); };
        if (w < 3) {
            const char* gx = as_pair((const char*)x + c8 * 16, scr);
            const char* ge = as_pair((const char*)ea + (lane & 1) * 16, scr);
            const uint32_t gx0 = (uint32_t)(uint64_t)gx, ge0 = (uint32_t)(uint64_t)ge, hi = (uint64_t)gx >> 32, he = (uint64_t)ge >> 32;
            const int s = (lane >> 1) & 3;
            const uint32_t xs0 = sb + SM_XS + w * NSTAGE * XS_BYTES;
            const uint32_t es0 = sb + SM_ES + w * NSTAGE * ES_BYTES + r4 * 64 + (((lane ^ (r4 >> 1)) & 1) << 4) + (s >> 1) * 256 + (s & 1) * 32;
            const uint32_t bars = sb + SM_BARS + w * 2 * STG;
            const uint32_t xoffA = (2 * r4) * 128 + ((c8 ^ (2 * r4)) << 4), xoffB = (2 * r4 + 1) * 128 + ((c8 ^ (2 * r4 + 1)) << 4);
            uint64_t pol;
            asm volatile("createpolicy.fractional.L2::evict_first.b64 %0, 1.0;" : "=l"(pol));
            asm volatile("bar.sync 6, 128;" ::: "memory");
            WS(15);
            uint32_t ph = 1, cur = w;
            uint32_t hist = 96 * 0x010101u;
            auto done3 = [&]() { uint32_t v = (hist >> 16) & 0xFF; asm("" : "+r"(v)); mbar_arrive(sb + SM_GBAR + v * 8); };
            const bool go = __reduce_or_sync(~0u, misc[1] == 0 && nn > 0);
            const uint32_t k32 = __shfl_sync(~0u, lane == 31 ? 0 : 32, lane), k15 = __shfl_sync(~0u, 15 | (lane & 1) << 7, lane), ca = SM_CLAIM + min(lane, 30) * 4, pa = sb + SM_TINFO + r4 * 8;
            const uint32_t pb = sb + SM_TINFO + s * 8 + 4, pc = sb + SM_TINFO + (lane & 3) * 8 + 6, xl = (lane & 8) << 1, xs = (lane & 1) << 4, ra = (lane & 15) * 16 + 16;
            auto row_of = [&](uint32_t o) { uint32_t v; asm volatile("ld.shared.u16 %0, [%1];" : "=r"(v) : "r"(pb + o) : "memory"); return v; };
            auto code_of = [&](uint32_t o) { uint32_t v; asm volatile("ld.shared.s16 %0, [%1];" : "=r"(v) : "r"(pc + o) : "memory"); return v; };
            uint32_t pw = lds32(pa + w * 32), pt = __reduce_or_sync(~0u, pw), cont = 1;
            uint4 rc = make_uint4(0, row_of(w * 32) ^ xs, code_of(w * 32) & (ONE_F | 0x1FFFu), 0);
            const uint32_t se0 = sb + SM_EID + s * 4, xab = xoffB - xoffA, das = 2 * (xs0 + xoffA) + XS_BYTES, des = 2 * es0 + ES_BYTES, brs = 2 * bars + STG;
            uint32_t br = bars, da = xs0 + xoffA, de = es0;
            #pragma unroll 1
            while (go) {
                uint32_t se, sx;
                asm("dp2a.lo.u32.u32 %0, %1, 4, %2;" : "=r"(se) : "r"(pw), "r"(se0));
                asm("dp2a.lo.u32.u32 %0, %1, 2, %2;" : "=r"(sx) : "r"(pw), "r"(sb + SM_SRC));
                const int dv = pw >> 27;
                const uint32_t db = da + xab;
                const uint32_t sel = (pt >> 16) & 15, nx = (pt >> 15) & (127 << 5);
                uint32_t g;
                auto claim = [&]() { asm volatile("atom.shared.add.u32 %0, [%1], %2;" : "=r"(g) : "r"(ca + (nx == 0 ? sb : sb + 4)), "r"(k32) : "memory"); };
                if (sel == 0) break;
                if (cont & 1) asm volatile("bar.sync 3, 480;" ::: "memory");
                switch (sel) {
#define CASE(L, P, GEN) case L: { \
                        uint32_t oe[(P + 1) / 2], o[P]; \
                        _Pragma("unroll") for (int j = 0; j < (P + 1) / 2; j++) oe[j] = lds32(se + j * 16); \
                        _Pragma("unroll") for (int j = 0; j < P; j++) o[j] = lds32(sx + j * 4); \
                        mbar_wait_h(br + 8, ph); \
                        _Pragma("unroll") for (int j = 0; j < (P + 1) / 2; j++) \
                            if (LO32) { if (!GEN && 2 * j + 2 < P) cpe<false>(he, de + j * 512, oe[j], ge0, 0, 0, pol); \
                                else if (2 * j + 1 < NPMAX || s < 2) cpe<true>(he, de + j * 512, oe[j], ge0, 4 * j + s, dv, pol); } \
                            else if (!GEN && 2 * j + 2 < P) cp16e(de + j * 512, ge, oe[j], pol); else if (2 * j + 1 < NPMAX || s < 2) cp16z<32>(de + j * 512, ge, oe[j], 4 * j + s, dv, pol); \
                        _Pragma("unroll") for (int j = 0; j < P - 1; j++) { \
                            if (LO32) { cpx<0, GEN>(hi, da + j * 1024, o[j], gx0, 2 * j, dv); cpx<1, GEN>(hi, db + j * 1024, o[j], gx0, 2 * j + 1, dv); } \
                            else if (GEN) { cp16z<128>(da + j * 1024, gx, o[j] & 0xFFFFu, 2 * j, dv, 0); cp16z<128>(db + j * 1024, gx, o[j] >> 16, 2 * j + 1, dv, 0); } \
                            else { cp16i<128>(da + j * 1024, gx, o[j] & 0xFFFFu); cp16i<128>(db + j * 1024, gx, o[j] >> 16); } } \
                        if (LO32) { cpx<0, true>(hi, da + (P - 1) * 1024, o[P - 1], gx0, 2 * P - 2, dv); cpx<1, true>(hi, db + (P - 1) * 1024, o[P - 1], gx0, 2 * P - 1, dv); } \
                        else { cp16z<128>(da + (P - 1) * 1024, gx, o[P - 1] & 0xFFFFu, 2 * P - 2, dv, 0); cp16z<128>(db + (P - 1) * 1024, gx, o[P - 1] >> 16, 2 * P - 1, dv, 0); } \
                    } break;
                    CASE(4, 4, false) CASE(5, 5, false) CASE(6, 6, false) CASE(7, 7, false) CASE(8, 8, false) CASE(9, 9, false) CASE(10, 10, false) CASE(11, 11, false)
                    CASE(15, NPMAX, true) CASE(14, 8, true) default: CASE(13, 5, true)
#undef CASE
                }
                claim();
                mbar_cp_arrive(br);
                done3();
                g = __reduce_min_sync(~0u, g);
                {
                    const uint32_t o = nx == 0 ? g : nx;
                    pw = lds32(pa + o);
                    const uint32_t ya = row_of(o), yb = code_of(o);
                    pt = __reduce_or_sync(~0u, pw);
                    const uint32_t brk = (cont | nx) > 1 ? C_BRK : 0u;
                    rc.x = ya ^ xl;
                    const uint32_t lv = brk | ((sel + (15 - NPMAX)) & 16) | (((pt >> 16) & 15) ^ sel);
                    rc.w = (yb & k15) | (lv ? 0x70000000u | brk : TAU_BITS);
                    asm volatile("st.shared.v4.u32 [%2], {%3, %0, %1, %4};\nxor.b32 %0, %5, %6;\nand.b32 %1, %7, %8;"
                                 : "+r"(rc.y), "+r"(rc.z) : "r"(br + ra), "r"(rc.x), "r"(rc.w), "r"(ya), "r"(xs), "r"(yb), "n"(ONE_F | 0x1FFFu) : "memory");
                    cont = nx;
                }
                mbar_arrive(br);
                hist = (hist << 8) | (nx == 0 ? cur : 96u);
                cur = nx == 0 ? g >> 5 : cur;
                ph ^= br != bars; br = brs - br;
                da = das - da; de = des - de;
            }
            if (cont & 1) asm volatile("bar.sync 3, 480;" ::: "memory");
            if (go) {
                mbar_wait(sb + SM_ABAR + 72, 0);
                const int g0 = 3 * max((ngroups + 2) / 3 - TR, 0) + w;
                uint32_t ro[TR], gb[TR]; uint4 xv[TR], xu[TR]; char* op[TR];
                const int gz = misc[4];
                #pragma unroll
                for (int k = 0; k < TR; k++) {
                    uint32_t nd;
                    asm volatile("ld.shared.u16 %0, [%1];" : "=r"(nd) : "r"(pa + (g0 + 3 * k) * 32 + 4) : "memory");
                    const uint32_t rb = nd == tab_at(NONE) ? 0u : row_bytes(nd);
                    xv[k] = __ldg((const uint4*)(gx + (size_t)node0 * 128 + rb));
                    op[k] = nd == tab_at(NONE) ? nullptr : (char*)out + (size_t)node0 * 128 + rb + c8 * 16;
                    ro[k] = sb + (nd ^ tk);
                    xu[k] = lds128(ro[k] + SM_XU);
                    gb[k] = __reduce_or_sync(~0u, g0 + 3 * k < gz ? sb + SM_GBAR + (g0 + 3 * k) * 8 : 0u);
                }
                #pragma unroll 1
                for (int k = 0; k < 3; k++) {
                    mbar_wait(k < 2 ? br + 8 : sb + SM_ABAR + 48 + w * 8, k < 2 ? ph : 0);
                    done3(); hist <<= 8;
                    ph ^= br != bars; br = brs - br;
                }
                #pragma unroll
                for (int k = 0; k < TR; k++) {
                    uint4 a = make_uint4(0, 0, 0, 0);
                    if (gb[k]) { mbar_wait(gb[k], 0); a = lds128(ro[k] + SM_TAB); }
                    finish(a, xu[k], xv[k]);
                    if (op[k]) *(uint4*)op[k] = a;
                }
            }
            cp_wait<0>();
        } else {
            const char* gx = as_pair((const char*)x + (size_t)node0 * 128 + c8 * 16, scr);
            const char* ob = as_pair((const char*)out + (size_t)node0 * 128 + c8 * 16, scr);
            asm volatile("bar.arrive 6, 128;" ::: "memory");
            WS(15);
            if (b == 0 && lane == 0) asm volatile("red.relaxed.gpu.global.add.u32 [%0], 1;" :: "l"(gbar) : "memory");
            if (misc[1] == 0) mbar_wait(sb + SM_ABAR + 72, 0);
            if (npb <= NPB_MAX - 4) sts32(sb + SM_MISC + 12, 0);
            const int rounds = misc[1] ? 0 : max((ngroups + 2) / 3 - TR, 0);
            const int gz = misc[4], fast = __reduce_min_sync(~0u, min(rounds, gz / 3));
            uint32_t wl = sb + SM_TINFO + r4 * 8 + 4, gbar = sb + SM_GBAR;
            auto row_at = [&](uint32_t a) { uint32_t n; asm volatile("ld.shared.u16 %0, [%1];" : "=r"(n) : "r"(a) : "memory"); return n; };
            auto fetch = [&](uint32_t n, uint4& v) {
                asm volatile("{\n.reg .b64 p;\ncvt.u64.u32 p, %5;\nadd.u64 p, p, %4;\nld.global.nc.L1::no_allocate.v4.u32 {%0,%1,%2,%3}, [p];\n}"
                             : "=r"(v.x), "=r"(v.y), "=r"(v.z), "=r"(v.w) : "l"(gx), "r"(n));
            };
            auto store = [&](uint32_t n, const uint4& a) {
                asm volatile("{\n.reg .b64 p;\ncvt.u64.u32 p, %1;\nadd.u64 p, p, %0;\nst.global.v4.u32 [p], {%2,%3,%4,%5};\n}" :: "l"(ob), "r"(n), "r"(a.x), "r"(a.y), "r"(a.z), "r"(a.w) : "memory");
            };
            uint32_t n0[3], o0[3]; uint4 x0[3];
            const uint32_t tw = __shfl_sync(~0u, tk, lane);
            if (fast) {
                #pragma unroll
                for (int r = 0; r < 3; r++) { const uint32_t v = row_at(wl + r * 32); n0[r] = row_bytes(v); o0[r] = v ^ tw; fetch(n0[r], x0[r]); }
            }
            #pragma unroll 1
            for (int k = 0; k < fast; k++) {
                wl += 96;
                #pragma unroll
                for (int r = 0; r < 3; r++) {
                    const uint32_t nd = n0[r];
                    const uint4 xu = lds128(sb + o0[r] + SM_XU);
                    const uint32_t v = row_at(wl + r * 32);
                    mbar_wait(gbar + r * 8, 0);
                    uint4 a = lds128(sb + o0[r] + SM_TAB);
                    n0[r] = row_bytes(v); o0[r] = v ^ tw;
                    finish(a, xu, x0[r]);
                    fetch(n0[r], x0[r]);
                    store(nd, a);
                }
                gbar += 24;
            }
            #pragma unroll 1
            for (int g = 3 * fast; g < 3 * rounds; g++) {
                const uint32_t v = row_at(sb + SM_TINFO + r4 * 8 + 4 + g * 32), nd = row_bytes(v), ro = sb + (v ^ tw);
                uint4 xv, a = make_uint4(0, 0, 0, 0);
                fetch(nd, xv);
                if (g < gz) { mbar_wait(sb + SM_GBAR + g * 8, 0); a = lds128(ro + SM_TAB); }
                finish(a, lds128(ro + SM_XU), xv);
                store(nd, a);
            }
        }
    }
    WS(17); WG1(); CG(2);
}

}

extern "C" void kernel_launch(void* const* d_in, const int* in_sizes, int n_in, void* d_out, int out_size) {
    const __nv_bfloat16* x = (const __nv_bfloat16*)d_in[0];
    const __nv_bfloat16* ea = (const __nv_bfloat16*)d_in[1];
    const int* src = (const int*)d_in[2];
    const int* dst = (const int*)d_in[3];
    const __nv_bfloat16* wa = (const __nv_bfloat16*)d_in[4];
    const __nv_bfloat16* wb = (const __nv_bfloat16*)d_in[5];
    const __nv_bfloat16* wc = (const __nv_bfloat16*)d_in[6];
    const __nv_bfloat16* wu = (const __nv_bfloat16*)d_in[7];
    const __nv_bfloat16* wv = (const __nv_bfloat16*)d_in[8];
    __nv_bfloat16* out = (__nv_bfloat16*)d_out;
    int N = in_sizes[0] / 64, E = in_sizes[2];
    static int sms = 0;
    static CUtensorMap tm1, tm2, tmw, tmx;
    static bool tm_ok = false;
    static void* gp = nullptr; static void* gb = nullptr;
    typedef CUresult (*EncFn)(CUtensorMap*, CUtensorMapDataType, cuuint32_t, void*, const cuuint64_t*, const cuuint64_t*, const cuuint32_t*,
                              const cuuint32_t*, CUtensorMapInterleave, CUtensorMapSwizzle, CUtensorMapL2promotion, CUtensorMapFloatOOBfill);
    static void* fn = nullptr;
    auto enc = [&](CUtensorMap* tm, const void* base, cuuint64_t cols, cuuint64_t rows, cuuint32_t bc, cuuint32_t br, CUtensorMapSwizzle sw) {
        cuuint64_t g2[2] = {cols, rows}, gs[1] = {cols * 4};
        cuuint32_t b2[2] = {bc, br}, es[2] = {1, 1};
        return ((EncFn)fn)(tm, CU_TENSOR_MAP_DATA_TYPE_UINT32, 2, (void*)base, g2, gs, b2, es, CU_TENSOR_MAP_INTERLEAVE_NONE, sw,
                           CU_TENSOR_MAP_L2_PROMOTION_NONE, CU_TENSOR_MAP_FLOAT_OOB_FILL_NONE) == CUDA_SUCCESS;
    };
    if (!sms) {
        cudaDeviceGetAttribute(&sms, cudaDevAttrMultiProcessorCount, 0);
        cudaDriverEntryPointQueryResult qr;
        cudaGetDriverEntryPoint("cuTensorMapEncodeTiled", &fn, cudaEnableDefault, &qr);
        cudaGetSymbolAddress(&gp, g_str); cudaGetSymbolAddress(&gb, g_bar);
        if (fn && gp && gb) {
            const cuuint32_t rows = sms < NB_MAX ? sms : NB_MAX;
            tm_ok = enc(&tm1, gp, (P1B + P2B) / 4, NB_MAX, CE / 2, rows, CU_TENSOR_MAP_SWIZZLE_NONE) && enc(&tm2, gp, (P1B + P2B) / 4, NB_MAX, CE, rows, CU_TENSOR_MAP_SWIZZLE_NONE);
        }
        cudaFuncSetAttribute(gcn_kernel<true>, cudaFuncAttributeMaxDynamicSharedMemorySize, SMEM_LAUNCH);
        cudaFuncSetAttribute(gcn_kernel<false>, cudaFuncAttributeMaxDynamicSharedMemorySize, SMEM_LAUNCH);
    }
    int nb = sms < NB_MAX ? sms : NB_MAX;
    int npb = (N + nb - 1) / nb;
    int ch = (((E + nb - 1) / nb) + 3) & ~3;
    const uintptr_t wp[4] = {(uintptr_t)wb, (uintptr_t)wv, (uintptr_t)wa, (uintptr_t)wu};
    uintptr_t wlo = wp[0], whi = wp[0], wal = 0;
    for (int i = 0; i < 4; i++) { wlo = wp[i] < wlo ? wp[i] : wlo; whi = wp[i] > whi ? wp[i] : whi; wal |= wp[i] - wp[0]; }
    bool ok = tm_ok && nb >= NB_MIN && npb < NPB_MAX && ch <= CH_MAX && !(E & 3) && N <= 65535 && npb >= 2 && !(wal & 127) && (whi - wlo) >> 7 < (1u << 30) &&
              !(((uintptr_t)src | (uintptr_t)dst | (uintptr_t)x | (uintptr_t)wb | (uintptr_t)wc) & 15);
    ok = ok && enc(&tmw, (const void*)wlo, 32, ((whi - wlo) >> 7) + 64, 32, 64, CU_TENSOR_MAP_SWIZZLE_128B) && enc(&tmx, x, 32, N, 32, 64, CU_TENSOR_MAP_SWIZZLE_128B);
    if (!ok) {
        int g = 1024, p = (N + g - 1) / g;
        slow_kernel<<<g, 256>>>(x, ea, src, dst, wa, wb, wc, wu, wv, out, N, E, p < 1 ? 1 : p);
        return;
    }
    int4 wrow = make_int4((int)((wp[0] - wlo) >> 7), (int)((wp[1] - wlo) >> 7), (int)((wp[2] - wlo) >> 7), (int)((wp[3] - wlo) >> 7));
    uint32_t magic = (uint32_t)((1ull << 32) / (uint32_t)npb) + 1u;
    void* args[] = {&dst, &gb, &gp, &src, &E, &ch, &N, &npb, &magic, &x, &ea, &wa, &wb, &wc, &wu, &wv, &out, &wrow, &tm1, &tm2, &tmw, &tmx};
    const bool lo32 = ((uintptr_t)x >> 32) == (((uintptr_t)x + (size_t)N * 128 - 1) >> 32) && ((uintptr_t)ea >> 32) == (((uintptr_t)ea + (size_t)E * 32 - 1) >> 32);
    cudaLaunchCooperativeKernel(lo32 && !FORCE64 ? (const void*)gcn_kernel<true> : (const void*)gcn_kernel<false>, dim3(nb), dim3(THREADS), args, SMEM_LAUNCH, cudaStreamPerThread);
}
```

```cpp
#include <cuda_runtime.h>
#include <cuda.h>
#include <cuda_bf16.h>
#include <stdint.h>

namespace {

constexpr int N_MAX = 65536;
constexpr int NPMAX = 11;
constexpr int NPMIN = 5;
constexpr int THREADS = 512;
constexpr int EPT = 12;
constexpr int CH_MAX = THREADS * EPT;
constexpr int NB_MAX = 134, NB_MIN = 120;
constexpr int CE = 64;
constexpr int P1B = NB_MAX * CE * 2;
constexpr int P2B = NB_MAX * CE * 4;
constexpr int HB = NB_MAX * 64;
constexpr int G_H1 = NB_MAX * (P1B + P2B), G_H2 = G_H1 + HB, G_L = G_H2 + HB, G_F = G_L + NB_MAX * 512;
constexpr int KM = 3, GRP_B = 1536, G_R = G_F + 2048, G_P = G_R + 2048, G_END = G_P + NB_MAX * KM * GRP_B;
#define BR1 7
#define BR2 9
#define BR3 12
#define BBIAS 175
#define FEN 1
#define PUBW 0
#define MRG 1
#define BAL 1
constexpr int R1 = BR1, R2 = BR2, R3 = BR3;
constexpr int GD = 100;
constexpr int NPB_MAX = 384;
constexpr int SLOT_CAP = 6784;
constexpr int TILE_CAP = 123;
constexpr int TILE_X = 8;
constexpr int NCLS = 64;
constexpr int NSTAGE = 2;
constexpr int PD = 300;
constexpr int TR = 2;
constexpr float LOG2E = 1.4426950408889634f;

__device__ __align__(256) uint4 g_str[G_END / 16];
__device__ __align__(128) unsigned g_bar[8];
__device__ float g_slow[N_MAX * 128];
__device__ float4 g_copy[NB_MAX * 384 * 2 * NPMAX];

#define WS(k)
#define WGD()
#define WG0()
#define WG1()
#define CG(k)
#define SMEM_LAUNCH SMEM_BYTES
#define XM 2
#define XN 6
#define XP 2
#define FORCE64 0
#define EDHI ((16ull << 32) | (3ull << 62))
template<int NP> struct TileMMA;
template<> struct TileMMA<5> {
  static __device__ __forceinline__ void issue(float* g, float* h, const uint32_t* w, uint32_t dx, uint64_t de, uint64_t dh, uint64_t dc) {
    asm volatile(
      "{\n.reg .b64 dx0, dx1, dx2, dx3;\n.reg .b32 l1, l2, l3, hx;\nmov.b32 hx, 0x40000040;\n"
      "add.u32 l1, %80, 2;\nadd.u32 l2, %80, 4;\nadd.u32 l3, %80, 6;\n"
      "mov.b64 dx0, {%80, hx};\nmov.b64 dx1, {l1, hx};\nmov.b64 dx2, {l2, hx};\nmov.b64 dx3, {l3, hx};\n"
      "wgmma.fence.sync.aligned;\n"
      "wgmma.mma_async.sync.aligned.m64n40k16.f32.bf16.bf16 {%0, %1, %2, %3, %4, %5, %6, %7, %8, %9, %10, %11, %12, %13, %14, %15, %16, %17, %18, %19}, {%76, %77, %78, %79}, %82, 0, 1, 1, 0;\n"
      "wgmma.mma_async.sync.aligned.m64n40k16.f32.bf16.bf16 {%0, %1, %2, %3, %4, %5, %6, %7, %8, %9, %10, %11, %12, %13, %14, %15, %16, %17, %18, %19}, {%56, %57, %58, %59}, %81, 1, 1, 1, 0;\n"
      "wgmma.mma_async.sync.aligned.m64n40k16.f32.bf16.bf16 {%0, %1, %2, %3, %4, %5, %6, %7, %8, %9, %10, %11, %12, %13, %14, %15, %16, %17, %18, %19}, {%40, %41, %42, %43}, dx0, 1, 1, 1, 0;\n"
      "wgmma.mma_async.sync.aligned.m64n40k16.f32.bf16.bf16 {%0, %1, %2, %3, %4, %5, %6, %7, %8, %9, %10, %11, %12, %13, %14, %15, %16, %17, %18, %19}, {%44, %45, %46, %47}, dx1, 1, 1, 1, 0;\n"
      "wgmma.mma_async.sync.aligned.m64n40k16.f32.bf16.bf16 {%0, %1, %2, %3, %4, %5, %6, %7, %8, %9, %10, %11, %12, %13, %14, %15, %16, %17, %18, %19}, {%48, %49, %50, %51}, dx2, 1, 1, 1, 0;\n"
      "wgmma.mma_async.sync.aligned.m64n40k16.f32.bf16.bf16 {%0, %1, %2, %3, %4, %5, %6, %7, %8, %9, %10, %11, %12, %13, %14, %15, %16, %17, %18, %19}, {%52, %53, %54, %55}, dx3, 1, 1, 1, 0;\n"
      "wgmma.commit_group.sync.aligned;\n"
      "wgmma.mma_async.sync.aligned.m64n40k16.f32.bf16.bf16 {%20, %21, %22, %23, %24, %25, %26, %27, %28, %29, %30, %31, %32, %33, %34, %35, %36, %37, %38, %39}, {%60, %61, %62, %63}, dx0, 0, 1, 1, 0;\n"
      "wgmma.mma_async.sync.aligned.m64n40k16.f32.bf16.bf16 {%20, %21, %22, %23, %24, %25, %26, %27, %28, %29, %30, %31, %32, %33, %34, %35, %36, %37, %38, %39}, {%64, %65, %66, %67}, dx1, 1, 1, 1, 0;\n"
      "wgmma.mma_async.sync.aligned.m64n40k16.f32.bf16.bf16 {%20, %21, %22, %23, %24, %25, %26, %27, %28, %29, %30, %31, %32, %33, %34, %35, %36, %37, %38, %39}, {%68, %69, %70, %71}, dx2, 1, 1, 1, 0;\n"
      "wgmma.mma_async.sync.aligned.m64n40k16.f32.bf16.bf16 {%20, %21, %22, %23, %24, %25, %26, %27, %28, %29, %30, %31, %32, %33, %34, %35, %36, %37, %38, %39}, {%72, %73, %74, %75}, dx3, 1, 1, 1, 0;\n"
      "wgmma.commit_group.sync.aligned;\n}\n"
      : "=f"(g[0]), "=f"(g[1]), "=f"(g[2]), "=f"(g[3]), "=f"(g[4]), "=f"(g[5]), "=f"(g[6]), "=f"(g[7]), "=f"(g[8]), "=f"(g[9]), "=f"(g[10]), "=f"(g[11]), "=f"(g[12]), "=f"(g[13]), "=f"(g[14]), "=f"(g[15]), "=f"(g[16]), "=f"(g[17]), "=f"(g[18]), "=f"(g[19]),
        "=f"(h[0]), "=f"(h[1]), "=f"(h[2]), "=f"(h[3]), "=f"(h[4]), "=f"(h[5]), "=f"(h[6]), "=f"(h[7]), "=f"(h[8]), "=f"(h[9]), "=f"(h[10]), "=f"(h[11]), "=f"(h[12]), "=f"(h[13]), "=f"(h[14]), "=f"(h[15]), "=f"(h[16]), "=f"(h[17]), "=f"(h[18]), "=f"(h[19])
      : "r"(w[0]), "r"(w[1]), "r"(w[2]), "r"(w[3]), "r"(w[4]), "r"(w[5]), "r"(w[6]), "r"(w[7]), "r"(w[8]), "r"(w[9]), "r"(w[10]), "r"(w[11]), "r"(w[12]), "r"(w[13]), "r"(w[14]), "r"(w[15]), "r"(w[16]), "r"(w[17]), "r"(w[18]), "r"(w[19]), "r"(w[20]), "r"(w[21]), "r"(w[22]), "r"(w[23]), "r"(w[24]), "r"(w[25]), "r"(w[26]), "r"(w[27]), "r"(w[28]), "r"(w[29]), "r"(w[30]), "r"(w[31]), "r"(w[32]), "r"(w[33]), "r"(w[34]), "r"(w[35]), "r"(w[36]), "r"(w[37]), "r"(w[38]), "r"(w[39]), "r"(dx), "l"(de), "l"(dh)
      : "memory");
  }
  static __device__ __forceinline__ void wait_g(float* g) {
    asm volatile("wgmma.wait_group.sync.aligned 1;\n"
      : "+f"(g[0]), "+f"(g[1]), "+f"(g[2]), "+f"(g[3]), "+f"(g[4]), "+f"(g[5]), "+f"(g[6]), "+f"(g[7]), "+f"(g[8]), "+f"(g[9]), "+f"(g[10]), "+f"(g[11]), "+f"(g[12]), "+f"(g[13]), "+f"(g[14]), "+f"(g[15]), "+f"(g[16]), "+f"(g[17]), "+f"(g[18]), "+f"(g[19])
      :: "memory");
  }
  static __device__ __forceinline__ void wait_h(float* h) {
    asm volatile("wgmma.wait_group.sync.aligned 0;\n"
      : "+f"(h[0]), "+f"(h[1]), "+f"(h[2]), "+f"(h[3]), "+f"(h[4]), "+f"(h[5]), "+f"(h[6]), "+f"(h[7]), "+f"(h[8]), "+f"(h[9]), "+f"(h[10]), "+f"(h[11]), "+f"(h[12]), "+f"(h[13]), "+f"(h[14]), "+f"(h[15]), "+f"(h[16]), "+f"(h[17]), "+f"(h[18]), "+f"(h[19])
      :: "memory");
  }
};
template<> struct TileMMA<6> {
  static __device__ __forceinline__ void issue(float* g, float* h, const uint32_t* w, uint32_t dx, uint64_t de, uint64_t dh, uint64_t dc) {
    asm volatile(
      "{\n.reg .b64 dx0, dx1, dx2, dx3;\n.reg .b32 l1, l2, l3, hx;\nmov.b32 hx, 0x40000040;\n"
      "add.u32 l1, %88, 2;\nadd.u32 l2, %88, 4;\nadd.u32 l3, %88, 6;\n"
      "mov.b64 dx0, {%88, hx};\nmov.b64 dx1, {l1, hx};\nmov.b64 dx2, {l2, hx};\nmov.b64 dx3, {l3, hx};\n"
      "wgmma.fence.sync.aligned;\n"
      "wgmma.mma_async.sync.aligned.m64n48k16.f32.bf16.bf16 {%0, %1, %2, %3, %4, %5, %6, %7, %8, %9, %10, %11, %12, %13, %14, %15, %16, %17, %18, %19, %20, %21, %22, %23}, {%84, %85, %86, %87}, %90, 0, 1, 1, 0;\n"
      "wgmma.mma_async.sync.aligned.m64n48k16.f32.bf16.bf16 {%0, %1, %2, %3, %4, %5, %6, %7, %8, %9, %10, %11, %12, %13, %14, %15, %16, %17, %18, %19, %20, %21, %22, %23}, {%64, %65, %66, %67}, %89, 1, 1, 1, 0;\n"
      "wgmma.mma_async.sync.aligned.m64n48k16.f32.bf16.bf16 {%0, %1, %2, %3, %4, %5, %6, %7, %8, %9, %10, %11, %12, %13, %14, %15, %16, %17, %18, %19, %20, %21, %22, %23}, {%48, %49, %50, %51}, dx0, 1, 1, 1, 0;\n"
      "wgmma.mma_async.sync.aligned.m64n48k16.f32.bf16.bf16 {%0, %1, %2, %3, %4, %5, %6, %7, %8, %9, %10, %11, %12, %13, %14, %15, %16, %17, %18, %19, %20, %21, %22, %23}, {%52, %53, %54, %55}, dx1, 1, 1, 1, 0;\n"
      "wgmma.mma_async.sync.aligned.m64n48k16.f32.bf16.bf16 {%0, %1, %2, %3, %4, %5, %6, %7, %8, %9, %10, %11, %12, %13, %14, %15, %16, %17, %18, %19, %20, %21, %22, %23}, {%56, %57, %58, %59}, dx2, 1, 1, 1, 0;\n"
      "wgmma.mma_async.sync.aligned.m64n48k16.f32.bf16.bf16 {%0, %1, %2, %3, %4, %5, %6, %7, %8, %9, %10, %11, %12, %13, %14, %15, %16, %17, %18, %19, %20, %21, %22, %23}, {%60, %61, %62, %63}, dx3, 1, 1, 1, 0;\n"
      "wgmma.commit_group.sync.aligned;\n"
      "wgmma.mma_async.sync.aligned.m64n48k16.f32.bf16.bf16 {%24, %25, %26, %27, %28, %29, %30, %31, %32, %33, %34, %35, %36, %37, %38, %39, %40, %41, %42, %43, %44, %45, %46, %47}, {%68, %69, %70, %71}, dx0, 0, 1, 1, 0;\n"
      "wgmma.mma_async.sync.aligned.m64n48k16.f32.bf16.bf16 {%24, %25, %26, %27, %28, %29, %30, %31, %32, %33, %34, %35, %36, %37, %38, %39, %40, %41, %42, %43, %44, %45, %46, %47}, {%72, %73, %74, %75}, dx1, 1, 1, 1, 0;\n"
      "wgmma.mma_async.sync.aligned.m64n48k16.f32.bf16.bf16 {%24, %25, %26, %27, %28, %29, %30, %31, %32, %33, %34, %35, %36, %37, %38, %39, %40, %41, %42, %43, %44, %45, %46, %47}, {%76, %77, %78, %79}, dx2, 1, 1, 1, 0;\n"
      "wgmma.mma_async.sync.aligned.m64n48k16.f32.bf16.bf16 {%24, %25, %26, %27, %28, %29, %30, %31, %32, %33, %34, %35, %36, %37, %38, %39, %40, %41, %42, %43, %44, %45, %46, %47}, {%80, %81, %82, %83}, dx3, 1, 1, 1, 0;\n"
      "wgmma.commit_group.sync.aligned;\n}\n"
      : "=f"(g[0]), "=f"(g[1]), "=f"(g[2]), "=f"(g[3]), "=f"(g[4]), "=f"(g[5]), "=f"(g[6]), "=f"(g[7]), "=f"(g[8]), "=f"(g[9]), "=f"(g[10]), "=f"(g[11]), "=f"(g[12]), "=f"(g[13]), "=f"(g[14]), "=f"(g[15]), "=f"(g[16]), "=f"(g[17]), "=f"(g[18]), "=f"(g[19]), "=f"(g[20]), "=f"(g[21]), "=f"(g[22]), "=f"(g[23]),
        "=f"(h[0]), "=f"(h[1]), "=f"(h[2]), "=f"(h[3]), "=f"(h[4]), "=f"(h[5]), "=f"(h[6]), "=f"(h[7]), "=f"(h[8]), "=f"(h[9]), "=f"(h[10]), "=f"(h[11]), "=f"(h[12]), "=f"(h[13]), "=f"(h[14]), "=f"(h[15]), "=f"(h[16]), "=f"(h[17]), "=f"(h[18]), "=f"(h[19]), "=f"(h[20]), "=f"(h[21]), "=f"(h[22]), "=f"(h[23])
      : "r"(w[0]), "r"(w[1]), "r"(w[2]), "r"(w[3]), "r"(w[4]), "r"(w[5]), "r"(w[6]), "r"(w[7]), "r"(w[8]), "r"(w[9]), "r"(w[10]), "r"(w[11]), "r"(w[12]), "r"(w[13]), "r"(w[14]), "r"(w[15]), "r"(w[16]), "r"(w[17]), "r"(w[18]), "r"(w[19]), "r"(w[20]), "r"(w[21]), "r"(w[22]), "r"(w[23]), "r"(w[24]), "r"(w[25]), "r"(w[26]), "r"(w[27]), "r"(w[28]), "r"(w[29]), "r"(w[30]), "r"(w[31]), "r"(w[32]), "r"(w[33]), "r"(w[34]), "r"(w[35]), "r"(w[36]), "r"(w[37]), "r"(w[38]), "r"(w[39]), "r"(dx), "l"(de), "l"(dh)
      : "memory");
  }
  static __device__ __forceinline__ void wait_g(float* g) {
    asm volatile("wgmma.wait_group.sync.aligned 1;\n"
      : "+f"(g[0]), "+f"(g[1]), "+f"(g[2]), "+f"(g[3]), "+f"(g[4]), "+f"(g[5]), "+f"(g[6]), "+f"(g[7]), "+f"(g[8]), "+f"(g[9]), "+f"(g[10]), "+f"(g[11]), "+f"(g[12]), "+f"(g[13]), "+f"(g[14]), "+f"(g[15]), "+f"(g[16]), "+f"(g[17]), "+f"(g[18]), "+f"(g[19]), "+f"(g[20]), "+f"(g[21]), "+f"(g[22]), "+f"(g[23])
      :: "memory");
  }
  static __device__ __forceinline__ void wait_h(float* h) {
    asm volatile("wgmma.wait_group.sync.aligned 0;\n"
      : "+f"(h[0]), "+f"(h[1]), "+f"(h[2]), "+f"(h[3]), "+f"(h[4]), "+f"(h[5]), "+f"(h[6]), "+f"(h[7]), "+f"(h[8]), "+f"(h[9]), "+f"(h[10]), "+f"(h[11]), "+f"(h[12]), "+f"(h[13]), "+f"(h[14]), "+f"(h[15]), "+f"(h[16]), "+f"(h[17]), "+f"(h[18]), "+f"(h[19]), "+f"(h[20]), "+f"(h[21]), "+f"(h[22]), "+f"(h[23])
      :: "memory");
  }
};
template<> struct TileMMA<7> {
  static __device__ __forceinline__ void issue(float* g, float* h, const uint32_t* w, uint32_t dx, uint64_t de, uint64_t dh, uint64_t dc) {
    asm volatile(
      "{\n.reg .b64 dx0, dx1, dx2, dx3;\n.reg .b32 l1, l2, l3, hx;\nmov.b32 hx, 0x40000040;\n"
      "add.u32 l1, %96, 2;\nadd.u32 l2, %96, 4;\nadd.u32 l3, %96, 6;\n"
      "mov.b64 dx0, {%96, hx};\nmov.b64 dx1, {l1, hx};\nmov.b64 dx2, {l2, hx};\nmov.b64 dx3, {l3, hx};\n"
      "wgmma.fence.sync.aligned;\n"
      "wgmma.mma_async.sync.aligned.m64n56k16.f32.bf16.bf16 {%0, %1, %2, %3, %4, %5, %6, %7, %8, %9, %10, %11, %12, %13, %14, %15, %16, %17, %18, %19, %20, %21, %22, %23, %24, %25, %26, %27}, {%92, %93, %94, %95}, %98, 0, 1, 1, 0;\n"
      "wgmma.mma_async.sync.aligned.m64n56k16.f32.bf16.bf16 {%0, %1, %2, %3, %4, %5, %6, %7, %8, %9, %10, %11, %12, %13, %14, %15, %16, %17, %18, %19, %20, %21, %22, %23, %24, %25, %26, %27}, {%72, %73, %74, %75}, %97, 1, 1, 1, 0;\n"
      "wgmma.mma_async.sync.aligned.m64n56k16.f32.bf16.bf16 {%0, %1, %2, %3, %4, %5, %6, %7, %8, %9, %10, %11, %12, %13, %14, %15, %16, %17, %18, %19, %20, %21, %22, %23, %24, %25, %26, %27}, {%56, %57, %58, %59}, dx0, 1, 1, 1, 0;\n"
      "wgmma.mma_async.sync.aligned.m64n56k16.f32.bf16.bf16 {%0, %1, %2, %3, %4, %5, %6, %7, %8, %9, %10, %11, %12, %13, %14, %15, %16, %17, %18, %19, %20, %21, %22, %23, %24, %25, %26, %27}, {%60, %61, %62, %63}, dx1, 1, 1, 1, 0;\n"
      "wgmma.mma_async.sync.aligned.m64n56k16.f32.bf16.bf16 {%0, %1, %2, %3, %4, %5, %6, %7, %8, %9, %10, %11, %12, %13, %14, %15, %16, %17, %18, %19, %20, %21, %22, %23, %24, %25, %26, %27}, {%64, %65, %66, %67}, dx2, 1, 1, 1, 0;\n"
      "wgmma.mma_async.sync.aligned.m64n56k16.f32.bf16.bf16 {%0, %1, %2, %3, %4, %5, %6, %7, %8, %9, %10, %11, %12, %13, %14, %15, %16, %17, %18, %19, %20, %21, %22, %23, %24, %25, %26, %27}, {%68, %69, %70, %71}, dx3, 1, 1, 1, 0;\n"
      "wgmma.commit_group.sync.aligned;\n"
      "wgmma.mma_async.sync.aligned.m64n56k16.f32.bf16.bf16 {%28, %29, %30, %31, %32, %33, %34, %35, %36, %37, %38, %39, %40, %41, %42, %43, %44, %45, %46, %47, %48, %49, %50, %51, %52, %53, %54, %55}, {%76, %77, %78, %79}, dx0, 0, 1, 1, 0;\n"
      "wgmma.mma_async.sync.aligned.m64n56k16.f32.bf16.bf16 {%28, %29, %30, %31, %32, %33, %34, %35, %36, %37, %38, %39, %40, %41, %42, %43, %44, %45, %46, %47, %48, %49, %50, %51, %52, %53, %54, %55}, {%80, %81, %82, %83}, dx1, 1, 1, 1, 0;\n"
      "wgmma.mma_async.sync.aligned.m64n56k16.f32.bf16.bf16 {%28, %29, %30, %31, %32, %33, %34, %35, %36, %37, %38, %39, %40, %41, %42, %43, %44, %45, %46, %47, %48, %49, %50, %51, %52, %53, %54, %55}, {%84, %85, %86, %87}, dx2, 1, 1, 1, 0;\n"
      "wgmma.mma_async.sync.aligned.m64n56k16.f32.bf16.bf16 {%28, %29, %30, %31, %32, %33, %34, %35, %36, %37, %38, %39, %40, %41, %42, %43, %44, %45, %46, %47, %48, %49, %50, %51, %52, %53, %54, %55}, {%88, %89, %90, %91}, dx3, 1, 1, 1, 0;\n"
      "wgmma.commit_group.sync.aligned;\n}\n"
      : "=f"(g[0]), "=f"(g[1]), "=f"(g[2]), "=f"(g[3]), "=f"(g[4]), "=f"(g[5]), "=f"(g[6]), "=f"(g[7]), "=f"(g[8]), "=f"(g[9]), "=f"(g[10]), "=f"(g[11]), "=f"(g[12]), "=f"(g[13]), "=f"(g[14]), "=f"(g[15]), "=f"(g[16]), "=f"(g[17]), "=f"(g[18]), "=f"(g[19]), "=f"(g[20]), "=f"(g[21]), "=f"(g[22]), "=f"(g[23]), "=f"(g[24]), "=f"(g[25]), "=f"(g[26]), "=f"(g[27]),
        "=f"(h[0]), "=f"(h[1]), "=f"(h[2]), "=f"(h[3]), "=f"(h[4]), "=f"(h[5]), "=f"(h[6]), "=f"(h[7]), "=f"(h[8]), "=f"(h[9]), "=f"(h[10]), "=f"(h[11]), "=f"(h[12]), "=f"(h[13]), "=f"(h[14]), "=f"(h[15]), "=f"(h[16]), "=f"(h[17]), "=f"(h[18]), "=f"(h[19]), "=f"(h[20]), "=f"(h[21]), "=f"(h[22]), "=f"(h[23]), "=f"(h[24]), "=f"(h[25]), "=f"(h[26]), "=f"(h[27])
      : "r"(w[0]), "r"(w[1]), "r"(w[2]), "r"(w[3]), "r"(w[4]), "r"(w[5]), "r"(w[6]), "r"(w[7]), "r"(w[8]), "r"(w[9]), "r"(w[10]), "r"(w[11]), "r"(w[12]), "r"(w[13]), "r"(w[14]), "r"(w[15]), "r"(w[16]), "r"(w[17]), "r"(w[18]), "r"(w[19]), "r"(w[20]), "r"(w[21]), "r"(w[22]), "r"(w[23]), "r"(w[24]), "r"(w[25]), "r"(w[26]), "r"(w[27]), "r"(w[28]), "r"(w[29]), "r"(w[30]), "r"(w[31]), "r"(w[32]), "r"(w[33]), "r"(w[34]), "r"(w[35]), "r"(w[36]), "r"(w[37]), "r"(w[38]), "r"(w[39]), "r"(dx), "l"(de), "l"(dh)
      : "memory");
  }
  static __device__ __forceinline__ void wait_g(float* g) {
    asm volatile("wgmma.wait_group.sync.aligned 1;\n"
      : "+f"(g[0]), "+f"(g[1]), "+f"(g[2]), "+f"(g[3]), "+f"(g[4]), "+f"(g[5]), "+f"(g[6]), "+f"(g[7]), "+f"(g[8]), "+f"(g[9]), "+f"(g[10]), "+f"(g[11]), "+f"(g[12]), "+f"(g[13]), "+f"(g[14]), "+f"(g[15]), "+f"(g[16]), "+f"(g[17]), "+f"(g[18]), "+f"(g[19]), "+f"(g[20]), "+f"(g[21]), "+f"(g[22]), "+f"(g[23]), "+f"(g[24]), "+f"(g[25]), "+f"(g[26]), "+f"(g[27])
      :: "memory");
  }
  static __device__ __forceinline__ void wait_h(float* h) {
    asm volatile("wgmma.wait_group.sync.aligned 0;\n"
      : "+f"(h[0]), "+f"(h[1]), "+f"(h[2]), "+f"(h[3]), "+f"(h[4]), "+f"(h[5]), "+f"(h[6]), "+f"(h[7]), "+f"(h[8]), "+f"(h[9]), "+f"(h[10]), "+f"(h[11]), "+f"(h[12]), "+f"(h[13]), "+f"(h[14]), "+f"(h[15]), "+f"(h[16]), "+f"(h[17]), "+f"(h[18]), "+f"(h[19]), "+f"(h[20]), "+f"(h[21]), "+f"(h[22]), "+f"(h[23]), "+f"(h[24]), "+f"(h[25]), "+f"(h[26]), "+f"(h[27])
      :: "memory");
  }
};
template<> struct TileMMA<8> {
  static __device__ __forceinline__ void issue(float* g, float* h, const uint32_t* w, uint32_t dx, uint64_t de, uint64_t dh, uint64_t dc) {
    asm volatile(
      "{\n.reg .b64 dx0, dx1, dx2, dx3;\n.reg .b32 l1, l2, l3, hx;\nmov.b32 hx, 0x40000040;\n"
      "add.u32 l1, %104, 2;\nadd.u32 l2, %104, 4;\nadd.u32 l3, %104, 6;\n"
      "mov.b64 dx0, {%104, hx};\nmov.b64 dx1, {l1, hx};\nmov.b64 dx2, {l2, hx};\nmov.b64 dx3, {l3, hx};\n"
      "wgmma.fence.sync.aligned;\n"
      "wgmma.mma_async.sync.aligned.m64n64k16.f32.bf16.bf16 {%0, %1, %2, %3, %4, %5, %6, %7, %8, %9, %10, %11, %12, %13, %14, %15, %16, %17, %18, %19, %20, %21, %22, %23, %24, %25, %26, %27, %28, %29, %30, %31}, {%100, %101, %102, %103}, %106, 0, 1, 1, 0;\n"
      "wgmma.mma_async.sync.aligned.m64n64k16.f32.bf16.bf16 {%0, %1, %2, %3, %4, %5, %6, %7, %8, %9, %10, %11, %12, %13, %14, %15, %16, %17, %18, %19, %20, %21, %22, %23, %24, %25, %26, %27, %28, %29, %30, %31}, {%80, %81, %82, %83}, %105, 1, 1, 1, 0;\n"
      "wgmma.mma_async.sync.aligned.m64n64k16.f32.bf16.bf16 {%0, %1, %2, %3, %4, %5, %6, %7, %8, %9, %10, %11, %12, %13, %14, %15, %16, %17, %18, %19, %20, %21, %22, %23, %24, %25, %26, %27, %28, %29, %30, %31}, {%64, %65, %66, %67}, dx0, 1, 1, 1, 0;\n"
      "wgmma.mma_async.sync.aligned.m64n64k16.f32.bf16.bf16 {%0, %1, %2, %3, %4, %5, %6, %7, %8, %9, %10, %11, %12, %13, %14, %15, %16, %17, %18, %19, %20, %21, %22, %23, %24, %25, %26, %27, %28, %29, %30, %31}, {%68, %69, %70, %71}, dx1, 1, 1, 1, 0;\n"
      "wgmma.mma_async.sync.aligned.m64n64k16.f32.bf16.bf16 {%0, %1, %2, %3, %4, %5, %6, %7, %8, %9, %10, %11, %12, %13, %14, %15, %16, %17, %18, %19, %20, %21, %22, %23, %24, %25, %26, %27, %28, %29, %30, %31}, {%72, %73, %74, %75}, dx2, 1, 1, 1, 0;\n"
      "wgmma.mma_async.sync.aligned.m64n64k16.f32.bf16.bf16 {%0, %1, %2, %3, %4, %5, %6, %7, %8, %9, %10, %11, %12, %13, %14, %15, %16, %17, %18, %19, %20, %21, %22, %23, %24, %25, %26, %27, %28, %29, %30, %31}, {%76, %77, %78, %79}, dx3, 1, 1, 1, 0;\n"
      "wgmma.commit_group.sync.aligned;\n"
      "wgmma.mma_async.sync.aligned.m64n64k16.f32.bf16.bf16 {%32, %33, %34, %35, %36, %37, %38, %39, %40, %41, %42, %43, %44, %45, %46, %47, %48, %49, %50, %51, %52, %53, %54, %55, %56, %57, %58, %59, %60, %61, %62, %63}, {%84, %85, %86, %87}, dx0, 0, 1, 1, 0;\n"
      "wgmma.mma_async.sync.aligned.m64n64k16.f32.bf16.bf16 {%32, %33, %34, %35, %36, %37, %38, %39, %40, %41, %42, %43, %44, %45, %46, %47, %48, %49, %50, %51, %52, %53, %54, %55, %56, %57, %58, %59, %60, %61, %62, %63}, {%88, %89, %90, %91}, dx1, 1, 1, 1, 0;\n"
      "wgmma.mma_async.sync.aligned.m64n64k16.f32.bf16.bf16 {%32, %33, %34, %35, %36, %37, %38, %39, %40, %41, %42, %43, %44, %45, %46, %47, %48, %49, %50, %51, %52, %53, %54, %55, %56, %57, %58, %59, %60, %61, %62, %63}, {%92, %93, %94, %95}, dx2, 1, 1, 1, 0;\n"
      "wgmma.mma_async.sync.aligned.m64n64k16.f32.bf16.bf16 {%32, %33, %34, %35, %36, %37, %38, %39, %40, %41, %42, %43, %44, %45, %46, %47, %48, %49, %50, %51, %52, %53, %54, %55, %56, %57, %58, %59, %60, %61, %62, %63}, {%96, %97, %98, %99}, dx3, 1, 1, 1, 0;\n"
      "wgmma.commit_group.sync.aligned;\n}\n"
      : "=f"(g[0]), "=f"(g[1]), "=f"(g[2]), "=f"(g[3]), "=f"(g[4]), "=f"(g[5]), "=f"(g[6]), "=f"(g[7]), "=f"(g[8]), "=f"(g[9]), "=f"(g[10]), "=f"(g[11]), "=f"(g[12]), "=f"(g[13]), "=f"(g[14]), "=f"(g[15]), "=f"(g[16]), "=f"(g[17]), "=f"(g[18]), "=f"(g[19]), "=f"(g[20]), "=f"(g[21]), "=f"(g[22]), "=f"(g[23]), "=f"(g[24]), "=f"(g[25]), "=f"(g[26]), "=f"(g[27]), "=f"(g[28]), "=f"(g[29]), "=f"(g[30]), "=f"(g[31]),
        "=f"(h[0]), "=f"(h[1]), "=f"(h[2]), "=f"(h[3]), "=f"(h[4]), "=f"(h[5]), "=f"(h[6]), "=f"(h[7]), "=f"(h[8]), "=f"(h[9]), "=f"(h[10]), "=f"(h[11]), "=f"(h[12]), "=f"(h[13]), "=f"(h[14]), "=f"(h[15]), "=f"(h[16]), "=f"(h[17]), "=f"(h[18]), "=f"(h[19]), "=f"(h[20]), "=f"(h[21]), "=f"(h[22]), "=f"(h[23]), "=f"(h[24]), "=f"(h[25]), "=f"(h[26]), "=f"(h[27]), "=f"(h[28]), "=f"(h[29]), "=f"(h[30]), "=f"(h[31])
      : "r"(w[0]), "r"(w[1]), "r"(w[2]), "r"(w[3]), "r"(w[4]), "r"(w[5]), "r"(w[6]), "r"(w[7]), "r"(w[8]), "r"(w[9]), "r"(w[10]), "r"(w[11]), "r"(w[12]), "r"(w[13]), "r"(w[14]), "r"(w[15]), "r"(w[16]), "r"(w[17]), "r"(w[18]), "r"(w[19]), "r"(w[20]), "r"(w[21]), "r"(w[22]), "r"(w[23]), "r"(w[24]), "r"(w[25]), "r"(w[26]), "r"(w[27]), "r"(w[28]), "r"(w[29]), "r"(w[30]), "r"(w[31]), "r"(w[32]), "r"(w[33]), "r"(w[34]), "r"(w[35]), "r"(w[36]), "r"(w[37]), "r"(w[38]), "r"(w[39]), "r"(dx), "l"(de), "l"(dh)
      : "memory");
  }
  static __device__ __forceinline__ void wait_g(float* g) {
    asm volatile("wgmma.wait_group.sync.aligned 1;\n"
      : "+f"(g[0]), "+f"(g[1]), "+f"(g[2]), "+f"(g[3]), "+f"(g[4]), "+f"(g[5]), "+f"(g[6]), "+f"(g[7]), "+f"(g[8]), "+f"(g[9]), "+f"(g[10]), "+f"(g[11]), "+f"(g[12]), "+f"(g[13]), "+f"(g[14]), "+f"(g[15]), "+f"(g[16]), "+f"(g[17]), "+f"(g[18]), "+f"(g[19]), "+f"(g[20]), "+f"(g[21]), "+f"(g[22]), "+f"(g[23]), "+f"(g[24]), "+f"(g[25]), "+f"(g[26]), "+f"(g[27]), "+f"(g[28]), "+f"(g[29]), "+f"(g[30]), "+f"(g[31])
      :: "memory");
  }
  static __device__ __forceinline__ void wait_h(float* h) {
    asm volatile("wgmma.wait_group.sync.aligned 0;\n"
      : "+f"(h[0]), "+f"(h[1]), "+f"(h[2]), "+f"(h[3]), "+f"(h[4]), "+f"(h[5]), "+f"(h[6]), "+f"(h[7]), "+f"(h[8]), "+f"(h[9]), "+f"(h[10]), "+f"(h[11]), "+f"(h[12]), "+f"(h[13]), "+f"(h[14]), "+f"(h[15]), "+f"(h[16]), "+f"(h[17]), "+f"(h[18]), "+f"(h[19]), "+f"(h[20]), "+f"(h[21]), "+f"(h[22]), "+f"(h[23]), "+f"(h[24]), "+f"(h[25]), "+f"(h[26]), "+f"(h[27]), "+f"(h[28]), "+f"(h[29]), "+f"(h[30]), "+f"(h[31])
      :: "memory");
  }
};
template<> struct TileMMA<9> {
  static __device__ __forceinline__ void issue(float* g, float* h, const uint32_t* w, uint32_t dx, uint64_t de, uint64_t dh, uint64_t dc) {
    asm volatile(
      "{\n.reg .b64 dx0, dx1, dx2, dx3;\n.reg .b32 l1, l2, l3, hx;\nmov.b32 hx, 0x40000040;\n"
      "add.u32 l1, %112, 2;\nadd.u32 l2, %112, 4;\nadd.u32 l3, %112, 6;\n"
      "mov.b64 dx0, {%112, hx};\nmov.b64 dx1, {l1, hx};\nmov.b64 dx2, {l2, hx};\nmov.b64 dx3, {l3, hx};\n"
      "wgmma.fence.sync.aligned;\n"
      "wgmma.mma_async.sync.aligned.m64n72k16.f32.bf16.bf16 {%0, %1, %2, %3, %4, %5, %6, %7, %8, %9, %10, %11, %12, %13, %14, %15, %16, %17, %18, %19, %20, %21, %22, %23, %24, %25, %26, %27, %28, %29, %30, %31, %32, %33, %34, %35}, {%108, %109, %110, %111}, %114, 0, 1, 1, 0;\n"
      "wgmma.mma_async.sync.aligned.m64n72k16.f32.bf16.bf16 {%0, %1, %2, %3, %4, %5, %6, %7, %8, %9, %10, %11, %12, %13, %14, %15, %16, %17, %18, %19, %20, %21, %22, %23, %24, %25, %26, %27, %28, %29, %30, %31, %32, %33, %34, %35}, {%88, %89, %90, %91}, %113, 1, 1, 1, 0;\n"
      "wgmma.mma_async.sync.aligned.m64n72k16.f32.bf16.bf16 {%0, %1, %2, %3, %4, %5, %6, %7, %8, %9, %10, %11, %12, %13, %14, %15, %16, %17, %18, %19, %20, %21, %22, %23, %24, %25, %26, %27, %28, %29, %30, %31, %32, %33, %34, %35}, {%72, %73, %74, %75}, dx0, 1, 1, 1, 0;\n"
      "wgmma.mma_async.sync.aligned.m64n72k16.f32.bf16.bf16 {%0, %1, %2, %3, %4, %5, %6, %7, %8, %9, %10, %11, %12, %13, %14, %15, %16, %17, %18, %19, %20, %21, %22, %23, %24, %25, %26, %27, %28, %29, %30, %31, %32, %33, %34, %35}, {%76, %77, %78, %79}, dx1, 1, 1, 1, 0;\n"
      "wgmma.mma_async.sync.aligned.m64n72k16.f32.bf16.bf16 {%0, %1, %2, %3, %4, %5, %6, %7, %8, %9, %10, %11, %12, %13, %14, %15, %16, %17, %18, %19, %20, %21, %22, %23, %24, %25, %26, %27, %28, %29, %30, %31, %32, %33, %34, %35}, {%80, %81, %82, %83}, dx2, 1, 1, 1, 0;\n"
      "wgmma.mma_async.sync.aligned.m64n72k16.f32.bf16.bf16 {%0, %1, %2, %3, %4, %5, %6, %7, %8, %9, %10, %11, %12, %13, %14, %15, %16, %17, %18, %19, %20, %21, %22, %23, %24, %25, %26, %27, %28, %29, %30, %31, %32, %33, %34, %35}, {%84, %85, %86, %87}, dx3, 1, 1, 1, 0;\n"
      "wgmma.commit_group.sync.aligned;\n"
      "wgmma.mma_async.sync.aligned.m64n72k16.f32.bf16.bf16 {%36, %37, %38, %39, %40, %41, %42, %43, %44, %45, %46, %47, %48, %49, %50, %51, %52, %53, %54, %55, %56, %57, %58, %59, %60, %61, %62, %63, %64, %65, %66, %67, %68, %69, %70, %71}, {%92, %93, %94, %95}, dx0, 0, 1, 1, 0;\n"
      "wgmma.mma_async.sync.aligned.m64n72k16.f32.bf16.bf16 {%36, %37, %38, %39, %40, %41, %42, %43, %44, %45, %46, %47, %48, %49, %50, %51, %52, %53, %54, %55, %56, %57, %58, %59, %60, %61, %62, %63, %64, %65, %66, %67, %68, %69, %70, %71}, {%96, %97, %98, %99}, dx1, 1, 1, 1, 0;\n"
      "wgmma.mma_async.sync.aligned.m64n72k16.f32.bf16.bf16 {%36, %37, %38, %39, %40, %41, %42, %43, %44, %45, %46, %47, %48, %49, %50, %51, %52, %53, %54, %55, %56, %57, %58, %59, %60, %61, %62, %63, %64, %65, %66, %67, %68, %69, %70, %71}, {%100, %101, %102, %103}, dx2, 1, 1, 1, 0;\n"
      "wgmma.mma_async.sync.aligned.m64n72k16.f32.bf16.bf16 {%36, %37, %38, %39, %40, %41, %42, %43, %44, %45, %46, %47, %48, %49, %50, %51, %52, %53, %54, %55, %56, %57, %58, %59, %60, %61, %62, %63, %64, %65, %66, %67, %68, %69, %70, %71}, {%104, %105, %106, %107}, dx3, 1, 1, 1, 0;\n"
      "wgmma.commit_group.sync.aligned;\n}\n"
      : "=f"(g[0]), "=f"(g[1]), "=f"(g[2]), "=f"(g[3]), "=f"(g[4]), "=f"(g[5]), "=f"(g[6]), "=f"(g[7]), "=f"(g[8]), "=f"(g[9]), "=f"(g[10]), "=f"(g[11]), "=f"(g[12]), "=f"(g[13]), "=f"(g[14]), "=f"(g[15]), "=f"(g[16]), "=f"(g[17]), "=f"(g[18]), "=f"(g[19]), "=f"(g[20]), "=f"(g[21]), "=f"(g[22]), "=f"(g[23]), "=f"(g[24]), "=f"(g[25]), "=f"(g[26]), "=f"(g[27]), "=f"(g[28]), "=f"(g[29]), "=f"(g[30]), "=f"(g[31]), "=f"(g[32]), "=f"(g[33]), "=f"(g[34]), "=f"(g[35]),
        "=f"(h[0]), "=f"(h[1]), "=f"(h[2]), "=f"(h[3]), "=f"(h[4]), "=f"(h[5]), "=f"(h[6]), "=f"(h[7]), "=f"(h[8]), "=f"(h[9]), "=f"(h[10]), "=f"(h[11]), "=f"(h[12]), "=f"(h[13]), "=f"(h[14]), "=f"(h[15]), "=f"(h[16]), "=f"(h[17]), "=f"(h[18]), "=f"(h[19]), "=f"(h[20]), "=f"(h[21]), "=f"(h[22]), "=f"(h[23]), "=f"(h[24]), "=f"(h[25]), "=f"(h[26]), "=f"(h[27]), "=f"(h[28]), "=f"(h[29]), "=f"(h[30]), "=f"(h[31]), "=f"(h[32]), "=f"(h[33]), "=f"(h[34]), "=f"(h[35])
      : "r"(w[0]), "r"(w[1]), "r"(w[2]), "r"(w[3]), "r"(w[4]), "r"(w[5]), "r"(w[6]), "r"(w[7]), "r"(w[8]), "r"(w[9]), "r"(w[10]), "r"(w[11]), "r"(w[12]), "r"(w[13]), "r"(w[14]), "r"(w[15]), "r"(w[16]), "r"(w[17]), "r"(w[18]), "r"(w[19]), "r"(w[20]), "r"(w[21]), "r"(w[22]), "r"(w[23]), "r"(w[24]), "r"(w[25]), "r"(w[26]), "r"(w[27]), "r"(w[28]), "r"(w[29]), "r"(w[30]), "r"(w[31]), "r"(w[32]), "r"(w[33]), "r"(w[34]), "r"(w[35]), "r"(w[36]), "r"(w[37]), "r"(w[38]), "r"(w[39]), "r"(dx), "l"(de), "l"(dh)
      : "memory");
  }
  static __device__ __forceinline__ void wait_g(float* g) {
    asm volatile("wgmma.wait_group.sync.aligned 1;\n"
      : "+f"(g[0]), "+f"(g[1]), "+f"(g[2]), "+f"(g[3]), "+f"(g[4]), "+f"(g[5]), "+f"(g[6]), "+f"(g[7]), "+f"(g[8]), "+f"(g[9]), "+f"(g[10]), "+f"(g[11]), "+f"(g[12]), "+f"(g[13]), "+f"(g[14]), "+f"(g[15]), "+f"(g[16]), "+f"(g[17]), "+f"(g[18]), "+f"(g[19]), "+f"(g[20]), "+f"(g[21]), "+f"(g[22]), "+f"(g[23]), "+f"(g[24]), "+f"(g[25]), "+f"(g[26]), "+f"(g[27]), "+f"(g[28]), "+f"(g[29]), "+f"(g[30]), "+f"(g[31]), "+f"(g[32]), "+f"(g[33]), "+f"(g[34]), "+f"(g[35])
      :: "memory");
  }
  static __device__ __forceinline__ void wait_h(float* h) {
    asm volatile("wgmma.wait_group.sync.aligned 0;\n"
      : "+f"(h[0]), "+f"(h[1]), "+f"(h[2]), "+f"(h[3]), "+f"(h[4]), "+f"(h[5]), "+f"(h[6]), "+f"(h[7]), "+f"(h[8]), "+f"(h[9]), "+f"(h[10]), "+f"(h[11]), "+f"(h[12]), "+f"(h[13]), "+f"(h[14]), "+f"(h[15]), "+f"(h[16]), "+f"(h[17]), "+f"(h[18]), "+f"(h[19]), "+f"(h[20]), "+f"(h[21]), "+f"(h[22]), "+f"(h[23]), "+f"(h[24]), "+f"(h[25]), "+f"(h[26]), "+f"(h[27]), "+f"(h[28]), "+f"(h[29]), "+f"(h[30]), "+f"(h[31]), "+f"(h[32]), "+f"(h[33]), "+f"(h[34]), "+f"(h[35])
      :: "memory");
  }
};
template<> struct TileMMA<10> {
  static __device__ __forceinline__ void issue(float* g, float* h, const uint32_t* w, uint32_t dx, uint64_t de, uint64_t dh, uint64_t dc) {
    asm volatile(
      "{\n.reg .b64 dx0, dx1, dx2, dx3;\n.reg .b32 l1, l2, l3, hx;\nmov.b32 hx, 0x40000040;\n"
      "add.u32 l1, %120, 2;\nadd.u32 l2, %120, 4;\nadd.u32 l3, %120, 6;\n"
      "mov.b64 dx0, {%120, hx};\nmov.b64 dx1, {l1, hx};\nmov.b64 dx2, {l2, hx};\nmov.b64 dx3, {l3, hx};\n"
      "wgmma.fence.sync.aligned;\n"
      "wgmma.mma_async.sync.aligned.m64n80k16.f32.bf16.bf16 {%0, %1, %2, %3, %4, %5, %6, %7, %8, %9, %10, %11, %12, %13, %14, %15, %16, %17, %18, %19, %20, %21, %22, %23, %24, %25, %26, %27, %28, %29, %30, %31, %32, %33, %34, %35, %36, %37, %38, %39}, {%116, %117, %118, %119}, %122, 0, 1, 1, 0;\n"
      "wgmma.mma_async.sync.aligned.m64n80k16.f32.bf16.bf16 {%0, %1, %2, %3, %4, %5, %6, %7, %8, %9, %10, %11, %12, %13, %14, %15, %16, %17, %18, %19, %20, %21, %22, %23, %24, %25, %26, %27, %28, %29, %30, %31, %32, %33, %34, %35, %36, %37, %38, %39}, {%96, %97, %98, %99}, %121, 1, 1, 1, 0;\n"
      "wgmma.mma_async.sync.aligned.m64n80k16.f32.bf16.bf16 {%0, %1, %2, %3, %4, %5, %6, %7, %8, %9, %10, %11, %12, %13, %14, %15, %16, %17, %18, %19, %20, %21, %22, %23, %24, %25, %26, %27, %28, %29, %30, %31, %32, %33, %34, %35, %36, %37, %38, %39}, {%80, %81, %82, %83}, dx0, 1, 1, 1, 0;\n"
      "wgmma.mma_async.sync.aligned.m64n80k16.f32.bf16.bf16 {%0, %1, %2, %3, %4, %5, %6, %7, %8, %9, %10, %11, %12, %13, %14, %15, %16, %17, %18, %19, %20, %21, %22, %23, %24, %25, %26, %27, %28, %29, %30, %31, %32, %33, %34, %35, %36, %37, %38, %39}, {%84, %85, %86, %87}, dx1, 1, 1, 1, 0;\n"
      "wgmma.mma_async.sync.aligned.m64n80k16.f32.bf16.bf16 {%0, %1, %2, %3, %4, %5, %6, %7, %8, %9, %10, %11, %12, %13, %14, %15, %16, %17, %18, %19, %20, %21, %22, %23, %24, %25, %26, %27, %28, %29, %30, %31, %32, %33, %34, %35, %36, %37, %38, %39}, {%88, %89, %90, %91}, dx2, 1, 1, 1, 0;\n"
      "wgmma.mma_async.sync.aligned.m64n80k16.f32.bf16.bf16 {%0, %1, %2, %3, %4, %5, %6, %7, %8, %9, %10, %11, %12, %13, %14, %15, %16, %17, %18, %19, %20, %21, %22, %23, %24, %25, %26, %27, %28, %29, %30, %31, %32, %33, %34, %35, %36, %37, %38, %39}, {%92, %93, %94, %95}, dx3, 1, 1, 1, 0;\n"
      "wgmma.commit_group.sync.aligned;\n"
      "wgmma.mma_async.sync.aligned.m64n80k16.f32.bf16.bf16 {%40, %41, %42, %43, %44, %45, %46, %47, %48, %49, %50, %51, %52, %53, %54, %55, %56, %57, %58, %59, %60, %61, %62, %63, %64, %65, %66, %67, %68, %69, %70, %71, %72, %73, %74, %75, %76, %77, %78, %79}, {%100, %101, %102, %103}, dx0, 0, 1, 1, 0;\n"
      "wgmma.mma_async.sync.aligned.m64n80k16.f32.bf16.bf16 {%40, %41, %42, %43, %44, %45, %46, %47, %48, %49, %50, %51, %52, %53, %54, %55, %56, %57, %58, %59, %60, %61, %62, %63, %64, %65, %66, %67, %68, %69, %70, %71, %72, %73, %74, %75, %76, %77, %78, %79}, {%104, %105, %106, %107}, dx1, 1, 1, 1, 0;\n"
      "wgmma.mma_async.sync.aligned.m64n80k16.f32.bf16.bf16 {%40, %41, %42, %43, %44, %45, %46, %47, %48, %49, %50, %51, %52, %53, %54, %55, %56, %57, %58, %59, %60, %61, %62, %63, %64, %65, %66, %67, %68, %69, %70, %71, %72, %73, %74, %75, %76, %77, %78, %79}, {%108, %109, %110, %111}, dx2, 1, 1, 1, 0;\n"
      "wgmma.mma_async.sync.aligned.m64n80k16.f32.bf16.bf16 {%40, %41, %42, %43, %44, %45, %46, %47, %48, %49, %50, %51, %52, %53, %54, %55, %56, %57, %58, %59, %60, %61, %62, %63, %64, %65, %66, %67, %68, %69, %70, %71, %72, %73, %74, %75, %76, %77, %78, %79}, {%112, %113, %114, %115}, dx3, 1, 1, 1, 0;\n"
      "wgmma.commit_group.sync.aligned;\n}\n"
      : "=f"(g[0]), "=f"(g[1]), "=f"(g[2]), "=f"(g[3]), "=f"(g[4]), "=f"(g[5]), "=f"(g[6]), "=f"(g[7]), "=f"(g[8]), "=f"(g[9]), "=f"(g[10]), "=f"(g[11]), "=f"(g[12]), "=f"(g[13]), "=f"(g[14]), "=f"(g[15]), "=f"(g[16]), "=f"(g[17]), "=f"(g[18]), "=f"(g[19]), "=f"(g[20]), "=f"(g[21]), "=f"(g[22]), "=f"(g[23]), "=f"(g[24]), "=f"(g[25]), "=f"(g[26]), "=f"(g[27]), "=f"(g[28]), "=f"(g[29]), "=f"(g[30]), "=f"(g[31]), "=f"(g[32]), "=f"(g[33]), "=f"(g[34]), "=f"(g[35]), "=f"(g[36]), "=f"(g[37]), "=f"(g[38]), "=f"(g[39]),
        "=f"(h[0]), "=f"(h[1]), "=f"(h[2]), "=f"(h[3]), "=f"(h[4]), "=f"(h[5]), "=f"(h[6]), "=f"(h[7]), "=f"(h[8]), "=f"(h[9]), "=f"(h[10]), "=f"(h[11]), "=f"(h[12]), "=f"(h[13]), "=f"(h[14]), "=f"(h[15]), "=f"(h[16]), "=f"(h[17]), "=f"(h[18]), "=f"(h[19]), "=f"(h[20]), "=f"(h[21]), "=f"(h[22]), "=f"(h[23]), "=f"(h[24]), "=f"(h[25]), "=f"(h[26]), "=f"(h[27]), "=f"(h[28]), "=f"(h[29]), "=f"(h[30]), "=f"(h[31]), "=f"(h[32]), "=f"(h[33]), "=f"(h[34]), "=f"(h[35]), "=f"(h[36]), "=f"(h[37]), "=f"(h[38]), "=f"(h[39])
      : "r"(w[0]), "r"(w[1]), "r"(w[2]), "r"(w[3]), "r"(w[4]), "r"(w[5]), "r"(w[6]), "r"(w[7]), "r"(w[8]), "r"(w[9]), "r"(w[10]), "r"(w[11]), "r"(w[12]), "r"(w[13]), "r"(w[14]), "r"(w[15]), "r"(w[16]), "r"(w[17]), "r"(w[18]), "r"(w[19]), "r"(w[20]), "r"(w[21]), "r"(w[22]), "r"(w[23]), "r"(w[24]), "r"(w[25]), "r"(w[26]), "r"(w[27]), "r"(w[28]), "r"(w[29]), "r"(w[30]), "r"(w[31]), "r"(w[32]), "r"(w[33]), "r"(w[34]), "r"(w[35]), "r"(w[36]), "r"(w[37]), "r"(w[38]), "r"(w[39]), "r"(dx), "l"(de), "l"(dh)
      : "memory");
  }
  static __device__ __forceinline__ void wait_g(float* g) {
    asm volatile("wgmma.wait_group.sync.aligned 1;\n"
      : "+f"(g[0]), "+f"(g[1]), "+f"(g[2]), "+f"(g[3]), "+f"(g[4]), "+f"(g[5]), "+f"(g[6]), "+f"(g[7]), "+f"(g[8]), "+f"(g[9]), "+f"(g[10]), "+f"(g[11]), "+f"(g[12]), "+f"(g[13]), "+f"(g[14]), "+f"(g[15]), "+f"(g[16]), "+f"(g[17]), "+f"(g[18]), "+f"(g[19]), "+f"(g[20]), "+f"(g[21]), "+f"(g[22]), "+f"(g[23]), "+f"(g[24]), "+f"(g[25]), "+f"(g[26]), "+f"(g[27]), "+f"(g[28]), "+f"(g[29]), "+f"(g[30]), "+f"(g[31]), "+f"(g[32]), "+f"(g[33]), "+f"(g[34]), "+f"(g[35]), "+f"(g[36]), "+f"(g[37]), "+f"(g[38]), "+f"(g[39])
      :: "memory");
  }
  static __device__ __forceinline__ void wait_h(float* h) {
    asm volatile("wgmma.wait_group.sync.aligned 0;\n"
      : "+f"(h[0]), "+f"(h[1]), "+f"(h[2]), "+f"(h[3]), "+f"(h[4]), "+f"(h[5]), "+f"(h[6]), "+f"(h[7]), "+f"(h[8]), "+f"(h[9]), "+f"(h[10]), "+f"(h[11]), "+f"(h[12]), "+f"(h[13]), "+f"(h[14]), "+f"(h[15]), "+f"(h[16]), "+f"(h[17]), "+f"(h[18]), "+f"(h[19]), "+f"(h[20]), "+f"(h[21]), "+f"(h[22]), "+f"(h[23]), "+f"(h[24]), "+f"(h[25]), "+f"(h[26]), "+f"(h[27]), "+f"(h[28]), "+f"(h[29]), "+f"(h[30]), "+f"(h[31]), "+f"(h[32]), "+f"(h[33]), "+f"(h[34]), "+f"(h[35]), "+f"(h[36]), "+f"(h[37]), "+f"(h[38]), "+f"(h[39])
      :: "memory");
  }
};
template<> struct TileMMA<11> {
  static __device__ __forceinline__ void issue(float* g, float* h, const uint32_t* w, uint32_t dx, uint64_t de, uint64_t dh, uint64_t dc) {
    asm volatile(
      "{\n.reg .b64 dx0, dx1, dx2, dx3;\n.reg .b32 l1, l2, l3, hx;\nmov.b32 hx, 0x40000040;\n"
      "add.u32 l1, %124, 2;\nadd.u32 l2, %124, 4;\nadd.u32 l3, %124, 6;\n"
      "mov.b64 dx0, {%124, hx};\nmov.b64 dx1, {l1, hx};\nmov.b64 dx2, {l2, hx};\nmov.b64 dx3, {l3, hx};\n"
      "wgmma.fence.sync.aligned;\n"
      "wgmma.mma_async.sync.aligned.m64n88k16.f32.bf16.bf16 {%0, %1, %2, %3, %4, %5, %6, %7, %8, %9, %10, %11, %12, %13, %14, %15, %16, %17, %18, %19, %20, %21, %22, %23, %24, %25, %26, %27, %28, %29, %30, %31, %32, %33, %34, %35, %36, %37, %38, %39, %40, %41, %42, %43}, {%120, %121, %122, %123}, %126, 0, 1, 1, 0;\n"
      "wgmma.mma_async.sync.aligned.m64n88k16.f32.bf16.bf16 {%0, %1, %2, %3, %4, %5, %6, %7, %8, %9, %10, %11, %12, %13, %14, %15, %16, %17, %18, %19, %20, %21, %22, %23, %24, %25, %26, %27, %28, %29, %30, %31, %32, %33, %34, %35, %36, %37, %38, %39, %40, %41, %42, %43}, %127, %125, 1, 1, 1, 0, 0;\n"
      "wgmma.mma_async.sync.aligned.m64n88k16.f32.bf16.bf16 {%0, %1, %2, %3, %4, %5, %6, %7, %8, %9, %10, %11, %12, %13, %14, %15, %16, %17, %18, %19, %20, %21, %22, %23, %24, %25, %26, %27, %28, %29, %30, %31, %32, %33, %34, %35, %36, %37, %38, %39, %40, %41, %42, %43}, {%88, %89, %90, %91}, dx0, 1, 1, 1, 0;\n"
      "wgmma.mma_async.sync.aligned.m64n88k16.f32.bf16.bf16 {%0, %1, %2, %3, %4, %5, %6, %7, %8, %9, %10, %11, %12, %13, %14, %15, %16, %17, %18, %19, %20, %21, %22, %23, %24, %25, %26, %27, %28, %29, %30, %31, %32, %33, %34, %35, %36, %37, %38, %39, %40, %41, %42, %43}, {%92, %93, %94, %95}, dx1, 1, 1, 1, 0;\n"
      "wgmma.mma_async.sync.aligned.m64n88k16.f32.bf16.bf16 {%0, %1, %2, %3, %4, %5, %6, %7, %8, %9, %10, %11, %12, %13, %14, %15, %16, %17, %18, %19, %20, %21, %22, %23, %24, %25, %26, %27, %28, %29, %30, %31, %32, %33, %34, %35, %36, %37, %38, %39, %40, %41, %42, %43}, {%96, %97, %98, %99}, dx2, 1, 1, 1, 0;\n"
      "wgmma.mma_async.sync.aligned.m64n88k16.f32.bf16.bf16 {%0, %1, %2, %3, %4, %5, %6, %7, %8, %9, %10, %11, %12, %13, %14, %15, %16, %17, %18, %19, %20, %21, %22, %23, %24, %25, %26, %27, %28, %29, %30, %31, %32, %33, %34, %35, %36, %37, %38, %39, %40, %41, %42, %43}, {%100, %101, %102, %103}, dx3, 1, 1, 1, 0;\n"
      "wgmma.commit_group.sync.aligned;\n"
      "wgmma.mma_async.sync.aligned.m64n88k16.f32.bf16.bf16 {%44, %45, %46, %47, %48, %49, %50, %51, %52, %53, %54, %55, %56, %57, %58, %59, %60, %61, %62, %63, %64, %65, %66, %67, %68, %69, %70, %71, %72, %73, %74, %75, %76, %77, %78, %79, %80, %81, %82, %83, %84, %85, %86, %87}, {%104, %105, %106, %107}, dx0, 0, 1, 1, 0;\n"
      "wgmma.mma_async.sync.aligned.m64n88k16.f32.bf16.bf16 {%44, %45, %46, %47, %48, %49, %50, %51, %52, %53, %54, %55, %56, %57, %58, %59, %60, %61, %62, %63, %64, %65, %66, %67, %68, %69, %70, %71, %72, %73, %74, %75, %76, %77, %78, %79, %80, %81, %82, %83, %84, %85, %86, %87}, {%108, %109, %110, %111}, dx1, 1, 1, 1, 0;\n"
      "wgmma.mma_async.sync.aligned.m64n88k16.f32.bf16.bf16 {%44, %45, %46, %47, %48, %49, %50, %51, %52, %53, %54, %55, %56, %57, %58, %59, %60, %61, %62, %63, %64, %65, %66, %67, %68, %69, %70, %71, %72, %73, %74, %75, %76, %77, %78, %79, %80, %81, %82, %83, %84, %85, %86, %87}, {%112, %113, %114, %115}, dx2, 1, 1, 1, 0;\n"
      "wgmma.mma_async.sync.aligned.m64n88k16.f32.bf16.bf16 {%44, %45, %46, %47, %48, %49, %50, %51, %52, %53, %54, %55, %56, %57, %58, %59, %60, %61, %62, %63, %64, %65, %66, %67, %68, %69, %70, %71, %72, %73, %74, %75, %76, %77, %78, %79, %80, %81, %82, %83, %84, %85, %86, %87}, {%116, %117, %118, %119}, dx3, 1, 1, 1, 0;\n"
      "wgmma.commit_group.sync.aligned;\n}\n"
      : "=f"(g[0]), "=f"(g[1]), "=f"(g[2]), "=f"(g[3]), "=f"(g[4]), "=f"(g[5]), "=f"(g[6]), "=f"(g[7]), "=f"(g[8]), "=f"(g[9]), "=f"(g[10]), "=f"(g[11]), "=f"(g[12]), "=f"(g[13]), "=f"(g[14]), "=f"(g[15]), "=f"(g[16]), "=f"(g[17]), "=f"(g[18]), "=f"(g[19]), "=f"(g[20]), "=f"(g[21]), "=f"(g[22]), "=f"(g[23]), "=f"(g[24]), "=f"(g[25]), "=f"(g[26]), "=f"(g[27]), "=f"(g[28]), "=f"(g[29]), "=f"(g[30]), "=f"(g[31]), "=f"(g[32]), "=f"(g[33]), "=f"(g[34]), "=f"(g[35]), "=f"(g[36]), "=f"(g[37]), "=f"(g[38]), "=f"(g[39]), "=f"(g[40]), "=f"(g[41]), "=f"(g[42]), "=f"(g[43]),
        "=f"(h[0]), "=f"(h[1]), "=f"(h[2]), "=f"(h[3]), "=f"(h[4]), "=f"(h[5]), "=f"(h[6]), "=f"(h[7]), "=f"(h[8]), "=f"(h[9]), "=f"(h[10]), "=f"(h[11]), "=f"(h[12]), "=f"(h[13]), "=f"(h[14]), "=f"(h[15]), "=f"(h[16]), "=f"(h[17]), "=f"(h[18]), "=f"(h[19]), "=f"(h[20]), "=f"(h[21]), "=f"(h[22]), "=f"(h[23]), "=f"(h[24]), "=f"(h[25]), "=f"(h[26]), "=f"(h[27]), "=f"(h[28]), "=f"(h[29]), "=f"(h[30]), "=f"(h[31]), "=f"(h[32]), "=f"(h[33]), "=f"(h[34]), "=f"(h[35]), "=f"(h[36]), "=f"(h[37]), "=f"(h[38]), "=f"(h[39]), "=f"(h[40]), "=f"(h[41]), "=f"(h[42]), "=f"(h[43])
      : "r"(w[0]), "r"(w[1]), "r"(w[2]), "r"(w[3]), "r"(w[4]), "r"(w[5]), "r"(w[6]), "r"(w[7]), "r"(w[8]), "r"(w[9]), "r"(w[10]), "r"(w[11]), "r"(w[12]), "r"(w[13]), "r"(w[14]), "r"(w[15]), "r"(w[20]), "r"(w[21]), "r"(w[22]), "r"(w[23]), "r"(w[24]), "r"(w[25]), "r"(w[26]), "r"(w[27]), "r"(w[28]), "r"(w[29]), "r"(w[30]), "r"(w[31]), "r"(w[32]), "r"(w[33]), "r"(w[34]), "r"(w[35]), "r"(w[36]), "r"(w[37]), "r"(w[38]), "r"(w[39]), "r"(dx), "l"(de), "l"(dh), "l"(dc)
      : "memory");
  }
  static __device__ __forceinline__ void wait_g(float* g) {
    asm volatile("wgmma.wait_group.sync.aligned 1;\n"
      : "+f"(g[0]), "+f"(g[1]), "+f"(g[2]), "+f"(g[3]), "+f"(g[4]), "+f"(g[5]), "+f"(g[6]), "+f"(g[7]), "+f"(g[8]), "+f"(g[9]), "+f"(g[10]), "+f"(g[11]), "+f"(g[12]), "+f"(g[13]), "+f"(g[14]), "+f"(g[15]), "+f"(g[16]), "+f"(g[17]), "+f"(g[18]), "+f"(g[19]), "+f"(g[20]), "+f"(g[21]), "+f"(g[22]), "+f"(g[23]), "+f"(g[24]), "+f"(g[25]), "+f"(g[26]), "+f"(g[27]), "+f"(g[28]), "+f"(g[29]), "+f"(g[30]), "+f"(g[31]), "+f"(g[32]), "+f"(g[33]), "+f"(g[34]), "+f"(g[35]), "+f"(g[36]), "+f"(g[37]), "+f"(g[38]), "+f"(g[39]), "+f"(g[40]), "+f"(g[41]), "+f"(g[42]), "+f"(g[43])
      :: "memory");
  }
  static __device__ __forceinline__ void wait_h(float* h) {
    asm volatile("wgmma.wait_group.sync.aligned 0;\n"
      : "+f"(h[0]), "+f"(h[1]), "+f"(h[2]), "+f"(h[3]), "+f"(h[4]), "+f"(h[5]), "+f"(h[6]), "+f"(h[7]), "+f"(h[8]), "+f"(h[9]), "+f"(h[10]), "+f"(h[11]), "+f"(h[12]), "+f"(h[13]), "+f"(h[14]), "+f"(h[15]), "+f"(h[16]), "+f"(h[17]), "+f"(h[18]), "+f"(h[19]), "+f"(h[20]), "+f"(h[21]), "+f"(h[22]), "+f"(h[23]), "+f"(h[24]), "+f"(h[25]), "+f"(h[26]), "+f"(h[27]), "+f"(h[28]), "+f"(h[29]), "+f"(h[30]), "+f"(h[31]), "+f"(h[32]), "+f"(h[33]), "+f"(h[34]), "+f"(h[35]), "+f"(h[36]), "+f"(h[37]), "+f"(h[38]), "+f"(h[39]), "+f"(h[40]), "+f"(h[41]), "+f"(h[42]), "+f"(h[43])
      :: "memory");
  }
};
__device__ __forceinline__ void node_mma(float* g, const uint32_t* w, uint64_t dx) {
    asm volatile(
      "{\n.reg .b64 dx1, dx2, dx3;\n"
      "add.s64 dx1, %48, 2;\nadd.s64 dx2, %48, 4;\nadd.s64 dx3, %48, 6;\n"
      "wgmma.fence.sync.aligned;\n"
      "wgmma.mma_async.sync.aligned.m64n64k16.f32.bf16.bf16 {%0, %1, %2, %3, %4, %5, %6, %7, %8, %9, %10, %11, %12, %13, %14, %15, %16, %17, %18, %19, %20, %21, %22, %23, %24, %25, %26, %27, %28, %29, %30, %31}, {%32, %33, %34, %35}, %48, 0, 1, 1, 0;\n"
      "wgmma.mma_async.sync.aligned.m64n64k16.f32.bf16.bf16 {%0, %1, %2, %3, %4, %5, %6, %7, %8, %9, %10, %11, %12, %13, %14, %15, %16, %17, %18, %19, %20, %21, %22, %23, %24, %25, %26, %27, %28, %29, %30, %31}, {%36, %37, %38, %39}, dx1, 1, 1, 1, 0;\n"
      "wgmma.mma_async.sync.aligned.m64n64k16.f32.bf16.bf16 {%0, %1, %2, %3, %4, %5, %6, %7, %8, %9, %10, %11, %12, %13, %14, %15, %16, %17, %18, %19, %20, %21, %22, %23, %24, %25, %26, %27, %28, %29, %30, %31}, {%40, %41, %42, %43}, dx2, 1, 1, 1, 0;\n"
      "wgmma.mma_async.sync.aligned.m64n64k16.f32.bf16.bf16 {%0, %1, %2, %3, %4, %5, %6, %7, %8, %9, %10, %11, %12, %13, %14, %15, %16, %17, %18, %19, %20, %21, %22, %23, %24, %25, %26, %27, %28, %29, %30, %31}, {%44, %45, %46, %47}, dx3, 1, 1, 1, 0;\n"
      "wgmma.commit_group.sync.aligned;\n}\n"
      : "=f"(g[0]), "=f"(g[1]), "=f"(g[2]), "=f"(g[3]), "=f"(g[4]), "=f"(g[5]), "=f"(g[6]), "=f"(g[7]), "=f"(g[8]), "=f"(g[9]), "=f"(g[10]), "=f"(g[11]), "=f"(g[12]), "=f"(g[13]), "=f"(g[14]), "=f"(g[15]), "=f"(g[16]), "=f"(g[17]), "=f"(g[18]), "=f"(g[19]), "=f"(g[20]), "=f"(g[21]), "=f"(g[22]), "=f"(g[23]), "=f"(g[24]), "=f"(g[25]), "=f"(g[26]), "=f"(g[27]), "=f"(g[28]), "=f"(g[29]), "=f"(g[30]), "=f"(g[31])
      : "r"(w[0]), "r"(w[1]), "r"(w[2]), "r"(w[3]), "r"(w[4]), "r"(w[5]), "r"(w[6]), "r"(w[7]), "r"(w[8]), "r"(w[9]), "r"(w[10]), "r"(w[11]), "r"(w[12]), "r"(w[13]), "r"(w[14]), "r"(w[15]), "l"(dx)
      : "memory");
}

__device__ __forceinline__ uint32_t smem_u32(const void* p) { return (uint32_t)__cvta_generic_to_shared(p); }
__device__ __forceinline__ float ex2f(float x) { float y; asm("ex2.approx.ftz.f32 %0, %1;" : "=f"(y) : "f"(x)); return y; }
__device__ __forceinline__ float rcpf(float x) { float y; asm("rcp.approx.ftz.f32 %0, %1;" : "=f"(y) : "f"(x)); return y; }
__device__ __forceinline__ uint32_t pack_bf16(float lo, float hi) {
    uint32_t r; asm("cvt.rn.bf16x2.f32 %0, %1, %2;" : "=r"(r) : "f"(hi), "f"(lo)); return r;
}
__device__ __forceinline__ float bf_lo(uint32_t v) { return __uint_as_float(v << 16); }
__device__ __forceinline__ float bf_hi(uint32_t v) { return __uint_as_float(v & 0xFFFF0000u); }
template<int STRIDE>
__device__ __forceinline__ void cp16i(uint32_t dst, const char* base, uint32_t idx) {
    asm volatile("{\n.reg .b64 a;\nmad.wide.u32 a, %2, %3, %1;\ncp.async.cg.shared.global [%0], [a], 16;\n}\n" :: "r"(dst), "l"(base), "r"(idx), "n"(STRIDE) : "memory");
}
__device__ __forceinline__ void cp16e(uint32_t dst, const char* base, uint32_t idx, uint64_t pol) {
    asm volatile("{\n.reg .b64 a;\nmad.wide.u32 a, %2, 32, %1;\ncp.async.cg.shared.global.L2::cache_hint [%0], [a], 16, %3;\n}\n" :: "r"(dst), "l"(base), "r"(idx), "l"(pol) : "memory");
}
template<int STRIDE>
__device__ __forceinline__ void cp16z(uint32_t dst, const char* base, uint32_t idx, int k, int n, uint64_t pol) {
    if (STRIDE == 32)
        asm volatile("{\n.reg .b64 a;\n.reg .pred p;\nsetp.ge.s32 p, %3, %4;\nmad.wide.u32 a, %2, 32, %1;\ncp.async.cg.shared.global.L2::cache_hint [%0], [a], 16, p, %5;\n}\n"
                     :: "r"(dst), "l"(base), "r"(idx), "r"(k), "r"(n), "l"(pol) : "memory");
    else
        asm volatile("{\n.reg .b64 a;\n.reg .pred p;\nsetp.ge.s32 p, %3, %4;\nmad.wide.u32 a, %2, 128, %1;\ncp.async.cg.shared.global [%0], [a], 16, p;\n}\n"
                     :: "r"(dst), "l"(base), "r"(idx), "r"(k), "r"(n) : "memory");
}
template<int HI, bool Z>
__device__ __forceinline__ void cpx(uint32_t hi, uint32_t dst, uint32_t p, uint32_t lo, int k, int n) {
    if (Z) asm volatile("{\n.reg .b32 l;\n.reg .b64 a;\n.reg .pred q;\nsetp.ge.s32 q, %5, %6;\ndp2a.lo.u32.u32 l, %1, %2, %3;\nmov.b64 a, {l, %0};\ncp.async.cg.shared.global [%4], [a], 16, q;\n}\n"
                        :: "r"(hi), "r"(p), "r"(HI ? 0x8000u : 0x80u), "r"(lo), "r"(dst), "r"(k), "r"(n) : "memory");
    else asm volatile("{\n.reg .b32 l;\n.reg .b64 a;\ndp2a.lo.u32.u32 l, %1, %2, %3;\nmov.b64 a, {l, %0};\ncp.async.cg.shared.global [%4], [a], 16;\n}\n"
                      :: "r"(hi), "r"(p), "r"(HI ? 0x8000u : 0x80u), "r"(lo), "r"(dst) : "memory");
}
template<bool Z>
__device__ __forceinline__ void cpe(uint32_t hi, uint32_t dst, uint32_t idx, uint32_t lo, int k, int n, uint64_t pol) {
    if (Z) asm volatile("{\n.reg .b32 l;\n.reg .b64 a;\n.reg .pred q;\nsetp.ge.s32 q, %5, %6;\nmad.lo.u32 l, %1, 32, %2;\nmov.b64 a, {l, %0};\ncp.async.cg.shared.global.L2::cache_hint [%3], [a], 16, q, %4;\n}\n"
                        :: "r"(hi), "r"(idx), "r"(lo), "r"(dst), "l"(pol), "r"(k), "r"(n) : "memory");
    else asm volatile("{\n.reg .b32 l;\n.reg .b64 a;\nmad.lo.u32 l, %1, 32, %2;\nmov.b64 a, {l, %0};\ncp.async.cg.shared.global.L2::cache_hint [%3], [a], 16, %4;\n}\n"
                      :: "r"(hi), "r"(idx), "r"(lo), "r"(dst), "l"(pol) : "memory");
}
__device__ __forceinline__ void cp_commit() { asm volatile("cp.async.commit_group;" ::: "memory"); }
template<int N> __device__ __forceinline__ void cp_wait() { asm volatile("cp.async.wait_group %0;" :: "n"(N) : "memory"); }
__device__ __forceinline__ void mbar_arrive(uint32_t bar) { asm volatile("mbarrier.arrive.shared.b64 _, [%0];" :: "r"(bar) : "memory"); }
__device__ __forceinline__ void mbar_cp_arrive(uint32_t bar) { asm volatile("cp.async.mbarrier.arrive.noinc.shared.b64 [%0];" :: "r"(bar) : "memory"); }
__device__ __forceinline__ void mbar_wait(uint32_t bar, uint32_t parity) {
    asm volatile("{\n.reg .pred p;\n.reg .u32 n;\nmbarrier.try_wait.parity.shared.b64 p, [%0], %1;\n@p bra DONE_%=;\nmov.u32 n, 0;\n"
                 "WAIT_%=:\nmbarrier.try_wait.parity.shared.b64 p, [%0], %1, 0x100000;\n@p bra DONE_%=;\n"
                 "add.u32 n, n, 1;\nsetp.lt.u32 p, n, 0x400000;\n@p bra WAIT_%=;\ntrap;\nDONE_%=:\n}\n"
                 :: "r"(bar), "r"(parity) : "memory");
}
__device__ __forceinline__ void mbar_wait_c(uint32_t bar, uint32_t parity) {
    asm volatile("{\n.reg .pred p;\nWAIT_%=:\nmbarrier.try_wait.parity.shared.b64 p, [%0], %1;\n@p bra DONE_%=;\nbra WAIT_%=;\nDONE_%=:\n}\n"
                 :: "r"(bar), "r"(parity) : "memory");
}
__device__ __forceinline__ void mbar_wait_h(uint32_t bar, uint32_t parity) {
    asm volatile("{\n.reg .pred p;\nWAIT_%=:\nmbarrier.try_wait.parity.shared.b64 p, [%0], %1, 0x100000;\n@p bra DONE_%=;\nbra WAIT_%=;\nDONE_%=:\n}\n"
                 :: "r"(bar), "r"(parity) : "memory");
}
__device__ __forceinline__ uint32_t lds32(uint32_t a) { uint32_t v; asm volatile("ld.shared.u32 %0, [%1];" : "=r"(v) : "r"(a) : "memory"); return v; }
__device__ __forceinline__ void sts32(uint32_t a, uint32_t v) { asm volatile("st.shared.u32 [%0], %1;" :: "r"(a), "r"(v) : "memory"); }
__device__ __forceinline__ uint2 lds64(uint32_t a) { uint2 v; asm volatile("ld.shared.v2.u32 {%0,%1}, [%2];" : "=r"(v.x), "=r"(v.y) : "r"(a) : "memory"); return v; }
__device__ __forceinline__ void sts64(uint32_t a, uint32_t x, uint32_t y) { asm volatile("st.shared.v2.u32 [%0], {%1,%2};" :: "r"(a), "r"(x), "r"(y) : "memory"); }
__device__ __forceinline__ uint4 lds128(uint32_t a) { uint4 v; asm volatile("ld.shared.v4.u32 {%0,%1,%2,%3}, [%4];" : "=r"(v.x), "=r"(v.y), "=r"(v.z), "=r"(v.w) : "r"(a) : "memory"); return v; }
__device__ __forceinline__ void sts128(uint32_t a, uint4 v) { asm volatile("st.shared.v4.u32 [%0], {%1,%2,%3,%4};" :: "r"(a), "r"(v.x), "r"(v.y), "r"(v.z), "r"(v.w) : "memory"); }
__device__ __forceinline__ void ldsm4t(uint32_t* v, uint32_t a) {
    asm volatile("ldmatrix.sync.aligned.m8n8.x4.trans.shared.b16 {%0,%1,%2,%3}, [%4];" : "=r"(v[0]), "=r"(v[1]), "=r"(v[2]), "=r"(v[3]) : "r"(a) : "memory");
}
__device__ __forceinline__ void stsm4t(uint32_t a, const uint32_t* v) {
    asm volatile("stmatrix.sync.aligned.m8n8.x4.trans.shared.b16 [%0], {%1,%2,%3,%4};" :: "r"(a), "r"(v[0]), "r"(v[1]), "r"(v[2]), "r"(v[3]) : "memory");
}
__device__ __forceinline__ int atoms_inc(uint32_t a) { int v; asm volatile("atom.shared.add.u32 %0, [%1], 1;" : "=r"(v) : "r"(a) : "memory"); return v; }
__device__ __forceinline__ float tanhf_a(float x) { float y; asm("tanh.approx.f32 %0, %1;" : "=f"(y) : "f"(x)); return y; }
__device__ __forceinline__ const char* as_pair(const void* p, uint32_t scratch) {
    const char* r;
    asm volatile("st.shared.u64 [%1], %2;\nld.volatile.shared.u64 %0, [%1];" : "=l"(r) : "r"(scratch), "l"(p) : "memory");
    return r;
}
__device__ __forceinline__ void ld_unit(uint4& v, const char* p, bool ok) {
    asm volatile("{\n.reg .pred q;\nsetp.ne.u32 q, %5, 0;\n@q ld.relaxed.gpu.global.v4.u32 {%0,%1,%2,%3}, [%4];\n}"
                 : "+r"(v.x), "+r"(v.y), "+r"(v.z), "+r"(v.w) : "l"(p), "r"((uint32_t)ok) : "memory");
}
__device__ __forceinline__ void ld_unit(uint2& v, const char* p, bool ok) {
    asm volatile("{\n.reg .pred q;\nsetp.ne.u32 q, %3, 0;\n@q ld.relaxed.gpu.global.v2.u32 {%0,%1}, [%2];\n}"
                 : "+r"(v.x), "+r"(v.y) : "l"(p), "r"((uint32_t)ok) : "memory");
}
#define ELECT "{\n.reg .pred p;\nelect.sync _|p, 0xffffffff;\n@p "
__device__ __forceinline__ void w_init(uint32_t bar, int n) { asm volatile(ELECT "mbarrier.init.shared.b64 [%0], %1;\n}" :: "r"(bar), "r"(n) : "memory"); }
__device__ __forceinline__ void w_expect(uint32_t bar, uint32_t bytes) { asm volatile(ELECT "mbarrier.arrive.expect_tx.shared.b64 _, [%0], %1;\n}" :: "r"(bar), "r"(bytes) : "memory"); }
__device__ __forceinline__ void w_ld(uint32_t dst, const void* src, int bytes, uint32_t bar) {
    asm volatile(ELECT "cp.async.bulk.shared::cluster.global.mbarrier::complete_tx::bytes [%0], [%1], %2, [%3];\n}" :: "r"(dst), "l"(src), "r"(bytes), "r"(bar) : "memory");
}
__device__ __forceinline__ void w_box_ld(uint32_t dst, const CUtensorMap* tm, int row, uint32_t bar) {
    asm volatile(ELECT "cp.async.bulk.tensor.2d.shared::cluster.global.mbarrier::complete_tx::bytes [%0], [%1, {%3, %4}], [%2];\n}"
        :: "r"(dst), "l"((uint64_t)tm), "r"(bar), "r"(0), "r"(row) : "memory");
}
__device__ __forceinline__ void w_st(void* dst, uint32_t src, int bytes) {
    asm volatile(ELECT "cp.async.bulk.global.shared::cta.bulk_group [%0], [%1], %2;\n}" :: "l"(dst), "r"(src), "r"(bytes) : "memory");
}
__device__ __forceinline__ void w_box_st(const CUtensorMap* tm, int col, uint32_t src) {
    asm volatile(ELECT "cp.async.bulk.tensor.2d.global.shared::cta.bulk_group [%0, {%2, %3}], [%1];\n}" :: "l"((uint64_t)tm), "r"(src), "r"(col), "r"(0) : "memory");
}
__device__ __forceinline__ void w_sent(unsigned* p, uint32_t src) {
    asm volatile(ELECT "cp.reduce.async.bulk.global.shared::cta.bulk_group.add.u32 [%0], [%1], 16;\n}" :: "l"(p), "r"(src) : "memory");
}
__device__ __forceinline__ void w_inc(unsigned* p) { asm volatile(ELECT "red.relaxed.gpu.global.add.u32 [%0], 1;\n}" :: "l"(p) : "memory"); }
__device__ __forceinline__ void w_hint(unsigned* p, uint32_t all) {
    #pragma unroll 1
    for (int i = 0; i < 4096; i++) {
        uint32_t v; asm volatile("ld.relaxed.gpu.global.u32 %0, [%1];" : "=r"(v) : "l"(p) : "memory");
        if (__all_sync(~0u, (int)(v - all) >= 0)) break;
    }
}

__device__ __forceinline__ void finish(uint4& a, const uint4& xu, const uint4& xv) {
    asm("{\n.reg .b32 z;\nfma.rn.relu.bf16x2 z, %0, %3, %1;\nadd.rn.bf16x2 %0, z, %2;\n}" : "+r"(a.x) : "r"(xu.x), "r"(xv.x), "r"(0x3F803F80u));
    asm("{\n.reg .b32 z;\nfma.rn.relu.bf16x2 z, %0, %3, %1;\nadd.rn.bf16x2 %0, z, %2;\n}" : "+r"(a.y) : "r"(xu.y), "r"(xv.y), "r"(0x3F803F80u));
    asm("{\n.reg .b32 z;\nfma.rn.relu.bf16x2 z, %0, %3, %1;\nadd.rn.bf16x2 %0, z, %2;\n}" : "+r"(a.z) : "r"(xu.z), "r"(xv.z), "r"(0x3F803F80u));
    asm("{\n.reg .b32 z;\nfma.rn.relu.bf16x2 z, %0, %3, %1;\nadd.rn.bf16x2 %0, z, %2;\n}" : "+r"(a.w) : "r"(xu.w), "r"(xv.w), "r"(0x3F803F80u));
}

constexpr float EPS2 = 2e-6f;
constexpr float TAU = 2.5e-5f;

constexpr uint32_t TAU_BITS = 0x3A103000u;
template<int NP>
__device__ __forceinline__ bool epi_fast(const float* g, const float* h, float m2, float tau, float& n0, float& d0, float& n1, float& d1, float& dmin)
{
    constexpr int JC = NP >= 6 ? NP - 3 : NP - 2;
    bool ok;
    #pragma unroll
    for (int j = 0; j < NP; j++) {
        float t0 = tanhf_a(g[4*j+0]), t1 = tanhf_a(g[4*j+1]), t2 = tanhf_a(g[4*j+2]), t3 = tanhf_a(g[4*j+3]);
        auto add_d = [&]() {
            if (j == 0) { d0 = t0 + (2.f * (JC + 1) + EPS2); d1 = t2 + (2.f * (JC + 1) + EPS2); } else { d0 += t0; d1 += t2; }
            d0 += t1; d1 += t3;
        };
        if (j <= JC) add_d();
        if (j == 0) { n0 = fmaf(t0, h[0], h[0]); n1 = fmaf(t2, h[2], h[2]); }
        t0 += 1.f; t2 += 1.f;
        if (j == NP - 1) { t1 = fmaf(t1, m2, m2); t3 = fmaf(t3, m2, m2); } else { t1 += 1.f; t3 += 1.f; }
        if (j > JC) add_d();
        if (j > 0) { n0 = fmaf(t0, h[4*j], n0); n1 = fmaf(t2, h[4*j+2], n1); }
        n0 = fmaf(t1, h[4*j+1], n0); n1 = fmaf(t3, h[4*j+3], n1);
        if (j == JC) { dmin = fminf(d0, d1); ok = dmin >= tau; }
    }
    return ok;
}

__device__ __noinline__ void slow_bin(const __nv_bfloat16* x, const __nv_bfloat16* ea, const int* src, const int* dst,
                                      const __nv_bfloat16* wa, const __nv_bfloat16* wb, const __nv_bfloat16* wc,
                                      const __nv_bfloat16* wu, const __nv_bfloat16* wv, __nv_bfloat16* out,
                                      int E, int node0, int nn, int nthr)
{
    const int tid = threadIdx.x, lane = tid & 31;
    for (int i = tid; i < nn * 128; i += nthr) g_slow[(size_t)node0 * 128 + i] = 0.f;
    asm volatile("bar.sync 1, %0;" :: "r"(nthr) : "memory");
    for (int e0 = (tid >> 5) * 32; e0 < E; e0 += nthr) {
        int d = (e0 + lane < E) ? dst[e0 + lane] - node0 : -1;
        unsigned m = __ballot_sync(~0u, d >= 0 && d < nn);
        while (m) {
            int l = __ffs(m) - 1; m &= m - 1;
            int e = e0 + l, n = node0 + __shfl_sync(~0u, d, l), s = src[e];
            float g0 = 0, g1 = 0, h0 = 0, h1 = 0;
            for (int k = 0; k < 64; k++) {
                float xs = __bfloat162float(x[(size_t)s * 64 + k]), xd = __bfloat162float(x[(size_t)n * 64 + k]);
                uint32_t b2 = *(const uint32_t*)(wb + k * 64 + 2 * lane), v2 = *(const uint32_t*)(wv + k * 64 + 2 * lane);
                uint32_t a2 = *(const uint32_t*)(wa + k * 64 + 2 * lane);
                g0 = fmaf(xs, bf_lo(b2), fmaf(xd, bf_lo(a2), g0)); g1 = fmaf(xs, bf_hi(b2), fmaf(xd, bf_hi(a2), g1));
                h0 = fmaf(xs, bf_lo(v2), h0); h1 = fmaf(xs, bf_hi(v2), h1);
            }
            for (int k = 0; k < 16; k++) {
                float ev = __bfloat162float(ea[(size_t)e * 16 + k]);
                uint32_t c2 = *(const uint32_t*)(wc + k * 64 + 2 * lane);
                g0 = fmaf(ev, bf_lo(c2), g0); g1 = fmaf(ev, bf_hi(c2), g1);
            }
            float s0 = rcpf(1.f + ex2f(-LOG2E * g0)), s1 = rcpf(1.f + ex2f(-LOG2E * g1));
            float* acc = g_slow + (size_t)n * 128 + 4 * lane;
            atomicAdd(acc + 0, s0 * h0); atomicAdd(acc + 1, s0);
            atomicAdd(acc + 2, s1 * h1); atomicAdd(acc + 3, s1);
        }
    }
    __threadfence();
    asm volatile("bar.sync 1, %0;" :: "r"(nthr) : "memory");
    for (int i = tid; i < nn * 32; i += nthr) {
        int n = node0 + (i >> 5), cp = i & 31;
        float4 a = __ldcg((const float4*)(g_slow + (size_t)n * 128 + 4 * cp));
        float u0 = 0, u1 = 0;
        for (int k = 0; k < 64; k++) {
            float xd = __bfloat162float(x[(size_t)n * 64 + k]);
            uint32_t w2 = *(const uint32_t*)(wu + k * 64 + 2 * cp);
            u0 = fmaf(xd, bf_lo(w2), u0); u1 = fmaf(xd, bf_hi(w2), u1);
        }
        uint32_t xv = *(const uint32_t*)(x + (size_t)n * 64 + 2 * cp);
        float z0 = u0 + a.x / (a.y + 1e-6f), z1 = u1 + a.z / (a.w + 1e-6f);
        *(uint32_t*)(out + (size_t)n * 64 + 2 * cp) = pack_bf16(bf_lo(xv) + fmaxf(z0, 0.f), bf_hi(xv) + fmaxf(z1, 0.f));
    }
}

__global__ void __launch_bounds__(256) slow_kernel(const __nv_bfloat16* x, const __nv_bfloat16* ea, const int* src, const int* dst,
        const __nv_bfloat16* wa, const __nv_bfloat16* wb, const __nv_bfloat16* wc, const __nv_bfloat16* wu, const __nv_bfloat16* wv,
        __nv_bfloat16* out, int N, int E, int npb)
{
    int node0 = blockIdx.x * npb;
    slow_bin(x, ea, src, dst, wa, wb, wc, wu, wv, out, E, node0, max(0, min(npb, N - node0)), 256);
}

constexpr int XS_BYTES = NPMAX * 1024;
constexpr int ES_BYTES = NPMAX * 256;
constexpr int SM_XS = 0;
constexpr int SM_XU = SM_XS + 3 * NSTAGE * XS_BYTES;
constexpr int SM_TAB = SM_XU + NPB_MAX * 128;
constexpr int SM_ES = SM_TAB + NPB_MAX * 128;
constexpr int SM_WC = SM_ES + 3 * NSTAGE * ES_BYTES;
constexpr int SM_OH = SM_WC + 2048;
constexpr int SM_EID = SM_OH + 128;
constexpr int SM_SRC = SM_EID + SLOT_CAP * 4;
constexpr int SM_TINFO = SM_SRC + SLOT_CAP * 2;
constexpr int SM_MISC = SM_TINFO + TILE_CAP * 32;
constexpr int SM_CLAIM = SM_MISC + 32 * 4;
constexpr int STG = 272;
constexpr int SM_BARS = SM_CLAIM + 32 * 4;
constexpr int SM_ABAR = SM_BARS + 6 * STG;
constexpr int SM_GBAR = SM_ABAR + 16 * 8;
constexpr int SMEM_BYTES = SM_GBAR + (GD + 1) * 8;
constexpr int SM_P2 = 0, SM_P1 = P2B + 256;
constexpr int SM_L1 = SM_P1 + P1B + 128;
constexpr int SM_DEG = SM_L1 + 256;
constexpr int SM_CLS = SM_DEG + 512 * 4;
constexpr int SM_HIST = SM_CLS + NCLS * 4;
constexpr int SM_XLIST = SM_HIST + NB_MAX * 4;
constexpr int SM_SORT = SM_XLIST + 8;
constexpr int SM_SDEG = SM_SORT + NPB_MAX * 4;
constexpr int SM_PAIR = SM_SDEG + NPB_MAX * 2;
constexpr int SM_ENT = SM_ES + 1024;
constexpr int SM_H1 = SM_P1 + HB, SM_H2 = SM_P1;
constexpr int SM_IDX = SM_EID;
constexpr int SM_WR = SM_TAB;
static_assert(TILE_CAP <= 128 && TR >= 2 && SM_ES % 256 == 0 && NSTAGE == 2 && SM_BARS % 16 == 0 && SM_TINFO % 16 == 0 && SM_EID % 128 == 0 && SM_TAB % 1024 == 0 && SM_XU % 1024 == 0 && SM_TINFO % 8 == 0 && SM_OH % 16 == 0 && SM_XLIST % 8 == 0 && SM_PAIR % 8 == 0, "align");
static_assert(SM_P1 % 128 == 0 && P1B + HB <= SM_SRC - SM_EID && 2 * HB <= P1B && SM_H1 + 5 * 128 * 16 <= SM_XU && NB_MAX * (CE / 4) <= 6 * 384 && NB_MAX * 4 <= 5 * 128 && NB_MIN * 4 >= 3 * 128 && SM_PAIR + 128 * 8 <= SM_XU && CH_MAX * 4 <= SM_SRC - SM_EID && SM_DEG >= 3 << 14, "alias");
static_assert(CE == 64 && SMEM_BYTES <= 232448, "smem");
constexpr uint32_t C_BRK = 16  , C_CONT = 32, C_MORE = 64;
constexpr uint32_t ONE_F = 0x3F800000u;
constexpr int NONE = NPB_MAX - 1;
__host__ __device__ constexpr uint32_t tab_at(uint32_t n) { return (n >> 2) * 512 + (n & 3) * 32 + ((n >> 2) & 1) * 16; }

__device__ __forceinline__ uint32_t unpad(uint32_t w1, int np, float ga, float gb, float& d0, float& d1, int& dv) {
    const int pad = (w1 >> 8) & 31;
    dv = 2 * np - 1 - pad + (w1 >= ONE_F);
    float t0 = TAU * 2 * np, t1 = t0;
    if (pad) {
        t0 = fmaxf(t0, d0 * (1.f / 1024)); t1 = fmaxf(t1, d1 * (1.f / 1024));
        asm volatile("tanh.approx.f32 %0, %0;\ntanh.approx.f32 %1, %1;" : "+f"(ga), "+f"(gb));
        d0 -= pad * (1.f + ga); d1 -= pad * (1.f + gb);
    }
    if (dv == 0) { d0 = d1 = EPS2; t0 = t1 = 0.f; }
    return __ballot_sync(~0u, d0 < t0 || d1 < t1);
}
constexpr int SM_COPY = SM_XU + tab_at(NPB_MAX - 4) - 16;
__device__ __noinline__ float4* exact_copy(uint32_t bad)
{
    extern __shared__ __align__(1024) uint8_t smem[];
    uint32_t old = 1;
    if (bad == 1u << (threadIdx.x & 31)) old = atomicExch((uint32_t*)(smem + SM_MISC + 12), 1u);
    return __all_sync(~0u, old) ? g_copy + (blockIdx.x * 12 + (threadIdx.x >> 5)) * (64 * NPMAX) + (threadIdx.x & 31) : nullptr;
}
__device__ __noinline__ float4 epi_exact(const float4* gh, int np, int dv, uint32_t bad)
{
    extern __shared__ __align__(1024) uint8_t smem[];
    float n0 = 0.f, d0 = 0.f, n1 = 0.f, d1 = 0.f;
    int j = 0, ho = 32 * NPMAX;
    const bool one = gh == nullptr;
    if (one) {
        dv = __shfl_sync(~0u, dv, __ffs(bad) - 1); j = min(threadIdx.x & 15, np); np = j + 1; ho = NPMAX;
        gh = (const float4*)(smem + SM_COPY) + j;
        __syncwarp();
    }
    #pragma unroll 1
    for (; j < np; j++, gh += 32) {
        const float4 g = gh[0], h = gh[ho];
        const bool ma = 2 * j < dv, mb = 2 * j + 1 < dv;
        const float e0 = 2.f * rcpf(1.f + ex2f(-2.f * LOG2E * g.x)), e1 = 2.f * rcpf(1.f + ex2f(-2.f * LOG2E * g.y));
        const float e2 = 2.f * rcpf(1.f + ex2f(-2.f * LOG2E * g.z)), e3 = 2.f * rcpf(1.f + ex2f(-2.f * LOG2E * g.w));
        if (ma) { d0 += e0; n0 = fmaf(e0, h.x, n0); d1 += e2; n1 = fmaf(e2, h.z, n1); }
        if (mb) { d0 += e1; n0 = fmaf(e1, h.y, n0); d1 += e3; n1 = fmaf(e3, h.w, n1); }
    }
    if (__all_sync(~0u, one)) {
        #pragma unroll
        for (int o = 1; o < 16; o <<= 1) {
            n0 += __shfl_xor_sync(~0u, n0, o); d0 += __shfl_xor_sync(~0u, d0, o);
            n1 += __shfl_xor_sync(~0u, n1, o); d1 += __shfl_xor_sync(~0u, d1, o);
        }
        *(volatile uint32_t*)(smem + SM_MISC + 12) = 0;
    }
    return make_float4(n0, d0 + EPS2, n1, d1 + EPS2);
}
template<int NP>
__device__ __forceinline__ void epi_dump(const float* g, const float* h, float4* gh, uint32_t sa, bool on) {
    if (__all_sync(~0u, gh == nullptr)) {
        #pragma unroll
        for (int i = 0; i < 2 * NP; i++) {
            const float* v = i < NP ? g + 4 * i : h + 4 * (i - NP);
            asm volatile("{\n.reg .pred p;\nsetp.ne.u32 p, %5, 0;\n@p st.shared.v4.f32 [%0], {%1,%2,%3,%4};\n}"
                         :: "r"(sa + (i < NP ? i : NPMAX + i - NP) * 16), "f"(v[0]), "f"(v[1]), "f"(v[2]), "f"(v[3]), "r"((uint32_t)on) : "memory");
        }
    } else {
        #pragma unroll
        for (int i = 0; i < 2 * NP; i++) {
            const float* v = i < NP ? g + 4 * i : h + 4 * (i - NP);
            asm volatile("st.global.v4.f32 [%0], {%1,%2,%3,%4};" :: "l"(gh + (i < NP ? i : NPMAX + i - NP) * 32), "f"(v[0]), "f"(v[1]), "f"(v[2]), "f"(v[3]) : "memory");
        }
    }
}
__device__ __forceinline__ uint32_t row_bytes(uint32_t o) { return (o & 0xFE00) | ((o << 2) & 0x180); }

__device__ __noinline__ int balance(int step, char* gs, uint32_t id, int ng, int npb)
{
    extern __shared__ __align__(1024) uint8_t smem[];
    const uint32_t sb = smem_u32(smem), lane = threadIdx.x & 31, b = blockIdx.x, r4 = lane >> 3;
    const uint32_t tw = ((lane & 1) << 4) | ((lane & 6) << 6), ti = sb + SM_TINFO + r4 * 8, st = sb + SM_MISC + 48;
    uint32_t now; asm volatile("mov.u32 %0, %%globaltimer_lo;" : "=r"(now));
    auto put = [&](uint32_t a, uint32_t v) { if (lane == 0) asm volatile("st.relaxed.gpu.global.v2.u32 [%0], {%1, %2};" :: "l"(gs + a), "r"(v), "r"(id) : "memory"); };
    auto get = [&](uint32_t a) {
        uint2 v;
        #pragma unroll 1
        for (uint32_t n = 0; ; n++) {
            asm volatile("ld.acquire.gpu.global.v2.u32 {%0, %1}, [%2];" : "=r"(v.x), "=r"(v.y) : "l"(gs + a) : "memory");
            if (__all_sync(~0u, v.y == id)) break;
            if (n > (1u << 22)) __trap();
        }
        return v.x;
    };
    int gn = ng;
    if (step < 0) {
        if (BAL && step == -1) {
            const uint32_t e = lds32(sb + SM_TINFO + 3 * R3 * 32);
            if ((e & 0xFFFF) >= KM * 64 && ((e >> 20) & 127) < 2 && ((lds32(sb + SM_TINFO + (ng - KM) * 32 + 4) >> 16) & 15) <= 8 && lds32(sb + SM_MISC + 24) == 0) {
                if (PUBW) mbar_wait_h(sb + SM_GBAR + (PUBW - 1) * 8, 0);
                #pragma unroll 1
                for (int j = 0; j < KM; j++) {
                    const uint32_t ta = (ng - 1 - j) * 32, s0 = lds32(sb + SM_TINFO + ta) & 0xFFFF;
                    const uint2 e = lds64(ti + ta);
                    char* p = gs + G_P + (b * KM + j) * GRP_B;
                    const uint32_t ro = sb + ((e.y & 0xFFFF) ^ tw);
                    *(uint4*)(p + lane * 16) = lds128(ro + SM_TAB);
                    *(uint4*)(p + 512 + lane * 16) = lds128(ro + SM_XU);
                    *(uint2*)(p + 1024 + lane * 8) = lds64(sb + SM_EID + s0 * 4 + lane * 8);
                    *(uint32_t*)(p + 1280 + lane * 4) = lds32(sb + SM_SRC + s0 * 2 + lane * 4);
                    *(uint2*)(p + 1408 + r4 * 8) = make_uint2(e.x >> 27 ? e.x - s0 : e.x, e.y);
                }
                uint32_t c = 0;
                #pragma unroll 1
                for (int g = 3 * R1 + 3 + lane; g < ng; g += 32) c += 93 + ((lds32(sb + SM_TINFO + g * 32 + 4) >> 16) & 15) * 42;
                sts32(st, (__reduce_add_sync(~0u, c) * 595) >> 10);
                if (FEN == 1) asm volatile("fence.acq_rel.gpu;" ::: "memory");
                if (FEN == 2) __threadfence();
                __syncwarp();
                return 1;
            }
        }
        put(G_F + b * 8, (now << 6) & ~511u);
    } else if (step == R2) {
        uint2 v[5];
        #pragma unroll 1
        for (uint32_t n = 0; ; n++) {
            bool ok = true;
            #pragma unroll
            for (int i = 0; i < 5; i++) asm volatile("ld.relaxed.gpu.global.v2.u32 {%0, %1}, [%2];" : "=r"(v[i].x), "=r"(v[i].y) : "l"(gs + G_F + min(lane + 32 * i, gridDim.x - 1) * 8) : "memory");
            #pragma unroll
            for (int i = 0; i < 5; i++) ok &= v[i].y == id;
            if (__all_sync(~0u, ok)) break;
            if (n > (1u << 22)) __trap();
        }
        const uint32_t ref = __shfl_sync(~0u, v[0].x, 0) - 0x80000000u, key = ((lds32(st) - ref) & ~511u) | b;
        uint32_t c = 0;
        #pragma unroll
        for (int i = 0; i < 5; i++) if (lane + 32 * i < gridDim.x && (v[i].x & 256)) c += 0x10000 + ((((v[i].x - ref) & ~511u) | (lane + 32 * i)) < key);
        c = __reduce_add_sync(~0u, c);
        put(G_R + (c & 0xFFFF) * 8, key);
        sts64(st, key, (c >> 16) - 1 - (c & 0xFFFF));
        __syncwarp();
        return gn;
    } else {
        const uint32_t pk = get(G_R + lds32(st + 4) * 8);
        const int df = (int)(pk >> 9) - (int)(lds32(st) >> 9), m = min((abs(df) * 8 + BBIAS) / 350, KM);
        gn += df < 0 ? -m : m;
        if (gn > ng) {
            uint4 ra[KM], ru[KM]; uint2 le[KM], e[KM]; uint32_t ls[KM];
            #pragma unroll
            for (int i = 0; i < KM; i++) {
                const char* p = gs + G_P + ((pk & 255) * KM + i) * GRP_B;
                ra[i] = __ldcg((const uint4*)(p + lane * 16)); ru[i] = __ldcg((const uint4*)(p + 512 + lane * 16));
                le[i] = __ldcg((const uint2*)(p + 1024 + lane * 8)); e[i] = __ldcg((const uint2*)(p + 1408 + r4 * 8));
                ls[i] = __ldcg((const uint32_t*)(p + 1280 + lane * 4));
            }
            #pragma unroll
            for (int i = 0; i < KM; i++) {
                const int j = (m - 1 - i) & 3;
                const bool some = (e[i].y & 0xFFFF) != tab_at(NONE);
                const uint32_t row = some ? lds32(ti + i * 32 + 4) & 0xFFFF : tab_at(NONE);
                if (some) { sts128(sb + (row ^ tw) + SM_TAB, ra[i]); sts128(sb + (row ^ tw) + SM_XU, ru[i]); }
                sts64(sb + SM_EID + i * 256 + lane * 8, le[i].x, le[i].y);
                sts32(sb + SM_SRC + i * 128 + lane * 4, ls[i]);
                sts32(sb + SM_MISC + 64 + j * 16 + r4 * 4, (pk & 255) * npb * 128 + row_bytes(e[i].y & 0xFFFF));
                sts64(ti + (ng + j) * 32, ((e[i].x & 0xF800FFFFu) + i * 64) | (((e[i].y >> 16) & 15) > 5 ? 14u << 16 : 13u << 16), (e[i].y & 0xFFFF0000u) | row);
            }
            __syncwarp();
        }
        sts32(sb + SM_TINFO + gn * 32 + lane * 4, lane & 1 ? tab_at(NONE) : 0);
        sts32(sb + SM_MISC + 16, gn);
    }
    sts32(sb + SM_MISC + 28, gn);
    __syncwarp();
    if (lane == 0) mbar_arrive(sb + SM_ABAR + 32);
    return step < 0 ? 0 : gn;
}
__device__ __forceinline__ uint32_t bin_bits(uint32_t b) { return (1u << (b & 7)) | ((b < 48 ? 0x100u : 0x400u) << (b >> 3)); }
__device__ __forceinline__ void place(uint32_t sbase, uint32_t slot, uint32_t v, uint32_t eb) {
    asm volatile("{\n.reg .pred p;\nsetp.lt.u32 p, %0, %5;\n@p st.shared.u32 [%1], %2;\n@p st.shared.u16 [%3], %4;\n}"
                 :: "r"(slot), "r"(sbase + SM_EID + slot * 4), "r"(eb + (v >> 19)), "r"(sbase + SM_SRC + slot * 2), "r"(v), "n"(SLOT_CAP) : "memory");
}
__device__ __forceinline__ uint64_t desc_sw128(uint32_t a) {
    return (uint64_t)((a & 0x3FFFF) >> 4) | ((uint64_t)1 << 16) | ((uint64_t)64 << 32) | ((uint64_t)1 << 62);
}

template<bool LO32>
__global__ void __launch_bounds__(THREADS, 1)
gcn_kernel(const int* __restrict__ dst, unsigned* gbar, char* gs, const int* __restrict__ src, int E, int ch, int N, int npb, uint32_t magic,
           const __nv_bfloat16* __restrict__ x, const __nv_bfloat16* __restrict__ ea,
           const __nv_bfloat16* __restrict__ wa, const __nv_bfloat16* __restrict__ wb, const __nv_bfloat16* __restrict__ wc,
           const __nv_bfloat16* __restrict__ wu, const __nv_bfloat16* __restrict__ wv,
           __nv_bfloat16* out, int4 wrow, const __grid_constant__ CUtensorMap tm1, const __grid_constant__ CUtensorMap tm2,
           const __grid_constant__ CUtensorMap tmw, const __grid_constant__ CUtensorMap tmx)
{
    extern __shared__ __align__(1024) uint8_t smem[];
    int* cls = (int*)(smem + SM_CLS);
    int* misc = (int*)(smem + SM_MISC);
    WG0(); WS(0); CG(0);
    const uint32_t sbase = smem_u32(smem);
    const int tid = threadIdx.x, lane = tid & 31;
    const int b = blockIdx.x, nb = gridDim.x;
    const int cnt = max(0, min(ch, E - b * ch));
    const int node0 = b * npb;
    uint32_t tag = 0;
    if (tid < 384) asm volatile("ld.relaxed.gpu.global.u32 %0, [%1];" : "=r"(tag) : "l"(gbar) : "memory");
    auto dst_ld = [&](int v, uint32_t n) {
        const uint32_t off = v * (THREADS * 4) + tid * 4;
        asm volatile("{\n.reg .pred q;\nsetp.lt.u32 q, %2, %3;\n@q cp.async.cg.shared.global [%0], [%1], 16;\n}"
                     :: "r"(sbase + SM_IDX + off * 4), "l"(dst + (uint32_t)(b * ch + off)), "r"(off), "r"(n) : "memory");
    };
    dst_ld(0, min(cnt, 384 * 4));
    const int warp = (int)__reduce_max_sync(~0u, (unsigned)tid >> 5);
    const uint32_t su = __reduce_or_sync(~0u, sbase);
    if (warp >= 12) {
        const int v = warp & 3;
        const uint32_t a1 = su + SM_ABAR + (v == 0 ? 80 : v == 1 ? 120 : v == 2 ? 32 : 40);
        w_init(su + SM_ABAR + v * 8, 1); w_init(a1, 1);
        w_expect(su + SM_ABAR + v * 8, v < 3 ? min(max(cnt * 4 - v * 8192, 0), 8192) : 4 * 8192 + 2048);
        if (v < 2) w_expect(a1, v == 0 ? nb * (CE * 2) : nb * 64);
        asm volatile("fence.mbarrier_init.release.cluster;" ::: "memory");
        dst_ld(0, cnt);
    }
    #pragma unroll
    for (int v = 0; v < EPT / 4; v++) {
        if (v) {
            uint32_t c0, c1; asm volatile("mov.u32 %0, %%clock;" : "=r"(c0)); do { asm volatile("mov.u32 %0, %%clock;" : "=r"(c1)); } while (__all_sync(~0u, c1 - c0 < PD));
            dst_ld(v, cnt);
        }
        cp_commit();
    }
    if (warp == 15) {
        w_box_ld(su + SM_WR, &tmw, wrow.x, su + SM_ABAR + 24); w_box_ld(su + SM_WR + 8192, &tmw, wrow.y, su + SM_ABAR + 24);
        w_box_ld(su + SM_WR + 16384, &tmw, wrow.z, su + SM_ABAR + 24); w_ld(su + SM_WR + 24576, wc, 2048, su + SM_ABAR + 24);
        w_box_ld(su + SM_WR + 40960, &tmw, wrow.w, su + SM_ABAR + 24);
    }
    const int wg = warp >> 2, w = warp & 3;
    const int q = lane >> 2, t = lane & 3;
    const int nn = max(0, min(npb, N - node0));
    if (sbase & 1023) __trap();

    sts32(sbase + SM_DEG + tid * 4, tid < NPB_MAX ? 0 : 0x80000000u);
    if (tid < NCLS + NB_MAX) cls[tid] = tid < NCLS ? 0 : ((tid - NCLS) * 20) & 63;
    else if (warp == 8) sts32(sbase + SM_OH + lane * 4, t != (q >> 1) ? 0u : 0x00003F00u);
    else if (warp == 11) misc[lane] = lane == 5 ? TILE_CAP - TILE_X : lane == 8 || lane == 3;
    if (warp == 14) sts32(sbase + SM_TINFO + 96 * 32 + lane * 4, lane & 1 ? tab_at(NONE) : 0);
    if (warp == 15) sts32(sbase + SM_CLAIM + lane * 4, lane == 0 ? 3 * 32 : 0x40000000);
    if (tid == 0) sts32(sbase + SM_XLIST, tag);
    tag = (tag & 1) | 2;
    if (wg < 3) {
        const uint32_t d0 = ((NPB_MAX + ((2 * lane) & 15) + 16 * (b & 1)) * 4 | (tag << 14)) * 0x10001u, d1 = d0 + 0x40004u, d2 = tag << 16;
        #pragma unroll 1
        for (int i = tid; i < (P1B + 384) / 16; i += 384) {
            sts128(sbase + SM_P1 + i * 16, make_uint4(d0, d0, d1, i == P1B / 16 + 11 ? 0x80000000u | (tag << 14) : d1));
            sts128(sbase + SM_P2 + i * 16, make_uint4(d2, d2, d2, d2)); sts128(sbase + SM_P2 + P1B - 128 + i * 16, make_uint4(d2, d2, d2, d2));
        }
    }
    WS(1);
    __syncthreads();
    if (wg == 3) tag = lds32(sbase + SM_P2) >> 16;
    uint32_t all = 0;
    if (wg == 3) all = (lds32(sbase + SM_XLIST) + 1) * nb;
    if (tid == 128) {
        asm volatile("prefetch.tensormap [%0];" :: "l"((uint64_t)&tm1) : "memory");
        asm volatile("prefetch.tensormap [%0];" :: "l"((uint64_t)&tm2) : "memory");
        asm volatile("prefetch.tensormap [%0];" :: "l"((uint64_t)&tmx) : "memory");
    }
    const uint32_t m4 = __reduce_or_sync(~0u, -4 * npb);
    uint32_t ent[EPT];
    #pragma unroll
    for (int v = 0; v < EPT / 4; v++) {
        if (v == 0) cp_wait<2>(); else if (v == 1) cp_wait<1>(); else cp_wait<0>();
        if (v == 0 && wg == 2 && w < 3) {
            const int n = min(cnt * 4 - w * 8192, 8192);
            if (n > 0) w_ld(su + SM_XU + w * 8192, src + b * ch + w * 2048, n, su + SM_ABAR + w * 8);
        }
        const uint32_t off = v * (THREADS * 4) + tid * 4;
        if (off < (uint32_t)cnt) {
            const uint4 u = lds128(sbase + SM_IDX + off * 4);
            uint32_t dv[4] = {u.x, u.y, u.z, u.w}, ps[4], ck[4];
            uint32_t* en = ent + 4 * v;
            #pragma unroll
            for (int k = 0; k < 4; k++) {
                dv[k] = min(dv[k], (uint32_t)(nb * npb - 1));
                ps[k] = __umulhi(dv[k], magic);
                asm volatile("atom.shared.add.u32 %0, [%1], 0x10001;" : "=r"(ck[k]) : "r"(sbase + SM_HIST + ps[k] * 4) : "memory");
            }
            #pragma unroll
            for (int k = 0; k < 4; k++) {
                dv[k] = ps[k] * m4 + (dv[k] * 4 + (tag << 14));
                en[k] = (ck[k] & 63) + ps[k] * CE;
            }
            if (__builtin_expect(max(max(ck[0], ck[1]), max(ck[2], ck[3])) >= CE << 16, 0)) {
                auto step = [&]() {
                    uint32_t e = en[0];
                    const uint32_t d = dv[0];
                    if (ck[0] >= CE << 16) {
                        uint32_t j; asm volatile("atom.shared.inc.u32 %0, [%1], 0x7fffffff;" : "=r"(j) : "r"(sbase + SM_MISC + 8) : "memory");
                        j = min(j + (j >= 15), 63u);
                        sts32(sbase + SM_L1 + j * 4, d | ((j < 63 ? e / CE : 255u) << 16));
                        e = NB_MAX * CE + j;
                    }
                    en[0] = en[1]; en[1] = en[2]; en[2] = en[3]; en[3] = e;
                    dv[0] = dv[1]; dv[1] = dv[2]; dv[2] = dv[3]; dv[3] = d;
                    ck[0] = ck[1]; ck[1] = ck[2]; ck[2] = ck[3];
                };
                if (v == 2) { step(); step(); step(); step(); }
                else {
                    #pragma unroll 1
                    for (int k = 0; k < 4; k++) step();
                }
            }
            #pragma unroll
            for (int k = 0; k < 4; k++)
                asm volatile("st.shared.u16 [%0], %1;" :: "r"(sbase + SM_P1 + en[k] * 2), "r"(dv[k]) : "memory");
        }
    }
    if (warp == 15) {
        #pragma unroll
        for (int v = 0; v < EPT / 4; v++) sts128(sbase + SM_ENT + v * 512 + lane * 16, make_uint4(ent[4*v], ent[4*v+1], ent[4*v+2], ent[4*v+3]));
    }
    asm volatile("fence.proxy.async.shared::cta;" ::: "memory");
    WS(5);
    __syncthreads();
    if (warp == 15) {
        w_inc(gbar + 1);
        const uint32_t n = __reduce_or_sync(~0u, lds32(su + SM_MISC + 8));
        if (__builtin_expect(n > 15, 0)) {
            const uint2 r = lds64(su + SM_L1 + lane * 8);
            uint32_t m = lane < 8 ? 0 : (r.x >> 24 ? 0 : bin_bits(r.x >> 16)) | (r.y >> 24 ? 0 : bin_bits(r.y >> 16));
            m = n > 62 ? 0x7FFF3FFFu : __reduce_or_sync(~0u, m);
            sts32(su + SM_L1 + 60, m | 0x80000000u | (tag << 14));
            asm volatile("fence.proxy.async.shared::cta;" ::: "memory");
            __syncwarp();
        }
        w_st(gs + G_H1 + b * 64, su + SM_L1, 64);
        w_box_st(&tm1, b * (CE / 2), su + SM_P1);
        w_st(gs + G_L + b * 512, su + SM_L1, 256);
        asm volatile("cp.async.bulk.commit_group;" ::: "memory");
    } else {
        mbar_wait_c(su + SM_ABAR, 0);
        auto put = [&](uint32_t off, const uint32_t* uu) {
            if (off < (uint32_t)cnt) {
                const uint4 sv = lds128(sbase + SM_XU + off * 4);
                const uint32_t ss[4] = {sv.x, sv.y, sv.z, sv.w};
                #pragma unroll
                for (int k = 0; k < 4; k++) sts32(sbase + SM_P2 + uu[k] * 4, (ss[k] & 0xFFFF) | (((off + k) << 19) + (tag << 16)));
            }
        };
        #pragma unroll
        for (int v = 0; v < EPT / 4; v++) { if (v) mbar_wait_c(su + SM_ABAR + v * 8, 0); put(v * (THREADS * 4) + tid * 4, ent + 4 * v); }
        if (wg == 3) {
            const uint4 e = lds128(sbase + SM_ENT + w * 512 + lane * 16);
            const uint32_t uu[4] = {e.x, e.y, e.z, e.w};
            put(w * (THREADS * 4) + (480 + lane) * 4, uu);
        }
        asm volatile("fence.proxy.async.shared::cta;" ::: "memory");
        WS(7);
        __syncwarp();
        asm volatile("bar.arrive 12, 512;" ::: "memory");
    }
    WS(8);

    const int ngroups = (nn + 3) >> 2;
    if (warp < 12) {
        asm volatile("setmaxnreg.inc.sync.aligned.u32 152;");
        const uint32_t ab = su + SM_ABAR;
        uint32_t wf[40], wn[16];
        const uint32_t mo = sbase + (8 * (lane >> 4) + (lane & 7)) * 128 + (((2 * w + ((lane >> 3) & 1)) ^ (lane & 7)) << 4);
        const uint32_t wca = __shfl_sync(~0u, sbase + SM_WC + (16 * w + q) * 32 + t * 4 + ((q >> 2) << 4), lane), l16 = __shfl_sync(~0u, (lane & 15) * 16, lane);
        mbar_wait_c(ab + 24, 0);
        {
            #pragma unroll
            for (int ks = 0; ks < 4; ks++) { ldsm4t(wf + 4 * ks, mo + SM_WR + ks * 2048); ldsm4t(wf + 20 + 4 * ks, mo + SM_WR + 8192 + ks * 2048); ldsm4t(wn + 4 * ks, mo + SM_WR + 16384 + ks * 2048); }
            auto half = [](uint32_t& v) { asm("mul.rn.bf16x2 %0, %0, %1;" : "+r"(v) : "r"(0x3F003F00u)); };
            uint32_t z = 0;
            #pragma unroll
            for (int i = 0; i < 16; i++) { half(wf[i]); z ^= wf[i]; }
            sts32(sbase + SM_ES + lane * 4, z);
            if (wg == 2) {
                uint32_t f[4];
                ldsm4t(f, (mo ^ ((lane & 7) << 4)) + SM_WR + 24576);
                half(f[0]); half(f[1]); half(f[2]); half(f[3]);
                sts32(wca, f[0]); sts32(wca + 256, f[1]); sts32(wca ^ 16, f[2]); sts32((wca ^ 16) + 256, f[3]);
                asm volatile("fence.proxy.async.shared::cta;" ::: "memory");
            }
        }
        const uint64_t wcd = __reduce_or_sync(~0u, (((sbase + SM_WC) & 0x3FFFF) >> 4) | (8u << 16)) | EDHI;
        const uint32_t bar0 = __reduce_or_sync(~0u, sbase + SM_BARS + wg * 2 * STG);
        const uint32_t xd0 = __reduce_or_sync(~0u, (((sbase + SM_XS + wg * NSTAGE * XS_BYTES) & 0x3FFFF) >> 4) | (1u << 16));
        const uint32_t ed0 = __reduce_or_sync(~0u, (((sbase + SM_ES + wg * NSTAGE * ES_BYTES) & 0x3FFFF) >> 4) | (8u << 16));
        const uint64_t ohd = __reduce_or_sync(~0u, ((sbase + SM_OH) & 0x3FFFF) >> 4);
        const uint32_t tabx = __reduce_or_sync(~0u, sbase + SM_TAB + w * 128);
        const uint32_t bars = __reduce_or_sync(~0u, 2 * bar0 + STG), xds = __reduce_or_sync(~0u, 2 * xd0 + XS_BYTES / 16), eds = __reduce_or_sync(~0u, 2 * ed0 + ES_BYTES / 16);
        const uint32_t xuo = __reduce_or_sync(~0u, sbase + SM_XU + wg * 16384);
        { const uint2 z = lds64(sbase + SM_OH + 8); wf[38] = z.x; wf[39] = z.y; }
        WS(9);
        constexpr int NU = 6;
        const uint32_t dm = ((NPB_MAX + lane) * 4 | (tag << 14)) * 0x10001u;
        const uint32_t db = sbase + SM_DEG - (tag << 14);
        const char* const g1 = gs + (uint32_t)(b * (P1B + P2B) + tid * 8);
        int rk[NU][4];
        uint32_t spins = 0;
        {
            uint2 r1[NU];
            mbar_wait_c(ab + 80, 0);
            WS(2);
            #pragma unroll
            for (int i = 0; i < NU; i++) {
                r1[i] = make_uint2(dm, dm);
                if (NB_MIN * 16 >= 384 * (i + 1) || tid + 384 * i < nb * 16) r1[i] = lds64(sbase + SM_IDX + (tid + 384 * i) * 8);
            }
            #pragma unroll 1
            while (true) {
                uint32_t bad = 0;
                #pragma unroll
                for (int i = 0; i < NU; i++) bad |= r1[i].y ^ dm;
                if (__builtin_expect(!__any_sync(~0u, bad & 0xC000), 1)) break;
                #pragma unroll
                for (int i = 0; i < NU; i++) ld_unit(r1[i], g1 + 384 * 8 * i, (r1[i].y ^ dm) & 0xC000);
                if (++spins > (1u << 22)) break;
            }
            WS(3);
            #pragma unroll
            for (int i = 0; i < NU; i++) {
                rk[i][0] = r1[i].x & 0xFFFF; rk[i][1] = r1[i].x >> 16; rk[i][2] = r1[i].y & 0xFFFF; rk[i][3] = r1[i].y >> 16;
                #pragma unroll
                for (int k = 0; k < 4; k++) asm volatile("red.shared.add.u32 [%0], 1;" :: "r"(db + min((uint32_t)rk[i][k], NPB_MAX * 4 + (tag << 14))) : "memory");
            }
        }
        WS(10);
        asm volatile("bar.sync 11, 512;" ::: "memory");
        int mycls = 0, mycr = 0, dg = lds32(sbase + SM_DEG + tid * 4);
        if (tid < nn) {
            mycls = NCLS - 1 - (dg <= 40 ? dg : min(41 + ((dg - 41) >> 3), NCLS - 1)); mycr = atomicAdd(&cls[mycls], 1);
        }
        int s0 = 0;
        if (__builtin_expect(dg > 40, 0)) s0 = max(SLOT_CAP - ((dg + 1) & ~1) - atomicAdd(&misc[6], (dg + 1) & ~1), 0);
        asm volatile("bar.sync 1, 384;" ::: "memory");
        WS(12);
        {
            const uint2 c = lds64(sbase + SM_CLS + lane * 8);
            const int v0 = c.x * (lane > 11 ? ((64 - 2 * lane) << 16) + 1 : 1), v1 = c.y * (lane >= 11 ? ((62 - 2 * lane) << 16) + 1 : 1);
            int inc = v0 + v1;
            #pragma unroll
            for (int o = 1; o < 32; o <<= 1) { int y = __shfl_up_sync(~0u, inc, o); if (lane >= o) inc += y; }
            const int e0 = __shfl_sync(~0u, inc - v0 - v1, mycls >> 1), e1 = __shfl_sync(~0u, inc - v1, mycls >> 1);
            const int e = (mycls & 1) ? e1 : e0;
            if (tid < nn) {
                if (dg <= 40) s0 = min((e >> 16) + mycr * ((dg + 1) & ~1), SLOT_CAP - 40);
                sts32(sbase + SM_DEG + tid * 4, s0);
            }
            const uint32_t pos = tid < nn ? (e & 0xFFFF) + mycr : tid;
            sts32(sbase + SM_SORT + pos * 4, tid < nn ? (uint32_t)tid | ((uint32_t)s0 << 16) : NONE);
            asm volatile("st.shared.u16 [%0], %1;" :: "r"(sbase + SM_SDEG + pos * 2), "r"(min(dg, 65535)) : "memory");
            if (tid == 383) { misc[4] = (nn - c.y + 3) >> 2; if ((inc >> 16) + misc[6] > SLOT_CAP - 40) misc[1] = 1; }
        }
        asm volatile("bar.sync 1, 384;" ::: "memory");
        WS(13);
        const uint32_t sv = lds32(sbase + SM_SORT + tid * 4);
        const uint2 d4 = lds64(sbase + SM_SDEG + (tid >> 2) * 8);
        const uint32_t slow = lds32(sbase + SM_MISC + 4);
        #pragma unroll
        for (int i = 0; i < NU; i++) {
            #pragma unroll
            for (int k = 0; k < 4; k++) rk[i][k] = atoms_inc(db + rk[i][k]);
        }
        if (__reduce_or_sync(~0u, slow) == 0) {
            const uint32_t nd = sv & 0xFFFF;
            const int g = tid >> 2;
            dg = ((t & 2 ? d4.y : d4.x) >> (16 * (t & 1))) & 0xFFFF;
            const uint32_t hi2 = __vmaxu2(d4.x, d4.y), lo2 = __vminu2(d4.x, d4.y);
            const int mx = max(hi2 >> 16, hi2 & 0xFFFF), mn = min(lo2 >> 16, lo2 & 0xFFFF);
            int left = (mx + 1) >> 1;
            int tl = g, nx = ngroups + 4 + g, nt = left > NPMAX ? 2 : 1;
            const bool odd = left > 2 * NPMAX || (nt == 2 && nx >= TILE_CAP - TILE_X);
            if (__builtin_expect(__any_sync(~0u, odd), 0)) {
                if (odd) nt = (left + NPMAX - 1) / NPMAX;
                if (odd && t == 0) { asm volatile("atom.shared.add.u32 %0, [%1], %2;" : "=r"(nx) : "r"(sbase + SM_MISC + 20), "r"(nt - 1) : "memory"); if (nx + nt - 1 > TILE_CAP) misc[1] = 1; }
                nx = __shfl_sync(~0u, nx, lane & ~3);
                if (odd && nx + nt - 1 > TILE_CAP) left = 0;
            }
            const uint32_t w0 = tab_at(nd);
            if (g >= ngroups + 4) tl = ngroups;
            uint32_t cont = 0;
            int done = 0;
            bool act = true;
            do {
                int np = nt <= 2 ? (left + nt - 1) >> (nt - 1) : (left + nt - 1) / nt;
                left -= np; nt = max(nt - 1, 1);
                if (np) np = max(np, NPMIN);
                const int dv = min(max(dg - done, 0), 2 * np);
                uint32_t code = (uint32_t)np | cont | (left > 0 ? C_MORE : 0u);
                const bool gen = mn - done < 2 * np - (np == NPMIN ? 1 : 2);
                if (np == 0) code = 0;
                const uint32_t w1 = code | (dv == 2 * np ? 0x8000u : (2 * np - 1 - dv) << 8);
                if (act) *(uint2*)(smem + SM_TINFO + tl * 32 + t * 8) = make_uint2((dv ? (sv >> 16) + done : 0) | ((gen ? (np > 8 ? 15 : np > 5 ? 14 : 13) : np) << 16) | ((left > 0 ? nx : g >= ngroups - (KM + 3)) << 20) | ((uint32_t)dv << 27), w0 | (np == 0 ? 0u : w1 << 16));
                tl = nx++; cont = C_CONT; done += 2 * np; act = left > 0;
            } while (__any_sync(~0u, act));
        }
        __syncwarp();
        asm volatile("bar.arrive 4, 512;" ::: "memory");
        WS(14);
        wf[16] = lds32(wca); wf[17] = lds32(wca + 256); wf[18] = lds32(wca ^ 16); wf[19] = lds32((wca ^ 16) + 256);
        #pragma unroll
        for (int pc = 0; pc < 3; pc++) {
            uint4 r2[2];
            mbar_wait_c(ab + pc * 8, 1);
            if (pc == 0) WS(4); if (pc == 2) WS(16);
            #pragma unroll
            for (int k = 0; k < 2; k++) {
                r2[k] = lds128(sbase + SM_P2 + (tid + 384 * (2 * pc + k)) * 16);
                if (rk[2 * pc + k][0] < 0) r2[k].w = tag << 16;
            }
            while (__builtin_expect(__any_sync(~0u, ((r2[0].w ^ (tag << 16)) | (r2[1].w ^ (tag << 16))) & 0x30000), 0)) {
                #pragma unroll
                for (int k = 0; k < 2; k++)
                    ld_unit(r2[k], g1 + (uint32_t)(tid * 8) + (P1B + 384 * 16 * (2 * pc + k)), (r2[k].w ^ (tag << 16)) & 0x30000);
                if (++spins > (1u << 22)) break;
            }
            #pragma unroll
            for (int k = 0; k < 2; k++) {
                const int i = 2 * pc + k;
                const uint32_t eb = ((tid >> 4) + 24 * i) * ch;
                place(sbase, rk[i][0], r2[k].x, eb); place(sbase, rk[i][1], r2[k].y, eb); place(sbase, rk[i][2], r2[k].z, eb); place(sbase, rk[i][3], r2[k].w, eb);
            }
        }
        WGD();
        __syncwarp();
        asm volatile("bar.arrive 3, 480;" ::: "memory");
        float g[4 * NPMAX], h[4 * NPMAX];
        float4 cyr = make_float4(0.f, 0.f, 0.f, 0.f);
        WS(15); CG(1);
        mbar_wait_c(ab + 88 + wg * 8, 0);
        auto pack = [&](uint32_t* v, const float* u) {
            #pragma unroll
            for (int i = 0; i < 16; i++) v[i] = pack_bf16(u[2*i], u[2*i+1]);
        };
        auto rows_st = [&](uint32_t p, const uint32_t* v) {
            #pragma unroll
            for (int i = 0; i < 4; i++) stsm4t(p + i * 2048, v + 4 * i);
        };
        {
            const uint64_t d0 = desc_sw128(xuo), d1 = d0 + 512;
            const uint32_t mr = sbase + wg * 16384 + w * 128 + (tab_at(8 * (lane >> 4) + (lane & 7)) ^ ((lane & 8) << 1));
            uint32_t v[16];
            node_mma(g, wn, d0); node_mma(h, wn, d1);
            TileMMA<8>::wait_g(g);
            pack(v, g); rows_st(mr + SM_TAB, v);
            TileMMA<8>::wait_h(h);
            #pragma unroll
            for (int ks = 0; ks < 4; ks++) ldsm4t(wn + 4 * ks, mo + SM_WR + 40960 + ks * 2048);
            node_mma(g, wn, d0);
            if (wg == 2) asm volatile("bar.sync 5, 384;" ::: "memory"); else asm volatile("bar.arrive 5, 384;" ::: "memory");
            pack(v, h); rows_st(mr + SM_TAB + 8192, v);
            node_mma(h, wn, d1);
            __syncwarp();
            if (lane == 0) mbar_arrive(sbase + SM_ABAR + 112);
            TileMMA<8>::wait_g(g);
            pack(v, g);
            asm volatile("bar.sync %0, 128;" :: "r"(8 + wg) : "memory");
            rows_st(mr + SM_XU, v);
            TileMMA<8>::wait_h(h);
            pack(v, h);
            asm volatile("bar.sync %0, 128;" :: "r"(8 + wg) : "memory");
            rows_st(mr + SM_XU + 8192, v);
            __syncwarp();
            if (lane == 0) mbar_arrive(sbase + SM_ABAR + 72);
            mbar_wait_c(ab + 112, 0);
            __syncwarp();
            if (__builtin_expect(__reduce_or_sync(~0u, misc[1]) != 0, 0)) { slow_bin(x, ea, src, dst, wa, wb, wc, wu, wv, out, E, node0, nn, 384); asm volatile("exit;"); }
            WS(6);
        }
        uint32_t bar = bar0, xd = xd0, ed = ed0, ph = 0;
        float pn0 = 0.f, pd0 = 1.f, pn1 = 0.f, pd1 = 1.f;
        uint4 rc;
        rc.x = lds32(sbase + SM_TINFO + wg * 32 + ((lane >> 1) & 3) * 8 + 4);
        uint32_t code = __reduce_or_sync(~0u, rc.x >> 16);
        rc.x = (rc.x & 0xFFFF) ^ ((lane & 8) << 1);
        uint32_t pst = tabx + tab_at(NONE);
        auto fetch_a = [&]() {
            asm volatile("ldmatrix.sync.aligned.m8n8.x2.trans.shared.b16 {%0,%1}, [%2];" : "=r"(wf[36]), "=r"(wf[37]) : "r"(tabx + rc.x) : "memory");
        };
        auto emit = [&]() {
            asm volatile("stmatrix.sync.aligned.m8n8.x1.trans.shared.b16 [%0], {%1};" :: "r"(pst), "r"(pack_bf16(pn0 * rcpf(pd0), pn1 * rcpf(pd1))) : "memory");
        };
        auto carry = [&]() {
            if (rc.z & C_CONT) { pn0 += cyr.x; pd0 += cyr.y; pn1 += cyr.z; pd1 += cyr.w; }
            if (rc.z & C_MORE) { cyr = make_float4(pn0, pd0 - EPS2, pn1, pd1 - EPS2); pn0 = pn1 = 0.f; pst = tabx + tab_at(NONE); }
        };
        fetch_a();
        while (true) {
            switch (code & 15) {
                default: goto finished;
#define TILE(P) { \
                    bool ok; float dmin; \
                    do { \
                        mbar_wait_c(bar, ph); \
                        TileMMA<P>::issue(g, h, wf, xd, ed | EDHI, ohd, wcd); \
                        const uint32_t eb = bar + 8; \
                        ph ^= bar != bar0; bar = bars - bar; xd = xds - xd; ed = eds - ed; \
                          \
                        asm volatile("{\n.reg .pred p;\nsetp.eq.u32 p, %0, 77;\n@p trap;\n}" :: "r"(xds) : "memory"); \
                        emit(); rc = lds128(eb + 8 + l16); \
                        TileMMA<P>::wait_g(g); fetch_a(); TileMMA<P>::wait_h(h); \
                        mbar_arrive(eb); \
                        asm volatile("add.u32 %0, %1, %2;" : "=r"(pst) : "r"(rc.y), "r"(tabx)); \
                        ok = epi_fast<P>(g, h, __uint_as_float(rc.z), __uint_as_float(rc.w), pn0, pd0, pn1, pd1, dmin); \
                    } while (__all_sync(~0u, ok)); \
                    code = __reduce_or_sync(~0u, rc.w); \
                    if (__builtin_expect(__any_sync(~0u, ((rc.z & 0x1F00) != 0) | (dmin < TAU * 2 * P)), 0)) { \
                        int dv; \
                        const uint32_t bad = unpad(rc.z, P, g[4 * P - 4], g[4 * P - 2], pd0, pd1, dv); \
                        if (__builtin_expect(bad != 0, 0)) { \
                            float4* gh = exact_copy(bad); \
                            const bool on = (bad >> lane) & 1; \
                            epi_dump<P>(g, h, gh, su + SM_COPY, on); \
                            const float4 r = epi_exact(gh, P, dv, bad); \
                            if (on) { pn0 = r.x; pd0 = r.y; pn1 = r.z; pd1 = r.w; } \
                        } \
                    } \
                    if (code & C_BRK) { carry(); if (P != 11 && (code & 15) == P) goto L##P; } \
                    if (P == 11) {         \
                        wf[16] = lds32(wca); wf[17] = lds32(wca + 256); wf[18] = lds32(wca ^ 16); wf[19] = lds32((wca ^ 16) + 256); \
                    } }
#define CASE(P, UP, DN) case P: L##P: TILE(P) \
                    if (P > NPMIN && (code & 15) == P - 1) goto L##DN; \
                    if ((code & 15) == UP) goto L##UP; \
                    break;
                CASE(11, 11, 10) CASE(10, 11, 9) CASE(9, 10, 8) CASE(8, 9, 7) CASE(7, 8, 6) CASE(6, 7, 5) CASE(5, 6, 5)
#undef CASE
#undef TILE
            }
        }
finished:
        emit();
        __syncwarp();
        if (lane == 0) mbar_arrive(sbase + SM_ABAR + 48 + wg * 8);
    } else {
        asm volatile("setmaxnreg.dec.sync.aligned.u32 56;");
        auto x_ld = [&](int i0, int i1) {
            #pragma unroll
            for (int i = i0; i < i1; i++) w_box_ld(su + SM_XU + i * 8192, &tmx, node0 + i * 64, su + SM_ABAR + 88 + (i >> 1) * 8);
        };
        if (w < 3) {
            #pragma unroll
            for (int i = 0; i < 2; i++) { w_init(su + SM_BARS + (w * 2 + i) * STG, 64); w_init(su + SM_BARS + (w * 2 + i) * STG + 8, 128); }
            w_init(su + SM_ABAR + 48 + w * 8, 4);
            w_init(su + (w == 0 ? SM_GBAR + 99 * 8 : w == 1 ? SM_ABAR + 72 : SM_ABAR + 112), w == 0 ? 32 : 12);
        } else {
            #pragma unroll
            for (int i = 0; i < 4; i++) { w_init(su + SM_ABAR + (i < 3 ? 88 + i * 8 : 40), 1); w_expect(su + SM_ABAR + (i < 3 ? 88 + i * 8 : 40), i < 3 ? 16384 : nb * 64); }
            asm volatile("fence.mbarrier_init.release.cluster;" ::: "memory");
            w_hint(gbar + 1, all);
            asm volatile("cp.async.bulk.wait_group.read 0;" ::: "memory");
            WS(2);
            w_ld(su + SM_IDX, gs + b * (P1B + P2B), nb * (CE * 2), su + SM_ABAR + 80);
            w_ld(su + SM_H1, gs + G_H1, nb * 64, su + SM_ABAR + 120);
            asm volatile("bar.sync 12, 512;" ::: "memory");
            w_box_st(&tm2, P1B / 4 + b * CE, su + SM_P2);
            w_st(gs + G_H2 + b * 64, su + SM_P2 + P2B, 64);
            w_st(gs + G_L + b * 512 + 256, su + SM_P2 + P2B, 256);
            w_sent(gbar + 4, su + SM_MISC + 32);
            asm volatile("cp.async.bulk.commit_group;" ::: "memory");
        }
        const uint32_t ab = su + SM_ABAR;
        uint32_t todo = 0;
        const uint32_t mb = (lane & 3) == 3 ? bin_bits(b) : ~0u;
        WS(12);
        mbar_wait_c(ab + 120, 0);
        WS(13);
        {
            uint4 r[5];
            #pragma unroll
            for (int i = 0; i < 5; i++) r[i] = lds128(sbase + SM_H1 + (tid - 384 + 128 * i) * 16);
            #pragma unroll
            for (int i = 0; i < 5; i++) {
                const uint32_t bb = b << 16;
                const uint32_t m = min(min(r[i].x ^ bb, r[i].y ^ bb), min(r[i].z ^ bb, r[i].w ^ bb)) >> 16;
                if ((m == 0) | (((r[i].w ^ (tag << 14)) & 0xC000) != 0) | ((~r[i].w & mb) == 0)) todo |= 1 << i;
            }
            todo &= tid - 384 + 512 < nb * 4 ? 31 : tid - 384 + 384 < nb * 4 ? 15 : 7;
        }
        #pragma unroll 1
        for (int put = 0; put < 2; put++) {
            uint32_t any = __reduce_or_sync(~0u, todo), m = 0, u = 0;
            #pragma unroll 1
            while (any | m) {
                uint4 r = make_uint4(0, 0, 0, 0), r2 = r;
                uint32_t s, go, gd;
                bool on;
                if (__builtin_expect(m == 0, 1)) {
                    const uint32_t i = __ffs(any) - 1;
                    any &= any - 1; u = tid - 384 + 128 * i; on = (todo >> i) & 1;
                    r = lds128(sbase + SM_H1 + u * 16); r2 = lds128(sbase + SM_H2 + u * 16);
                    s = u >> 2; go = G_H1 + u * 16; gd = HB;
                } else {
                    s = ((u & ~31) + __ffs(m) - 1) >> 2; m &= m - 1; on = lane < 12;
                    go = G_L + s * 512 + 64 + lane * 16; gd = 256;
                }
                #pragma unroll 1
                for (int n = 0; n < (1 << 22); n++) {
                    const bool b1 = on && ((r.w >> 14) & 3) != tag, b2 = on && put && ((r2.w >> 16) & 3) != tag;
                    if (__builtin_expect(!__any_sync(~0u, b1 | b2), 1)) break;
                    ld_unit(r, gs + go, b1); ld_unit(r2, gs + go + gd, b2);
                }
                if (gd == HB) m = __ballot_sync(~0u, on && (~r.w & mb) == 0);
                if (on && r.w >> 16 == 255) sts32(sbase + SM_MISC + 4, 1);
                const uint32_t e[4] = {r.x, r.y, r.z, r.w}, v[4] = {r2.x, r2.y, r2.z, r2.w};
                uint32_t slot[4];
                #pragma unroll
                for (int k = 0; k < 4; k++) slot[k] = atoms_inc(sbase + SM_DEG + (on && e[k] >> 16 == (uint32_t)b ? (e[k] & 0x3FFF) : (NPB_MAX + lane) * 4));
                if (put) {
                    #pragma unroll
                    for (int k = 0; k < 4; k++) place(sbase, slot[k], v[k], s * ch);
                }
            }
            if (put == 0) {
                WS(4);
                asm volatile("bar.arrive 11, 512;" ::: "memory");
                if (w == 3) {
                    x_ld(0, 1);
                    w_expect(su + SM_ABAR, 12288); w_expect(su + SM_ABAR + 8, 12288); w_expect(su + SM_ABAR + 16, nb * (CE * 4) - 24576);
                    w_hint(gbar + 4, all);
                    asm volatile("cp.async.bulk.wait_group.read 0;" ::: "memory");
                    WS(3);
                    const char* g2 = gs + b * (P1B + P2B) + P1B;
                    w_ld(su + SM_P2, g2, 12288, su + SM_ABAR);
                    w_ld(su + SM_P2 + 12288, g2 + 12288, 12288, su + SM_ABAR + 8);
                    w_ld(su + SM_P2 + 24576, g2 + 24576, nb * (CE * 4) - 24576, su + SM_ABAR + 16);
                    w_ld(su + SM_H2, gs + G_H2, nb * 64, su + SM_ABAR + 40);
                    x_ld(1, XM);
                    mbar_wait_c(ab, 1); x_ld(XM, XN);
                    if (XN < 6) { mbar_wait_c(ab + XP * 8, 1); x_ld(XN, 6); }
                } else {
                    #pragma unroll 11
                    for (int i = 0; i < 33; i++) w_init(su + SM_GBAR + (w * 33 + i) * 8, 32);
                    w_init(su + SM_GBAR + GD * 8, 32);
                }
                asm volatile("bar.sync 4, 512;" ::: "memory");
                mbar_wait_c(ab + 40, 0);
            }
        }
        __syncwarp();
        WS(10);
        WGD();
        const uint32_t scr = sbase + SM_PAIR + (tid & 127) * 8;
        const int r4 = lane >> 3, c8 = lane & 7;
        const uint32_t sb = su;
        const uint32_t tk = ((c8 & 1) << 4) | ((c8 >> 1) << 7);
        if (w < 3) {
            const char* gx = as_pair((const char*)x + c8 * 16, scr);
            const char* ge = as_pair((const char*)ea + (lane & 1) * 16, scr);
            const uint32_t gx0 = (uint32_t)(uint64_t)gx, ge0 = (uint32_t)(uint64_t)ge, hi = (uint64_t)gx >> 32, he = (uint64_t)ge >> 32;
            const int s = (lane >> 1) & 3;
            const uint32_t xs0 = sb + SM_XS + w * NSTAGE * XS_BYTES;
            const uint32_t es0 = sb + SM_ES + w * NSTAGE * ES_BYTES + r4 * 64 + (((lane ^ (r4 >> 1)) & 1) << 4) + (s >> 1) * 256 + (s & 1) * 32;
            const uint32_t bars = sb + SM_BARS + w * 2 * STG;
            const uint32_t xoffA = (2 * r4) * 128 + ((c8 ^ (2 * r4)) << 4), xoffB = (2 * r4 + 1) * 128 + ((c8 ^ (2 * r4 + 1)) << 4);
            uint64_t pol;
            asm volatile("createpolicy.fractional.L2::evict_first.b64 %0, 1.0;" : "=l"(pol));
            asm volatile("bar.sync 6, 128;" ::: "memory");
            WS(15);
            uint32_t ph = 1, cur = w;
            uint32_t hist = GD * 0x010101u;
            auto done3 = [&]() { uint32_t v = (hist >> 16) & 0xFF; asm("" : "+r"(v)); mbar_arrive(sb + SM_GBAR + v * 8); };
            const bool go = __reduce_or_sync(~0u, misc[1] == 0 && nn > 0);
            const uint32_t k32 = __shfl_sync(~0u, lane == 31 ? 0 : 32, lane), k15 = __shfl_sync(~0u, 15 | (lane & 1) << 7, lane), ca = SM_CLAIM + min(lane, 30) * 4, pa = sb + SM_TINFO + r4 * 8;
            const uint32_t pb = sb + SM_TINFO + s * 8 + 4, pc = sb + SM_TINFO + (lane & 3) * 8 + 6, xl = (lane & 8) << 1, xs = (lane & 1) << 4, ra = (lane & 15) * 16 + 16;
            auto row_of = [&](uint32_t o) { uint32_t v; asm volatile("ld.shared.u16 %0, [%1];" : "=r"(v) : "r"(pb + o) : "memory"); return v; };
            auto code_of = [&](uint32_t o) { uint32_t v; asm volatile("ld.shared.s16 %0, [%1];" : "=r"(v) : "r"(pc + o) : "memory"); return v; };
            uint32_t pw = lds32(pa + w * 32), pt = __reduce_or_sync(~0u, pw), cont = 1;
            uint4 rc = make_uint4(0, row_of(w * 32) ^ xs, code_of(w * 32) & (ONE_F | 0x1FFFu), 0);
            const uint32_t se0 = sb + SM_EID + s * 4, xab = xoffB - xoffA, das = 2 * (xs0 + xoffA) + XS_BYTES, des = 2 * es0 + ES_BYTES, brs = 2 * bars + STG;
            uint32_t br = bars, da = xs0 + xoffA, de = es0;
            #pragma unroll 1
            while (go) {
                uint32_t se, sx;
                asm("dp2a.lo.u32.u32 %0, %1, 4, %2;" : "=r"(se) : "r"(pw), "r"(se0));
                asm("dp2a.lo.u32.u32 %0, %1, 2, %2;" : "=r"(sx) : "r"(pw), "r"(sb + SM_SRC));
                const int dv = pw >> 27;
                const uint32_t db = da + xab;
                const uint32_t sel = (pt >> 16) & 15, nf = (pt >> 15) & (127 << 5), nx = nf == 32 ? 0u : nf;
                uint32_t g;
                auto claim = [&]() { asm volatile("atom.shared.add.u32 %0, [%1], %2;" : "=r"(g) : "r"(ca + (nx == 0 ? sb : sb + 4)), "r"(k32) : "memory"); };
                if (sel == 0) break;
                if ((cont & 1) | (nf ^ nx)) {
                    if (cont & 1) asm volatile("bar.sync 3, 480;" ::: "memory");
                    if (nf != nx) mbar_wait_c(sb + SM_ABAR + 32, 0);
                }
                switch (sel) {
#define CASE(L, P, GEN) case L: { \
                        uint32_t oe[(P + 1) / 2], o[P]; \
                        _Pragma("unroll") for (int j = 0; j < (P + 1) / 2; j++) oe[j] = lds32(se + j * 16); \
                        _Pragma("unroll") for (int j = 0; j < P; j++) o[j] = lds32(sx + j * 4); \
                        mbar_wait_h(br + 8, ph); \
                        _Pragma("unroll") for (int j = 0; j < (P + 1) / 2; j++) \
                            if (LO32) { if (!GEN && 2 * j + 2 < P) cpe<false>(he, de + j * 512, oe[j], ge0, 0, 0, pol); \
                                else if (2 * j + 1 < NPMAX || s < 2) cpe<true>(he, de + j * 512, oe[j], ge0, 4 * j + s, dv, pol); } \
                            else if (!GEN && 2 * j + 2 < P) cp16e(de + j * 512, ge, oe[j], pol); else if (2 * j + 1 < NPMAX || s < 2) cp16z<32>(de + j * 512, ge, oe[j], 4 * j + s, dv, pol); \
                        _Pragma("unroll") for (int j = 0; j < P - 1; j++) { \
                            if (LO32) { cpx<0, GEN>(hi, da + j * 1024, o[j], gx0, 2 * j, dv); cpx<1, GEN>(hi, db + j * 1024, o[j], gx0, 2 * j + 1, dv); } \
                            else if (GEN) { cp16z<128>(da + j * 1024, gx, o[j] & 0xFFFFu, 2 * j, dv, 0); cp16z<128>(db + j * 1024, gx, o[j] >> 16, 2 * j + 1, dv, 0); } \
                            else { cp16i<128>(da + j * 1024, gx, o[j] & 0xFFFFu); cp16i<128>(db + j * 1024, gx, o[j] >> 16); } } \
                        if (LO32) { cpx<0, true>(hi, da + (P - 1) * 1024, o[P - 1], gx0, 2 * P - 2, dv); cpx<1, true>(hi, db + (P - 1) * 1024, o[P - 1], gx0, 2 * P - 1, dv); } \
                        else { cp16z<128>(da + (P - 1) * 1024, gx, o[P - 1] & 0xFFFFu, 2 * P - 2, dv, 0); cp16z<128>(db + (P - 1) * 1024, gx, o[P - 1] >> 16, 2 * P - 1, dv, 0); } \
                    } break;
                    CASE(11, 11, false)
                    CASE(6, 6, false) CASE(7, 7, false) CASE(8, 8, false) CASE(9, 9, false) CASE(10, 10, false)
                    CASE(15, NPMAX, true) CASE(14, 8, true) default: CASE(13, 5, true)
#undef CASE
                }
                claim();
                mbar_cp_arrive(br);
                done3();
                g = __reduce_min_sync(~0u, g);
                {
                    const uint32_t o = nx == 0 ? g : nx;
                    pw = lds32(pa + o);
                    const uint32_t ya = row_of(o), yb = code_of(o);
                    pt = __reduce_or_sync(~0u, pw);
                    const uint32_t brk = (cont | nx) > 1 ? C_BRK : 0u;
                    rc.x = ya ^ xl;
                    const uint32_t lv = brk | ((sel + (15 - NPMAX)) & 16) | (((pt >> 16) & 15) ^ sel);
                    rc.w = (yb & k15) | (lv ? 0x70000000u | brk : TAU_BITS);
                    asm volatile("st.shared.v4.u32 [%2], {%3, %0, %1, %4};\nxor.b32 %0, %5, %6;\nand.b32 %1, %7, %8;"
                                 : "+r"(rc.y), "+r"(rc.z) : "r"(br + ra), "r"(rc.x), "r"(rc.w), "r"(ya), "r"(xs), "r"(yb), "n"(ONE_F | 0x1FFFu) : "memory");
                    cont = nx;
                }
                mbar_arrive(br);
                hist = (hist << 8) | (nx == 0 ? cur : (uint32_t)GD);
                cur = nx == 0 ? g >> 5 : cur;
                ph ^= br != bars; br = brs - br;
                da = das - da; de = des - de;
            }
            if (cont & 1) asm volatile("bar.sync 3, 480;" ::: "memory");
            if (go) {
                mbar_wait(sb + SM_ABAR + 32, 0);
                const int g0 = 3 * max((misc[7] + 2) / 3 - TR, 0) + w;
                uint32_t ro[TR], gb[TR]; uint4 xv[TR], xu[TR]; char* op[TR];
                const int gz = misc[4];
                #pragma unroll
                for (int k = 0; k < TR; k++) {
                    uint32_t nd;
                    asm volatile("ld.shared.u16 %0, [%1];" : "=r"(nd) : "r"(pa + (g0 + 3 * k) * 32 + 4) : "memory");
                    uint32_t rb = node0 * 128 + row_bytes(nd);
                    if (g0 + 3 * k >= ngroups) rb = misc[16 + ((g0 + 3 * k - ngroups) & 3) * 4 + r4];
                    if (nd == tab_at(NONE)) rb = 0;
                    xv[k] = __ldg((const uint4*)(gx + rb));
                    op[k] = nd == tab_at(NONE) ? nullptr : (char*)out + rb + c8 * 16;
                    ro[k] = sb + (nd ^ tk);
                    xu[k] = lds128(ro[k] + SM_XU);
                    gb[k] = __reduce_or_sync(~0u, g0 + 3 * k < gz ? sb + SM_GBAR + (g0 + 3 * k) * 8 : 0u);
                }
                #pragma unroll 1
                for (int k = 0; k < 3; k++) {
                    mbar_wait(k < 2 ? br + 8 : sb + SM_ABAR + 48 + w * 8, k < 2 ? ph : 0);
                    done3(); hist <<= 8;
                    ph ^= br != bars; br = brs - br;
                }
                #pragma unroll
                for (int k = 0; k < TR; k++) {
                    uint4 a = make_uint4(0, 0, 0, 0);
                    if (gb[k]) { mbar_wait(gb[k], 0); a = lds128(ro[k] + SM_TAB); }
                    finish(a, xu[k], xv[k]);
                    if (op[k]) *(uint4*)op[k] = a;
                }
            }
            cp_wait<0>();
        } else {
            const char* gx = as_pair((const char*)x + (size_t)node0 * 128 + c8 * 16, scr);
            const char* ob = as_pair((const char*)out + (size_t)node0 * 128 + c8 * 16, scr);
            asm volatile("bar.arrive 6, 128;" ::: "memory");
            WS(15);
            if (b == 0 && lane == 0) asm volatile("red.relaxed.gpu.global.add.u32 [%0], 1;" :: "l"(gbar) : "memory");
            if (misc[1] == 0) mbar_wait(sb + SM_ABAR + 72, 0);
            if (npb <= NPB_MAX - 4) sts32(sb + SM_MISC + 12, 0);
            int rounds = misc[1] ? 0 : max((ngroups + 2) / 3 - TR, 0);
            const int gz = misc[4];
            int fast = __reduce_min_sync(~0u, min(rounds, gz / 3));
            uint32_t wl = sb + SM_TINFO + r4 * 8 + 4, gbar = sb + SM_GBAR;
            auto row_at = [&](uint32_t a) { uint32_t n; asm volatile("ld.shared.u16 %0, [%1];" : "=r"(n) : "r"(a) : "memory"); return n; };
            auto fetch = [&](uint32_t n, uint4& v) {
                asm volatile("{\n.reg .b64 p;\ncvt.u64.u32 p, %5;\nadd.u64 p, p, %4;\nld.global.nc.L1::no_allocate.v4.u32 {%0,%1,%2,%3}, [p];\n}"
                             : "=r"(v.x), "=r"(v.y), "=r"(v.z), "=r"(v.w) : "l"(gx), "r"(n));
            };
            auto store = [&](uint32_t n, const uint4& a) {
                asm volatile("{\n.reg .b64 p;\ncvt.u64.u32 p, %1;\nadd.u64 p, p, %0;\nst.global.v4.u32 [p], {%2,%3,%4,%5};\n}" :: "l"(ob), "r"(n), "r"(a.x), "r"(a.y), "r"(a.z), "r"(a.w) : "memory");
            };
            uint32_t n0[3], o0[3]; uint4 x0[3];
            const uint32_t tw = __shfl_sync(~0u, tk, lane);
            int step = fast > R3 + 3 && gz == ngroups ? -1 : -2, k = 0;
            #pragma unroll 1
            do {
                const int gn = __reduce_max_sync(~0u, balance(step, gs, all, ngroups, npb));
                if (step == R3) fast = rounds = (gn + 2) / 3 - TR;
                const bool pub = step < 0 && gn;
                step = gn == 0 || step == R3 ? fast - 1 : step < 0 ? R2 : R3;
                if (fast) {
                    #pragma unroll
                    for (int r = 0; r < 3; r++) { const uint32_t v = row_at(wl + r * 32); n0[r] = row_bytes(v); o0[r] = v ^ tw; fetch(n0[r], x0[r]); }
                }
                #pragma unroll 1
                for (; k <= step; k++) {
                    const uint32_t wn = k < step ? wl + 96 : wl;
                    uint4 xu[3], a[3]; uint32_t v[3];
                    #pragma unroll
                    for (int r = 0; r < 3; r++) { xu[r] = lds128(sb + o0[r] + SM_XU); v[r] = row_at(wn + r * 32); }
                    mbar_wait_h(gbar, 0); mbar_wait_h(gbar + 8, 0); mbar_wait(gbar + 16, 0);
                    #pragma unroll
                    for (int r = 0; r < 3; r++) a[r] = lds128(sb + o0[r] + SM_TAB);
                    #pragma unroll
                    for (int r = 0; r < 3; r++) {
                        finish(a[r], xu[r], x0[r]);
                        store(n0[r], a[r]);
                        n0[r] = row_bytes(v[r]); o0[r] = v[r] ^ tw;
                        fetch(n0[r], x0[r]);
                    }
                    gbar += 24; wl += 96;
                    if (pub && k == R1) {
                        uint32_t now; asm volatile("mov.u32 %0, %%globaltimer_lo;" : "=r"(now));
                        now = __reduce_max_sync(~0u, (((now + lds32(sb + SM_MISC + 48)) << 6) & ~511u) | 256);
                        sts32(sb + SM_MISC + 48, now);
                        asm volatile(ELECT "st.relaxed.gpu.global.v2.u32 [%0], {%1, %2};\n}" :: "l"(gs + G_F + b * 8), "r"(now), "r"(all) : "memory");
                    }
                }
            } while (k < fast);
            #pragma unroll 1
            for (int g = 3 * fast; g < 3 * rounds; g++) {
                const uint32_t v = row_at(sb + SM_TINFO + r4 * 8 + 4 + g * 32), nd = row_bytes(v), ro = sb + (v ^ tw);
                uint4 xv, a = make_uint4(0, 0, 0, 0);
                fetch(nd, xv);
                if (g < gz) { mbar_wait(sb + SM_GBAR + g * 8, 0); a = lds128(ro + SM_TAB); }
                finish(a, lds128(ro + SM_XU), xv);
                store(nd, a);
            }
        }
    }
    WS(17); WG1(); CG(2);
}

}

extern "C" void kernel_launch(void* const* d_in, const int* in_sizes, int n_in, void* d_out, int out_size) {
    const __nv_bfloat16* x = (const __nv_bfloat16*)d_in[0];
    const __nv_bfloat16* ea = (const __nv_bfloat16*)d_in[1];
    const int* src = (const int*)d_in[2];
    const int* dst = (const int*)d_in[3];
    const __nv_bfloat16* wa = (const __nv_bfloat16*)d_in[4];
    const __nv_bfloat16* wb = (const __nv_bfloat16*)d_in[5];
    const __nv_bfloat16* wc = (const __nv_bfloat16*)d_in[6];
    const __nv_bfloat16* wu = (const __nv_bfloat16*)d_in[7];
    const __nv_bfloat16* wv = (const __nv_bfloat16*)d_in[8];
    __nv_bfloat16* out = (__nv_bfloat16*)d_out;
    int N = in_sizes[0] / 64, E = in_sizes[2];
    static int sms = 0;
    static CUtensorMap tm1, tm2, tmw, tmx;
    static bool tm_ok = false;
    static void* gp = nullptr; static void* gb = nullptr;
    typedef CUresult (*EncFn)(CUtensorMap*, CUtensorMapDataType, cuuint32_t, void*, const cuuint64_t*, const cuuint64_t*, const cuuint32_t*,
                              const cuuint32_t*, CUtensorMapInterleave, CUtensorMapSwizzle, CUtensorMapL2promotion, CUtensorMapFloatOOBfill);
    static void* fn = nullptr;
    auto enc = [&](CUtensorMap* tm, const void* base, cuuint64_t cols, cuuint64_t rows, cuuint32_t bc, cuuint32_t br, CUtensorMapSwizzle sw) {
        cuuint64_t g2[2] = {cols, rows}, gs[1] = {cols * 4};
        cuuint32_t b2[2] = {bc, br}, es[2] = {1, 1};
        return ((EncFn)fn)(tm, CU_TENSOR_MAP_DATA_TYPE_UINT32, 2, (void*)base, g2, gs, b2, es, CU_TENSOR_MAP_INTERLEAVE_NONE, sw,
                           CU_TENSOR_MAP_L2_PROMOTION_NONE, CU_TENSOR_MAP_FLOAT_OOB_FILL_NONE) == CUDA_SUCCESS;
    };
    if (!sms) {
        cudaDeviceGetAttribute(&sms, cudaDevAttrMultiProcessorCount, 0);
        cudaDriverEntryPointQueryResult qr;
        cudaGetDriverEntryPoint("cuTensorMapEncodeTiled", &fn, cudaEnableDefault, &qr);
        cudaGetSymbolAddress(&gp, g_str); cudaGetSymbolAddress(&gb, g_bar);
        if (fn && gp && gb) {
            const cuuint32_t rows = sms < NB_MAX ? sms : NB_MAX;
            tm_ok = enc(&tm1, gp, (P1B + P2B) / 4, NB_MAX, CE / 2, rows, CU_TENSOR_MAP_SWIZZLE_NONE) && enc(&tm2, gp, (P1B + P2B) / 4, NB_MAX, CE, rows, CU_TENSOR_MAP_SWIZZLE_NONE);
        }
        cudaFuncSetAttribute(gcn_kernel<true>, cudaFuncAttributeMaxDynamicSharedMemorySize, SMEM_LAUNCH);
        cudaFuncSetAttribute(gcn_kernel<false>, cudaFuncAttributeMaxDynamicSharedMemorySize, SMEM_LAUNCH);
    }
    int nb = sms < NB_MAX ? sms : NB_MAX;
    int npb = (N + nb - 1) / nb;
    int ch = (((E + nb - 1) / nb) + 3) & ~3;
    const uintptr_t wp[4] = {(uintptr_t)wb, (uintptr_t)wv, (uintptr_t)wa, (uintptr_t)wu};
    uintptr_t wlo = wp[0], whi = wp[0], wal = 0;
    for (int i = 0; i < 4; i++) { wlo = wp[i] < wlo ? wp[i] : wlo; whi = wp[i] > whi ? wp[i] : whi; wal |= wp[i] - wp[0]; }
    bool ok = tm_ok && nb >= NB_MIN && npb < NPB_MAX && ch <= CH_MAX && !(E & 3) && N <= 65535 && npb >= 2 && !(wal & 127) && (whi - wlo) >> 7 < (1u << 30) &&
              !(((uintptr_t)src | (uintptr_t)dst | (uintptr_t)x | (uintptr_t)wb | (uintptr_t)wc) & 15);
    ok = ok && enc(&tmw, (const void*)wlo, 32, ((whi - wlo) >> 7) + 64, 32, 64, CU_TENSOR_MAP_SWIZZLE_128B) && enc(&tmx, x, 32, N, 32, 64, CU_TENSOR_MAP_SWIZZLE_128B);
    if (!ok) {
        int g = 1024, p = (N + g - 1) / g;
        slow_kernel<<<g, 256>>>(x, ea, src, dst, wa, wb, wc, wu, wv, out, N, E, p < 1 ? 1 : p);
        return;
    }
    int4 wrow = make_int4((int)((wp[0] - wlo) >> 7), (int)((wp[1] - wlo) >> 7), (int)((wp[2] - wlo) >> 7), (int)((wp[3] - wlo) >> 7));
    uint32_t magic = (uint32_t)((1ull << 32) / (uint32_t)npb) + 1u;
    void* args[] = {&dst, &gb, &gp, &src, &E, &ch, &N, &npb, &magic, &x, &ea, &wa, &wb, &wc, &wu, &wv, &out, &wrow, &tm1, &tm2, &tmw, &tmx};
    const bool lo32 = ((uintptr_t)x >> 32) == (((uintptr_t)x + (size_t)N * 128 - 1) >> 32) && ((uintptr_t)ea >> 32) == (((uintptr_t)ea + (size_t)E * 32 - 1) >> 32);
    cudaLaunchCooperativeKernel(lo32 && !FORCE64 ? (const void*)gcn_kernel<true> : (const void*)gcn_kernel<false>, dim3(nb), dim3(THREADS), args, SMEM_LAUNCH, cudaStreamPerThread);
}
```

```cpp
#include <cuda_runtime.h>
#include <cuda.h>
#include <cuda_bf16.h>
#include <stdint.h>

namespace {

constexpr int N_MAX = 65536;
constexpr int NPMAX = 11;
constexpr int NPMIN = 5;
constexpr int THREADS = 512;
constexpr int EPT = 12;
constexpr int CH_MAX = THREADS * EPT;
constexpr int NB_MAX = 134, NB_MIN = 120;
constexpr int CE = 64;
constexpr int P1B = NB_MAX * CE * 2;
constexpr int P2B = NB_MAX * CE * 4;
constexpr int HB = NB_MAX * 64;
constexpr int G_H1 = NB_MAX * (P1B + P2B), G_H2 = G_H1 + HB, G_L = G_H2 + HB, G_F = G_L + NB_MAX * 512;
constexpr int KM = 3, GRP_B = 1536, G_R = G_F + 2048, G_P = G_R + 2048, G_END = G_P + NB_MAX * KM * GRP_B;
#define BR1 9
#define BR2 11
#define BR3 14
#define BBIAS 175
#define FEN 1
#define PUBW 0
#define MRG 1
#define WARMX 0
#define PMIN 8
#define DVS 0
#define WMAP 1
#define BAL 1
constexpr int R1 = BR1, R2 = BR2, R3 = BR3;
constexpr int GD = 100;
constexpr int NPB_MAX = 384;
constexpr int SLOT_CAP = 6784;
constexpr int TILE_CAP = 123;
constexpr int TILE_X = 8;
constexpr int NCLS = 64;
constexpr int NSTAGE = 2;
constexpr int PD = 300;
constexpr int TR = 2;
constexpr float LOG2E = 1.4426950408889634f;

__device__ __align__(256) uint4 g_str[G_END / 16];
__device__ __align__(128) unsigned g_bar[8];
__device__ float g_slow[N_MAX * 128];
__device__ float4 g_copy[NB_MAX * 384 * 2 * NPMAX];

#define WS(k)
#define WGD()
#define WG0()
#define WG1()
#define CG(k)
#define SMEM_LAUNCH SMEM_BYTES
#define XM 2
#define XN 6
#define XP 2
#define FORCE64 0
#define EDHI ((16ull << 32) | (3ull << 62))
template<int NP> struct TileMMA;
template<> struct TileMMA<5> {
  static __device__ __forceinline__ void issue(float* g, float* h, const uint32_t* w, uint32_t dx, uint64_t de, uint64_t dh, uint64_t dc) {
    asm volatile(
      "{\n.reg .b64 dx0, dx1, dx2, dx3;\n.reg .b32 l1, l2, l3, hx;\nmov.b32 hx, 0x40000040;\n"
      "add.u32 l1, %80, 2;\nadd.u32 l2, %80, 4;\nadd.u32 l3, %80, 6;\n"
      "mov.b64 dx0, {%80, hx};\nmov.b64 dx1, {l1, hx};\nmov.b64 dx2, {l2, hx};\nmov.b64 dx3, {l3, hx};\n"
      "wgmma.fence.sync.aligned;\n"
      "wgmma.mma_async.sync.aligned.m64n40k16.f32.bf16.bf16 {%0, %1, %2, %3, %4, %5, %6, %7, %8, %9, %10, %11, %12, %13, %14, %15, %16, %17, %18, %19}, {%76, %77, %78, %79}, %82, 0, 1, 1, 0;\n"
      "wgmma.mma_async.sync.aligned.m64n40k16.f32.bf16.bf16 {%0, %1, %2, %3, %4, %5, %6, %7, %8, %9, %10, %11, %12, %13, %14, %15, %16, %17, %18, %19}, {%56, %57, %58, %59}, %81, 1, 1, 1, 0;\n"
      "wgmma.mma_async.sync.aligned.m64n40k16.f32.bf16.bf16 {%0, %1, %2, %3, %4, %5, %6, %7, %8, %9, %10, %11, %12, %13, %14, %15, %16, %17, %18, %19}, {%40, %41, %42, %43}, dx0, 1, 1, 1, 0;\n"
      "wgmma.mma_async.sync.aligned.m64n40k16.f32.bf16.bf16 {%0, %1, %2, %3, %4, %5, %6, %7, %8, %9, %10, %11, %12, %13, %14, %15, %16, %17, %18, %19}, {%44, %45, %46, %47}, dx1, 1, 1, 1, 0;\n"
      "wgmma.mma_async.sync.aligned.m64n40k16.f32.bf16.bf16 {%0, %1, %2, %3, %4, %5, %6, %7, %8, %9, %10, %11, %12, %13, %14, %15, %16, %17, %18, %19}, {%48, %49, %50, %51}, dx2, 1, 1, 1, 0;\n"
      "wgmma.mma_async.sync.aligned.m64n40k16.f32.bf16.bf16 {%0, %1, %2, %3, %4, %5, %6, %7, %8, %9, %10, %11, %12, %13, %14, %15, %16, %17, %18, %19}, {%52, %53, %54, %55}, dx3, 1, 1, 1, 0;\n"
      "wgmma.commit_group.sync.aligned;\n"
      "wgmma.mma_async.sync.aligned.m64n40k16.f32.bf16.bf16 {%20, %21, %22, %23, %24, %25, %26, %27, %28, %29, %30, %31, %32, %33, %34, %35, %36, %37, %38, %39}, {%60, %61, %62, %63}, dx0, 0, 1, 1, 0;\n"
      "wgmma.mma_async.sync.aligned.m64n40k16.f32.bf16.bf16 {%20, %21, %22, %23, %24, %25, %26, %27, %28, %29, %30, %31, %32, %33, %34, %35, %36, %37, %38, %39}, {%64, %65, %66, %67}, dx1, 1, 1, 1, 0;\n"
      "wgmma.mma_async.sync.aligned.m64n40k16.f32.bf16.bf16 {%20, %21, %22, %23, %24, %25, %26, %27, %28, %29, %30, %31, %32, %33, %34, %35, %36, %37, %38, %39}, {%68, %69, %70, %71}, dx2, 1, 1, 1, 0;\n"
      "wgmma.mma_async.sync.aligned.m64n40k16.f32.bf16.bf16 {%20, %21, %22, %23, %24, %25, %26, %27, %28, %29, %30, %31, %32, %33, %34, %35, %36, %37, %38, %39}, {%72, %73, %74, %75}, dx3, 1, 1, 1, 0;\n"
      "wgmma.commit_group.sync.aligned;\n}\n"
      : "=f"(g[0]), "=f"(g[1]), "=f"(g[2]), "=f"(g[3]), "=f"(g[4]), "=f"(g[5]), "=f"(g[6]), "=f"(g[7]), "=f"(g[8]), "=f"(g[9]), "=f"(g[10]), "=f"(g[11]), "=f"(g[12]), "=f"(g[13]), "=f"(g[14]), "=f"(g[15]), "=f"(g[16]), "=f"(g[17]), "=f"(g[18]), "=f"(g[19]),
        "=f"(h[0]), "=f"(h[1]), "=f"(h[2]), "=f"(h[3]), "=f"(h[4]), "=f"(h[5]), "=f"(h[6]), "=f"(h[7]), "=f"(h[8]), "=f"(h[9]), "=f"(h[10]), "=f"(h[11]), "=f"(h[12]), "=f"(h[13]), "=f"(h[14]), "=f"(h[15]), "=f"(h[16]), "=f"(h[17]), "=f"(h[18]), "=f"(h[19])
      : "r"(w[0]), "r"(w[1]), "r"(w[2]), "r"(w[3]), "r"(w[4]), "r"(w[5]), "r"(w[6]), "r"(w[7]), "r"(w[8]), "r"(w[9]), "r"(w[10]), "r"(w[11]), "r"(w[12]), "r"(w[13]), "r"(w[14]), "r"(w[15]), "r"(w[16]), "r"(w[17]), "r"(w[18]), "r"(w[19]), "r"(w[20]), "r"(w[21]), "r"(w[22]), "r"(w[23]), "r"(w[24]), "r"(w[25]), "r"(w[26]), "r"(w[27]), "r"(w[28]), "r"(w[29]), "r"(w[30]), "r"(w[31]), "r"(w[32]), "r"(w[33]), "r"(w[34]), "r"(w[35]), "r"(w[36]), "r"(w[37]), "r"(w[38]), "r"(w[39]), "r"(dx), "l"(de), "l"(dh)
      : "memory");
  }
  static __device__ __forceinline__ void wait_g(float* g) {
    asm volatile("wgmma.wait_group.sync.aligned 1;\n"
      : "+f"(g[0]), "+f"(g[1]), "+f"(g[2]), "+f"(g[3]), "+f"(g[4]), "+f"(g[5]), "+f"(g[6]), "+f"(g[7]), "+f"(g[8]), "+f"(g[9]), "+f"(g[10]), "+f"(g[11]), "+f"(g[12]), "+f"(g[13]), "+f"(g[14]), "+f"(g[15]), "+f"(g[16]), "+f"(g[17]), "+f"(g[18]), "+f"(g[19])
      :: "memory");
  }
  static __device__ __forceinline__ void wait_h(float* h) {
    asm volatile("wgmma.wait_group.sync.aligned 0;\n"
      : "+f"(h[0]), "+f"(h[1]), "+f"(h[2]), "+f"(h[3]), "+f"(h[4]), "+f"(h[5]), "+f"(h[6]), "+f"(h[7]), "+f"(h[8]), "+f"(h[9]), "+f"(h[10]), "+f"(h[11]), "+f"(h[12]), "+f"(h[13]), "+f"(h[14]), "+f"(h[15]), "+f"(h[16]), "+f"(h[17]), "+f"(h[18]), "+f"(h[19])
      :: "memory");
  }
};
template<> struct TileMMA<6> {
  static __device__ __forceinline__ void issue(float* g, float* h, const uint32_t* w, uint32_t dx, uint64_t de, uint64_t dh, uint64_t dc) {
    asm volatile(
      "{\n.reg .b64 dx0, dx1, dx2, dx3;\n.reg .b32 l1, l2, l3, hx;\nmov.b32 hx, 0x40000040;\n"
      "add.u32 l1, %88, 2;\nadd.u32 l2, %88, 4;\nadd.u32 l3, %88, 6;\n"
      "mov.b64 dx0, {%88, hx};\nmov.b64 dx1, {l1, hx};\nmov.b64 dx2, {l2, hx};\nmov.b64 dx3, {l3, hx};\n"
      "wgmma.fence.sync.aligned;\n"
      "wgmma.mma_async.sync.aligned.m64n48k16.f32.bf16.bf16 {%0, %1, %2, %3, %4, %5, %6, %7, %8, %9, %10, %11, %12, %13, %14, %15, %16, %17, %18, %19, %20, %21, %22, %23}, {%84, %85, %86, %87}, %90, 0, 1, 1, 0;\n"
      "wgmma.mma_async.sync.aligned.m64n48k16.f32.bf16.bf16 {%0, %1, %2, %3, %4, %5, %6, %7, %8, %9, %10, %11, %12, %13, %14, %15, %16, %17, %18, %19, %20, %21, %22, %23}, {%64, %65, %66, %67}, %89, 1, 1, 1, 0;\n"
      "wgmma.mma_async.sync.aligned.m64n48k16.f32.bf16.bf16 {%0, %1, %2, %3, %4, %5, %6, %7, %8, %9, %10, %11, %12, %13, %14, %15, %16, %17, %18, %19, %20, %21, %22, %23}, {%48, %49, %50, %51}, dx0, 1, 1, 1, 0;\n"
      "wgmma.mma_async.sync.aligned.m64n48k16.f32.bf16.bf16 {%0, %1, %2, %3, %4, %5, %6, %7, %8, %9, %10, %11, %12, %13, %14, %15, %16, %17, %18, %19, %20, %21, %22, %23}, {%52, %53, %54, %55}, dx1, 1, 1, 1, 0;\n"
      "wgmma.mma_async.sync.aligned.m64n48k16.f32.bf16.bf16 {%0, %1, %2, %3, %4, %5, %6, %7, %8, %9, %10, %11, %12, %13, %14, %15, %16, %17, %18, %19, %20, %21, %22, %23}, {%56, %57, %58, %59}, dx2, 1, 1, 1, 0;\n"
      "wgmma.mma_async.sync.aligned.m64n48k16.f32.bf16.bf16 {%0, %1, %2, %3, %4, %5, %6, %7, %8, %9, %10, %11, %12, %13, %14, %15, %16, %17, %18, %19, %20, %21, %22, %23}, {%60, %61, %62, %63}, dx3, 1, 1, 1, 0;\n"
      "wgmma.commit_group.sync.aligned;\n"
      "wgmma.mma_async.sync.aligned.m64n48k16.f32.bf16.bf16 {%24, %25, %26, %27, %28, %29, %30, %31, %32, %33, %34, %35, %36, %37, %38, %39, %40, %41, %42, %43, %44, %45, %46, %47}, {%68, %69, %70, %71}, dx0, 0, 1, 1, 0;\n"
      "wgmma.mma_async.sync.aligned.m64n48k16.f32.bf16.bf16 {%24, %25, %26, %27, %28, %29, %30, %31, %32, %33, %34, %35, %36, %37, %38, %39, %40, %41, %42, %43, %44, %45, %46, %47}, {%72, %73, %74, %75}, dx1, 1, 1, 1, 0;\n"
      "wgmma.mma_async.sync.aligned.m64n48k16.f32.bf16.bf16 {%24, %25, %26, %27, %28, %29, %30, %31, %32, %33, %34, %35, %36, %37, %38, %39, %40, %41, %42, %43, %44, %45, %46, %47}, {%76, %77, %78, %79}, dx2, 1, 1, 1, 0;\n"
      "wgmma.mma_async.sync.aligned.m64n48k16.f32.bf16.bf16 {%24, %25, %26, %27, %28, %29, %30, %31, %32, %33, %34, %35, %36, %37, %38, %39, %40, %41, %42, %43, %44, %45, %46, %47}, {%80, %81, %82, %83}, dx3, 1, 1, 1, 0;\n"
      "wgmma.commit_group.sync.aligned;\n}\n"
      : "=f"(g[0]), "=f"(g[1]), "=f"(g[2]), "=f"(g[3]), "=f"(g[4]), "=f"(g[5]), "=f"(g[6]), "=f"(g[7]), "=f"(g[8]), "=f"(g[9]), "=f"(g[10]), "=f"(g[11]), "=f"(g[12]), "=f"(g[13]), "=f"(g[14]), "=f"(g[15]), "=f"(g[16]), "=f"(g[17]), "=f"(g[18]), "=f"(g[19]), "=f"(g[20]), "=f"(g[21]), "=f"(g[22]), "=f"(g[23]),
        "=f"(h[0]), "=f"(h[1]), "=f"(h[2]), "=f"(h[3]), "=f"(h[4]), "=f"(h[5]), "=f"(h[6]), "=f"(h[7]), "=f"(h[8]), "=f"(h[9]), "=f"(h[10]), "=f"(h[11]), "=f"(h[12]), "=f"(h[13]), "=f"(h[14]), "=f"(h[15]), "=f"(h[16]), "=f"(h[17]), "=f"(h[18]), "=f"(h[19]), "=f"(h[20]), "=f"(h[21]), "=f"(h[22]), "=f"(h[23])
      : "r"(w[0]), "r"(w[1]), "r"(w[2]), "r"(w[3]), "r"(w[4]), "r"(w[5]), "r"(w[6]), "r"(w[7]), "r"(w[8]), "r"(w[9]), "r"(w[10]), "r"(w[11]), "r"(w[12]), "r"(w[13]), "r"(w[14]), "r"(w[15]), "r"(w[16]), "r"(w[17]), "r"(w[18]), "r"(w[19]), "r"(w[20]), "r"(w[21]), "r"(w[22]), "r"(w[23]), "r"(w[24]), "r"(w[25]), "r"(w[26]), "r"(w[27]), "r"(w[28]), "r"(w[29]), "r"(w[30]), "r"(w[31]), "r"(w[32]), "r"(w[33]), "r"(w[34]), "r"(w[35]), "r"(w[36]), "r"(w[37]), "r"(w[38]), "r"(w[39]), "r"(dx), "l"(de), "l"(dh)
      : "memory");
  }
  static __device__ __forceinline__ void wait_g(float* g) {
    asm volatile("wgmma.wait_group.sync.aligned 1;\n"
      : "+f"(g[0]), "+f"(g[1]), "+f"(g[2]), "+f"(g[3]), "+f"(g[4]), "+f"(g[5]), "+f"(g[6]), "+f"(g[7]), "+f"(g[8]), "+f"(g[9]), "+f"(g[10]), "+f"(g[11]), "+f"(g[12]), "+f"(g[13]), "+f"(g[14]), "+f"(g[15]), "+f"(g[16]), "+f"(g[17]), "+f"(g[18]), "+f"(g[19]), "+f"(g[20]), "+f"(g[21]), "+f"(g[22]), "+f"(g[23])
      :: "memory");
  }
  static __device__ __forceinline__ void wait_h(float* h) {
    asm volatile("wgmma.wait_group.sync.aligned 0;\n"
      : "+f"(h[0]), "+f"(h[1]), "+f"(h[2]), "+f"(h[3]), "+f"(h[4]), "+f"(h[5]), "+f"(h[6]), "+f"(h[7]), "+f"(h[8]), "+f"(h[9]), "+f"(h[10]), "+f"(h[11]), "+f"(h[12]), "+f"(h[13]), "+f"(h[14]), "+f"(h[15]), "+f"(h[16]), "+f"(h[17]), "+f"(h[18]), "+f"(h[19]), "+f"(h[20]), "+f"(h[21]), "+f"(h[22]), "+f"(h[23])
      :: "memory");
  }
};
template<> struct TileMMA<7> {
  static __device__ __forceinline__ void issue(float* g, float* h, const uint32_t* w, uint32_t dx, uint64_t de, uint64_t dh, uint64_t dc) {
    asm volatile(
      "{\n.reg .b64 dx0, dx1, dx2, dx3;\n.reg .b32 l1, l2, l3, hx;\nmov.b32 hx, 0x40000040;\n"
      "add.u32 l1, %96, 2;\nadd.u32 l2, %96, 4;\nadd.u32 l3, %96, 6;\n"
      "mov.b64 dx0, {%96, hx};\nmov.b64 dx1, {l1, hx};\nmov.b64 dx2, {l2, hx};\nmov.b64 dx3, {l3, hx};\n"
      "wgmma.fence.sync.aligned;\n"
      "wgmma.mma_async.sync.aligned.m64n56k16.f32.bf16.bf16 {%0, %1, %2, %3, %4, %5, %6, %7, %8, %9, %10, %11, %12, %13, %14, %15, %16, %17, %18, %19, %20, %21, %22, %23, %24, %25, %26, %27}, {%92, %93, %94, %95}, %98, 0, 1, 1, 0;\n"
      "wgmma.mma_async.sync.aligned.m64n56k16.f32.bf16.bf16 {%0, %1, %2, %3, %4, %5, %6, %7, %8, %9, %10, %11, %12, %13, %14, %15, %16, %17, %18, %19, %20, %21, %22, %23, %24, %25, %26, %27}, {%72, %73, %74, %75}, %97, 1, 1, 1, 0;\n"
      "wgmma.mma_async.sync.aligned.m64n56k16.f32.bf16.bf16 {%0, %1, %2, %3, %4, %5, %6, %7, %8, %9, %10, %11, %12, %13, %14, %15, %16, %17, %18, %19, %20, %21, %22, %23, %24, %25, %26, %27}, {%56, %57, %58, %59}, dx0, 1, 1, 1, 0;\n"
      "wgmma.mma_async.sync.aligned.m64n56k16.f32.bf16.bf16 {%0, %1, %2, %3, %4, %5, %6, %7, %8, %9, %10, %11, %12, %13, %14, %15, %16, %17, %18, %19, %20, %21, %22, %23, %24, %25, %26, %27}, {%60, %61, %62, %63}, dx1, 1, 1, 1, 0;\n"
      "wgmma.mma_async.sync.aligned.m64n56k16.f32.bf16.bf16 {%0, %1, %2, %3, %4, %5, %6, %7, %8, %9, %10, %11, %12, %13, %14, %15, %16, %17, %18, %19, %20, %21, %22, %23, %24, %25, %26, %27}, {%64, %65, %66, %67}, dx2, 1, 1, 1, 0;\n"
      "wgmma.mma_async.sync.aligned.m64n56k16.f32.bf16.bf16 {%0, %1, %2, %3, %4, %5, %6, %7, %8, %9, %10, %11, %12, %13, %14, %15, %16, %17, %18, %19, %20, %21, %22, %23, %24, %25, %26, %27}, {%68, %69, %70, %71}, dx3, 1, 1, 1, 0;\n"
      "wgmma.commit_group.sync.aligned;\n"
      "wgmma.mma_async.sync.aligned.m64n56k16.f32.bf16.bf16 {%28, %29, %30, %31, %32, %33, %34, %35, %36, %37, %38, %39, %40, %41, %42, %43, %44, %45, %46, %47, %48, %49, %50, %51, %52, %53, %54, %55}, {%76, %77, %78, %79}, dx0, 0, 1, 1, 0;\n"
      "wgmma.mma_async.sync.aligned.m64n56k16.f32.bf16.bf16 {%28, %29, %30, %31, %32, %33, %34, %35, %36, %37, %38, %39, %40, %41, %42, %43, %44, %45, %46, %47, %48, %49, %50, %51, %52, %53, %54, %55}, {%80, %81, %82, %83}, dx1, 1, 1, 1, 0;\n"
      "wgmma.mma_async.sync.aligned.m64n56k16.f32.bf16.bf16 {%28, %29, %30, %31, %32, %33, %34, %35, %36, %37, %38, %39, %40, %41, %42, %43, %44, %45, %46, %47, %48, %49, %50, %51, %52, %53, %54, %55}, {%84, %85, %86, %87}, dx2, 1, 1, 1, 0;\n"
      "wgmma.mma_async.sync.aligned.m64n56k16.f32.bf16.bf16 {%28, %29, %30, %31, %32, %33, %34, %35, %36, %37, %38, %39, %40, %41, %42, %43, %44, %45, %46, %47, %48, %49, %50, %51, %52, %53, %54, %55}, {%88, %89, %90, %91}, dx3, 1, 1, 1, 0;\n"
      "wgmma.commit_group.sync.aligned;\n}\n"
      : "=f"(g[0]), "=f"(g[1]), "=f"(g[2]), "=f"(g[3]), "=f"(g[4]), "=f"(g[5]), "=f"(g[6]), "=f"(g[7]), "=f"(g[8]), "=f"(g[9]), "=f"(g[10]), "=f"(g[11]), "=f"(g[12]), "=f"(g[13]), "=f"(g[14]), "=f"(g[15]), "=f"(g[16]), "=f"(g[17]), "=f"(g[18]), "=f"(g[19]), "=f"(g[20]), "=f"(g[21]), "=f"(g[22]), "=f"(g[23]), "=f"(g[24]), "=f"(g[25]), "=f"(g[26]), "=f"(g[27]),
        "=f"(h[0]), "=f"(h[1]), "=f"(h[2]), "=f"(h[3]), "=f"(h[4]), "=f"(h[5]), "=f"(h[6]), "=f"(h[7]), "=f"(h[8]), "=f"(h[9]), "=f"(h[10]), "=f"(h[11]), "=f"(h[12]), "=f"(h[13]), "=f"(h[14]), "=f"(h[15]), "=f"(h[16]), "=f"(h[17]), "=f"(h[18]), "=f"(h[19]), "=f"(h[20]), "=f"(h[21]), "=f"(h[22]), "=f"(h[23]), "=f"(h[24]), "=f"(h[25]), "=f"(h[26]), "=f"(h[27])
      : "r"(w[0]), "r"(w[1]), "r"(w[2]), "r"(w[3]), "r"(w[4]), "r"(w[5]), "r"(w[6]), "r"(w[7]), "r"(w[8]), "r"(w[9]), "r"(w[10]), "r"(w[11]), "r"(w[12]), "r"(w[13]), "r"(w[14]), "r"(w[15]), "r"(w[16]), "r"(w[17]), "r"(w[18]), "r"(w[19]), "r"(w[20]), "r"(w[21]), "r"(w[22]), "r"(w[23]), "r"(w[24]), "r"(w[25]), "r"(w[26]), "r"(w[27]), "r"(w[28]), "r"(w[29]), "r"(w[30]), "r"(w[31]), "r"(w[32]), "r"(w[33]), "r"(w[34]), "r"(w[35]), "r"(w[36]), "r"(w[37]), "r"(w[38]), "r"(w[39]), "r"(dx), "l"(de), "l"(dh)
      : "memory");
  }
  static __device__ __forceinline__ void wait_g(float* g) {
    asm volatile("wgmma.wait_group.sync.aligned 1;\n"
      : "+f"(g[0]), "+f"(g[1]), "+f"(g[2]), "+f"(g[3]), "+f"(g[4]), "+f"(g[5]), "+f"(g[6]), "+f"(g[7]), "+f"(g[8]), "+f"(g[9]), "+f"(g[10]), "+f"(g[11]), "+f"(g[12]), "+f"(g[13]), "+f"(g[14]), "+f"(g[15]), "+f"(g[16]), "+f"(g[17]), "+f"(g[18]), "+f"(g[19]), "+f"(g[20]), "+f"(g[21]), "+f"(g[22]), "+f"(g[23]), "+f"(g[24]), "+f"(g[25]), "+f"(g[26]), "+f"(g[27])
      :: "memory");
  }
  static __device__ __forceinline__ void wait_h(float* h) {
    asm volatile("wgmma.wait_group.sync.aligned 0;\n"
      : "+f"(h[0]), "+f"(h[1]), "+f"(h[2]), "+f"(h[3]), "+f"(h[4]), "+f"(h[5]), "+f"(h[6]), "+f"(h[7]), "+f"(h[8]), "+f"(h[9]), "+f"(h[10]), "+f"(h[11]), "+f"(h[12]), "+f"(h[13]), "+f"(h[14]), "+f"(h[15]), "+f"(h[16]), "+f"(h[17]), "+f"(h[18]), "+f"(h[19]), "+f"(h[20]), "+f"(h[21]), "+f"(h[22]), "+f"(h[23]), "+f"(h[24]), "+f"(h[25]), "+f"(h[26]), "+f"(h[27])
      :: "memory");
  }
};
template<> struct TileMMA<8> {
  static __device__ __forceinline__ void issue(float* g, float* h, const uint32_t* w, uint32_t dx, uint64_t de, uint64_t dh, uint64_t dc) {
    asm volatile(
      "{\n.reg .b64 dx0, dx1, dx2, dx3;\n.reg .b32 l1, l2, l3, hx;\nmov.b32 hx, 0x40000040;\n"
      "add.u32 l1, %104, 2;\nadd.u32 l2, %104, 4;\nadd.u32 l3, %104, 6;\n"
      "mov.b64 dx0, {%104, hx};\nmov.b64 dx1, {l1, hx};\nmov.b64 dx2, {l2, hx};\nmov.b64 dx3, {l3, hx};\n"
      "wgmma.fence.sync.aligned;\n"
      "wgmma.mma_async.sync.aligned.m64n64k16.f32.bf16.bf16 {%0, %1, %2, %3, %4, %5, %6, %7, %8, %9, %10, %11, %12, %13, %14, %15, %16, %17, %18, %19, %20, %21, %22, %23, %24, %25, %26, %27, %28, %29, %30, %31}, {%100, %101, %102, %103}, %106, 0, 1, 1, 0;\n"
      "wgmma.mma_async.sync.aligned.m64n64k16.f32.bf16.bf16 {%0, %1, %2, %3, %4, %5, %6, %7, %8, %9, %10, %11, %12, %13, %14, %15, %16, %17, %18, %19, %20, %21, %22, %23, %24, %25, %26, %27, %28, %29, %30, %31}, {%80, %81, %82, %83}, %105, 1, 1, 1, 0;\n"
      "wgmma.mma_async.sync.aligned.m64n64k16.f32.bf16.bf16 {%0, %1, %2, %3, %4, %5, %6, %7, %8, %9, %10, %11, %12, %13, %14, %15, %16, %17, %18, %19, %20, %21, %22, %23, %24, %25, %26, %27, %28, %29, %30, %31}, {%64, %65, %66, %67}, dx0, 1, 1, 1, 0;\n"
      "wgmma.mma_async.sync.aligned.m64n64k16.f32.bf16.bf16 {%0, %1, %2, %3, %4, %5, %6, %7, %8, %9, %10, %11, %12, %13, %14, %15, %16, %17, %18, %19, %20, %21, %22, %23, %24, %25, %26, %27, %28, %29, %30, %31}, {%68, %69, %70, %71}, dx1, 1, 1, 1, 0;\n"
      "wgmma.mma_async.sync.aligned.m64n64k16.f32.bf16.bf16 {%0, %1, %2, %3, %4, %5, %6, %7, %8, %9, %10, %11, %12, %13, %14, %15, %16, %17, %18, %19, %20, %21, %22, %23, %24, %25, %26, %27, %28, %29, %30, %31}, {%72, %73, %74, %75}, dx2, 1, 1, 1, 0;\n"
      "wgmma.mma_async.sync.aligned.m64n64k16.f32.bf16.bf16 {%0, %1, %2, %3, %4, %5, %6, %7, %8, %9, %10, %11, %12, %13, %14, %15, %16, %17, %18, %19, %20, %21, %22, %23, %24, %25, %26, %27, %28, %29, %30, %31}, {%76, %77, %78, %79}, dx3, 1, 1, 1, 0;\n"
      "wgmma.commit_group.sync.aligned;\n"
      "wgmma.mma_async.sync.aligned.m64n64k16.f32.bf16.bf16 {%32, %33, %34, %35, %36, %37, %38, %39, %40, %41, %42, %43, %44, %45, %46, %47, %48, %49, %50, %51, %52, %53, %54, %55, %56, %57, %58, %59, %60, %61, %62, %63}, {%84, %85, %86, %87}, dx0, 0, 1, 1, 0;\n"
      "wgmma.mma_async.sync.aligned.m64n64k16.f32.bf16.bf16 {%32, %33, %34, %35, %36, %37, %38, %39, %40, %41, %42, %43, %44, %45, %46, %47, %48, %49, %50, %51, %52, %53, %54, %55, %56, %57, %58, %59, %60, %61, %62, %63}, {%88, %89, %90, %91}, dx1, 1, 1, 1, 0;\n"
      "wgmma.mma_async.sync.aligned.m64n64k16.f32.bf16.bf16 {%32, %33, %34, %35, %36, %37, %38, %39, %40, %41, %42, %43, %44, %45, %46, %47, %48, %49, %50, %51, %52, %53, %54, %55, %56, %57, %58, %59, %60, %61, %62, %63}, {%92, %93, %94, %95}, dx2, 1, 1, 1, 0;\n"
      "wgmma.mma_async.sync.aligned.m64n64k16.f32.bf16.bf16 {%32, %33, %34, %35, %36, %37, %38, %39, %40, %41, %42, %43, %44, %45, %46, %47, %48, %49, %50, %51, %52, %53, %54, %55, %56, %57, %58, %59, %60, %61, %62, %63}, {%96, %97, %98, %99}, dx3, 1, 1, 1, 0;\n"
      "wgmma.commit_group.sync.aligned;\n}\n"
      : "=f"(g[0]), "=f"(g[1]), "=f"(g[2]), "=f"(g[3]), "=f"(g[4]), "=f"(g[5]), "=f"(g[6]), "=f"(g[7]), "=f"(g[8]), "=f"(g[9]), "=f"(g[10]), "=f"(g[11]), "=f"(g[12]), "=f"(g[13]), "=f"(g[14]), "=f"(g[15]), "=f"(g[16]), "=f"(g[17]), "=f"(g[18]), "=f"(g[19]), "=f"(g[20]), "=f"(g[21]), "=f"(g[22]), "=f"(g[23]), "=f"(g[24]), "=f"(g[25]), "=f"(g[26]), "=f"(g[27]), "=f"(g[28]), "=f"(g[29]), "=f"(g[30]), "=f"(g[31]),
        "=f"(h[0]), "=f"(h[1]), "=f"(h[2]), "=f"(h[3]), "=f"(h[4]), "=f"(h[5]), "=f"(h[6]), "=f"(h[7]), "=f"(h[8]), "=f"(h[9]), "=f"(h[10]), "=f"(h[11]), "=f"(h[12]), "=f"(h[13]), "=f"(h[14]), "=f"(h[15]), "=f"(h[16]), "=f"(h[17]), "=f"(h[18]), "=f"(h[19]), "=f"(h[20]), "=f"(h[21]), "=f"(h[22]), "=f"(h[23]), "=f"(h[24]), "=f"(h[25]), "=f"(h[26]), "=f"(h[27]), "=f"(h[28]), "=f"(h[29]), "=f"(h[30]), "=f"(h[31])
      : "r"(w[0]), "r"(w[1]), "r"(w[2]), "r"(w[3]), "r"(w[4]), "r"(w[5]), "r"(w[6]), "r"(w[7]), "r"(w[8]), "r"(w[9]), "r"(w[10]), "r"(w[11]), "r"(w[12]), "r"(w[13]), "r"(w[14]), "r"(w[15]), "r"(w[16]), "r"(w[17]), "r"(w[18]), "r"(w[19]), "r"(w[20]), "r"(w[21]), "r"(w[22]), "r"(w[23]), "r"(w[24]), "r"(w[25]), "r"(w[26]), "r"(w[27]), "r"(w[28]), "r"(w[29]), "r"(w[30]), "r"(w[31]), "r"(w[32]), "r"(w[33]), "r"(w[34]), "r"(w[35]), "r"(w[36]), "r"(w[37]), "r"(w[38]), "r"(w[39]), "r"(dx), "l"(de), "l"(dh)
      : "memory");
  }
  static __device__ __forceinline__ void wait_g(float* g) {
    asm volatile("wgmma.wait_group.sync.aligned 1;\n"
      : "+f"(g[0]), "+f"(g[1]), "+f"(g[2]), "+f"(g[3]), "+f"(g[4]), "+f"(g[5]), "+f"(g[6]), "+f"(g[7]), "+f"(g[8]), "+f"(g[9]), "+f"(g[10]), "+f"(g[11]), "+f"(g[12]), "+f"(g[13]), "+f"(g[14]), "+f"(g[15]), "+f"(g[16]), "+f"(g[17]), "+f"(g[18]), "+f"(g[19]), "+f"(g[20]), "+f"(g[21]), "+f"(g[22]), "+f"(g[23]), "+f"(g[24]), "+f"(g[25]), "+f"(g[26]), "+f"(g[27]), "+f"(g[28]), "+f"(g[29]), "+f"(g[30]), "+f"(g[31])
      :: "memory");
  }
  static __device__ __forceinline__ void wait_h(float* h) {
    asm volatile("wgmma.wait_group.sync.aligned 0;\n"
      : "+f"(h[0]), "+f"(h[1]), "+f"(h[2]), "+f"(h[3]), "+f"(h[4]), "+f"(h[5]), "+f"(h[6]), "+f"(h[7]), "+f"(h[8]), "+f"(h[9]), "+f"(h[10]), "+f"(h[11]), "+f"(h[12]), "+f"(h[13]), "+f"(h[14]), "+f"(h[15]), "+f"(h[16]), "+f"(h[17]), "+f"(h[18]), "+f"(h[19]), "+f"(h[20]), "+f"(h[21]), "+f"(h[22]), "+f"(h[23]), "+f"(h[24]), "+f"(h[25]), "+f"(h[26]), "+f"(h[27]), "+f"(h[28]), "+f"(h[29]), "+f"(h[30]), "+f"(h[31])
      :: "memory");
  }
};
template<> struct TileMMA<9> {
  static __device__ __forceinline__ void issue(float* g, float* h, const uint32_t* w, uint32_t dx, uint64_t de, uint64_t dh, uint64_t dc) {
    asm volatile(
      "{\n.reg .b64 dx0, dx1, dx2, dx3;\n.reg .b32 l1, l2, l3, hx;\nmov.b32 hx, 0x40000040;\n"
      "add.u32 l1, %112, 2;\nadd.u32 l2, %112, 4;\nadd.u32 l3, %112, 6;\n"
      "mov.b64 dx0, {%112, hx};\nmov.b64 dx1, {l1, hx};\nmov.b64 dx2, {l2, hx};\nmov.b64 dx3, {l3, hx};\n"
      "wgmma.fence.sync.aligned;\n"
      "wgmma.mma_async.sync.aligned.m64n72k16.f32.bf16.bf16 {%0, %1, %2, %3, %4, %5, %6, %7, %8, %9, %10, %11, %12, %13, %14, %15, %16, %17, %18, %19, %20, %21, %22, %23, %24, %25, %26, %27, %28, %29, %30, %31, %32, %33, %34, %35}, {%108, %109, %110, %111}, %114, 0, 1, 1, 0;\n"
      "wgmma.mma_async.sync.aligned.m64n72k16.f32.bf16.bf16 {%0, %1, %2, %3, %4, %5, %6, %7, %8, %9, %10, %11, %12, %13, %14, %15, %16, %17, %18, %19, %20, %21, %22, %23, %24, %25, %26, %27, %28, %29, %30, %31, %32, %33, %34, %35}, {%88, %89, %90, %91}, %113, 1, 1, 1, 0;\n"
      "wgmma.mma_async.sync.aligned.m64n72k16.f32.bf16.bf16 {%0, %1, %2, %3, %4, %5, %6, %7, %8, %9, %10, %11, %12, %13, %14, %15, %16, %17, %18, %19, %20, %21, %22, %23, %24, %25, %26, %27, %28, %29, %30, %31, %32, %33, %34, %35}, {%72, %73, %74, %75}, dx0, 1, 1, 1, 0;\n"
      "wgmma.mma_async.sync.aligned.m64n72k16.f32.bf16.bf16 {%0, %1, %2, %3, %4, %5, %6, %7, %8, %9, %10, %11, %12, %13, %14, %15, %16, %17, %18, %19, %20, %21, %22, %23, %24, %25, %26, %27, %28, %29, %30, %31, %32, %33, %34, %35}, {%76, %77, %78, %79}, dx1, 1, 1, 1, 0;\n"
      "wgmma.mma_async.sync.aligned.m64n72k16.f32.bf16.bf16 {%0, %1, %2, %3, %4, %5, %6, %7, %8, %9, %10, %11, %12, %13, %14, %15, %16, %17, %18, %19, %20, %21, %22, %23, %24, %25, %26, %27, %28, %29, %30, %31, %32, %33, %34, %35}, {%80, %81, %82, %83}, dx2, 1, 1, 1, 0;\n"
      "wgmma.mma_async.sync.aligned.m64n72k16.f32.bf16.bf16 {%0, %1, %2, %3, %4, %5, %6, %7, %8, %9, %10, %11, %12, %13, %14, %15, %16, %17, %18, %19, %20, %21, %22, %23, %24, %25, %26, %27, %28, %29, %30, %31, %32, %33, %34, %35}, {%84, %85, %86, %87}, dx3, 1, 1, 1, 0;\n"
      "wgmma.commit_group.sync.aligned;\n"
      "wgmma.mma_async.sync.aligned.m64n72k16.f32.bf16.bf16 {%36, %37, %38, %39, %40, %41, %42, %43, %44, %45, %46, %47, %48, %49, %50, %51, %52, %53, %54, %55, %56, %57, %58, %59, %60, %61, %62, %63, %64, %65, %66, %67, %68, %69, %70, %71}, {%92, %93, %94, %95}, dx0, 0, 1, 1, 0;\n"
      "wgmma.mma_async.sync.aligned.m64n72k16.f32.bf16.bf16 {%36, %37, %38, %39, %40, %41, %42, %43, %44, %45, %46, %47, %48, %49, %50, %51, %52, %53, %54, %55, %56, %57, %58, %59, %60, %61, %62, %63, %64, %65, %66, %67, %68, %69, %70, %71}, {%96, %97, %98, %99}, dx1, 1, 1, 1, 0;\n"
      "wgmma.mma_async.sync.aligned.m64n72k16.f32.bf16.bf16 {%36, %37, %38, %39, %40, %41, %42, %43, %44, %45, %46, %47, %48, %49, %50, %51, %52, %53, %54, %55, %56, %57, %58, %59, %60, %61, %62, %63, %64, %65, %66, %67, %68, %69, %70, %71}, {%100, %101, %102, %103}, dx2, 1, 1, 1, 0;\n"
      "wgmma.mma_async.sync.aligned.m64n72k16.f32.bf16.bf16 {%36, %37, %38, %39, %40, %41, %42, %43, %44, %45, %46, %47, %48, %49, %50, %51, %52, %53, %54, %55, %56, %57, %58, %59, %60, %61, %62, %63, %64, %65, %66, %67, %68, %69, %70, %71}, {%104, %105, %106, %107}, dx3, 1, 1, 1, 0;\n"
      "wgmma.commit_group.sync.aligned;\n}\n"
      : "=f"(g[0]), "=f"(g[1]), "=f"(g[2]), "=f"(g[3]), "=f"(g[4]), "=f"(g[5]), "=f"(g[6]), "=f"(g[7]), "=f"(g[8]), "=f"(g[9]), "=f"(g[10]), "=f"(g[11]), "=f"(g[12]), "=f"(g[13]), "=f"(g[14]), "=f"(g[15]), "=f"(g[16]), "=f"(g[17]), "=f"(g[18]), "=f"(g[19]), "=f"(g[20]), "=f"(g[21]), "=f"(g[22]), "=f"(g[23]), "=f"(g[24]), "=f"(g[25]), "=f"(g[26]), "=f"(g[27]), "=f"(g[28]), "=f"(g[29]), "=f"(g[30]), "=f"(g[31]), "=f"(g[32]), "=f"(g[33]), "=f"(g[34]), "=f"(g[35]),
        "=f"(h[0]), "=f"(h[1]), "=f"(h[2]), "=f"(h[3]), "=f"(h[4]), "=f"(h[5]), "=f"(h[6]), "=f"(h[7]), "=f"(h[8]), "=f"(h[9]), "=f"(h[10]), "=f"(h[11]), "=f"(h[12]), "=f"(h[13]), "=f"(h[14]), "=f"(h[15]), "=f"(h[16]), "=f"(h[17]), "=f"(h[18]), "=f"(h[19]), "=f"(h[20]), "=f"(h[21]), "=f"(h[22]), "=f"(h[23]), "=f"(h[24]), "=f"(h[25]), "=f"(h[26]), "=f"(h[27]), "=f"(h[28]), "=f"(h[29]), "=f"(h[30]), "=f"(h[31]), "=f"(h[32]), "=f"(h[33]), "=f"(h[34]), "=f"(h[35])
      : "r"(w[0]), "r"(w[1]), "r"(w[2]), "r"(w[3]), "r"(w[4]), "r"(w[5]), "r"(w[6]), "r"(w[7]), "r"(w[8]), "r"(w[9]), "r"(w[10]), "r"(w[11]), "r"(w[12]), "r"(w[13]), "r"(w[14]), "r"(w[15]), "r"(w[16]), "r"(w[17]), "r"(w[18]), "r"(w[19]), "r"(w[20]), "r"(w[21]), "r"(w[22]), "r"(w[23]), "r"(w[24]), "r"(w[25]), "r"(w[26]), "r"(w[27]), "r"(w[28]), "r"(w[29]), "r"(w[30]), "r"(w[31]), "r"(w[32]), "r"(w[33]), "r"(w[34]), "r"(w[35]), "r"(w[36]), "r"(w[37]), "r"(w[38]), "r"(w[39]), "r"(dx), "l"(de), "l"(dh)
      : "memory");
  }
  static __device__ __forceinline__ void wait_g(float* g) {
    asm volatile("wgmma.wait_group.sync.aligned 1;\n"
      : "+f"(g[0]), "+f"(g[1]), "+f"(g[2]), "+f"(g[3]), "+f"(g[4]), "+f"(g[5]), "+f"(g[6]), "+f"(g[7]), "+f"(g[8]), "+f"(g[9]), "+f"(g[10]), "+f"(g[11]), "+f"(g[12]), "+f"(g[13]), "+f"(g[14]), "+f"(g[15]), "+f"(g[16]), "+f"(g[17]), "+f"(g[18]), "+f"(g[19]), "+f"(g[20]), "+f"(g[21]), "+f"(g[22]), "+f"(g[23]), "+f"(g[24]), "+f"(g[25]), "+f"(g[26]), "+f"(g[27]), "+f"(g[28]), "+f"(g[29]), "+f"(g[30]), "+f"(g[31]), "+f"(g[32]), "+f"(g[33]), "+f"(g[34]), "+f"(g[35])
      :: "memory");
  }
  static __device__ __forceinline__ void wait_h(float* h) {
    asm volatile("wgmma.wait_group.sync.aligned 0;\n"
      : "+f"(h[0]), "+f"(h[1]), "+f"(h[2]), "+f"(h[3]), "+f"(h[4]), "+f"(h[5]), "+f"(h[6]), "+f"(h[7]), "+f"(h[8]), "+f"(h[9]), "+f"(h[10]), "+f"(h[11]), "+f"(h[12]), "+f"(h[13]), "+f"(h[14]), "+f"(h[15]), "+f"(h[16]), "+f"(h[17]), "+f"(h[18]), "+f"(h[19]), "+f"(h[20]), "+f"(h[21]), "+f"(h[22]), "+f"(h[23]), "+f"(h[24]), "+f"(h[25]), "+f"(h[26]), "+f"(h[27]), "+f"(h[28]), "+f"(h[29]), "+f"(h[30]), "+f"(h[31]), "+f"(h[32]), "+f"(h[33]), "+f"(h[34]), "+f"(h[35])
      :: "memory");
  }
};
template<> struct TileMMA<10> {
  static __device__ __forceinline__ void issue(float* g, float* h, const uint32_t* w, uint32_t dx, uint64_t de, uint64_t dh, uint64_t dc) {
    asm volatile(
      "{\n.reg .b64 dx0, dx1, dx2, dx3;\n.reg .b32 l1, l2, l3, hx;\nmov.b32 hx, 0x40000040;\n"
      "add.u32 l1, %120, 2;\nadd.u32 l2, %120, 4;\nadd.u32 l3, %120, 6;\n"
      "mov.b64 dx0, {%120, hx};\nmov.b64 dx1, {l1, hx};\nmov.b64 dx2, {l2, hx};\nmov.b64 dx3, {l3, hx};\n"
      "wgmma.fence.sync.aligned;\n"
      "wgmma.mma_async.sync.aligned.m64n80k16.f32.bf16.bf16 {%0, %1, %2, %3, %4, %5, %6, %7, %8, %9, %10, %11, %12, %13, %14, %15, %16, %17, %18, %19, %20, %21, %22, %23, %24, %25, %26, %27, %28, %29, %30, %31, %32, %33, %34, %35, %36, %37, %38, %39}, {%116, %117, %118, %119}, %122, 0, 1, 1, 0;\n"
      "wgmma.mma_async.sync.aligned.m64n80k16.f32.bf16.bf16 {%0, %1, %2, %3, %4, %5, %6, %7, %8, %9, %10, %11, %12, %13, %14, %15, %16, %17, %18, %19, %20, %21, %22, %23, %24, %25, %26, %27, %28, %29, %30, %31, %32, %33, %34, %35, %36, %37, %38, %39}, {%96, %97, %98, %99}, %121, 1, 1, 1, 0;\n"
      "wgmma.mma_async.sync.aligned.m64n80k16.f32.bf16.bf16 {%0, %1, %2, %3, %4, %5, %6, %7, %8, %9, %10, %11, %12, %13, %14, %15, %16, %17, %18, %19, %20, %21, %22, %23, %24, %25, %26, %27, %28, %29, %30, %31, %32, %33, %34, %35, %36, %37, %38, %39}, {%80, %81, %82, %83}, dx0, 1, 1, 1, 0;\n"
      "wgmma.mma_async.sync.aligned.m64n80k16.f32.bf16.bf16 {%0, %1, %2, %3, %4, %5, %6, %7, %8, %9, %10, %11, %12, %13, %14, %15, %16, %17, %18, %19, %20, %21, %22, %23, %24, %25, %26, %27, %28, %29, %30, %31, %32, %33, %34, %35, %36, %37, %38, %39}, {%84, %85, %86, %87}, dx1, 1, 1, 1, 0;\n"
      "wgmma.mma_async.sync.aligned.m64n80k16.f32.bf16.bf16 {%0, %1, %2, %3, %4, %5, %6, %7, %8, %9, %10, %11, %12, %13, %14, %15, %16, %17, %18, %19, %20, %21, %22, %23, %24, %25, %26, %27, %28, %29, %30, %31, %32, %33, %34, %35, %36, %37, %38, %39}, {%88, %89, %90, %91}, dx2, 1, 1, 1, 0;\n"
      "wgmma.mma_async.sync.aligned.m64n80k16.f32.bf16.bf16 {%0, %1, %2, %3, %4, %5, %6, %7, %8, %9, %10, %11, %12, %13, %14, %15, %16, %17, %18, %19, %20, %21, %22, %23, %24, %25, %26, %27, %28, %29, %30, %31, %32, %33, %34, %35, %36, %37, %38, %39}, {%92, %93, %94, %95}, dx3, 1, 1, 1, 0;\n"
      "wgmma.commit_group.sync.aligned;\n"
      "wgmma.mma_async.sync.aligned.m64n80k16.f32.bf16.bf16 {%40, %41, %42, %43, %44, %45, %46, %47, %48, %49, %50, %51, %52, %53, %54, %55, %56, %57, %58, %59, %60, %61, %62, %63, %64, %65, %66, %67, %68, %69, %70, %71, %72, %73, %74, %75, %76, %77, %78, %79}, {%100, %101, %102, %103}, dx0, 0, 1, 1, 0;\n"
      "wgmma.mma_async.sync.aligned.m64n80k16.f32.bf16.bf16 {%40, %41, %42, %43, %44, %45, %46, %47, %48, %49, %50, %51, %52, %53, %54, %55, %56, %57, %58, %59, %60, %61, %62, %63, %64, %65, %66, %67, %68, %69, %70, %71, %72, %73, %74, %75, %76, %77, %78, %79}, {%104, %105, %106, %107}, dx1, 1, 1, 1, 0;\n"
      "wgmma.mma_async.sync.aligned.m64n80k16.f32.bf16.bf16 {%40, %41, %42, %43, %44, %45, %46, %47, %48, %49, %50, %51, %52, %53, %54, %55, %56, %57, %58, %59, %60, %61, %62, %63, %64, %65, %66, %67, %68, %69, %70, %71, %72, %73, %74, %75, %76, %77, %78, %79}, {%108, %109, %110, %111}, dx2, 1, 1, 1, 0;\n"
      "wgmma.mma_async.sync.aligned.m64n80k16.f32.bf16.bf16 {%40, %41, %42, %43, %44, %45, %46, %47, %48, %49, %50, %51, %52, %53, %54, %55, %56, %57, %58, %59, %60, %61, %62, %63, %64, %65, %66, %67, %68, %69, %70, %71, %72, %73, %74, %75, %76, %77, %78, %79}, {%112, %113, %114, %115}, dx3, 1, 1, 1, 0;\n"
      "wgmma.commit_group.sync.aligned;\n}\n"
      : "=f"(g[0]), "=f"(g[1]), "=f"(g[2]), "=f"(g[3]), "=f"(g[4]), "=f"(g[5]), "=f"(g[6]), "=f"(g[7]), "=f"(g[8]), "=f"(g[9]), "=f"(g[10]), "=f"(g[11]), "=f"(g[12]), "=f"(g[13]), "=f"(g[14]), "=f"(g[15]), "=f"(g[16]), "=f"(g[17]), "=f"(g[18]), "=f"(g[19]), "=f"(g[20]), "=f"(g[21]), "=f"(g[22]), "=f"(g[23]), "=f"(g[24]), "=f"(g[25]), "=f"(g[26]), "=f"(g[27]), "=f"(g[28]), "=f"(g[29]), "=f"(g[30]), "=f"(g[31]), "=f"(g[32]), "=f"(g[33]), "=f"(g[34]), "=f"(g[35]), "=f"(g[36]), "=f"(g[37]), "=f"(g[38]), "=f"(g[39]),
        "=f"(h[0]), "=f"(h[1]), "=f"(h[2]), "=f"(h[3]), "=f"(h[4]), "=f"(h[5]), "=f"(h[6]), "=f"(h[7]), "=f"(h[8]), "=f"(h[9]), "=f"(h[10]), "=f"(h[11]), "=f"(h[12]), "=f"(h[13]), "=f"(h[14]), "=f"(h[15]), "=f"(h[16]), "=f"(h[17]), "=f"(h[18]), "=f"(h[19]), "=f"(h[20]), "=f"(h[21]), "=f"(h[22]), "=f"(h[23]), "=f"(h[24]), "=f"(h[25]), "=f"(h[26]), "=f"(h[27]), "=f"(h[28]), "=f"(h[29]), "=f"(h[30]), "=f"(h[31]), "=f"(h[32]), "=f"(h[33]), "=f"(h[34]), "=f"(h[35]), "=f"(h[36]), "=f"(h[37]), "=f"(h[38]), "=f"(h[39])
      : "r"(w[0]), "r"(w[1]), "r"(w[2]), "r"(w[3]), "r"(w[4]), "r"(w[5]), "r"(w[6]), "r"(w[7]), "r"(w[8]), "r"(w[9]), "r"(w[10]), "r"(w[11]), "r"(w[12]), "r"(w[13]), "r"(w[14]), "r"(w[15]), "r"(w[16]), "r"(w[17]), "r"(w[18]), "r"(w[19]), "r"(w[20]), "r"(w[21]), "r"(w[22]), "r"(w[23]), "r"(w[24]), "r"(w[25]), "r"(w[26]), "r"(w[27]), "r"(w[28]), "r"(w[29]), "r"(w[30]), "r"(w[31]), "r"(w[32]), "r"(w[33]), "r"(w[34]), "r"(w[35]), "r"(w[36]), "r"(w[37]), "r"(w[38]), "r"(w[39]), "r"(dx), "l"(de), "l"(dh)
      : "memory");
  }
  static __device__ __forceinline__ void wait_g(float* g) {
    asm volatile("wgmma.wait_group.sync.aligned 1;\n"
      : "+f"(g[0]), "+f"(g[1]), "+f"(g[2]), "+f"(g[3]), "+f"(g[4]), "+f"(g[5]), "+f"(g[6]), "+f"(g[7]), "+f"(g[8]), "+f"(g[9]), "+f"(g[10]), "+f"(g[11]), "+f"(g[12]), "+f"(g[13]), "+f"(g[14]), "+f"(g[15]), "+f"(g[16]), "+f"(g[17]), "+f"(g[18]), "+f"(g[19]), "+f"(g[20]), "+f"(g[21]), "+f"(g[22]), "+f"(g[23]), "+f"(g[24]), "+f"(g[25]), "+f"(g[26]), "+f"(g[27]), "+f"(g[28]), "+f"(g[29]), "+f"(g[30]), "+f"(g[31]), "+f"(g[32]), "+f"(g[33]), "+f"(g[34]), "+f"(g[35]), "+f"(g[36]), "+f"(g[37]), "+f"(g[38]), "+f"(g[39])
      :: "memory");
  }
  static __device__ __forceinline__ void wait_h(float* h) {
    asm volatile("wgmma.wait_group.sync.aligned 0;\n"
      : "+f"(h[0]), "+f"(h[1]), "+f"(h[2]), "+f"(h[3]), "+f"(h[4]), "+f"(h[5]), "+f"(h[6]), "+f"(h[7]), "+f"(h[8]), "+f"(h[9]), "+f"(h[10]), "+f"(h[11]), "+f"(h[12]), "+f"(h[13]), "+f"(h[14]), "+f"(h[15]), "+f"(h[16]), "+f"(h[17]), "+f"(h[18]), "+f"(h[19]), "+f"(h[20]), "+f"(h[21]), "+f"(h[22]), "+f"(h[23]), "+f"(h[24]), "+f"(h[25]), "+f"(h[26]), "+f"(h[27]), "+f"(h[28]), "+f"(h[29]), "+f"(h[30]), "+f"(h[31]), "+f"(h[32]), "+f"(h[33]), "+f"(h[34]), "+f"(h[35]), "+f"(h[36]), "+f"(h[37]), "+f"(h[38]), "+f"(h[39])
      :: "memory");
  }
};
template<> struct TileMMA<11> {
  static __device__ __forceinline__ void issue(float* g, float* h, const uint32_t* w, uint32_t dx, uint64_t de, uint64_t dh, uint64_t dc) {
    asm volatile(
      "{\n.reg .b64 dx0, dx1, dx2, dx3;\n.reg .b32 l1, l2, l3, hx;\nmov.b32 hx, 0x40000040;\n"
      "add.u32 l1, %124, 2;\nadd.u32 l2, %124, 4;\nadd.u32 l3, %124, 6;\n"
      "mov.b64 dx0, {%124, hx};\nmov.b64 dx1, {l1, hx};\nmov.b64 dx2, {l2, hx};\nmov.b64 dx3, {l3, hx};\n"
      "wgmma.fence.sync.aligned;\n"
      "wgmma.mma_async.sync.aligned.m64n88k16.f32.bf16.bf16 {%0, %1, %2, %3, %4, %5, %6, %7, %8, %9, %10, %11, %12, %13, %14, %15, %16, %17, %18, %19, %20, %21, %22, %23, %24, %25, %26, %27, %28, %29, %30, %31, %32, %33, %34, %35, %36, %37, %38, %39, %40, %41, %42, %43}, {%120, %121, %122, %123}, %126, 0, 1, 1, 0;\n"
      "wgmma.mma_async.sync.aligned.m64n88k16.f32.bf16.bf16 {%0, %1, %2, %3, %4, %5, %6, %7, %8, %9, %10, %11, %12, %13, %14, %15, %16, %17, %18, %19, %20, %21, %22, %23, %24, %25, %26, %27, %28, %29, %30, %31, %32, %33, %34, %35, %36, %37, %38, %39, %40, %41, %42, %43}, %127, %125, 1, 1, 1, 0, 0;\n"
      "wgmma.mma_async.sync.aligned.m64n88k16.f32.bf16.bf16 {%0, %1, %2, %3, %4, %5, %6, %7, %8, %9, %10, %11, %12, %13, %14, %15, %16, %17, %18, %19, %20, %21, %22, %23, %24, %25, %26, %27, %28, %29, %30, %31, %32, %33, %34, %35, %36, %37, %38, %39, %40, %41, %42, %43}, {%88, %89, %90, %91}, dx0, 1, 1, 1, 0;\n"
      "wgmma.mma_async.sync.aligned.m64n88k16.f32.bf16.bf16 {%0, %1, %2, %3, %4, %5, %6, %7, %8, %9, %10, %11, %12, %13, %14, %15, %16, %17, %18, %19, %20, %21, %22, %23, %24, %25, %26, %27, %28, %29, %30, %31, %32, %33, %34, %35, %36, %37, %38, %39, %40, %41, %42, %43}, {%92, %93, %94, %95}, dx1, 1, 1, 1, 0;\n"
      "wgmma.mma_async.sync.aligned.m64n88k16.f32.bf16.bf16 {%0, %1, %2, %3, %4, %5, %6, %7, %8, %9, %10, %11, %12, %13, %14, %15, %16, %17, %18, %19, %20, %21, %22, %23, %24, %25, %26, %27, %28, %29, %30, %31, %32, %33, %34, %35, %36, %37, %38, %39, %40, %41, %42, %43}, {%96, %97, %98, %99}, dx2, 1, 1, 1, 0;\n"
      "wgmma.mma_async.sync.aligned.m64n88k16.f32.bf16.bf16 {%0, %1, %2, %3, %4, %5, %6, %7, %8, %9, %10, %11, %12, %13, %14, %15, %16, %17, %18, %19, %20, %21, %22, %23, %24, %25, %26, %27, %28, %29, %30, %31, %32, %33, %34, %35, %36, %37, %38, %39, %40, %41, %42, %43}, {%100, %101, %102, %103}, dx3, 1, 1, 1, 0;\n"
      "wgmma.commit_group.sync.aligned;\n"
      "wgmma.mma_async.sync.aligned.m64n88k16.f32.bf16.bf16 {%44, %45, %46, %47, %48, %49, %50, %51, %52, %53, %54, %55, %56, %57, %58, %59, %60, %61, %62, %63, %64, %65, %66, %67, %68, %69, %70, %71, %72, %73, %74, %75, %76, %77, %78, %79, %80, %81, %82, %83, %84, %85, %86, %87}, {%104, %105, %106, %107}, dx0, 0, 1, 1, 0;\n"
      "wgmma.mma_async.sync.aligned.m64n88k16.f32.bf16.bf16 {%44, %45, %46, %47, %48, %49, %50, %51, %52, %53, %54, %55, %56, %57, %58, %59, %60, %61, %62, %63, %64, %65, %66, %67, %68, %69, %70, %71, %72, %73, %74, %75, %76, %77, %78, %79, %80, %81, %82, %83, %84, %85, %86, %87}, {%108, %109, %110, %111}, dx1, 1, 1, 1, 0;\n"
      "wgmma.mma_async.sync.aligned.m64n88k16.f32.bf16.bf16 {%44, %45, %46, %47, %48, %49, %50, %51, %52, %53, %54, %55, %56, %57, %58, %59, %60, %61, %62, %63, %64, %65, %66, %67, %68, %69, %70, %71, %72, %73, %74, %75, %76, %77, %78, %79, %80, %81, %82, %83, %84, %85, %86, %87}, {%112, %113, %114, %115}, dx2, 1, 1, 1, 0;\n"
      "wgmma.mma_async.sync.aligned.m64n88k16.f32.bf16.bf16 {%44, %45, %46, %47, %48, %49, %50, %51, %52, %53, %54, %55, %56, %57, %58, %59, %60, %61, %62, %63, %64, %65, %66, %67, %68, %69, %70, %71, %72, %73, %74, %75, %76, %77, %78, %79, %80, %81, %82, %83, %84, %85, %86, %87}, {%116, %117, %118, %119}, dx3, 1, 1, 1, 0;\n"
      "wgmma.commit_group.sync.aligned;\n}\n"
      : "=f"(g[0]), "=f"(g[1]), "=f"(g[2]), "=f"(g[3]), "=f"(g[4]), "=f"(g[5]), "=f"(g[6]), "=f"(g[7]), "=f"(g[8]), "=f"(g[9]), "=f"(g[10]), "=f"(g[11]), "=f"(g[12]), "=f"(g[13]), "=f"(g[14]), "=f"(g[15]), "=f"(g[16]), "=f"(g[17]), "=f"(g[18]), "=f"(g[19]), "=f"(g[20]), "=f"(g[21]), "=f"(g[22]), "=f"(g[23]), "=f"(g[24]), "=f"(g[25]), "=f"(g[26]), "=f"(g[27]), "=f"(g[28]), "=f"(g[29]), "=f"(g[30]), "=f"(g[31]), "=f"(g[32]), "=f"(g[33]), "=f"(g[34]), "=f"(g[35]), "=f"(g[36]), "=f"(g[37]), "=f"(g[38]), "=f"(g[39]), "=f"(g[40]), "=f"(g[41]), "=f"(g[42]), "=f"(g[43]),
        "=f"(h[0]), "=f"(h[1]), "=f"(h[2]), "=f"(h[3]), "=f"(h[4]), "=f"(h[5]), "=f"(h[6]), "=f"(h[7]), "=f"(h[8]), "=f"(h[9]), "=f"(h[10]), "=f"(h[11]), "=f"(h[12]), "=f"(h[13]), "=f"(h[14]), "=f"(h[15]), "=f"(h[16]), "=f"(h[17]), "=f"(h[18]), "=f"(h[19]), "=f"(h[20]), "=f"(h[21]), "=f"(h[22]), "=f"(h[23]), "=f"(h[24]), "=f"(h[25]), "=f"(h[26]), "=f"(h[27]), "=f"(h[28]), "=f"(h[29]), "=f"(h[30]), "=f"(h[31]), "=f"(h[32]), "=f"(h[33]), "=f"(h[34]), "=f"(h[35]), "=f"(h[36]), "=f"(h[37]), "=f"(h[38]), "=f"(h[39]), "=f"(h[40]), "=f"(h[41]), "=f"(h[42]), "=f"(h[43])
      : "r"(w[0]), "r"(w[1]), "r"(w[2]), "r"(w[3]), "r"(w[4]), "r"(w[5]), "r"(w[6]), "r"(w[7]), "r"(w[8]), "r"(w[9]), "r"(w[10]), "r"(w[11]), "r"(w[12]), "r"(w[13]), "r"(w[14]), "r"(w[15]), "r"(w[20]), "r"(w[21]), "r"(w[22]), "r"(w[23]), "r"(w[24]), "r"(w[25]), "r"(w[26]), "r"(w[27]), "r"(w[28]), "r"(w[29]), "r"(w[30]), "r"(w[31]), "r"(w[32]), "r"(w[33]), "r"(w[34]), "r"(w[35]), "r"(w[36]), "r"(w[37]), "r"(w[38]), "r"(w[39]), "r"(dx), "l"(de), "l"(dh), "l"(dc)
      : "memory");
  }
  static __device__ __forceinline__ void wait_g(float* g) {
    asm volatile("wgmma.wait_group.sync.aligned 1;\n"
      : "+f"(g[0]), "+f"(g[1]), "+f"(g[2]), "+f"(g[3]), "+f"(g[4]), "+f"(g[5]), "+f"(g[6]), "+f"(g[7]), "+f"(g[8]), "+f"(g[9]), "+f"(g[10]), "+f"(g[11]), "+f"(g[12]), "+f"(g[13]), "+f"(g[14]), "+f"(g[15]), "+f"(g[16]), "+f"(g[17]), "+f"(g[18]), "+f"(g[19]), "+f"(g[20]), "+f"(g[21]), "+f"(g[22]), "+f"(g[23]), "+f"(g[24]), "+f"(g[25]), "+f"(g[26]), "+f"(g[27]), "+f"(g[28]), "+f"(g[29]), "+f"(g[30]), "+f"(g[31]), "+f"(g[32]), "+f"(g[33]), "+f"(g[34]), "+f"(g[35]), "+f"(g[36]), "+f"(g[37]), "+f"(g[38]), "+f"(g[39]), "+f"(g[40]), "+f"(g[41]), "+f"(g[42]), "+f"(g[43])
      :: "memory");
  }
  static __device__ __forceinline__ void wait_h(float* h) {
    asm volatile("wgmma.wait_group.sync.aligned 0;\n"
      : "+f"(h[0]), "+f"(h[1]), "+f"(h[2]), "+f"(h[3]), "+f"(h[4]), "+f"(h[5]), "+f"(h[6]), "+f"(h[7]), "+f"(h[8]), "+f"(h[9]), "+f"(h[10]), "+f"(h[11]), "+f"(h[12]), "+f"(h[13]), "+f"(h[14]), "+f"(h[15]), "+f"(h[16]), "+f"(h[17]), "+f"(h[18]), "+f"(h[19]), "+f"(h[20]), "+f"(h[21]), "+f"(h[22]), "+f"(h[23]), "+f"(h[24]), "+f"(h[25]), "+f"(h[26]), "+f"(h[27]), "+f"(h[28]), "+f"(h[29]), "+f"(h[30]), "+f"(h[31]), "+f"(h[32]), "+f"(h[33]), "+f"(h[34]), "+f"(h[35]), "+f"(h[36]), "+f"(h[37]), "+f"(h[38]), "+f"(h[39]), "+f"(h[40]), "+f"(h[41]), "+f"(h[42]), "+f"(h[43])
      :: "memory");
  }
};
__device__ __forceinline__ void node_mma(float* g, const uint32_t* w, uint64_t dx) {
    asm volatile(
      "{\n.reg .b64 dx1, dx2, dx3;\n"
      "add.s64 dx1, %48, 2;\nadd.s64 dx2, %48, 4;\nadd.s64 dx3, %48, 6;\n"
      "wgmma.fence.sync.aligned;\n"
      "wgmma.mma_async.sync.aligned.m64n64k16.f32.bf16.bf16 {%0, %1, %2, %3, %4, %5, %6, %7, %8, %9, %10, %11, %12, %13, %14, %15, %16, %17, %18, %19, %20, %21, %22, %23, %24, %25, %26, %27, %28, %29, %30, %31}, {%32, %33, %34, %35}, %48, 0, 1, 1, 0;\n"
      "wgmma.mma_async.sync.aligned.m64n64k16.f32.bf16.bf16 {%0, %1, %2, %3, %4, %5, %6, %7, %8, %9, %10, %11, %12, %13, %14, %15, %16, %17, %18, %19, %20, %21, %22, %23, %24, %25, %26, %27, %28, %29, %30, %31}, {%36, %37, %38, %39}, dx1, 1, 1, 1, 0;\n"
      "wgmma.mma_async.sync.aligned.m64n64k16.f32.bf16.bf16 {%0, %1, %2, %3, %4, %5, %6, %7, %8, %9, %10, %11, %12, %13, %14, %15, %16, %17, %18, %19, %20, %21, %22, %23, %24, %25, %26, %27, %28, %29, %30, %31}, {%40, %41, %42, %43}, dx2, 1, 1, 1, 0;\n"
      "wgmma.mma_async.sync.aligned.m64n64k16.f32.bf16.bf16 {%0, %1, %2, %3, %4, %5, %6, %7, %8, %9, %10, %11, %12, %13, %14, %15, %16, %17, %18, %19, %20, %21, %22, %23, %24, %25, %26, %27, %28, %29, %30, %31}, {%44, %45, %46, %47}, dx3, 1, 1, 1, 0;\n"
      "wgmma.commit_group.sync.aligned;\n}\n"
      : "=f"(g[0]), "=f"(g[1]), "=f"(g[2]), "=f"(g[3]), "=f"(g[4]), "=f"(g[5]), "=f"(g[6]), "=f"(g[7]), "=f"(g[8]), "=f"(g[9]), "=f"(g[10]), "=f"(g[11]), "=f"(g[12]), "=f"(g[13]), "=f"(g[14]), "=f"(g[15]), "=f"(g[16]), "=f"(g[17]), "=f"(g[18]), "=f"(g[19]), "=f"(g[20]), "=f"(g[21]), "=f"(g[22]), "=f"(g[23]), "=f"(g[24]), "=f"(g[25]), "=f"(g[26]), "=f"(g[27]), "=f"(g[28]), "=f"(g[29]), "=f"(g[30]), "=f"(g[31])
      : "r"(w[0]), "r"(w[1]), "r"(w[2]), "r"(w[3]), "r"(w[4]), "r"(w[5]), "r"(w[6]), "r"(w[7]), "r"(w[8]), "r"(w[9]), "r"(w[10]), "r"(w[11]), "r"(w[12]), "r"(w[13]), "r"(w[14]), "r"(w[15]), "l"(dx)
      : "memory");
}

__device__ __forceinline__ uint32_t smem_u32(const void* p) { return (uint32_t)__cvta_generic_to_shared(p); }
__device__ __forceinline__ float ex2f(float x) { float y; asm("ex2.approx.ftz.f32 %0, %1;" : "=f"(y) : "f"(x)); return y; }
__device__ __forceinline__ float rcpf(float x) { float y; asm("rcp.approx.ftz.f32 %0, %1;" : "=f"(y) : "f"(x)); return y; }
__device__ __forceinline__ uint32_t pack_bf16(float lo, float hi) {
    uint32_t r; asm("cvt.rn.bf16x2.f32 %0, %1, %2;" : "=r"(r) : "f"(hi), "f"(lo)); return r;
}
__device__ __forceinline__ float bf_lo(uint32_t v) { return __uint_as_float(v << 16); }
__device__ __forceinline__ float bf_hi(uint32_t v) { return __uint_as_float(v & 0xFFFF0000u); }
template<int STRIDE>
__device__ __forceinline__ void cp16i(uint32_t dst, const char* base, uint32_t idx) {
    asm volatile("{\n.reg .b64 a;\nmad.wide.u32 a, %2, %3, %1;\ncp.async.cg.shared.global [%0], [a], 16;\n}\n" :: "r"(dst), "l"(base), "r"(idx), "n"(STRIDE) : "memory");
}
__device__ __forceinline__ void cp16e(uint32_t dst, const char* base, uint32_t idx, uint64_t pol) {
    asm volatile("{\n.reg .b64 a;\nmad.wide.u32 a, %2, 32, %1;\ncp.async.cg.shared.global.L2::cache_hint [%0], [a], 16, %3;\n}\n" :: "r"(dst), "l"(base), "r"(idx), "l"(pol) : "memory");
}
template<int STRIDE>
__device__ __forceinline__ void cp16z(uint32_t dst, const char* base, uint32_t idx, int k, int n, uint64_t pol) {
    if (STRIDE == 32)
        asm volatile("{\n.reg .b64 a;\n.reg .pred p;\nsetp.ge.s32 p, %3, %4;\nmad.wide.u32 a, %2, 32, %1;\ncp.async.cg.shared.global.L2::cache_hint [%0], [a], 16, p, %5;\n}\n"
                     :: "r"(dst), "l"(base), "r"(idx), "r"(k), "r"(n), "l"(pol) : "memory");
    else
        asm volatile("{\n.reg .b64 a;\n.reg .pred p;\nsetp.ge.s32 p, %3, %4;\nmad.wide.u32 a, %2, 128, %1;\ncp.async.cg.shared.global [%0], [a], 16, p;\n}\n"
                     :: "r"(dst), "l"(base), "r"(idx), "r"(k), "r"(n) : "memory");
}
template<int HI, bool Z>
__device__ __forceinline__ void cpx(uint32_t hi, uint32_t dst, uint32_t p, uint32_t lo, int k, int n) {
    if (Z) asm volatile("{\n.reg .b32 l;\n.reg .b64 a;\n.reg .pred q;\nsetp.ge.s32 q, %5, %6;\ndp2a.lo.u32.u32 l, %1, %2, %3;\nmov.b64 a, {l, %0};\ncp.async.cg.shared.global [%4], [a], 16, q;\n}\n"
                        :: "r"(hi), "r"(p), "r"(HI ? 0x8000u : 0x80u), "r"(lo), "r"(dst), "r"(k), "r"(n) : "memory");
    else asm volatile("{\n.reg .b32 l;\n.reg .b64 a;\ndp2a.lo.u32.u32 l, %1, %2, %3;\nmov.b64 a, {l, %0};\ncp.async.cg.shared.global [%4], [a], 16;\n}\n"
                      :: "r"(hi), "r"(p), "r"(HI ? 0x8000u : 0x80u), "r"(lo), "r"(dst) : "memory");
}
template<bool Z>
__device__ __forceinline__ void cpe(uint32_t hi, uint32_t dst, uint32_t idx, uint32_t lo, int k, int n, uint64_t pol) {
    if (Z) asm volatile("{\n.reg .b32 l;\n.reg .b64 a;\n.reg .pred q;\nsetp.ge.s32 q, %5, %6;\nmad.lo.u32 l, %1, 32, %2;\nmov.b64 a, {l, %0};\ncp.async.cg.shared.global.L2::cache_hint [%3], [a], 16, q, %4;\n}\n"
                        :: "r"(hi), "r"(idx), "r"(lo), "r"(dst), "l"(pol), "r"(k), "r"(n) : "memory");
    else asm volatile("{\n.reg .b32 l;\n.reg .b64 a;\nmad.lo.u32 l, %1, 32, %2;\nmov.b64 a, {l, %0};\ncp.async.cg.shared.global.L2::cache_hint [%3], [a], 16, %4;\n}\n"
                      :: "r"(hi), "r"(idx), "r"(lo), "r"(dst), "l"(pol) : "memory");
}
__device__ __forceinline__ void cp_commit() { asm volatile("cp.async.commit_group;" ::: "memory"); }
template<int N> __device__ __forceinline__ void cp_wait() { asm volatile("cp.async.wait_group %0;" :: "n"(N) : "memory"); }
__device__ __forceinline__ void mbar_arrive(uint32_t bar) { asm volatile("mbarrier.arrive.shared.b64 _, [%0];" :: "r"(bar) : "memory"); }
__device__ __forceinline__ void mbar_cp_arrive(uint32_t bar) { asm volatile("cp.async.mbarrier.arrive.noinc.shared.b64 [%0];" :: "r"(bar) : "memory"); }
__device__ __forceinline__ void mbar_wait(uint32_t bar, uint32_t parity) {
    asm volatile("{\n.reg .pred p;\n.reg .u32 n;\nmbarrier.try_wait.parity.shared.b64 p, [%0], %1;\n@p bra DONE_%=;\nmov.u32 n, 0;\n"
                 "WAIT_%=:\nmbarrier.try_wait.parity.shared.b64 p, [%0], %1, 0x100000;\n@p bra DONE_%=;\n"
                 "add.u32 n, n, 1;\nsetp.lt.u32 p, n, 0x400000;\n@p bra WAIT_%=;\ntrap;\nDONE_%=:\n}\n"
                 :: "r"(bar), "r"(parity) : "memory");
}
__device__ __forceinline__ void mbar_wait_c(uint32_t bar, uint32_t parity) {
    asm volatile("{\n.reg .pred p;\nWAIT_%=:\nmbarrier.try_wait.parity.shared.b64 p, [%0], %1;\n@p bra DONE_%=;\nbra WAIT_%=;\nDONE_%=:\n}\n"
                 :: "r"(bar), "r"(parity) : "memory");
}
__device__ __forceinline__ void mbar_wait_h(uint32_t bar, uint32_t parity) {
    asm volatile("{\n.reg .pred p;\nWAIT_%=:\nmbarrier.try_wait.parity.shared.b64 p, [%0], %1, 0x100000;\n@p bra DONE_%=;\nbra WAIT_%=;\nDONE_%=:\n}\n"
                 :: "r"(bar), "r"(parity) : "memory");
}
__device__ __forceinline__ uint32_t lds32(uint32_t a) { uint32_t v; asm volatile("ld.shared.u32 %0, [%1];" : "=r"(v) : "r"(a) : "memory"); return v; }
__device__ __forceinline__ void sts32(uint32_t a, uint32_t v) { asm volatile("st.shared.u32 [%0], %1;" :: "r"(a), "r"(v) : "memory"); }
__device__ __forceinline__ uint2 lds64(uint32_t a) { uint2 v; asm volatile("ld.shared.v2.u32 {%0,%1}, [%2];" : "=r"(v.x), "=r"(v.y) : "r"(a) : "memory"); return v; }
__device__ __forceinline__ void sts64(uint32_t a, uint32_t x, uint32_t y) { asm volatile("st.shared.v2.u32 [%0], {%1,%2};" :: "r"(a), "r"(x), "r"(y) : "memory"); }
__device__ __forceinline__ uint4 lds128(uint32_t a) { uint4 v; asm volatile("ld.shared.v4.u32 {%0,%1,%2,%3}, [%4];" : "=r"(v.x), "=r"(v.y), "=r"(v.z), "=r"(v.w) : "r"(a) : "memory"); return v; }
__device__ __forceinline__ void sts128(uint32_t a, uint4 v) { asm volatile("st.shared.v4.u32 [%0], {%1,%2,%3,%4};" :: "r"(a), "r"(v.x), "r"(v.y), "r"(v.z), "r"(v.w) : "memory"); }
__device__ __forceinline__ void ldsm4t(uint32_t* v, uint32_t a) {
    asm volatile("ldmatrix.sync.aligned.m8n8.x4.trans.shared.b16 {%0,%1,%2,%3}, [%4];" : "=r"(v[0]), "=r"(v[1]), "=r"(v[2]), "=r"(v[3]) : "r"(a) : "memory");
}
__device__ __forceinline__ void stsm4t(uint32_t a, const uint32_t* v) {
    asm volatile("stmatrix.sync.aligned.m8n8.x4.trans.shared.b16 [%0], {%1,%2,%3,%4};" :: "r"(a), "r"(v[0]), "r"(v[1]), "r"(v[2]), "r"(v[3]) : "memory");
}
__device__ __forceinline__ int atoms_inc(uint32_t a) { int v; asm volatile("atom.shared.add.u32 %0, [%1], 1;" : "=r"(v) : "r"(a) : "memory"); return v; }
__device__ __forceinline__ float tanhf_a(float x) { float y; asm("tanh.approx.f32 %0, %1;" : "=f"(y) : "f"(x)); return y; }
__device__ __forceinline__ const char* as_pair(const void* p, uint32_t scratch) {
    const char* r;
    asm volatile("st.shared.u64 [%1], %2;\nld.volatile.shared.u64 %0, [%1];" : "=l"(r) : "r"(scratch), "l"(p) : "memory");
    return r;
}
__device__ __forceinline__ void ld_unit(uint4& v, const char* p, bool ok) {
    asm volatile("{\n.reg .pred q;\nsetp.ne.u32 q, %5, 0;\n@q ld.relaxed.gpu.global.v4.u32 {%0,%1,%2,%3}, [%4];\n}"
                 : "+r"(v.x), "+r"(v.y), "+r"(v.z), "+r"(v.w) : "l"(p), "r"((uint32_t)ok) : "memory");
}
__device__ __forceinline__ void ld_unit(uint2& v, const char* p, bool ok) {
    asm volatile("{\n.reg .pred q;\nsetp.ne.u32 q, %3, 0;\n@q ld.relaxed.gpu.global.v2.u32 {%0,%1}, [%2];\n}"
                 : "+r"(v.x), "+r"(v.y) : "l"(p), "r"((uint32_t)ok) : "memory");
}
#define ELECT "{\n.reg .pred p;\nelect.sync _|p, 0xffffffff;\n@p "
__device__ __forceinline__ void w_init(uint32_t bar, int n) { asm volatile(ELECT "mbarrier.init.shared.b64 [%0], %1;\n}" :: "r"(bar), "r"(n) : "memory"); }
__device__ __forceinline__ void w_expect(uint32_t bar, uint32_t bytes) { asm volatile(ELECT "mbarrier.arrive.expect_tx.shared.b64 _, [%0], %1;\n}" :: "r"(bar), "r"(bytes) : "memory"); }
__device__ __forceinline__ void w_ld(uint32_t dst, const void* src, int bytes, uint32_t bar) {
    asm volatile(ELECT "cp.async.bulk.shared::cluster.global.mbarrier::complete_tx::bytes [%0], [%1], %2, [%3];\n}" :: "r"(dst), "l"(src), "r"(bytes), "r"(bar) : "memory");
}
__device__ __forceinline__ void w_box_ld(uint32_t dst, const CUtensorMap* tm, int row, uint32_t bar) {
    asm volatile(ELECT "cp.async.bulk.tensor.2d.shared::cluster.global.mbarrier::complete_tx::bytes [%0], [%1, {%3, %4}], [%2];\n}"
        :: "r"(dst), "l"((uint64_t)tm), "r"(bar), "r"(0), "r"(row) : "memory");
}
__device__ __forceinline__ void w_st(void* dst, uint32_t src, int bytes) {
    asm volatile(ELECT "cp.async.bulk.global.shared::cta.bulk_group [%0], [%1], %2;\n}" :: "l"(dst), "r"(src), "r"(bytes) : "memory");
}
__device__ __forceinline__ void w_box_st(const CUtensorMap* tm, int col, uint32_t src) {
    asm volatile(ELECT "cp.async.bulk.tensor.2d.global.shared::cta.bulk_group [%0, {%2, %3}], [%1];\n}" :: "l"((uint64_t)tm), "r"(src), "r"(col), "r"(0) : "memory");
}
__device__ __forceinline__ void w_sent(unsigned* p, uint32_t src) {
    asm volatile(ELECT "cp.reduce.async.bulk.global.shared::cta.bulk_group.add.u32 [%0], [%1], 16;\n}" :: "l"(p), "r"(src) : "memory");
}
__device__ __forceinline__ void w_inc(unsigned* p) { asm volatile(ELECT "red.relaxed.gpu.global.add.u32 [%0], 1;\n}" :: "l"(p) : "memory"); }
__device__ __forceinline__ void w_hint(unsigned* p, uint32_t all) {
    #pragma unroll 1
    for (int i = 0; i < 4096; i++) {
        uint32_t v; asm volatile("ld.relaxed.gpu.global.u32 %0, [%1];" : "=r"(v) : "l"(p) : "memory");
        if (__all_sync(~0u, (int)(v - all) >= 0)) break;
    }
}

__device__ __forceinline__ void finish(uint4& a, const uint4& xu, const uint4& xv) {
    asm("{\n.reg .b32 z;\nfma.rn.relu.bf16x2 z, %0, %3, %1;\nadd.rn.bf16x2 %0, z, %2;\n}" : "+r"(a.x) : "r"(xu.x), "r"(xv.x), "r"(0x3F803F80u));
    asm("{\n.reg .b32 z;\nfma.rn.relu.bf16x2 z, %0, %3, %1;\nadd.rn.bf16x2 %0, z, %2;\n}" : "+r"(a.y) : "r"(xu.y), "r"(xv.y), "r"(0x3F803F80u));
    asm("{\n.reg .b32 z;\nfma.rn.relu.bf16x2 z, %0, %3, %1;\nadd.rn.bf16x2 %0, z, %2;\n}" : "+r"(a.z) : "r"(xu.z), "r"(xv.z), "r"(0x3F803F80u));
    asm("{\n.reg .b32 z;\nfma.rn.relu.bf16x2 z, %0, %3, %1;\nadd.rn.bf16x2 %0, z, %2;\n}" : "+r"(a.w) : "r"(xu.w), "r"(xv.w), "r"(0x3F803F80u));
}

constexpr float EPS2 = 2e-6f;
constexpr float TAU = 2.5e-5f;

constexpr uint32_t TAU_BITS = 0x3A103000u;
template<int NP>
__device__ __forceinline__ bool epi_fast(const float* g, const float* h, float m2, float tau, float& n0, float& d0, float& n1, float& d1, float& dmin)
{
    constexpr int JC = NP >= 6 ? NP - 3 : NP - 2;
    bool ok;
    #pragma unroll
    for (int j = 0; j < NP; j++) {
        float t0 = tanhf_a(g[4*j+0]), t1 = tanhf_a(g[4*j+1]), t2 = tanhf_a(g[4*j+2]), t3 = tanhf_a(g[4*j+3]);
        auto add_d = [&]() {
            if (j == 0) { d0 = t0 + (2.f * (JC + 1) + EPS2); d1 = t2 + (2.f * (JC + 1) + EPS2); } else { d0 += t0; d1 += t2; }
            d0 += t1; d1 += t3;
        };
        if (j <= JC) add_d();
        if (j == 0) { n0 = fmaf(t0, h[0], h[0]); n1 = fmaf(t2, h[2], h[2]); }
        t0 += 1.f; t2 += 1.f;
        if (j == NP - 1) { t1 = fmaf(t1, m2, m2); t3 = fmaf(t3, m2, m2); } else { t1 += 1.f; t3 += 1.f; }
        if (j > JC) add_d();
        if (j > 0) { n0 = fmaf(t0, h[4*j], n0); n1 = fmaf(t2, h[4*j+2], n1); }
        n0 = fmaf(t1, h[4*j+1], n0); n1 = fmaf(t3, h[4*j+3], n1);
        if (j == JC) { dmin = fminf(d0, d1); ok = dmin >= tau; }
    }
    return ok;
}

__device__ __noinline__ void slow_bin(const __nv_bfloat16* x, const __nv_bfloat16* ea, const int* src, const int* dst,
                                      const __nv_bfloat16* wa, const __nv_bfloat16* wb, const __nv_bfloat16* wc,
                                      const __nv_bfloat16* wu, const __nv_bfloat16* wv, __nv_bfloat16* out,
                                      int E, int node0, int nn, int nthr)
{
    const int tid = threadIdx.x, lane = tid & 31;
    for (int i = tid; i < nn * 128; i += nthr) g_slow[(size_t)node0 * 128 + i] = 0.f;
    asm volatile("bar.sync 1, %0;" :: "r"(nthr) : "memory");
    for (int e0 = (tid >> 5) * 32; e0 < E; e0 += nthr) {
        int d = (e0 + lane < E) ? dst[e0 + lane] - node0 : -1;
        unsigned m = __ballot_sync(~0u, d >= 0 && d < nn);
        while (m) {
            int l = __ffs(m) - 1; m &= m - 1;
            int e = e0 + l, n = node0 + __shfl_sync(~0u, d, l), s = src[e];
            float g0 = 0, g1 = 0, h0 = 0, h1 = 0;
            for (int k = 0; k < 64; k++) {
                float xs = __bfloat162float(x[(size_t)s * 64 + k]), xd = __bfloat162float(x[(size_t)n * 64 + k]);
                uint32_t b2 = *(const uint32_t*)(wb + k * 64 + 2 * lane), v2 = *(const uint32_t*)(wv + k * 64 + 2 * lane);
                uint32_t a2 = *(const uint32_t*)(wa + k * 64 + 2 * lane);
                g0 = fmaf(xs, bf_lo(b2), fmaf(xd, bf_lo(a2), g0)); g1 = fmaf(xs, bf_hi(b2), fmaf(xd, bf_hi(a2), g1));
                h0 = fmaf(xs, bf_lo(v2), h0); h1 = fmaf(xs, bf_hi(v2), h1);
            }
            for (int k = 0; k < 16; k++) {
                float ev = __bfloat162float(ea[(size_t)e * 16 + k]);
                uint32_t c2 = *(const uint32_t*)(wc + k * 64 + 2 * lane);
                g0 = fmaf(ev, bf_lo(c2), g0); g1 = fmaf(ev, bf_hi(c2), g1);
            }
            float s0 = rcpf(1.f + ex2f(-LOG2E * g0)), s1 = rcpf(1.f + ex2f(-LOG2E * g1));
            float* acc = g_slow + (size_t)n * 128 + 4 * lane;
            atomicAdd(acc + 0, s0 * h0); atomicAdd(acc + 1, s0);
            atomicAdd(acc + 2, s1 * h1); atomicAdd(acc + 3, s1);
        }
    }
    __threadfence();
    asm volatile("bar.sync 1, %0;" :: "r"(nthr) : "memory");
    for (int i = tid; i < nn * 32; i += nthr) {
        int n = node0 + (i >> 5), cp = i & 31;
        float4 a = __ldcg((const float4*)(g_slow + (size_t)n * 128 + 4 * cp));
        float u0 = 0, u1 = 0;
        for (int k = 0; k < 64; k++) {
            float xd = __bfloat162float(x[(size_t)n * 64 + k]);
            uint32_t w2 = *(const uint32_t*)(wu + k * 64 + 2 * cp);
            u0 = fmaf(xd, bf_lo(w2), u0); u1 = fmaf(xd, bf_hi(w2), u1);
        }
        uint32_t xv = *(const uint32_t*)(x + (size_t)n * 64 + 2 * cp);
        float z0 = u0 + a.x / (a.y + 1e-6f), z1 = u1 + a.z / (a.w + 1e-6f);
        *(uint32_t*)(out + (size_t)n * 64 + 2 * cp) = pack_bf16(bf_lo(xv) + fmaxf(z0, 0.f), bf_hi(xv) + fmaxf(z1, 0.f));
    }
}

__global__ void __launch_bounds__(256) slow_kernel(const __nv_bfloat16* x, const __nv_bfloat16* ea, const int* src, const int* dst,
        const __nv_bfloat16* wa, const __nv_bfloat16* wb, const __nv_bfloat16* wc, const __nv_bfloat16* wu, const __nv_bfloat16* wv,
        __nv_bfloat16* out, int N, int E, int npb)
{
    int node0 = blockIdx.x * npb;
    slow_bin(x, ea, src, dst, wa, wb, wc, wu, wv, out, E, node0, max(0, min(npb, N - node0)), 256);
}

constexpr int XS_BYTES = NPMAX * 1024;
constexpr int ES_BYTES = NPMAX * 256;
constexpr int SM_XS = 0;
constexpr int SM_XU = SM_XS + 3 * NSTAGE * XS_BYTES;
constexpr int SM_TAB = SM_XU + NPB_MAX * 128;
constexpr int SM_ES = SM_TAB + NPB_MAX * 128;
constexpr int SM_WC = SM_ES + 3 * NSTAGE * ES_BYTES;
constexpr int SM_OH = SM_WC + 2048;
constexpr int SM_EID = SM_OH + 128;
constexpr int SM_SRC = SM_EID + SLOT_CAP * 4;
constexpr int SM_TINFO = SM_SRC + SLOT_CAP * 2;
constexpr int SM_MISC = SM_TINFO + TILE_CAP * 32;
constexpr int SM_CLAIM = SM_MISC + 32 * 4;
constexpr int STG = 272;
constexpr int SM_BARS = SM_CLAIM + 32 * 4;
constexpr int SM_ABAR = SM_BARS + 6 * STG;
constexpr int SM_GBAR = SM_ABAR + 16 * 8;
constexpr int SMEM_BYTES = SM_GBAR + (GD + 1) * 8;
constexpr int SM_P2 = 0, SM_P1 = P2B + 256;
constexpr int SM_L1 = SM_P1 + P1B + 128;
constexpr int SM_DEG = SM_L1 + 256;
constexpr int SM_CLS = SM_DEG + 512 * 4;
constexpr int SM_HIST = SM_CLS + NCLS * 4;
constexpr int SM_XLIST = SM_HIST + NB_MAX * 4;
constexpr int SM_SORT = SM_XLIST + 8;
constexpr int SM_SDEG = SM_SORT + NPB_MAX * 4;
constexpr int SM_PAIR = SM_SDEG + NPB_MAX * 2;
constexpr int SM_ENT = SM_ES + 1024;
constexpr int SM_H1 = SM_P1 + HB, SM_H2 = SM_P1;
constexpr int SM_IDX = SM_EID;
constexpr int SM_WR = SM_TAB;
static_assert(TILE_CAP <= 128 && TR >= 2 && SM_ES % 256 == 0 && NSTAGE == 2 && SM_BARS % 16 == 0 && SM_TINFO % 16 == 0 && SM_EID % 128 == 0 && SM_TAB % 1024 == 0 && SM_XU % 1024 == 0 && SM_TINFO % 8 == 0 && SM_OH % 16 == 0 && SM_XLIST % 8 == 0 && SM_PAIR % 8 == 0, "align");
static_assert(SM_P1 % 128 == 0 && P1B + HB <= SM_SRC - SM_EID && 2 * HB <= P1B && SM_H1 + 5 * 128 * 16 <= SM_XU && NB_MAX * (CE / 4) <= 6 * 384 && NB_MAX * 4 <= 5 * 128 && NB_MIN * 4 >= 3 * 128 && SM_PAIR + 128 * 8 <= SM_XU && CH_MAX * 4 <= SM_SRC - SM_EID && SM_DEG >= 3 << 14, "alias");
static_assert(CE == 64 && SMEM_BYTES <= 232448, "smem");
constexpr uint32_t C_BRK = 16  , C_CONT = 32, C_MORE = 64;
constexpr uint32_t ONE_F = 0x3F800000u;
constexpr int NONE = NPB_MAX - 1;
__host__ __device__ constexpr uint32_t tab_at(uint32_t n) { return (n >> 2) * 512 + (n & 3) * 32 + ((n >> 2) & 1) * 16; }

__device__ __forceinline__ bool unpad(uint32_t w1, int np, float ga, float gb, float& d0, float& d1, int& dv) {
    const int pad = (w1 >> 8) & 31;
    dv = 2 * np - 1 - pad + (w1 >= ONE_F);
    float t0 = TAU * 2 * np, t1 = t0;
    if (pad) {
        t0 = fmaxf(t0, d0 * (1.f / 1024)); t1 = fmaxf(t1, d1 * (1.f / 1024));
        asm volatile("tanh.approx.f32 %0, %0;\ntanh.approx.f32 %1, %1;" : "+f"(ga), "+f"(gb));
        d0 -= pad * (1.f + ga); d1 -= pad * (1.f + gb);
    }
    if (dv == 0) { d0 = d1 = EPS2; t0 = t1 = 0.f; }
    return d0 < t0 || d1 < t1;
}
constexpr int SM_COPY = SM_XU + tab_at(NPB_MAX - 4) - 16;
__device__ __forceinline__ void exact_quad(const float4 g, const float4 h, int k, int dv, float4& r) {
    const float e0 = 2.f * rcpf(1.f + ex2f(-2.f * LOG2E * g.x)), e1 = 2.f * rcpf(1.f + ex2f(-2.f * LOG2E * g.y));
    const float e2 = 2.f * rcpf(1.f + ex2f(-2.f * LOG2E * g.z)), e3 = 2.f * rcpf(1.f + ex2f(-2.f * LOG2E * g.w));
    if (k < dv) { r.y += e0; r.x = fmaf(e0, h.x, r.x); r.w += e2; r.z = fmaf(e2, h.z, r.z); }
    if (k + 1 < dv) { r.y += e1; r.x = fmaf(e1, h.y, r.x); r.w += e3; r.z = fmaf(e3, h.w, r.z); }
}
__device__ __forceinline__ float4 ldsf4(uint32_t a) { const uint4 v = lds128(a); return make_float4(__uint_as_float(v.x), __uint_as_float(v.y), __uint_as_float(v.z), __uint_as_float(v.w)); }
__device__ __noinline__ float4 exact_1(uint32_t sa, uint32_t l16)
{
    __syncwarp();
    const float4 g = ldsf4(sa + l16), h = ldsf4(sa + NPMAX * 16 + l16);
    float4 r = make_float4(0.f, 0.f, 0.f, 0.f);
    exact_quad(g, h, l16 >> 3, lds32(sa + 496), r);
    __syncwarp();
    sts128(sa + l16, make_uint4(__float_as_uint(r.x), __float_as_uint(r.y), __float_as_uint(r.z), __float_as_uint(r.w)));
    __syncwarp();
    r = make_float4(0.f, EPS2, 0.f, EPS2);
    #pragma unroll
    for (int j = 0; j < NPMAX; j++) { const float4 v = ldsf4(sa + j * 16); r.x += v.x; r.y += v.y; r.z += v.z; r.w += v.w; }
    __syncwarp();
    sts32(sa + (SM_MISC + 12 - SM_COPY), 0);
    return r;
}
__device__ __noinline__ float4* exact_copy() { return g_copy + (blockIdx.x * 12 + (threadIdx.x >> 5)) * (64 * NPMAX) + (threadIdx.x & 31); }
__device__ __noinline__ float4 exact_all(const float4* gh, int np, int dv)
{
    float4 r = make_float4(0.f, EPS2, 0.f, EPS2);
    #pragma unroll 1
    for (int j = 0; j < np; j++, gh += 32) exact_quad(gh[0], gh[32 * NPMAX], 2 * j, dv, r);
    return r;
}
template<int NP>
__device__ __forceinline__ float4 epi_exact(const float* g, const float* h, uint32_t bad, bool on, int dv, uint32_t sa, uint32_t l16) {
    uint32_t old = 1;
    if ((bad & (bad - 1)) == 0) asm volatile(ELECT "atom.shared.exch.b32 %0, [%1], 1;\n}" : "+r"(old) : "r"(sa + (SM_MISC + 12 - SM_COPY)) : "memory");
    if (__any_sync(~0u, old == 0)) {
        #pragma unroll
        for (int i = 0; i < 2 * NP; i++) {
            const float* v = i < NP ? g + 4 * i : h + 4 * (i - NP);
            asm volatile("{\n.reg .pred p;\nsetp.ne.u32 p, %5, 0;\n@p st.shared.v4.f32 [%0], {%1,%2,%3,%4};\n}"
                         :: "r"(sa + (i < NP ? i : NPMAX + i - NP) * 16), "f"(v[0]), "f"(v[1]), "f"(v[2]), "f"(v[3]), "r"((uint32_t)on) : "memory");
        }
        asm volatile("{\n.reg .pred p;\nsetp.ne.u32 p, %2, 0;\n@p st.shared.u32 [%0], %1;\n}" :: "r"(sa + 496), "r"(dv), "r"((uint32_t)on) : "memory");
        return exact_1(sa, l16);
    }
    float4* gh = exact_copy();
    #pragma unroll
    for (int i = 0; i < 2 * NP; i++) {
        const float* v = i < NP ? g + 4 * i : h + 4 * (i - NP);
        asm volatile("st.global.v4.f32 [%0], {%1,%2,%3,%4};" :: "l"(gh + (i < NP ? i : NPMAX + i - NP) * 32), "f"(v[0]), "f"(v[1]), "f"(v[2]), "f"(v[3]) : "memory");
    }
    return exact_all(gh, NP, dv);
}
__device__ __forceinline__ uint32_t row_bytes(uint32_t o) { return (o & 0xFE00) | ((o << 2) & 0x180); }

__device__ __noinline__ int balance(int step, char* gs, uint32_t id, int ng, int npb)
{
    extern __shared__ __align__(1024) uint8_t smem[];
    const uint32_t sb = smem_u32(smem), lane = threadIdx.x & 31, b = blockIdx.x, r4 = lane >> 3;
    const uint32_t tw = ((lane & 1) << 4) | ((lane & 6) << 6), ti = sb + SM_TINFO + r4 * 8, st = sb + SM_MISC + 48;
    uint32_t now; asm volatile("mov.u32 %0, %%globaltimer_lo;" : "=r"(now));
    auto put = [&](uint32_t a, uint32_t v) { if (lane == 0) asm volatile("st.relaxed.gpu.global.v2.u32 [%0], {%1, %2};" :: "l"(gs + a), "r"(v), "r"(id) : "memory"); };
    auto get = [&](uint32_t a) {
        uint2 v;
        #pragma unroll 1
        for (uint32_t n = 0; ; n++) {
            asm volatile("ld.acquire.gpu.global.v2.u32 {%0, %1}, [%2];" : "=r"(v.x), "=r"(v.y) : "l"(gs + a) : "memory");
            if (__all_sync(~0u, v.y == id)) break;
            if (n > (1u << 22)) __trap();
        }
        return v.x;
    };
    int gn = ng;
    if (step < 0) {
        if (BAL && step == -1) {
            const uint32_t e = lds32(sb + SM_TINFO + (3 * R1 + 3) * 32);
            if ((e & 0xFFFF) >= KM * 64 && ((e >> 20) & 127) < 2 && ((lds32(sb + SM_TINFO + (ng - KM) * 32 + 4) >> 16) & 15) <= 8 && lds32(sb + SM_MISC + 24) == 0) {
                if (PUBW) mbar_wait_h(sb + SM_GBAR + (PUBW - 1) * 8, 0);
                #pragma unroll 1
                for (int j = 0; j < KM; j++) {
                    const uint32_t ta = (ng - 1 - j) * 32, s0 = lds32(sb + SM_TINFO + ta) & 0xFFFF;
                    const uint2 e = lds64(ti + ta);
                    char* p = gs + G_P + (b * KM + j) * GRP_B;
                    const uint32_t ro = sb + ((e.y & 0xFFFF) ^ tw);
                    *(uint4*)(p + lane * 16) = lds128(ro + SM_TAB);
                    *(uint4*)(p + 512 + lane * 16) = lds128(ro + SM_XU);
                    *(uint2*)(p + 1024 + lane * 8) = lds64(sb + SM_EID + s0 * 4 + lane * 8);
                    *(uint32_t*)(p + 1280 + lane * 4) = lds32(sb + SM_SRC + s0 * 2 + lane * 4);
                    *(uint2*)(p + 1408 + r4 * 8) = make_uint2(e.x >> 27 ? e.x - s0 : e.x, e.y);
                }
                uint32_t c = 0;
                #pragma unroll 1
                for (int g = 3 * R1 + 3 + lane; g < ng; g += 32) c += 93 + ((lds32(sb + SM_TINFO + g * 32 + 4) >> 16) & 15) * 42;
                sts32(st, (__reduce_add_sync(~0u, c) * 595) >> 10);
                if (FEN == 1) asm volatile("fence.acq_rel.gpu;" ::: "memory");
                if (FEN == 2) __threadfence();
                __syncwarp();
                return 1;
            }
        }
        put(G_F + b * 8, (now << 6) & ~511u);
    } else if (step == R2) {
        uint2 v[5];
        #pragma unroll 1
        for (uint32_t n = 0; ; n++) {
            bool ok = true;
            #pragma unroll
            for (int i = 0; i < 5; i++) asm volatile("ld.relaxed.gpu.global.v2.u32 {%0, %1}, [%2];" : "=r"(v[i].x), "=r"(v[i].y) : "l"(gs + G_F + min(lane + 32 * i, gridDim.x - 1) * 8) : "memory");
            #pragma unroll
            for (int i = 0; i < 5; i++) ok &= v[i].y == id;
            if (__all_sync(~0u, ok)) break;
            if (n > (1u << 22)) __trap();
        }
        const uint32_t ref = __shfl_sync(~0u, v[0].x, 0) - 0x80000000u, key = ((lds32(st) - ref) & ~511u) | b;
        uint32_t c = 0;
        #pragma unroll
        for (int i = 0; i < 5; i++) if (lane + 32 * i < gridDim.x && (v[i].x & 256)) c += 0x10000 + ((((v[i].x - ref) & ~511u) | (lane + 32 * i)) < key);
        c = __reduce_add_sync(~0u, c);
        put(G_R + (c & 0xFFFF) * 8, key);
        sts64(st, key, (c >> 16) - 1 - (c & 0xFFFF));
        __syncwarp();
        return gn;
    } else {
        const uint32_t pk = get(G_R + lds32(st + 4) * 8);
        const int df = (int)(pk >> 9) - (int)(lds32(st) >> 9), m = min((abs(df) * 8 + BBIAS) / 350, KM);
        gn += df < 0 ? -m : m;
        if (gn > ng) {
            uint4 ra[KM], ru[KM]; uint2 le[KM], e[KM]; uint32_t ls[KM];
            #pragma unroll
            for (int i = 0; i < KM; i++) {
                const char* p = gs + G_P + ((pk & 255) * KM + i) * GRP_B;
                ra[i] = __ldcg((const uint4*)(p + lane * 16)); ru[i] = __ldcg((const uint4*)(p + 512 + lane * 16));
                le[i] = __ldcg((const uint2*)(p + 1024 + lane * 8)); e[i] = __ldcg((const uint2*)(p + 1408 + r4 * 8));
                ls[i] = __ldcg((const uint32_t*)(p + 1280 + lane * 4));
            }
            #pragma unroll
            for (int i = 0; i < KM; i++) {
                const int j = (m - 1 - i) & 3;
                const bool some = (e[i].y & 0xFFFF) != tab_at(NONE);
                const uint32_t row = some ? lds32(ti + i * 32 + 4) & 0xFFFF : tab_at(NONE);
                if (some) { sts128(sb + (row ^ tw) + SM_TAB, ra[i]); sts128(sb + (row ^ tw) + SM_XU, ru[i]); }
                sts64(sb + SM_EID + i * 256 + lane * 8, le[i].x, le[i].y);
                sts32(sb + SM_SRC + i * 128 + lane * 4, ls[i]);
                sts32(sb + SM_MISC + 64 + j * 16 + r4 * 4, (pk & 255) * npb * 128 + row_bytes(e[i].y & 0xFFFF));
                sts64(ti + (ng + j) * 32, ((e[i].x & 0xF800FFFFu) + i * 64) | (((e[i].y >> 16) & 15) > 5 ? 14u << 16 : 13u << 16), (e[i].y & 0xFFFF0000u) | row);
            }
            __syncwarp();
        }
        sts32(sb + SM_TINFO + gn * 32 + lane * 4, lane & 1 ? tab_at(NONE) : 0);
        sts32(sb + SM_MISC + 16, gn);
    }
    sts32(sb + SM_MISC + 28, gn);
    __syncwarp();
    if (lane == 0) mbar_arrive(sb + SM_ABAR + 32);
    return step < 0 ? 0 : gn;
}
__device__ __forceinline__ uint32_t bin_bits(uint32_t b) { return (1u << (b & 7)) | ((b < 48 ? 0x100u : 0x400u) << (b >> 3)); }
__device__ __forceinline__ void place(uint32_t sbase, uint32_t slot, uint32_t v, uint32_t eb) {
    asm volatile("{\n.reg .pred p;\nsetp.lt.u32 p, %0, %5;\n@p st.shared.u32 [%1], %2;\n@p st.shared.u16 [%3], %4;\n}"
                 :: "r"(slot), "r"(sbase + SM_EID + slot * 4), "r"(eb + (v >> 19)), "r"(sbase + SM_SRC + slot * 2), "r"(v), "n"(SLOT_CAP) : "memory");
}
__device__ __forceinline__ uint64_t desc_sw128(uint32_t a) {
    return (uint64_t)((a & 0x3FFFF) >> 4) | ((uint64_t)1 << 16) | ((uint64_t)64 << 32) | ((uint64_t)1 << 62);
}

template<bool LO32>
__global__ void __launch_bounds__(THREADS, 1)
gcn_kernel(const int* __restrict__ dst, unsigned* gbar, char* gs, const int* __restrict__ src, int E, int ch, int N, int npb, uint32_t magic,
           const __nv_bfloat16* __restrict__ x, const __nv_bfloat16* __restrict__ ea,
           const __nv_bfloat16* __restrict__ wa, const __nv_bfloat16* __restrict__ wb, const __nv_bfloat16* __restrict__ wc,
           const __nv_bfloat16* __restrict__ wu, const __nv_bfloat16* __restrict__ wv,
           __nv_bfloat16* out, int4 wrow, const __grid_constant__ CUtensorMap tm1, const __grid_constant__ CUtensorMap tm2,
           const __grid_constant__ CUtensorMap tmw, const __grid_constant__ CUtensorMap tmx)
{
    extern __shared__ __align__(1024) uint8_t smem[];
    int* cls = (int*)(smem + SM_CLS);
    int* misc = (int*)(smem + SM_MISC);
    WG0(); WS(0); CG(0);
    const uint32_t sbase = smem_u32(smem);
    const int tid = threadIdx.x, lane = tid & 31;
    const int b = blockIdx.x, nb = gridDim.x;
    const int cnt = max(0, min(ch, E - b * ch));
    const int node0 = b * npb;
    uint32_t tag = 0;
    if (tid < 384) asm volatile("ld.relaxed.gpu.global.u32 %0, [%1];" : "=r"(tag) : "l"(gbar) : "memory");
    auto dst_ld = [&](int v, uint32_t n) {
        const uint32_t off = v * (THREADS * 4) + tid * 4;
        asm volatile("{\n.reg .pred q;\nsetp.lt.u32 q, %2, %3;\n@q cp.async.cg.shared.global [%0], [%1], 16;\n}"
                     :: "r"(sbase + SM_IDX + off * 4), "l"(dst + (uint32_t)(b * ch + off)), "r"(off), "r"(n) : "memory");
    };
    dst_ld(0, min(cnt, 384 * 4));
    const int warp = (int)__reduce_max_sync(~0u, (unsigned)tid >> 5);
    const uint32_t su = __reduce_or_sync(~0u, sbase);
    if (warp >= 12) {
        const int v = warp & 3;
        const uint32_t a1 = su + SM_ABAR + (v == 0 ? 80 : v == 1 ? 120 : v == 2 ? 32 : 40);
        w_init(su + SM_ABAR + v * 8, 1); w_init(a1, 1);
        w_expect(su + SM_ABAR + v * 8, v < 3 ? min(max(cnt * 4 - v * 8192, 0), 8192) : 4 * 8192 + 2048);
        if (v < 2) w_expect(a1, v == 0 ? nb * (CE * 2) : nb * 64);
        asm volatile("fence.mbarrier_init.release.cluster;" ::: "memory");
        dst_ld(0, cnt);
    }
    #pragma unroll
    for (int v = 0; v < EPT / 4; v++) {
        if (v) {
            uint32_t c0, c1; asm volatile("mov.u32 %0, %%clock;" : "=r"(c0)); do { asm volatile("mov.u32 %0, %%clock;" : "=r"(c1)); } while (__all_sync(~0u, c1 - c0 < PD));
            dst_ld(v, cnt);
        }
        cp_commit();
    }
    if (warp == 15) {
        w_box_ld(su + SM_WR, &tmw, wrow.x, su + SM_ABAR + 24); w_box_ld(su + SM_WR + 8192, &tmw, wrow.y, su + SM_ABAR + 24);
        w_box_ld(su + SM_WR + 16384, &tmw, wrow.z, su + SM_ABAR + 24); w_ld(su + SM_WR + 24576, wc, 2048, su + SM_ABAR + 24);
        w_box_ld(su + SM_WR + 40960, &tmw, wrow.w, su + SM_ABAR + 24);
    }
    const int wg = warp >> 2, w = warp & 3;
    const int q = lane >> 2, t = lane & 3;
    const int nn = max(0, min(npb, N - node0));
    if (sbase & 1023) __trap();

    sts32(sbase + SM_DEG + tid * 4, tid < NPB_MAX ? 0 : 0x80000000u);
    if (tid < NCLS + NB_MAX) cls[tid] = tid < NCLS ? 0 : ((tid - NCLS) * 20) & 63;
    else if (warp == 8) sts32(sbase + SM_OH + lane * 4, t != (q >> 1) ? 0u : 0x00003F00u);
    else if (warp == 11) misc[lane] = lane == 5 ? TILE_CAP - TILE_X : lane == 8 || lane == 3;
    if (warp == 14) sts32(sbase + SM_TINFO + 96 * 32 + lane * 4, lane & 1 ? tab_at(NONE) : 0);
    if (warp == 15) sts32(sbase + SM_CLAIM + lane * 4, lane == 0 ? 3 * 32 : 0x40000000);
    if (tid == 0) sts32(sbase + SM_XLIST, tag);
    tag = (tag & 1) | 2;
    if (wg < 3) {
        const uint32_t d0 = ((NPB_MAX + ((2 * lane) & 15) + 16 * (b & 1)) * 4 | (tag << 14)) * 0x10001u, d1 = d0 + 0x40004u, d2 = tag << 16;
        #pragma unroll 1
        for (int i = tid; i < (P1B + 384) / 16; i += 384) {
            sts128(sbase + SM_P1 + i * 16, make_uint4(d0, d0, d1, i == P1B / 16 + 11 ? 0x80000000u | (tag << 14) : d1));
            sts128(sbase + SM_P2 + i * 16, make_uint4(d2, d2, d2, d2)); sts128(sbase + SM_P2 + P1B - 128 + i * 16, make_uint4(d2, d2, d2, d2));
        }
    }
    WS(1);
    __syncthreads();
    if (wg == 3) tag = lds32(sbase + SM_P2) >> 16;
    uint32_t all = 0;
    if (wg == 3) all = (lds32(sbase + SM_XLIST) + 1) * nb;
    if (tid == 128) {
        asm volatile("prefetch.tensormap [%0];" :: "l"((uint64_t)&tm1) : "memory");
        asm volatile("prefetch.tensormap [%0];" :: "l"((uint64_t)&tm2) : "memory");
        asm volatile("prefetch.tensormap [%0];" :: "l"((uint64_t)&tmx) : "memory");
    }
    const uint32_t m4 = __reduce_or_sync(~0u, -4 * npb);
    uint32_t ent[EPT];
    #pragma unroll
    for (int v = 0; v < EPT / 4; v++) {
        if (v == 0) cp_wait<2>(); else if (v == 1) cp_wait<1>(); else cp_wait<0>();
        if (v == 0 && wg == 2 && w < 3) {
            const int n = min(cnt * 4 - w * 8192, 8192);
            if (n > 0) w_ld(su + SM_XU + w * 8192, src + b * ch + w * 2048, n, su + SM_ABAR + w * 8);
        }
        const uint32_t off = v * (THREADS * 4) + tid * 4;
        if (off < (uint32_t)cnt) {
            const uint4 u = lds128(sbase + SM_IDX + off * 4);
            uint32_t dv[4] = {u.x, u.y, u.z, u.w}, ps[4], ck[4];
            uint32_t* en = ent + 4 * v;
            #pragma unroll
            for (int k = 0; k < 4; k++) {
                dv[k] = min(dv[k], (uint32_t)(nb * npb - 1));
                ps[k] = __umulhi(dv[k], magic);
                asm volatile("atom.shared.add.u32 %0, [%1], 0x10001;" : "=r"(ck[k]) : "r"(sbase + SM_HIST + ps[k] * 4) : "memory");
            }
            #pragma unroll
            for (int k = 0; k < 4; k++) {
                dv[k] = ps[k] * m4 + (dv[k] * 4 + (tag << 14));
                en[k] = (ck[k] & 63) + ps[k] * CE;
            }
            if (__builtin_expect(max(max(ck[0], ck[1]), max(ck[2], ck[3])) >= CE << 16, 0)) {
                auto step = [&]() {
                    uint32_t e = en[0];
                    const uint32_t d = dv[0];
                    if (ck[0] >= CE << 16) {
                        uint32_t j; asm volatile("atom.shared.inc.u32 %0, [%1], 0x7fffffff;" : "=r"(j) : "r"(sbase + SM_MISC + 8) : "memory");
                        j = min(j + (j >= 15), 63u);
                        sts32(sbase + SM_L1 + j * 4, d | ((j < 63 ? e / CE : 255u) << 16));
                        e = NB_MAX * CE + j;
                    }
                    en[0] = en[1]; en[1] = en[2]; en[2] = en[3]; en[3] = e;
                    dv[0] = dv[1]; dv[1] = dv[2]; dv[2] = dv[3]; dv[3] = d;
                    ck[0] = ck[1]; ck[1] = ck[2]; ck[2] = ck[3];
                };
                if (v == 2) { step(); step(); step(); step(); }
                else {
                    #pragma unroll 1
                    for (int k = 0; k < 4; k++) step();
                }
            }
            #pragma unroll
            for (int k = 0; k < 4; k++)
                asm volatile("st.shared.u16 [%0], %1;" :: "r"(sbase + SM_P1 + en[k] * 2), "r"(dv[k]) : "memory");
        }
    }
    if (warp == 15) {
        #pragma unroll
        for (int v = 0; v < EPT / 4; v++) sts128(sbase + SM_ENT + v * 512 + lane * 16, make_uint4(ent[4*v], ent[4*v+1], ent[4*v+2], ent[4*v+3]));
    }
    asm volatile("fence.proxy.async.shared::cta;" ::: "memory");
    WS(5);
    __syncthreads();
    if (warp == 15) {
        w_inc(gbar + 1);
        const uint32_t n = __reduce_or_sync(~0u, lds32(su + SM_MISC + 8));
        if (__builtin_expect(n > 15, 0)) {
            const uint2 r = lds64(su + SM_L1 + lane * 8);
            uint32_t m = lane < 8 ? 0 : (r.x >> 24 ? 0 : bin_bits(r.x >> 16)) | (r.y >> 24 ? 0 : bin_bits(r.y >> 16));
            m = n > 62 ? 0x7FFF3FFFu : __reduce_or_sync(~0u, m);
            sts32(su + SM_L1 + 60, m | 0x80000000u | (tag << 14));
            asm volatile("fence.proxy.async.shared::cta;" ::: "memory");
            __syncwarp();
        }
        w_st(gs + G_H1 + b * 64, su + SM_L1, 64);
        w_box_st(&tm1, b * (CE / 2), su + SM_P1);
        w_st(gs + G_L + b * 512, su + SM_L1, 256);
        asm volatile("cp.async.bulk.commit_group;" ::: "memory");
    } else {
        mbar_wait_c(su + SM_ABAR, 0);
        auto put = [&](uint32_t off, const uint32_t* uu) {
            if (off < (uint32_t)cnt) {
                const uint4 sv = lds128(sbase + SM_XU + off * 4);
                const uint32_t ss[4] = {sv.x, sv.y, sv.z, sv.w};
                #pragma unroll
                for (int k = 0; k < 4; k++) sts32(sbase + SM_P2 + uu[k] * 4, (ss[k] & 0xFFFF) | (((off + k) << 19) + (tag << 16)));
            }
        };
        #pragma unroll
        for (int v = 0; v < EPT / 4; v++) { if (v) mbar_wait_c(su + SM_ABAR + v * 8, 0); put(v * (THREADS * 4) + tid * 4, ent + 4 * v); }
        if (wg == 3) {
            const uint4 e = lds128(sbase + SM_ENT + w * 512 + lane * 16);
            const uint32_t uu[4] = {e.x, e.y, e.z, e.w};
            put(w * (THREADS * 4) + (480 + lane) * 4, uu);
        }
        asm volatile("fence.proxy.async.shared::cta;" ::: "memory");
        WS(7);
        __syncwarp();
        asm volatile("bar.arrive 12, 512;" ::: "memory");
    }
    WS(8);

    const int ngroups = (nn + 3) >> 2;
    if (warp < 12) {
        asm volatile("setmaxnreg.inc.sync.aligned.u32 152;");
        const uint32_t ab = su + SM_ABAR;
        uint32_t wf[40], wn[16];
        const uint32_t mo = sbase + (8 * (lane >> 4) + (lane & 7)) * 128 + (((2 * w + ((lane >> 3) & 1)) ^ (lane & 7)) << 4);
        const uint32_t wca = __shfl_sync(~0u, sbase + SM_WC + (16 * w + q) * 32 + t * 4 + ((q >> 2) << 4), lane), l16 = __shfl_sync(~0u, (lane & 15) * 16, lane);
        if (WARMX && warp == 11) {
            const float4 r = exact_1(su + SM_COPY, l16);
            sts32(su + SM_MISC + 12, 1 | (__float_as_uint(r.x + r.y + r.z + r.w) & 2));
        }
        mbar_wait_c(ab + 24, 0);
        {
            #pragma unroll
            for (int ks = 0; ks < 4; ks++) { ldsm4t(wf + 4 * ks, mo + SM_WR + ks * 2048); ldsm4t(wf + 20 + 4 * ks, mo + SM_WR + 8192 + ks * 2048); ldsm4t(wn + 4 * ks, mo + SM_WR + 16384 + ks * 2048); }
            auto half = [](uint32_t& v) { asm("mul.rn.bf16x2 %0, %0, %1;" : "+r"(v) : "r"(0x3F003F00u)); };
            uint32_t z = 0;
            #pragma unroll
            for (int i = 0; i < 16; i++) { half(wf[i]); z ^= wf[i]; }
            sts32(sbase + SM_ES + lane * 4, z);
            if (wg == 2) {
                uint32_t f[4];
                ldsm4t(f, (mo ^ ((lane & 7) << 4)) + SM_WR + 24576);
                half(f[0]); half(f[1]); half(f[2]); half(f[3]);
                sts32(wca, f[0]); sts32(wca + 256, f[1]); sts32(wca ^ 16, f[2]); sts32((wca ^ 16) + 256, f[3]);
                asm volatile("fence.proxy.async.shared::cta;" ::: "memory");
            }
        }
        const uint64_t wcd = __reduce_or_sync(~0u, (((sbase + SM_WC) & 0x3FFFF) >> 4) | (8u << 16)) | EDHI;
        const uint32_t bar0 = __reduce_or_sync(~0u, sbase + SM_BARS + wg * 2 * STG);
        const uint32_t xd0 = __reduce_or_sync(~0u, (((sbase + SM_XS + wg * NSTAGE * XS_BYTES) & 0x3FFFF) >> 4) | (1u << 16));
        const uint32_t ed0 = __reduce_or_sync(~0u, (((sbase + SM_ES + wg * NSTAGE * ES_BYTES) & 0x3FFFF) >> 4) | (8u << 16));
        const uint64_t ohd = __reduce_or_sync(~0u, ((sbase + SM_OH) & 0x3FFFF) >> 4);
        const uint32_t tabx = __reduce_or_sync(~0u, sbase + SM_TAB + w * 128);
        const uint32_t bars = __reduce_or_sync(~0u, 2 * bar0 + STG), xds = __reduce_or_sync(~0u, 2 * xd0 + XS_BYTES / 16), eds = __reduce_or_sync(~0u, 2 * ed0 + ES_BYTES / 16);
        const uint32_t xuo = __reduce_or_sync(~0u, sbase + SM_XU + wg * 16384);
        { const uint2 z = lds64(sbase + SM_OH + 8); wf[38] = z.x; wf[39] = z.y; }
        WS(9);
        constexpr int NU = 6;
        const uint32_t dm = ((NPB_MAX + lane) * 4 | (tag << 14)) * 0x10001u;
        const uint32_t db = sbase + SM_DEG - (tag << 14);
        const char* const g1 = gs + (uint32_t)(b * (P1B + P2B) + tid * 8);
        int rk[NU][4];
        uint32_t spins = 0;
        {
            uint2 r1[NU];
            mbar_wait_c(ab + 80, 0);
            WS(2);
            #pragma unroll
            for (int i = 0; i < NU; i++) {
                r1[i] = make_uint2(dm, dm);
                if (NB_MIN * 16 >= 384 * (i + 1) || tid + 384 * i < nb * 16) r1[i] = lds64(sbase + SM_IDX + (tid + 384 * i) * 8);
            }
            #pragma unroll 1
            while (true) {
                uint32_t bad = 0;
                #pragma unroll
                for (int i = 0; i < NU; i++) bad |= r1[i].y ^ dm;
                if (__builtin_expect(!__any_sync(~0u, bad & 0xC000), 1)) break;
                #pragma unroll
                for (int i = 0; i < NU; i++) ld_unit(r1[i], g1 + 384 * 8 * i, (r1[i].y ^ dm) & 0xC000);
                if (++spins > (1u << 22)) break;
            }
            WS(3);
            #pragma unroll
            for (int i = 0; i < NU; i++) {
                rk[i][0] = r1[i].x & 0xFFFF; rk[i][1] = r1[i].x >> 16; rk[i][2] = r1[i].y & 0xFFFF; rk[i][3] = r1[i].y >> 16;
                #pragma unroll
                for (int k = 0; k < 4; k++) asm volatile("red.shared.add.u32 [%0], 1;" :: "r"(db + min((uint32_t)rk[i][k], NPB_MAX * 4 + (tag << 14))) : "memory");
            }
        }
        WS(10);
        asm volatile("bar.sync 11, 512;" ::: "memory");
        int mycls = 0, mycr = 0, dg = lds32(sbase + SM_DEG + tid * 4);
        if (tid < nn) {
            mycls = NCLS - 1 - (dg <= 40 ? dg : min(41 + ((dg - 41) >> 3), NCLS - 1)); mycr = atomicAdd(&cls[mycls], 1);
        }
        int s0 = 0;
        if (__builtin_expect(dg > 40, 0)) s0 = max(SLOT_CAP - ((dg + 1) & ~1) - atomicAdd(&misc[6], (dg + 1) & ~1), 0);
        asm volatile("bar.sync 1, 384;" ::: "memory");
        WS(12);
        {
            const uint2 c = lds64(sbase + SM_CLS + lane * 8);
            const int v0 = c.x * (lane > 11 ? ((64 - 2 * lane) << 16) + 1 : 1), v1 = c.y * (lane >= 11 ? ((62 - 2 * lane) << 16) + 1 : 1);
            int inc = v0 + v1;
            #pragma unroll
            for (int o = 1; o < 32; o <<= 1) { int y = __shfl_up_sync(~0u, inc, o); if (lane >= o) inc += y; }
            const int e0 = __shfl_sync(~0u, inc - v0 - v1, mycls >> 1), e1 = __shfl_sync(~0u, inc - v1, mycls >> 1);
            const int e = (mycls & 1) ? e1 : e0;
            if (tid < nn) {
                if (dg <= 40) s0 = min((e >> 16) + mycr * ((dg + 1) & ~1), SLOT_CAP - 40);
                sts32(sbase + SM_DEG + tid * 4, s0);
            }
            const uint32_t pos = tid < nn ? (e & 0xFFFF) + mycr : tid;
            sts32(sbase + SM_SORT + pos * 4, tid < nn ? (uint32_t)tid | ((uint32_t)s0 << 16) : NONE);
            asm volatile("st.shared.u16 [%0], %1;" :: "r"(sbase + SM_SDEG + pos * 2), "r"(min(dg, 65535)) : "memory");
            if (tid == 383) { misc[4] = (nn - c.y + 3) >> 2; if ((inc >> 16) + misc[6] > SLOT_CAP - 40) misc[1] = 1; }
        }
        asm volatile("bar.sync 1, 384;" ::: "memory");
        WS(13);
        const uint32_t sv = lds32(sbase + SM_SORT + tid * 4);
        const uint2 d4 = lds64(sbase + SM_SDEG + (tid >> 2) * 8);
        const uint32_t slow = lds32(sbase + SM_MISC + 4);
        #pragma unroll
        for (int i = 0; i < NU; i++) {
            #pragma unroll
            for (int k = 0; k < 4; k++) rk[i][k] = atoms_inc(db + rk[i][k]);
        }
        if (__reduce_or_sync(~0u, slow) == 0) {
            const uint32_t nd = sv & 0xFFFF;
            const int g = tid >> 2;
            dg = ((t & 2 ? d4.y : d4.x) >> (16 * (t & 1))) & 0xFFFF;
            const uint32_t hi2 = __vmaxu2(d4.x, d4.y), lo2 = __vminu2(d4.x, d4.y);
            const int mx = max(hi2 >> 16, hi2 & 0xFFFF), mn = min(lo2 >> 16, lo2 & 0xFFFF);
            int left = (mx + 1) >> 1;
            int tl = g, nx = ngroups + 4 + g, nt = left > NPMAX ? 2 : 1;
            const bool odd = left > 2 * NPMAX || (nt == 2 && nx >= TILE_CAP - TILE_X);
            if (__builtin_expect(__any_sync(~0u, odd), 0)) {
                if (odd) nt = (left + NPMAX - 1) / NPMAX;
                if (odd && t == 0) { asm volatile("atom.shared.add.u32 %0, [%1], %2;" : "=r"(nx) : "r"(sbase + SM_MISC + 20), "r"(nt - 1) : "memory"); if (nx + nt - 1 > TILE_CAP) misc[1] = 1; }
                nx = __shfl_sync(~0u, nx, lane & ~3);
                if (odd && nx + nt - 1 > TILE_CAP) left = 0;
            }
            const uint32_t w0 = tab_at(nd);
            if (g >= ngroups + 4) tl = ngroups;
            uint32_t cont = 0;
            int done = 0;
            bool act = true;
            do {
                int np = nt <= 2 ? (left + nt - 1) >> (nt - 1) : (left + nt - 1) / nt;
                left -= np; nt = max(nt - 1, 1);
                if (np) np = max(np, NPMIN);
                const int dv = min(max(dg - done, 0), 2 * np);
                uint32_t code = (uint32_t)np | cont | (left > 0 ? C_MORE : 0u);
                const bool gen = mn - done < 2 * np - (np == NPMIN ? 1 : 2);
                if (np == 0) code = 0;
                const uint32_t w1 = code | (dv == 2 * np ? 0x8000u : (2 * np - 1 - dv) << 8);
                if (act) *(uint2*)(smem + SM_TINFO + tl * 32 + t * 8) = make_uint2((dv ? (sv >> 16) + done : 0) | ((gen ? (np > 8 ? 15 : np > 5 ? 14 : 13) : np) << 16) | ((left > 0 ? nx : g >= ngroups - (KM + 3)) << 20) | ((uint32_t)dv << 27), w0 | (np == 0 ? 0u : w1 << 16));
                tl = nx++; cont = C_CONT; done += 2 * np; act = left > 0;
            } while (__any_sync(~0u, act));
        }
        __syncwarp();
        asm volatile("bar.arrive 4, 512;" ::: "memory");
        WS(14);
        wf[16] = lds32(wca); wf[17] = lds32(wca + 256); wf[18] = lds32(wca ^ 16); wf[19] = lds32((wca ^ 16) + 256);
        #pragma unroll
        for (int pc = 0; pc < 3; pc++) {
            uint4 r2[2];
            mbar_wait_c(ab + pc * 8, 1);
            if (pc == 0) WS(4); if (pc == 2) WS(16);
            #pragma unroll
            for (int k = 0; k < 2; k++) {
                r2[k] = lds128(sbase + SM_P2 + (tid + 384 * (2 * pc + k)) * 16);
                if (rk[2 * pc + k][0] < 0) r2[k].w = tag << 16;
            }
            while (__builtin_expect(__any_sync(~0u, ((r2[0].w ^ (tag << 16)) | (r2[1].w ^ (tag << 16))) & 0x30000), 0)) {
                #pragma unroll
                for (int k = 0; k < 2; k++)
                    ld_unit(r2[k], g1 + (uint32_t)(tid * 8) + (P1B + 384 * 16 * (2 * pc + k)), (r2[k].w ^ (tag << 16)) & 0x30000);
                if (++spins > (1u << 22)) break;
            }
            #pragma unroll
            for (int k = 0; k < 2; k++) {
                const int i = 2 * pc + k;
                const uint32_t eb = ((tid >> 4) + 24 * i) * ch;
                place(sbase, rk[i][0], r2[k].x, eb); place(sbase, rk[i][1], r2[k].y, eb); place(sbase, rk[i][2], r2[k].z, eb); place(sbase, rk[i][3], r2[k].w, eb);
            }
        }
        WGD();
        __syncwarp();
        asm volatile("bar.arrive 3, 480;" ::: "memory");
        float g[4 * NPMAX], h[4 * NPMAX];
        float4 cyr = make_float4(0.f, 0.f, 0.f, 0.f);
        WS(15); CG(1);
        mbar_wait_c(ab + 88 + wg * 8, 0);
        auto pack = [&](uint32_t* v, const float* u) {
            #pragma unroll
            for (int i = 0; i < 16; i++) v[i] = pack_bf16(u[2*i], u[2*i+1]);
        };
        auto rows_st = [&](uint32_t p, const uint32_t* v) {
            #pragma unroll
            for (int i = 0; i < 4; i++) stsm4t(p + i * 2048, v + 4 * i);
        };
        {
            const uint64_t d0 = desc_sw128(xuo), d1 = d0 + 512;
            const uint32_t mr = sbase + wg * 16384 + w * 128 + (tab_at(8 * (lane >> 4) + (lane & 7)) ^ ((lane & 8) << 1));
            uint32_t v[16];
            node_mma(g, wn, d0); node_mma(h, wn, d1);
            TileMMA<8>::wait_g(g);
            pack(v, g); rows_st(mr + SM_TAB, v);
            TileMMA<8>::wait_h(h);
            #pragma unroll
            for (int ks = 0; ks < 4; ks++) ldsm4t(wn + 4 * ks, mo + SM_WR + 40960 + ks * 2048);
            node_mma(g, wn, d0);
            if (wg == 2) asm volatile("bar.sync 5, 384;" ::: "memory"); else asm volatile("bar.arrive 5, 384;" ::: "memory");
            pack(v, h); rows_st(mr + SM_TAB + 8192, v);
            node_mma(h, wn, d1);
            __syncwarp();
            if (lane == 0) mbar_arrive(sbase + SM_ABAR + 112);
            TileMMA<8>::wait_g(g);
            pack(v, g);
            asm volatile("bar.sync %0, 128;" :: "r"(8 + wg) : "memory");
            rows_st(mr + SM_XU, v);
            TileMMA<8>::wait_h(h);
            pack(v, h);
            asm volatile("bar.sync %0, 128;" :: "r"(8 + wg) : "memory");
            rows_st(mr + SM_XU + 8192, v);
            __syncwarp();
            if (lane == 0) mbar_arrive(sbase + SM_ABAR + 72);
            mbar_wait_c(ab + 112, 0);
            __syncwarp();
            if (__builtin_expect(__reduce_or_sync(~0u, misc[1]) != 0, 0)) { slow_bin(x, ea, src, dst, wa, wb, wc, wu, wv, out, E, node0, nn, 384); asm volatile("exit;"); }
            WS(6);
        }
        uint32_t bar = bar0, xd = xd0, ed = ed0, ph = 0;
        float pn0 = 0.f, pd0 = 1.f, pn1 = 0.f, pd1 = 1.f;
        uint4 rc;
        rc.x = lds32(sbase + SM_TINFO + wg * 32 + ((lane >> 1) & 3) * 8 + 4);
        uint32_t code = __reduce_or_sync(~0u, rc.x >> 16);
        rc.x = (rc.x & 0xFFFF) ^ ((lane & 8) << 1);
        uint32_t pst = tabx + tab_at(NONE);
        auto fetch_a = [&]() {
            asm volatile("ldmatrix.sync.aligned.m8n8.x2.trans.shared.b16 {%0,%1}, [%2];" : "=r"(wf[36]), "=r"(wf[37]) : "r"(tabx + rc.x) : "memory");
        };
        auto emit = [&]() {
            asm volatile("stmatrix.sync.aligned.m8n8.x1.trans.shared.b16 [%0], {%1};" :: "r"(pst), "r"(pack_bf16(pn0 * rcpf(pd0), pn1 * rcpf(pd1))) : "memory");
        };
        auto carry = [&]() {
            if (rc.z & C_CONT) { pn0 += cyr.x; pd0 += cyr.y; pn1 += cyr.z; pd1 += cyr.w; }
            if (rc.z & C_MORE) { cyr = make_float4(pn0, pd0 - EPS2, pn1, pd1 - EPS2); pn0 = pn1 = 0.f; pst = tabx + tab_at(NONE); }
        };
        fetch_a();
        while (true) {
            switch (code & 15) {
                default: goto finished;
#define TILE(P) { \
                    bool ok; float dmin; \
                    do { \
                        mbar_wait_c(bar, ph); \
                        TileMMA<P>::issue(g, h, wf, xd, ed | EDHI, ohd, wcd); \
                        const uint32_t eb = bar + 8; \
                        ph ^= bar != bar0; bar = bars - bar; xd = xds - xd; ed = eds - ed; \
                          \
                        asm volatile("{\n.reg .pred p;\nsetp.eq.u32 p, %0, 77;\n@p trap;\n}" :: "r"(xds) : "memory"); \
                        emit(); rc = lds128(eb + 8 + l16); \
                        TileMMA<P>::wait_g(g); fetch_a(); TileMMA<P>::wait_h(h); \
                        mbar_arrive(eb); \
                        asm volatile("add.u32 %0, %1, %2;" : "=r"(pst) : "r"(rc.y), "r"(tabx)); \
                        ok = epi_fast<P>(g, h, __uint_as_float(rc.z), __uint_as_float(rc.w), pn0, pd0, pn1, pd1, dmin); \
                    } while (__all_sync(~0u, ok)); \
                    code = __reduce_or_sync(~0u, rc.w); \
                    if (__builtin_expect(__any_sync(~0u, ((rc.z & 0x1F00) != 0) | (dmin < TAU * 2 * P)), 0)) { \
                        int dv; \
                        const bool on = unpad(rc.z, P, g[4 * P - 4], g[4 * P - 2], pd0, pd1, dv); \
                        const uint32_t bad = __ballot_sync(~0u, on); \
                        if (__builtin_expect(bad != 0, 0)) { \
                            const float4 r = epi_exact<P>(g, h, bad, on, dv, su + SM_COPY, l16); \
                            if (on) { pn0 = r.x; pd0 = r.y; pn1 = r.z; pd1 = r.w; } \
                        } \
                    } \
                    if (code & C_BRK) { carry(); if (P != 11 && (code & 15) == P) goto L##P; } \
                    if (P == 11) {         \
                        wf[16] = lds32(wca); wf[17] = lds32(wca + 256); wf[18] = lds32(wca ^ 16); wf[19] = lds32((wca ^ 16) + 256); \
                    } }
#define CASE(P, UP, DN) case P: L##P: TILE(P) \
                    if (P > NPMIN && (code & 15) == P - 1) goto L##DN; \
                    if ((code & 15) == UP) goto L##UP; \
                    break;
                CASE(11, 11, 10) CASE(10, 11, 9) CASE(9, 10, 8) CASE(8, 9, 7) CASE(7, 8, 6) CASE(6, 7, 5) CASE(5, 6, 5)
#undef CASE
#undef TILE
            }
        }
finished:
        emit();
        __syncwarp();
        if (lane == 0) mbar_arrive(sbase + SM_ABAR + 48 + wg * 8);
    } else {
        asm volatile("setmaxnreg.dec.sync.aligned.u32 56;");
        auto x_ld = [&](int i0, int i1) {
            #pragma unroll
            for (int i = i0; i < i1; i++) w_box_ld(su + SM_XU + i * 8192, &tmx, node0 + i * 64, su + SM_ABAR + 88 + (i >> 1) * 8);
        };
        if (w < 3) {
            #pragma unroll
            for (int i = 0; i < 2; i++) { w_init(su + SM_BARS + (w * 2 + i) * STG, 64); w_init(su + SM_BARS + (w * 2 + i) * STG + 8, 128); }
            w_init(su + SM_ABAR + 48 + w * 8, 4);
            w_init(su + (w == 0 ? SM_GBAR + 99 * 8 : w == 1 ? SM_ABAR + 72 : SM_ABAR + 112), w == 0 ? 32 : 12);
        } else {
            #pragma unroll
            for (int i = 0; i < 4; i++) { w_init(su + SM_ABAR + (i < 3 ? 88 + i * 8 : 40), 1); w_expect(su + SM_ABAR + (i < 3 ? 88 + i * 8 : 40), i < 3 ? 16384 : nb * 64); }
            asm volatile("fence.mbarrier_init.release.cluster;" ::: "memory");
            w_hint(gbar + 1, all);
            asm volatile("cp.async.bulk.wait_group.read 0;" ::: "memory");
            WS(2);
            w_ld(su + SM_IDX, gs + b * (P1B + P2B), nb * (CE * 2), su + SM_ABAR + 80);
            w_ld(su + SM_H1, gs + G_H1, nb * 64, su + SM_ABAR + 120);
            asm volatile("bar.sync 12, 512;" ::: "memory");
            w_box_st(&tm2, P1B / 4 + b * CE, su + SM_P2);
            w_st(gs + G_H2 + b * 64, su + SM_P2 + P2B, 64);
            w_st(gs + G_L + b * 512 + 256, su + SM_P2 + P2B, 256);
            w_sent(gbar + 4, su + SM_MISC + 32);
            asm volatile("cp.async.bulk.commit_group;" ::: "memory");
        }
        const uint32_t ab = su + SM_ABAR;
        uint32_t todo = 0;
        const uint32_t mb = (lane & 3) == 3 ? bin_bits(b) : ~0u;
        WS(12);
        mbar_wait_c(ab + 120, 0);
        WS(13);
        {
            uint4 r[5];
            #pragma unroll
            for (int i = 0; i < 5; i++) r[i] = lds128(sbase + SM_H1 + (tid - 384 + 128 * i) * 16);
            #pragma unroll
            for (int i = 0; i < 5; i++) {
                const uint32_t bb = b << 16;
                const uint32_t m = min(min(r[i].x ^ bb, r[i].y ^ bb), min(r[i].z ^ bb, r[i].w ^ bb)) >> 16;
                if ((m == 0) | (((r[i].w ^ (tag << 14)) & 0xC000) != 0) | ((~r[i].w & mb) == 0)) todo |= 1 << i;
            }
            todo &= tid - 384 + 512 < nb * 4 ? 31 : tid - 384 + 384 < nb * 4 ? 15 : 7;
        }
        #pragma unroll 1
        for (int put = 0; put < 2; put++) {
            uint32_t any = __reduce_or_sync(~0u, todo), m = 0, u = 0;
            #pragma unroll 1
            while (any | m) {
                uint4 r = make_uint4(0, 0, 0, 0), r2 = r;
                uint32_t s, go, gd;
                bool on;
                if (__builtin_expect(m == 0, 1)) {
                    const uint32_t i = __ffs(any) - 1;
                    any &= any - 1; u = tid - 384 + 128 * i; on = (todo >> i) & 1;
                    r = lds128(sbase + SM_H1 + u * 16); r2 = lds128(sbase + SM_H2 + u * 16);
                    s = u >> 2; go = G_H1 + u * 16; gd = HB;
                } else {
                    s = ((u & ~31) + __ffs(m) - 1) >> 2; m &= m - 1; on = lane < 12;
                    go = G_L + s * 512 + 64 + lane * 16; gd = 256;
                }
                #pragma unroll 1
                for (int n = 0; n < (1 << 22); n++) {
                    const bool b1 = on && ((r.w >> 14) & 3) != tag, b2 = on && put && ((r2.w >> 16) & 3) != tag;
                    if (__builtin_expect(!__any_sync(~0u, b1 | b2), 1)) break;
                    ld_unit(r, gs + go, b1); ld_unit(r2, gs + go + gd, b2);
                }
                if (gd == HB) m = __ballot_sync(~0u, on && (~r.w & mb) == 0);
                if (on && r.w >> 16 == 255) sts32(sbase + SM_MISC + 4, 1);
                const uint32_t e[4] = {r.x, r.y, r.z, r.w}, v[4] = {r2.x, r2.y, r2.z, r2.w};
                uint32_t slot[4];
                #pragma unroll
                for (int k = 0; k < 4; k++) slot[k] = atoms_inc(sbase + SM_DEG + (on && e[k] >> 16 == (uint32_t)b ? (e[k] & 0x3FFF) : (NPB_MAX + lane) * 4));
                if (put) {
                    #pragma unroll
                    for (int k = 0; k < 4; k++) place(sbase, slot[k], v[k], s * ch);
                }
            }
            if (put == 0) {
                WS(4);
                asm volatile("bar.arrive 11, 512;" ::: "memory");
                if (w == 3) {
                    x_ld(0, 1);
                    w_expect(su + SM_ABAR, 12288); w_expect(su + SM_ABAR + 8, 12288); w_expect(su + SM_ABAR + 16, nb * (CE * 4) - 24576);
                    w_hint(gbar + 4, all);
                    asm volatile("cp.async.bulk.wait_group.read 0;" ::: "memory");
                    WS(3);
                    const char* g2 = gs + b * (P1B + P2B) + P1B;
                    w_ld(su + SM_P2, g2, 12288, su + SM_ABAR);
                    w_ld(su + SM_P2 + 12288, g2 + 12288, 12288, su + SM_ABAR + 8);
                    w_ld(su + SM_P2 + 24576, g2 + 24576, nb * (CE * 4) - 24576, su + SM_ABAR + 16);
                    w_ld(su + SM_H2, gs + G_H2, nb * 64, su + SM_ABAR + 40);
                    x_ld(1, XM);
                    mbar_wait_c(ab, 1); x_ld(XM, XN);
                    if (XN < 6) { mbar_wait_c(ab + XP * 8, 1); x_ld(XN, 6); }
                } else {
                    #pragma unroll 11
                    for (int i = 0; i < 33; i++) w_init(su + SM_GBAR + (w * 33 + i) * 8, 32);
                    w_init(su + SM_GBAR + GD * 8, 32);
                }
                asm volatile("bar.sync 4, 512;" ::: "memory");
                mbar_wait_c(ab + 40, 0);
            }
        }
        __syncwarp();
        WS(10);
        WGD();
        const uint32_t scr = sbase + SM_PAIR + (tid & 127) * 8;
        const int r4 = lane >> 3, c8 = lane & 7;
        const uint32_t sb = su;
        const uint32_t tk = ((c8 & 1) << 4) | ((c8 >> 1) << 7);
        if (w < 3) {
            const char* gx = as_pair((const char*)x + c8 * 16, scr);
            const char* ge = as_pair((const char*)ea + (lane & 1) * 16, scr);
            const uint32_t gx0 = (uint32_t)(uint64_t)gx, ge0 = (uint32_t)(uint64_t)ge, hi = (uint64_t)gx >> 32, he = (uint64_t)ge >> 32;
            const int s = (lane >> 1) & 3;
            const uint32_t xs0 = sb + SM_XS + w * NSTAGE * XS_BYTES;
            const uint32_t es0 = sb + SM_ES + w * NSTAGE * ES_BYTES + r4 * 64 + (((lane ^ (r4 >> 1)) & 1) << 4) + (s >> 1) * 256 + (s & 1) * 32;
            const uint32_t bars = sb + SM_BARS + w * 2 * STG;
            const uint32_t xoffA = (2 * r4) * 128 + ((c8 ^ (2 * r4)) << 4);
            uint64_t pol;
            asm volatile("createpolicy.fractional.L2::evict_first.b64 %0, 1.0;" : "=l"(pol));
            asm volatile("bar.sync 6, 128;" ::: "memory");
            WS(15);
            uint32_t ph = 1, cur = w;
            uint32_t hist = GD * 0x010101u;
            auto done3 = [&]() { uint32_t v = (hist >> 16) & 0xFF; asm("" : "+r"(v)); mbar_arrive(sb + SM_GBAR + v * 8); };
            const bool go = __reduce_or_sync(~0u, misc[1] == 0 && nn > 0);
            const uint32_t ra = __shfl_sync(~0u, (lane & 15) * 16 + 32, lane), k15 = __shfl_sync(~0u, 15 | (lane & 1) << 7, lane), ca = SM_CLAIM + min(lane, 30) * 4, pa = sb + SM_TINFO + r4 * 8;
            const uint32_t pb = sb + SM_TINFO + s * 8 + 4, pc = sb + SM_TINFO + (lane & 3) * 8 + 6, xl = (lane & 8) << 1, xs = ra & 16;
            auto row_of = [&](uint32_t o) { uint32_t v; asm volatile("ld.shared.u16 %0, [%1];" : "=r"(v) : "r"(pb + o) : "memory"); return v; };
            auto code_of = [&](uint32_t o) { uint32_t v; asm volatile("ld.shared.s16 %0, [%1];" : "=r"(v) : "r"(pc + o) : "memory"); return v; };
            uint32_t pw = lds32(pa + w * 32), pt = __reduce_or_sync(~0u, pw), cont = 1;
            uint4 rc = make_uint4(0, row_of(w * 32) ^ xs, code_of(w * 32) & (ONE_F | 0x1FFFu), 0);
            const uint32_t se0 = sb + SM_EID + s * 4, brs = 2 * bars + STG;
            uint32_t br = bars, da = xs0 + xoffA, de = es0, ue = ES_BYTES;
            #pragma unroll 1
            while (go) {
                uint32_t se, sx;
                asm("dp2a.lo.u32.u32 %0, %1, 4, %2;" : "=r"(se) : "r"(pw), "r"(se0));
                asm("dp2a.lo.u32.u32 %0, %1, 2, %2;" : "=r"(sx) : "r"(pw), "r"(sb + SM_SRC));
                const int dv = pw >> 27, ds = DVS ? dv - s : dv, s1 = DVS ? 0 : s;
                const uint32_t db = da ^ 0x90;
                const uint32_t sel = (pt >> 16) & 15, nf = (pt >> 15) & (127 << 5), nx = nf == 32 ? 0u : nf;
                uint32_t g;
                auto claim = [&]() { asm volatile("atom.shared.add.u32 %0, [%1], %2;" : "=r"(g) : "r"(ca + (nx == 0 ? sb : sb + 4)), "r"(ra) : "memory"); };
                if (sel == 0) break;
                if ((cont & 1) | (nf ^ nx)) {
                    if (cont & 1) asm volatile("bar.sync 3, 480;" ::: "memory");
                    if (nf != nx) mbar_wait_c(sb + SM_ABAR + 32, 0);
                }
                switch (sel) {
#define CASE(L, P, GEN) case L: { \
                        uint32_t oe[(P + 1) / 2], o[P]; \
                        _Pragma("unroll") for (int j = 0; j < (P + 1) / 2; j++) oe[j] = lds32(se + j * 16); \
                        _Pragma("unroll") for (int j = 0; j < P; j++) o[j] = lds32(sx + j * 4); \
                        mbar_wait_h(br + 8, ph); \
                        _Pragma("unroll") for (int j = 0; j < (P + 1) / 2; j++) \
                            if (LO32) { if (!GEN && 2 * j + 2 < P) cpe<false>(he, de + j * 512, oe[j], ge0, 0, 0, pol); \
                                else if (2 * j + 1 < NPMAX || s < 2) cpe<true>(he, de + j * 512, oe[j], ge0, 4 * j + s1, ds, pol); } \
                            else if (!GEN && 2 * j + 2 < P) cp16e(de + j * 512, ge, oe[j], pol); else if (2 * j + 1 < NPMAX || s < 2) cp16z<32>(de + j * 512, ge, oe[j], 4 * j + s1, ds, pol); \
                        _Pragma("unroll") for (int j = 0; j < P - 1; j++) { \
                            if (LO32) { cpx<0, GEN>(hi, da + j * 1024, o[j], gx0, 2 * j, dv); cpx<1, GEN>(hi, db + j * 1024, o[j], gx0, 2 * j + 1, dv); } \
                            else if (GEN) { cp16z<128>(da + j * 1024, gx, o[j] & 0xFFFFu, 2 * j, dv, 0); cp16z<128>(db + j * 1024, gx, o[j] >> 16, 2 * j + 1, dv, 0); } \
                            else { cp16i<128>(da + j * 1024, gx, o[j] & 0xFFFFu); cp16i<128>(db + j * 1024, gx, o[j] >> 16); } } \
                        if (LO32) { cpx<0, true>(hi, da + (P - 1) * 1024, o[P - 1], gx0, 2 * P - 2, dv); cpx<1, true>(hi, db + (P - 1) * 1024, o[P - 1], gx0, 2 * P - 1, dv); } \
                        else { cp16z<128>(da + (P - 1) * 1024, gx, o[P - 1] & 0xFFFFu, 2 * P - 2, dv, 0); cp16z<128>(db + (P - 1) * 1024, gx, o[P - 1] >> 16, 2 * P - 1, dv, 0); } \
                    } break;
                    CASE(11, 11, false)
                    CASE(6, 6, false) CASE(7, 7, false) CASE(8, 8, false) CASE(9, 9, false) CASE(10, 10, false)
                    CASE(15, NPMAX, true) CASE(14, 8, true) default: CASE(13, 5, true)
#undef CASE
                }
                claim();
                mbar_cp_arrive(br);
                done3();
                g = __reduce_min_sync(~0u, g);
                {
                    const uint32_t o = nx == 0 ? g : nx;
                    pw = lds32(pa + o);
                    const uint32_t ya = row_of(o), yb = code_of(o);
                    pt = __reduce_or_sync(~0u, pw);
                    const uint32_t brk = (cont | nx) > 1 ? C_BRK : 0u;
                    rc.x = ya ^ xl;
                    const uint32_t lv = brk | ((sel + (15 - NPMAX)) & 16) | (((pt >> 16) & 15) ^ sel);
                    rc.w = (yb & k15) | (lv ? 0x70000000u | brk : TAU_BITS);
                    asm volatile("st.shared.v4.u32 [%2], {%3, %0, %1, %4};\nxor.b32 %0, %5, %6;\nand.b32 %1, %7, %8;"
                                 : "+r"(rc.y), "+r"(rc.z) : "r"(br + ra - 16), "r"(rc.x), "r"(rc.w), "r"(ya), "r"(xs), "r"(yb), "n"(ONE_F | 0x1FFFu) : "memory");
                    cont = nx;
                }
                mbar_arrive(br);
                hist = (hist << 8) | (nx == 0 ? cur : (uint32_t)GD);
                cur = nx == 0 ? g >> 5 : cur;
                da += ue * 4; de += ue; ue = -ue;
                ph ^= br != bars; br = brs - br;
            }
            if (cont & 1) asm volatile("bar.sync 3, 480;" ::: "memory");
            if (go) {
                mbar_wait(sb + SM_ABAR + 32, 0);
                const int g0 = 3 * max((misc[7] + 2) / 3 - TR, 0) + w;
                uint32_t ro[TR], gb[TR]; uint4 xv[TR], xu[TR]; char* op[TR];
                const int gz = misc[4];
                #pragma unroll
                for (int k = 0; k < TR; k++) {
                    uint32_t nd;
                    asm volatile("ld.shared.u16 %0, [%1];" : "=r"(nd) : "r"(pa + (g0 + 3 * k) * 32 + 4) : "memory");
                    uint32_t rb = node0 * 128 + row_bytes(nd);
                    if (g0 + 3 * k >= ngroups) rb = misc[16 + ((g0 + 3 * k - ngroups) & 3) * 4 + r4];
                    if (nd == tab_at(NONE)) rb = 0;
                    xv[k] = __ldg((const uint4*)(gx + rb));
                    op[k] = nd == tab_at(NONE) ? nullptr : (char*)out + rb + c8 * 16;
                    ro[k] = sb + (nd ^ tk);
                    xu[k] = lds128(ro[k] + SM_XU);
                    gb[k] = __reduce_or_sync(~0u, g0 + 3 * k < gz ? sb + SM_GBAR + (g0 + 3 * k) * 8 : 0u);
                }
                #pragma unroll 1
                for (int k = 0; k < 3; k++) {
                    mbar_wait(k < 2 ? br + 8 : sb + SM_ABAR + 48 + w * 8, k < 2 ? ph : 0);
                    done3(); hist <<= 8;
                    ph ^= br != bars; br = brs - br;
                }
                #pragma unroll
                for (int k = 0; k < TR; k++) {
                    uint4 a = make_uint4(0, 0, 0, 0);
                    if (gb[k]) { mbar_wait(gb[k], 0); a = lds128(ro[k] + SM_TAB); }
                    finish(a, xu[k], xv[k]);
                    if (op[k]) *(uint4*)op[k] = a;
                }
            }
            cp_wait<0>();
        } else {
            const int r4 = WMAP ? (lane >> 1) & 3 : lane >> 3, c8 = WMAP ? (lane >> 3) * 2 + (lane & 1) : lane & 7;
            const uint32_t tk = ((c8 & 1) << 4) | ((c8 >> 1) << 7);
            const char* gx = as_pair((const char*)x + (size_t)node0 * 128 + c8 * 16, scr);
            const char* ob = as_pair((const char*)out + (size_t)node0 * 128 + c8 * 16, scr);
            asm volatile("bar.sync 6, 128;" ::: "memory");
            WS(15);
            if (b == 0 && lane == 0) asm volatile("red.relaxed.gpu.global.add.u32 [%0], 1;" :: "l"(gbar) : "memory");
            if (misc[1] == 0) mbar_wait(sb + SM_ABAR + 72, 0);
            if (npb <= NPB_MAX - 4) sts32(sb + SM_MISC + 12, 0);
            int rounds = misc[1] ? 0 : max((ngroups + 2) / 3 - TR, 0);
            const int gz = misc[4];
            int fast = __reduce_min_sync(~0u, min(rounds, gz / 3));
            const uint32_t wl = SM_TINFO + r4 * 8 + 4;
            uint32_t ko = sb;
            auto row_at = [&](uint32_t a) { uint32_t n; asm volatile("ld.shared.u16 %0, [%1];" : "=r"(n) : "r"(a) : "memory"); return n; };
            auto fetch = [&](uint32_t n, uint4& v) {
                asm volatile("{\n.reg .b64 p;\ncvt.u64.u32 p, %5;\nadd.u64 p, p, %4;\nld.global.nc.L1::no_allocate.v4.u32 {%0,%1,%2,%3}, [p];\n}"
                             : "=r"(v.x), "=r"(v.y), "=r"(v.z), "=r"(v.w) : "l"(gx), "r"(n));
            };
            auto store = [&](uint32_t n, const uint4& a) {
                asm volatile("{\n.reg .b64 p;\ncvt.u64.u32 p, %1;\nadd.u64 p, p, %0;\nst.global.v4.u32 [p], {%2,%3,%4,%5};\n}" :: "l"(ob), "r"(n), "r"(a.x), "r"(a.y), "r"(a.z), "r"(a.w) : "memory");
            };
            const uint32_t tw = __shfl_sync(~0u, tk, lane);
            int step = fast > R3 + PMIN && gz == ngroups ? -1 : -2, k = 0;
            #pragma unroll 1
            do {
                const int gn = __reduce_max_sync(~0u, balance(step, gs, all, ngroups, npb));
                if (step == R3) fast = rounds = (gn + 2) / 3 - TR;
                const bool pub = step < 0 && gn;
                step = gn == 0 || step == R3 ? fast - 1 : step < 0 ? R2 : R3;
                const uint32_t lim = step == fast - 1 ? ~0u : (ngroups - (KM + 3)) * 32;
                if (fast == 0) break;
                uint32_t n0[3], o0[3]; uint4 x0[3];
                #pragma unroll
                for (int r = 0; r < 3; r++) { const uint32_t v = row_at(wl + ko + r * 32); n0[r] = row_bytes(v); o0[r] = v ^ tw; fetch(n0[r], x0[r]); }
                #pragma unroll 1
                for (; k <= step; k++) {
                    const uint32_t wn = k < step ? ko + 96 : ko, gbar = sb + SM_GBAR + k * 24;
                    uint4 xu[3], a[3]; uint32_t v[3], ok;
                    #pragma unroll
                    for (int r = 0; r < 3; r++) { xu[r] = lds128(sb + o0[r] + SM_XU); v[r] = row_at(wl + wn + r * 32); }
#define TRY(o) "mbarrier.try_wait.parity.shared.b64 p, [%1 + " o "], 0, 4000;\n@p bra A_%=;\n"
#define NEXT(o) TRY(o) TRY(o) TRY(o) "bra B_%=;\n"
                    asm volatile("{\n.reg .pred p, q, r;\n.reg .b32 c, n;\nmov.u32 n, 0;\n"
                                 "A_%=:\nmbarrier.test_wait.parity.shared.b64 p, [%1], 0;\nmbarrier.test_wait.parity.shared.b64 q, [%1 + 8], 0;\nmbarrier.test_wait.parity.shared.b64 r, [%1 + 16], 0;\n"
                                 "@!r bra W2_%=;\n@!q bra W1_%=;\n@p bra D_%=;\n"
                                 NEXT("0") "W1_%=:\n" NEXT("8") "W2_%=:\n" NEXT("16")
                                 "B_%=:\nld.volatile.shared.u32 c, [%2];\nadd.u32 n, n, 1;\nsetp.gt.u32 q, n, 0x100000;\n@q trap;\nsetp.le.u32 q, c, %3;\n@q bra A_%=;\n"
                                 "D_%=:\nselp.u32 %0, 1, 0, p;\n}" : "=r"(ok) : "r"(gbar), "r"(sb + SM_CLAIM), "r"(lim) : "memory");
#undef NEXT
#undef TRY
                    if (!ok) break;
                    #pragma unroll
                    for (int r = 0; r < 3; r++) a[r] = lds128(sb + o0[r] + SM_TAB);
                    #pragma unroll
                    for (int r = 0; r < 3; r++) {
                        finish(a[r], xu[r], x0[r]);
                        const uint32_t nd = n0[r];
                        n0[r] = row_bytes(v[r]); o0[r] = v[r] ^ tw;
                        fetch(n0[r], x0[r]);
                        store(nd, a[r]);
                    }
                    ko += 96;
                    if (pub && k == R1) {
                        uint32_t now; asm volatile("mov.u32 %0, %%globaltimer_lo;" : "=r"(now));
                        now = __reduce_max_sync(~0u, (((now + lds32(sb + SM_MISC + 48)) << 6) & ~511u) | 256);
                        sts32(sb + SM_MISC + 48, now);
                        asm volatile(ELECT "st.relaxed.gpu.global.v2.u32 [%0], {%1, %2};\n}" :: "l"(gs + G_F + b * 8), "r"(now), "r"(all) : "memory");
                    }
                }
                if (k <= R1) step = -2;
            } while (k < fast);
            #pragma unroll 1
            for (int g = 3 * fast; g < 3 * rounds; g++) {
                const uint32_t v = row_at(sb + SM_TINFO + r4 * 8 + 4 + g * 32), nd = row_bytes(v), ro = sb + (v ^ tw);
                uint4 xv, a = make_uint4(0, 0, 0, 0);
                fetch(nd, xv);
                if (g < gz) { mbar_wait(sb + SM_GBAR + g * 8, 0); a = lds128(ro + SM_TAB); }
                finish(a, lds128(ro + SM_XU), xv);
                store(nd, a);
            }
        }
    }
    WS(17); WG1(); CG(2);
}

}

extern "C" void kernel_launch(void* const* d_in, const int* in_sizes, int n_in, void* d_out, int out_size) {
    const __nv_bfloat16* x = (const __nv_bfloat16*)d_in[0];
    const __nv_bfloat16* ea = (const __nv_bfloat16*)d_in[1];
    const int* src = (const int*)d_in[2];
    const int* dst = (const int*)d_in[3];
    const __nv_bfloat16* wa = (const __nv_bfloat16*)d_in[4];
    const __nv_bfloat16* wb = (const __nv_bfloat16*)d_in[5];
    const __nv_bfloat16* wc = (const __nv_bfloat16*)d_in[6];
    const __nv_bfloat16* wu = (const __nv_bfloat16*)d_in[7];
    const __nv_bfloat16* wv = (const __nv_bfloat16*)d_in[8];
    __nv_bfloat16* out = (__nv_bfloat16*)d_out;
    int N = in_sizes[0] / 64, E = in_sizes[2];
    static int sms = 0;
    static CUtensorMap tm1, tm2, tmw, tmx;
    static bool tm_ok = false;
    static void* gp = nullptr; static void* gb = nullptr;
    typedef CUresult (*EncFn)(CUtensorMap*, CUtensorMapDataType, cuuint32_t, void*, const cuuint64_t*, const cuuint64_t*, const cuuint32_t*,
                              const cuuint32_t*, CUtensorMapInterleave, CUtensorMapSwizzle, CUtensorMapL2promotion, CUtensorMapFloatOOBfill);
    static void* fn = nullptr;
    auto enc = [&](CUtensorMap* tm, const void* base, cuuint64_t cols, cuuint64_t rows, cuuint32_t bc, cuuint32_t br, CUtensorMapSwizzle sw) {
        cuuint64_t g2[2] = {cols, rows}, gs[1] = {cols * 4};
        cuuint32_t b2[2] = {bc, br}, es[2] = {1, 1};
        return ((EncFn)fn)(tm, CU_TENSOR_MAP_DATA_TYPE_UINT32, 2, (void*)base, g2, gs, b2, es, CU_TENSOR_MAP_INTERLEAVE_NONE, sw,
                           CU_TENSOR_MAP_L2_PROMOTION_NONE, CU_TENSOR_MAP_FLOAT_OOB_FILL_NONE) == CUDA_SUCCESS;
    };
    if (!sms) {
        cudaDeviceGetAttribute(&sms, cudaDevAttrMultiProcessorCount, 0);
        cudaDriverEntryPointQueryResult qr;
        cudaGetDriverEntryPoint("cuTensorMapEncodeTiled", &fn, cudaEnableDefault, &qr);
        cudaGetSymbolAddress(&gp, g_str); cudaGetSymbolAddress(&gb, g_bar);
        if (fn && gp && gb) {
            const cuuint32_t rows = sms < NB_MAX ? sms : NB_MAX;
            tm_ok = enc(&tm1, gp, (P1B + P2B) / 4, NB_MAX, CE / 2, rows, CU_TENSOR_MAP_SWIZZLE_NONE) && enc(&tm2, gp, (P1B + P2B) / 4, NB_MAX, CE, rows, CU_TENSOR_MAP_SWIZZLE_NONE);
        }
        cudaFuncSetAttribute(gcn_kernel<true>, cudaFuncAttributeMaxDynamicSharedMemorySize, SMEM_LAUNCH);
        cudaFuncSetAttribute(gcn_kernel<false>, cudaFuncAttributeMaxDynamicSharedMemorySize, SMEM_LAUNCH);
    }
    int nb = sms < NB_MAX ? sms : NB_MAX;
    int npb = (N + nb - 1) / nb;
    int ch = (((E + nb - 1) / nb) + 3) & ~3;
    const uintptr_t wp[4] = {(uintptr_t)wb, (uintptr_t)wv, (uintptr_t)wa, (uintptr_t)wu};
    uintptr_t wlo = wp[0], whi = wp[0], wal = 0;
    for (int i = 0; i < 4; i++) { wlo = wp[i] < wlo ? wp[i] : wlo; whi = wp[i] > whi ? wp[i] : whi; wal |= wp[i] - wp[0]; }
    bool ok = tm_ok && nb >= NB_MIN && npb < NPB_MAX && ch <= CH_MAX && !(E & 3) && N <= 65535 && npb >= 2 && !(wal & 127) && (whi - wlo) >> 7 < (1u << 30) &&
              !(((uintptr_t)src | (uintptr_t)dst | (uintptr_t)x | (uintptr_t)wb | (uintptr_t)wc) & 15);
    ok = ok && enc(&tmw, (const void*)wlo, 32, ((whi - wlo) >> 7) + 64, 32, 64, CU_TENSOR_MAP_SWIZZLE_128B) && enc(&tmx, x, 32, N, 32, 64, CU_TENSOR_MAP_SWIZZLE_128B);
    if (!ok) {
        int g = 1024, p = (N + g - 1) / g;
        slow_kernel<<<g, 256>>>(x, ea, src, dst, wa, wb, wc, wu, wv, out, N, E, p < 1 ? 1 : p);
        return;
    }
    int4 wrow = make_int4((int)((wp[0] - wlo) >> 7), (int)((wp[1] - wlo) >> 7), (int)((wp[2] - wlo) >> 7), (int)((wp[3] - wlo) >> 7));
    uint32_t magic = (uint32_t)((1ull << 32) / (uint32_t)npb) + 1u;
    void* args[] = {&dst, &gb, &gp, &src, &E, &ch, &N, &npb, &magic, &x, &ea, &wa, &wb, &wc, &wu, &wv, &out, &wrow, &tm1, &tm2, &tmw, &tmx};
    const bool lo32 = ((uintptr_t)x >> 32) == (((uintptr_t)x + (size_t)N * 128 - 1) >> 32) && ((uintptr_t)ea >> 32) == (((uintptr_t)ea + (size_t)E * 32 - 1) >> 32);
    cudaLaunchCooperativeKernel(lo32 && !FORCE64 ? (const void*)gcn_kernel<true> : (const void*)gcn_kernel<false>, dim3(nb), dim3(THREADS), args, SMEM_LAUNCH, cudaStreamPerThread);
}
```

```cpp
#include <cuda_runtime.h>
#include <cuda.h>
#include <cuda_bf16.h>
#include <stdint.h>

namespace {

constexpr int N_MAX = 65536;
constexpr int NPMAX = 11;
constexpr int NPMIN = 5;
constexpr int THREADS = 512;
constexpr int EPT = 12;
constexpr int CH_MAX = THREADS * EPT;
constexpr int NB_MAX = 134, NB_MIN = 120;
constexpr int CE = 64;
constexpr int P1B = NB_MAX * CE * 2;
constexpr int P2B = NB_MAX * CE * 4;
constexpr int HB = NB_MAX * 64;
constexpr int G_H1 = NB_MAX * (P1B + P2B), G_H2 = G_H1 + HB, G_L = G_H2 + HB, G_F = G_L + NB_MAX * 512;
constexpr int KM = 4, GRP_B = 1536, G_R = G_F + 2048, G_P = G_R + 2048, G_END = G_P + NB_MAX * KM * GRP_B;
#define BAL 1
#define PMIN 8
constexpr int R1 = 9, R2 = 11, R3 = 14;
constexpr int GD = 100;
constexpr int NPB_MAX = 384;
constexpr int SLOT_CAP = 6784;
constexpr int TILE_CAP = 123;
constexpr int TILE_X = 8;
constexpr int NCLS = 64;
constexpr int NSTAGE = 2;
constexpr int PD = 300;
constexpr int TR = 2;
constexpr float LOG2E = 1.4426950408889634f;

__device__ __align__(256) uint4 g_str[G_END / 16];
__device__ __align__(128) unsigned g_bar[8];
__device__ float g_slow[N_MAX * 128];
__device__ float4 g_copy[NB_MAX * 384 * 2 * NPMAX];

#define WS(k)
#define WGD()
#define WG0()
#define WG1()
#define CG(k)
#define SMEM_LAUNCH SMEM_BYTES
#define FORCE64 0
#define EDHI ((16ull << 32) | (3ull << 62))
template<int NP> struct TileMMA;
template<> struct TileMMA<5> {
  static __device__ __forceinline__ void issue(float* g, float* h, const uint32_t* w, uint32_t dx, uint64_t de, uint64_t dh, uint64_t dc) {
    asm volatile(
      "{\n.reg .b64 dx0, dx1, dx2, dx3;\n.reg .b32 l1, l2, l3, hx;\nmov.b32 hx, 0x40000040;\n"
      "add.u32 l1, %80, 2;\nadd.u32 l2, %80, 4;\nadd.u32 l3, %80, 6;\n"
      "mov.b64 dx0, {%80, hx};\nmov.b64 dx1, {l1, hx};\nmov.b64 dx2, {l2, hx};\nmov.b64 dx3, {l3, hx};\n"
      "wgmma.fence.sync.aligned;\n"
      "wgmma.mma_async.sync.aligned.m64n40k16.f32.bf16.bf16 {%0, %1, %2, %3, %4, %5, %6, %7, %8, %9, %10, %11, %12, %13, %14, %15, %16, %17, %18, %19}, {%76, %77, %78, %79}, %82, 0, 1, 1, 0;\n"
      "wgmma.mma_async.sync.aligned.m64n40k16.f32.bf16.bf16 {%0, %1, %2, %3, %4, %5, %6, %7, %8, %9, %10, %11, %12, %13, %14, %15, %16, %17, %18, %19}, {%56, %57, %58, %59}, %81, 1, 1, 1, 0;\n"
      "wgmma.mma_async.sync.aligned.m64n40k16.f32.bf16.bf16 {%0, %1, %2, %3, %4, %5, %6, %7, %8, %9, %10, %11, %12, %13, %14, %15, %16, %17, %18, %19}, {%40, %41, %42, %43}, dx0, 1, 1, 1, 0;\n"
      "wgmma.mma_async.sync.aligned.m64n40k16.f32.bf16.bf16 {%0, %1, %2, %3, %4, %5, %6, %7, %8, %9, %10, %11, %12, %13, %14, %15, %16, %17, %18, %19}, {%44, %45, %46, %47}, dx1, 1, 1, 1, 0;\n"
      "wgmma.mma_async.sync.aligned.m64n40k16.f32.bf16.bf16 {%0, %1, %2, %3, %4, %5, %6, %7, %8, %9, %10, %11, %12, %13, %14, %15, %16, %17, %18, %19}, {%48, %49, %50, %51}, dx2, 1, 1, 1, 0;\n"
      "wgmma.mma_async.sync.aligned.m64n40k16.f32.bf16.bf16 {%0, %1, %2, %3, %4, %5, %6, %7, %8, %9, %10, %11, %12, %13, %14, %15, %16, %17, %18, %19}, {%52, %53, %54, %55}, dx3, 1, 1, 1, 0;\n"
      "wgmma.commit_group.sync.aligned;\n"
      "wgmma.mma_async.sync.aligned.m64n40k16.f32.bf16.bf16 {%20, %21, %22, %23, %24, %25, %26, %27, %28, %29, %30, %31, %32, %33, %34, %35, %36, %37, %38, %39}, {%60, %61, %62, %63}, dx0, 0, 1, 1, 0;\n"
      "wgmma.mma_async.sync.aligned.m64n40k16.f32.bf16.bf16 {%20, %21, %22, %23, %24, %25, %26, %27, %28, %29, %30, %31, %32, %33, %34, %35, %36, %37, %38, %39}, {%64, %65, %66, %67}, dx1, 1, 1, 1, 0;\n"
      "wgmma.mma_async.sync.aligned.m64n40k16.f32.bf16.bf16 {%20, %21, %22, %23, %24, %25, %26, %27, %28, %29, %30, %31, %32, %33, %34, %35, %36, %37, %38, %39}, {%68, %69, %70, %71}, dx2, 1, 1, 1, 0;\n"
      "wgmma.mma_async.sync.aligned.m64n40k16.f32.bf16.bf16 {%20, %21, %22, %23, %24, %25, %26, %27, %28, %29, %30, %31, %32, %33, %34, %35, %36, %37, %38, %39}, {%72, %73, %74, %75}, dx3, 1, 1, 1, 0;\n"
      "wgmma.commit_group.sync.aligned;\n}\n"
      : "=f"(g[0]), "=f"(g[1]), "=f"(g[2]), "=f"(g[3]), "=f"(g[4]), "=f"(g[5]), "=f"(g[6]), "=f"(g[7]), "=f"(g[8]), "=f"(g[9]), "=f"(g[10]), "=f"(g[11]), "=f"(g[12]), "=f"(g[13]), "=f"(g[14]), "=f"(g[15]), "=f"(g[16]), "=f"(g[17]), "=f"(g[18]), "=f"(g[19]),
        "=f"(h[0]), "=f"(h[1]), "=f"(h[2]), "=f"(h[3]), "=f"(h[4]), "=f"(h[5]), "=f"(h[6]), "=f"(h[7]), "=f"(h[8]), "=f"(h[9]), "=f"(h[10]), "=f"(h[11]), "=f"(h[12]), "=f"(h[13]), "=f"(h[14]), "=f"(h[15]), "=f"(h[16]), "=f"(h[17]), "=f"(h[18]), "=f"(h[19])
      : "r"(w[0]), "r"(w[1]), "r"(w[2]), "r"(w[3]), "r"(w[4]), "r"(w[5]), "r"(w[6]), "r"(w[7]), "r"(w[8]), "r"(w[9]), "r"(w[10]), "r"(w[11]), "r"(w[12]), "r"(w[13]), "r"(w[14]), "r"(w[15]), "r"(w[16]), "r"(w[17]), "r"(w[18]), "r"(w[19]), "r"(w[20]), "r"(w[21]), "r"(w[22]), "r"(w[23]), "r"(w[24]), "r"(w[25]), "r"(w[26]), "r"(w[27]), "r"(w[28]), "r"(w[29]), "r"(w[30]), "r"(w[31]), "r"(w[32]), "r"(w[33]), "r"(w[34]), "r"(w[35]), "r"(w[36]), "r"(w[37]), "r"(w[38]), "r"(w[39]), "r"(dx), "l"(de), "l"(dh)
      : "memory");
  }
  static __device__ __forceinline__ void wait_g(float* g) {
    asm volatile("wgmma.wait_group.sync.aligned 1;\n"
      : "+f"(g[0]), "+f"(g[1]), "+f"(g[2]), "+f"(g[3]), "+f"(g[4]), "+f"(g[5]), "+f"(g[6]), "+f"(g[7]), "+f"(g[8]), "+f"(g[9]), "+f"(g[10]), "+f"(g[11]), "+f"(g[12]), "+f"(g[13]), "+f"(g[14]), "+f"(g[15]), "+f"(g[16]), "+f"(g[17]), "+f"(g[18]), "+f"(g[19])
      :: "memory");
  }
  static __device__ __forceinline__ void wait_h(float* h) {
    asm volatile("wgmma.wait_group.sync.aligned 0;\n"
      : "+f"(h[0]), "+f"(h[1]), "+f"(h[2]), "+f"(h[3]), "+f"(h[4]), "+f"(h[5]), "+f"(h[6]), "+f"(h[7]), "+f"(h[8]), "+f"(h[9]), "+f"(h[10]), "+f"(h[11]), "+f"(h[12]), "+f"(h[13]), "+f"(h[14]), "+f"(h[15]), "+f"(h[16]), "+f"(h[17]), "+f"(h[18]), "+f"(h[19])
      :: "memory");
  }
};
template<> struct TileMMA<6> {
  static __device__ __forceinline__ void issue(float* g, float* h, const uint32_t* w, uint32_t dx, uint64_t de, uint64_t dh, uint64_t dc) {
    asm volatile(
      "{\n.reg .b64 dx0, dx1, dx2, dx3;\n.reg .b32 l1, l2, l3, hx;\nmov.b32 hx, 0x40000040;\n"
      "add.u32 l1, %88, 2;\nadd.u32 l2, %88, 4;\nadd.u32 l3, %88, 6;\n"
      "mov.b64 dx0, {%88, hx};\nmov.b64 dx1, {l1, hx};\nmov.b64 dx2, {l2, hx};\nmov.b64 dx3, {l3, hx};\n"
      "wgmma.fence.sync.aligned;\n"
      "wgmma.mma_async.sync.aligned.m64n48k16.f32.bf16.bf16 {%0, %1, %2, %3, %4, %5, %6, %7, %8, %9, %10, %11, %12, %13, %14, %15, %16, %17, %18, %19, %20, %21, %22, %23}, {%84, %85, %86, %87}, %90, 0, 1, 1, 0;\n"
      "wgmma.mma_async.sync.aligned.m64n48k16.f32.bf16.bf16 {%0, %1, %2, %3, %4, %5, %6, %7, %8, %9, %10, %11, %12, %13, %14, %15, %16, %17, %18, %19, %20, %21, %22, %23}, {%64, %65, %66, %67}, %89, 1, 1, 1, 0;\n"
      "wgmma.mma_async.sync.aligned.m64n48k16.f32.bf16.bf16 {%0, %1, %2, %3, %4, %5, %6, %7, %8, %9, %10, %11, %12, %13, %14, %15, %16, %17, %18, %19, %20, %21, %22, %23}, {%48, %49, %50, %51}, dx0, 1, 1, 1, 0;\n"
      "wgmma.mma_async.sync.aligned.m64n48k16.f32.bf16.bf16 {%0, %1, %2, %3, %4, %5, %6, %7, %8, %9, %10, %11, %12, %13, %14, %15, %16, %17, %18, %19, %20, %21, %22, %23}, {%52, %53, %54, %55}, dx1, 1, 1, 1, 0;\n"
      "wgmma.mma_async.sync.aligned.m64n48k16.f32.bf16.bf16 {%0, %1, %2, %3, %4, %5, %6, %7, %8, %9, %10, %11, %12, %13, %14, %15, %16, %17, %18, %19, %20, %21, %22, %23}, {%56, %57, %58, %59}, dx2, 1, 1, 1, 0;\n"
      "wgmma.mma_async.sync.aligned.m64n48k16.f32.bf16.bf16 {%0, %1, %2, %3, %4, %5, %6, %7, %8, %9, %10, %11, %12, %13, %14, %15, %16, %17, %18, %19, %20, %21, %22, %23}, {%60, %61, %62, %63}, dx3, 1, 1, 1, 0;\n"
      "wgmma.commit_group.sync.aligned;\n"
      "wgmma.mma_async.sync.aligned.m64n48k16.f32.bf16.bf16 {%24, %25, %26, %27, %28, %29, %30, %31, %32, %33, %34, %35, %36, %37, %38, %39, %40, %41, %42, %43, %44, %45, %46, %47}, {%68, %69, %70, %71}, dx0, 0, 1, 1, 0;\n"
      "wgmma.mma_async.sync.aligned.m64n48k16.f32.bf16.bf16 {%24, %25, %26, %27, %28, %29, %30, %31, %32, %33, %34, %35, %36, %37, %38, %39, %40, %41, %42, %43, %44, %45, %46, %47}, {%72, %73, %74, %75}, dx1, 1, 1, 1, 0;\n"
      "wgmma.mma_async.sync.aligned.m64n48k16.f32.bf16.bf16 {%24, %25, %26, %27, %28, %29, %30, %31, %32, %33, %34, %35, %36, %37, %38, %39, %40, %41, %42, %43, %44, %45, %46, %47}, {%76, %77, %78, %79}, dx2, 1, 1, 1, 0;\n"
      "wgmma.mma_async.sync.aligned.m64n48k16.f32.bf16.bf16 {%24, %25, %26, %27, %28, %29, %30, %31, %32, %33, %34, %35, %36, %37, %38, %39, %40, %41, %42, %43, %44, %45, %46, %47}, {%80, %81, %82, %83}, dx3, 1, 1, 1, 0;\n"
      "wgmma.commit_group.sync.aligned;\n}\n"
      : "=f"(g[0]), "=f"(g[1]), "=f"(g[2]), "=f"(g[3]), "=f"(g[4]), "=f"(g[5]), "=f"(g[6]), "=f"(g[7]), "=f"(g[8]), "=f"(g[9]), "=f"(g[10]), "=f"(g[11]), "=f"(g[12]), "=f"(g[13]), "=f"(g[14]), "=f"(g[15]), "=f"(g[16]), "=f"(g[17]), "=f"(g[18]), "=f"(g[19]), "=f"(g[20]), "=f"(g[21]), "=f"(g[22]), "=f"(g[23]),
        "=f"(h[0]), "=f"(h[1]), "=f"(h[2]), "=f"(h[3]), "=f"(h[4]), "=f"(h[5]), "=f"(h[6]), "=f"(h[7]), "=f"(h[8]), "=f"(h[9]), "=f"(h[10]), "=f"(h[11]), "=f"(h[12]), "=f"(h[13]), "=f"(h[14]), "=f"(h[15]), "=f"(h[16]), "=f"(h[17]), "=f"(h[18]), "=f"(h[19]), "=f"(h[20]), "=f"(h[21]), "=f"(h[22]), "=f"(h[23])
      : "r"(w[0]), "r"(w[1]), "r"(w[2]), "r"(w[3]), "r"(w[4]), "r"(w[5]), "r"(w[6]), "r"(w[7]), "r"(w[8]), "r"(w[9]), "r"(w[10]), "r"(w[11]), "r"(w[12]), "r"(w[13]), "r"(w[14]), "r"(w[15]), "r"(w[16]), "r"(w[17]), "r"(w[18]), "r"(w[19]), "r"(w[20]), "r"(w[21]), "r"(w[22]), "r"(w[23]), "r"(w[24]), "r"(w[25]), "r"(w[26]), "r"(w[27]), "r"(w[28]), "r"(w[29]), "r"(w[30]), "r"(w[31]), "r"(w[32]), "r"(w[33]), "r"(w[34]), "r"(w[35]), "r"(w[36]), "r"(w[37]), "r"(w[38]), "r"(w[39]), "r"(dx), "l"(de), "l"(dh)
      : "memory");
  }
  static __device__ __forceinline__ void wait_g(float* g) {
    asm volatile("wgmma.wait_group.sync.aligned 1;\n"
      : "+f"(g[0]), "+f"(g[1]), "+f"(g[2]), "+f"(g[3]), "+f"(g[4]), "+f"(g[5]), "+f"(g[6]), "+f"(g[7]), "+f"(g[8]), "+f"(g[9]), "+f"(g[10]), "+f"(g[11]), "+f"(g[12]), "+f"(g[13]), "+f"(g[14]), "+f"(g[15]), "+f"(g[16]), "+f"(g[17]), "+f"(g[18]), "+f"(g[19]), "+f"(g[20]), "+f"(g[21]), "+f"(g[22]), "+f"(g[23])
      :: "memory");
  }
  static __device__ __forceinline__ void wait_h(float* h) {
    asm volatile("wgmma.wait_group.sync.aligned 0;\n"
      : "+f"(h[0]), "+f"(h[1]), "+f"(h[2]), "+f"(h[3]), "+f"(h[4]), "+f"(h[5]), "+f"(h[6]), "+f"(h[7]), "+f"(h[8]), "+f"(h[9]), "+f"(h[10]), "+f"(h[11]), "+f"(h[12]), "+f"(h[13]), "+f"(h[14]), "+f"(h[15]), "+f"(h[16]), "+f"(h[17]), "+f"(h[18]), "+f"(h[19]), "+f"(h[20]), "+f"(h[21]), "+f"(h[22]), "+f"(h[23])
      :: "memory");
  }
};
template<> struct TileMMA<7> {
  static __device__ __forceinline__ void issue(float* g, float* h, const uint32_t* w, uint32_t dx, uint64_t de, uint64_t dh, uint64_t dc) {
    asm volatile(
      "{\n.reg .b64 dx0, dx1, dx2, dx3;\n.reg .b32 l1, l2, l3, hx;\nmov.b32 hx, 0x40000040;\n"
      "add.u32 l1, %96, 2;\nadd.u32 l2, %96, 4;\nadd.u32 l3, %96, 6;\n"
      "mov.b64 dx0, {%96, hx};\nmov.b64 dx1, {l1, hx};\nmov.b64 dx2, {l2, hx};\nmov.b64 dx3, {l3, hx};\n"
      "wgmma.fence.sync.aligned;\n"
      "wgmma.mma_async.sync.aligned.m64n56k16.f32.bf16.bf16 {%0, %1, %2, %3, %4, %5, %6, %7, %8, %9, %10, %11, %12, %13, %14, %15, %16, %17, %18, %19, %20, %21, %22, %23, %24, %25, %26, %27}, {%92, %93, %94, %95}, %98, 0, 1, 1, 0;\n"
      "wgmma.mma_async.sync.aligned.m64n56k16.f32.bf16.bf16 {%0, %1, %2, %3, %4, %5, %6, %7, %8, %9, %10, %11, %12, %13, %14, %15, %16, %17, %18, %19, %20, %21, %22, %23, %24, %25, %26, %27}, {%72, %73, %74, %75}, %97, 1, 1, 1, 0;\n"
      "wgmma.mma_async.sync.aligned.m64n56k16.f32.bf16.bf16 {%0, %1, %2, %3, %4, %5, %6, %7, %8, %9, %10, %11, %12, %13, %14, %15, %16, %17, %18, %19, %20, %21, %22, %23, %24, %25, %26, %27}, {%56, %57, %58, %59}, dx0, 1, 1, 1, 0;\n"
      "wgmma.mma_async.sync.aligned.m64n56k16.f32.bf16.bf16 {%0, %1, %2, %3, %4, %5, %6, %7, %8, %9, %10, %11, %12, %13, %14, %15, %16, %17, %18, %19, %20, %21, %22, %23, %24, %25, %26, %27}, {%60, %61, %62, %63}, dx1, 1, 1, 1, 0;\n"
      "wgmma.mma_async.sync.aligned.m64n56k16.f32.bf16.bf16 {%0, %1, %2, %3, %4, %5, %6, %7, %8, %9, %10, %11, %12, %13, %14, %15, %16, %17, %18, %19, %20, %21, %22, %23, %24, %25, %26, %27}, {%64, %65, %66, %67}, dx2, 1, 1, 1, 0;\n"
      "wgmma.mma_async.sync.aligned.m64n56k16.f32.bf16.bf16 {%0, %1, %2, %3, %4, %5, %6, %7, %8, %9, %10, %11, %12, %13, %14, %15, %16, %17, %18, %19, %20, %21, %22, %23, %24, %25, %26, %27}, {%68, %69, %70, %71}, dx3, 1, 1, 1, 0;\n"
      "wgmma.commit_group.sync.aligned;\n"
      "wgmma.mma_async.sync.aligned.m64n56k16.f32.bf16.bf16 {%28, %29, %30, %31, %32, %33, %34, %35, %36, %37, %38, %39, %40, %41, %42, %43, %44, %45, %46, %47, %48, %49, %50, %51, %52, %53, %54, %55}, {%76, %77, %78, %79}, dx0, 0, 1, 1, 0;\n"
      "wgmma.mma_async.sync.aligned.m64n56k16.f32.bf16.bf16 {%28, %29, %30, %31, %32, %33, %34, %35, %36, %37, %38, %39, %40, %41, %42, %43, %44, %45, %46, %47, %48, %49, %50, %51, %52, %53, %54, %55}, {%80, %81, %82, %83}, dx1, 1, 1, 1, 0;\n"
      "wgmma.mma_async.sync.aligned.m64n56k16.f32.bf16.bf16 {%28, %29, %30, %31, %32, %33, %34, %35, %36, %37, %38, %39, %40, %41, %42, %43, %44, %45, %46, %47, %48, %49, %50, %51, %52, %53, %54, %55}, {%84, %85, %86, %87}, dx2, 1, 1, 1, 0;\n"
      "wgmma.mma_async.sync.aligned.m64n56k16.f32.bf16.bf16 {%28, %29, %30, %31, %32, %33, %34, %35, %36, %37, %38, %39, %40, %41, %42, %43, %44, %45, %46, %47, %48, %49, %50, %51, %52, %53, %54, %55}, {%88, %89, %90, %91}, dx3, 1, 1, 1, 0;\n"
      "wgmma.commit_group.sync.aligned;\n}\n"
      : "=f"(g[0]), "=f"(g[1]), "=f"(g[2]), "=f"(g[3]), "=f"(g[4]), "=f"(g[5]), "=f"(g[6]), "=f"(g[7]), "=f"(g[8]), "=f"(g[9]), "=f"(g[10]), "=f"(g[11]), "=f"(g[12]), "=f"(g[13]), "=f"(g[14]), "=f"(g[15]), "=f"(g[16]), "=f"(g[17]), "=f"(g[18]), "=f"(g[19]), "=f"(g[20]), "=f"(g[21]), "=f"(g[22]), "=f"(g[23]), "=f"(g[24]), "=f"(g[25]), "=f"(g[26]), "=f"(g[27]),
        "=f"(h[0]), "=f"(h[1]), "=f"(h[2]), "=f"(h[3]), "=f"(h[4]), "=f"(h[5]), "=f"(h[6]), "=f"(h[7]), "=f"(h[8]), "=f"(h[9]), "=f"(h[10]), "=f"(h[11]), "=f"(h[12]), "=f"(h[13]), "=f"(h[14]), "=f"(h[15]), "=f"(h[16]), "=f"(h[17]), "=f"(h[18]), "=f"(h[19]), "=f"(h[20]), "=f"(h[21]), "=f"(h[22]), "=f"(h[23]), "=f"(h[24]), "=f"(h[25]), "=f"(h[26]), "=f"(h[27])
      : "r"(w[0]), "r"(w[1]), "r"(w[2]), "r"(w[3]), "r"(w[4]), "r"(w[5]), "r"(w[6]), "r"(w[7]), "r"(w[8]), "r"(w[9]), "r"(w[10]), "r"(w[11]), "r"(w[12]), "r"(w[13]), "r"(w[14]), "r"(w[15]), "r"(w[16]), "r"(w[17]), "r"(w[18]), "r"(w[19]), "r"(w[20]), "r"(w[21]), "r"(w[22]), "r"(w[23]), "r"(w[24]), "r"(w[25]), "r"(w[26]), "r"(w[27]), "r"(w[28]), "r"(w[29]), "r"(w[30]), "r"(w[31]), "r"(w[32]), "r"(w[33]), "r"(w[34]), "r"(w[35]), "r"(w[36]), "r"(w[37]), "r"(w[38]), "r"(w[39]), "r"(dx), "l"(de), "l"(dh)
      : "memory");
  }
  static __device__ __forceinline__ void wait_g(float* g) {
    asm volatile("wgmma.wait_group.sync.aligned 1;\n"
      : "+f"(g[0]), "+f"(g[1]), "+f"(g[2]), "+f"(g[3]), "+f"(g[4]), "+f"(g[5]), "+f"(g[6]), "+f"(g[7]), "+f"(g[8]), "+f"(g[9]), "+f"(g[10]), "+f"(g[11]), "+f"(g[12]), "+f"(g[13]), "+f"(g[14]), "+f"(g[15]), "+f"(g[16]), "+f"(g[17]), "+f"(g[18]), "+f"(g[19]), "+f"(g[20]), "+f"(g[21]), "+f"(g[22]), "+f"(g[23]), "+f"(g[24]), "+f"(g[25]), "+f"(g[26]), "+f"(g[27])
      :: "memory");
  }
  static __device__ __forceinline__ void wait_h(float* h) {
    asm volatile("wgmma.wait_group.sync.aligned 0;\n"
      : "+f"(h[0]), "+f"(h[1]), "+f"(h[2]), "+f"(h[3]), "+f"(h[4]), "+f"(h[5]), "+f"(h[6]), "+f"(h[7]), "+f"(h[8]), "+f"(h[9]), "+f"(h[10]), "+f"(h[11]), "+f"(h[12]), "+f"(h[13]), "+f"(h[14]), "+f"(h[15]), "+f"(h[16]), "+f"(h[17]), "+f"(h[18]), "+f"(h[19]), "+f"(h[20]), "+f"(h[21]), "+f"(h[22]), "+f"(h[23]), "+f"(h[24]), "+f"(h[25]), "+f"(h[26]), "+f"(h[27])
      :: "memory");
  }
};
template<> struct TileMMA<8> {
  static __device__ __forceinline__ void issue(float* g, float* h, const uint32_t* w, uint32_t dx, uint64_t de, uint64_t dh, uint64_t dc) {
    asm volatile(
      "{\n.reg .b64 dx0, dx1, dx2, dx3;\n.reg .b32 l1, l2, l3, hx;\nmov.b32 hx, 0x40000040;\n"
      "add.u32 l1, %104, 2;\nadd.u32 l2, %104, 4;\nadd.u32 l3, %104, 6;\n"
      "mov.b64 dx0, {%104, hx};\nmov.b64 dx1, {l1, hx};\nmov.b64 dx2, {l2, hx};\nmov.b64 dx3, {l3, hx};\n"
      "wgmma.fence.sync.aligned;\n"
      "wgmma.mma_async.sync.aligned.m64n64k16.f32.bf16.bf16 {%0, %1, %2, %3, %4, %5, %6, %7, %8, %9, %10, %11, %12, %13, %14, %15, %16, %17, %18, %19, %20, %21, %22, %23, %24, %25, %26, %27, %28, %29, %30, %31}, {%100, %101, %102, %103}, %106, 0, 1, 1, 0;\n"
      "wgmma.mma_async.sync.aligned.m64n64k16.f32.bf16.bf16 {%0, %1, %2, %3, %4, %5, %6, %7, %8, %9, %10, %11, %12, %13, %14, %15, %16, %17, %18, %19, %20, %21, %22, %23, %24, %25, %26, %27, %28, %29, %30, %31}, {%80, %81, %82, %83}, %105, 1, 1, 1, 0;\n"
      "wgmma.mma_async.sync.aligned.m64n64k16.f32.bf16.bf16 {%0, %1, %2, %3, %4, %5, %6, %7, %8, %9, %10, %11, %12, %13, %14, %15, %16, %17, %18, %19, %20, %21, %22, %23, %24, %25, %26, %27, %28, %29, %30, %31}, {%64, %65, %66, %67}, dx0, 1, 1, 1, 0;\n"
      "wgmma.mma_async.sync.aligned.m64n64k16.f32.bf16.bf16 {%0, %1, %2, %3, %4, %5, %6, %7, %8, %9, %10, %11, %12, %13, %14, %15, %16, %17, %18, %19, %20, %21, %22, %23, %24, %25, %26, %27, %28, %29, %30, %31}, {%68, %69, %70, %71}, dx1, 1, 1, 1, 0;\n"
      "wgmma.mma_async.sync.aligned.m64n64k16.f32.bf16.bf16 {%0, %1, %2, %3, %4, %5, %6, %7, %8, %9, %10, %11, %12, %13, %14, %15, %16, %17, %18, %19, %20, %21, %22, %23, %24, %25, %26, %27, %28, %29, %30, %31}, {%72, %73, %74, %75}, dx2, 1, 1, 1, 0;\n"
      "wgmma.mma_async.sync.aligned.m64n64k16.f32.bf16.bf16 {%0, %1, %2, %3, %4, %5, %6, %7, %8, %9, %10, %11, %12, %13, %14, %15, %16, %17, %18, %19, %20, %21, %22, %23, %24, %25, %26, %27, %28, %29, %30, %31}, {%76, %77, %78, %79}, dx3, 1, 1, 1, 0;\n"
      "wgmma.commit_group.sync.aligned;\n"
      "wgmma.mma_async.sync.aligned.m64n64k16.f32.bf16.bf16 {%32, %33, %34, %35, %36, %37, %38, %39, %40, %41, %42, %43, %44, %45, %46, %47, %48, %49, %50, %51, %52, %53, %54, %55, %56, %57, %58, %59, %60, %61, %62, %63}, {%84, %85, %86, %87}, dx0, 0, 1, 1, 0;\n"
      "wgmma.mma_async.sync.aligned.m64n64k16.f32.bf16.bf16 {%32, %33, %34, %35, %36, %37, %38, %39, %40, %41, %42, %43, %44, %45, %46, %47, %48, %49, %50, %51, %52, %53, %54, %55, %56, %57, %58, %59, %60, %61, %62, %63}, {%88, %89, %90, %91}, dx1, 1, 1, 1, 0;\n"
      "wgmma.mma_async.sync.aligned.m64n64k16.f32.bf16.bf16 {%32, %33, %34, %35, %36, %37, %38, %39, %40, %41, %42, %43, %44, %45, %46, %47, %48, %49, %50, %51, %52, %53, %54, %55, %56, %57, %58, %59, %60, %61, %62, %63}, {%92, %93, %94, %95}, dx2, 1, 1, 1, 0;\n"
      "wgmma.mma_async.sync.aligned.m64n64k16.f32.bf16.bf16 {%32, %33, %34, %35, %36, %37, %38, %39, %40, %41, %42, %43, %44, %45, %46, %47, %48, %49, %50, %51, %52, %53, %54, %55, %56, %57, %58, %59, %60, %61, %62, %63}, {%96, %97, %98, %99}, dx3, 1, 1, 1, 0;\n"
      "wgmma.commit_group.sync.aligned;\n}\n"
      : "=f"(g[0]), "=f"(g[1]), "=f"(g[2]), "=f"(g[3]), "=f"(g[4]), "=f"(g[5]), "=f"(g[6]), "=f"(g[7]), "=f"(g[8]), "=f"(g[9]), "=f"(g[10]), "=f"(g[11]), "=f"(g[12]), "=f"(g[13]), "=f"(g[14]), "=f"(g[15]), "=f"(g[16]), "=f"(g[17]), "=f"(g[18]), "=f"(g[19]), "=f"(g[20]), "=f"(g[21]), "=f"(g[22]), "=f"(g[23]), "=f"(g[24]), "=f"(g[25]), "=f"(g[26]), "=f"(g[27]), "=f"(g[28]), "=f"(g[29]), "=f"(g[30]), "=f"(g[31]),
        "=f"(h[0]), "=f"(h[1]), "=f"(h[2]), "=f"(h[3]), "=f"(h[4]), "=f"(h[5]), "=f"(h[6]), "=f"(h[7]), "=f"(h[8]), "=f"(h[9]), "=f"(h[10]), "=f"(h[11]), "=f"(h[12]), "=f"(h[13]), "=f"(h[14]), "=f"(h[15]), "=f"(h[16]), "=f"(h[17]), "=f"(h[18]), "=f"(h[19]), "=f"(h[20]), "=f"(h[21]), "=f"(h[22]), "=f"(h[23]), "=f"(h[24]), "=f"(h[25]), "=f"(h[26]), "=f"(h[27]), "=f"(h[28]), "=f"(h[29]), "=f"(h[30]), "=f"(h[31])
      : "r"(w[0]), "r"(w[1]), "r"(w[2]), "r"(w[3]), "r"(w[4]), "r"(w[5]), "r"(w[6]), "r"(w[7]), "r"(w[8]), "r"(w[9]), "r"(w[10]), "r"(w[11]), "r"(w[12]), "r"(w[13]), "r"(w[14]), "r"(w[15]), "r"(w[16]), "r"(w[17]), "r"(w[18]), "r"(w[19]), "r"(w[20]), "r"(w[21]), "r"(w[22]), "r"(w[23]), "r"(w[24]), "r"(w[25]), "r"(w[26]), "r"(w[27]), "r"(w[28]), "r"(w[29]), "r"(w[30]), "r"(w[31]), "r"(w[32]), "r"(w[33]), "r"(w[34]), "r"(w[35]), "r"(w[36]), "r"(w[37]), "r"(w[38]), "r"(w[39]), "r"(dx), "l"(de), "l"(dh)
      : "memory");
  }
  static __device__ __forceinline__ void wait_g(float* g) {
    asm volatile("wgmma.wait_group.sync.aligned 1;\n"
      : "+f"(g[0]), "+f"(g[1]), "+f"(g[2]), "+f"(g[3]), "+f"(g[4]), "+f"(g[5]), "+f"(g[6]), "+f"(g[7]), "+f"(g[8]), "+f"(g[9]), "+f"(g[10]), "+f"(g[11]), "+f"(g[12]), "+f"(g[13]), "+f"(g[14]), "+f"(g[15]), "+f"(g[16]), "+f"(g[17]), "+f"(g[18]), "+f"(g[19]), "+f"(g[20]), "+f"(g[21]), "+f"(g[22]), "+f"(g[23]), "+f"(g[24]), "+f"(g[25]), "+f"(g[26]), "+f"(g[27]), "+f"(g[28]), "+f"(g[29]), "+f"(g[30]), "+f"(g[31])
      :: "memory");
  }
  static __device__ __forceinline__ void wait_h(float* h) {
    asm volatile("wgmma.wait_group.sync.aligned 0;\n"
      : "+f"(h[0]), "+f"(h[1]), "+f"(h[2]), "+f"(h[3]), "+f"(h[4]), "+f"(h[5]), "+f"(h[6]), "+f"(h[7]), "+f"(h[8]), "+f"(h[9]), "+f"(h[10]), "+f"(h[11]), "+f"(h[12]), "+f"(h[13]), "+f"(h[14]), "+f"(h[15]), "+f"(h[16]), "+f"(h[17]), "+f"(h[18]), "+f"(h[19]), "+f"(h[20]), "+f"(h[21]), "+f"(h[22]), "+f"(h[23]), "+f"(h[24]), "+f"(h[25]), "+f"(h[26]), "+f"(h[27]), "+f"(h[28]), "+f"(h[29]), "+f"(h[30]), "+f"(h[31])
      :: "memory");
  }
};
template<> struct TileMMA<9> {
  static __device__ __forceinline__ void issue(float* g, float* h, const uint32_t* w, uint32_t dx, uint64_t de, uint64_t dh, uint64_t dc) {
    asm volatile(
      "{\n.reg .b64 dx0, dx1, dx2, dx3;\n.reg .b32 l1, l2, l3, hx;\nmov.b32 hx, 0x40000040;\n"
      "add.u32 l1, %112, 2;\nadd.u32 l2, %112, 4;\nadd.u32 l3, %112, 6;\n"
      "mov.b64 dx0, {%112, hx};\nmov.b64 dx1, {l1, hx};\nmov.b64 dx2, {l2, hx};\nmov.b64 dx3, {l3, hx};\n"
      "wgmma.fence.sync.aligned;\n"
      "wgmma.mma_async.sync.aligned.m64n72k16.f32.bf16.bf16 {%0, %1, %2, %3, %4, %5, %6, %7, %8, %9, %10, %11, %12, %13, %14, %15, %16, %17, %18, %19, %20, %21, %22, %23, %24, %25, %26, %27, %28, %29, %30, %31, %32, %33, %34, %35}, {%108, %109, %110, %111}, %114, 0, 1, 1, 0;\n"
      "wgmma.mma_async.sync.aligned.m64n72k16.f32.bf16.bf16 {%0, %1, %2, %3, %4, %5, %6, %7, %8, %9, %10, %11, %12, %13, %14, %15, %16, %17, %18, %19, %20, %21, %22, %23, %24, %25, %26, %27, %28, %29, %30, %31, %32, %33, %34, %35}, {%88, %89, %90, %91}, %113, 1, 1, 1, 0;\n"
      "wgmma.mma_async.sync.aligned.m64n72k16.f32.bf16.bf16 {%0, %1, %2, %3, %4, %5, %6, %7, %8, %9, %10, %11, %12, %13, %14, %15, %16, %17, %18, %19, %20, %21, %22, %23, %24, %25, %26, %27, %28, %29, %30, %31, %32, %33, %34, %35}, {%72, %73, %74, %75}, dx0, 1, 1, 1, 0;\n"
      "wgmma.mma_async.sync.aligned.m64n72k16.f32.bf16.bf16 {%0, %1, %2, %3, %4, %5, %6, %7, %8, %9, %10, %11, %12, %13, %14, %15, %16, %17, %18, %19, %20, %21, %22, %23, %24, %25, %26, %27, %28, %29, %30, %31, %32, %33, %34, %35}, {%76, %77, %78, %79}, dx1, 1, 1, 1, 0;\n"
      "wgmma.mma_async.sync.aligned.m64n72k16.f32.bf16.bf16 {%0, %1, %2, %3, %4, %5, %6, %7, %8, %9, %10, %11, %12, %13, %14, %15, %16, %17, %18, %19, %20, %21, %22, %23, %24, %25, %26, %27, %28, %29, %30, %31, %32, %33, %34, %35}, {%80, %81, %82, %83}, dx2, 1, 1, 1, 0;\n"
      "wgmma.mma_async.sync.aligned.m64n72k16.f32.bf16.bf16 {%0, %1, %2, %3, %4, %5, %6, %7, %8, %9, %10, %11, %12, %13, %14, %15, %16, %17, %18, %19, %20, %21, %22, %23, %24, %25, %26, %27, %28, %29, %30, %31, %32, %33, %34, %35}, {%84, %85, %86, %87}, dx3, 1, 1, 1, 0;\n"
      "wgmma.commit_group.sync.aligned;\n"
      "wgmma.mma_async.sync.aligned.m64n72k16.f32.bf16.bf16 {%36, %37, %38, %39, %40, %41, %42, %43, %44, %45, %46, %47, %48, %49, %50, %51, %52, %53, %54, %55, %56, %57, %58, %59, %60, %61, %62, %63, %64, %65, %66, %67, %68, %69, %70, %71}, {%92, %93, %94, %95}, dx0, 0, 1, 1, 0;\n"
      "wgmma.mma_async.sync.aligned.m64n72k16.f32.bf16.bf16 {%36, %37, %38, %39, %40, %41, %42, %43, %44, %45, %46, %47, %48, %49, %50, %51, %52, %53, %54, %55, %56, %57, %58, %59, %60, %61, %62, %63, %64, %65, %66, %67, %68, %69, %70, %71}, {%96, %97, %98, %99}, dx1, 1, 1, 1, 0;\n"
      "wgmma.mma_async.sync.aligned.m64n72k16.f32.bf16.bf16 {%36, %37, %38, %39, %40, %41, %42, %43, %44, %45, %46, %47, %48, %49, %50, %51, %52, %53, %54, %55, %56, %57, %58, %59, %60, %61, %62, %63, %64, %65, %66, %67, %68, %69, %70, %71}, {%100, %101, %102, %103}, dx2, 1, 1, 1, 0;\n"
      "wgmma.mma_async.sync.aligned.m64n72k16.f32.bf16.bf16 {%36, %37, %38, %39, %40, %41, %42, %43, %44, %45, %46, %47, %48, %49, %50, %51, %52, %53, %54, %55, %56, %57, %58, %59, %60, %61, %62, %63, %64, %65, %66, %67, %68, %69, %70, %71}, {%104, %105, %106, %107}, dx3, 1, 1, 1, 0;\n"
      "wgmma.commit_group.sync.aligned;\n}\n"
      : "=f"(g[0]), "=f"(g[1]), "=f"(g[2]), "=f"(g[3]), "=f"(g[4]), "=f"(g[5]), "=f"(g[6]), "=f"(g[7]), "=f"(g[8]), "=f"(g[9]), "=f"(g[10]), "=f"(g[11]), "=f"(g[12]), "=f"(g[13]), "=f"(g[14]), "=f"(g[15]), "=f"(g[16]), "=f"(g[17]), "=f"(g[18]), "=f"(g[19]), "=f"(g[20]), "=f"(g[21]), "=f"(g[22]), "=f"(g[23]), "=f"(g[24]), "=f"(g[25]), "=f"(g[26]), "=f"(g[27]), "=f"(g[28]), "=f"(g[29]), "=f"(g[30]), "=f"(g[31]), "=f"(g[32]), "=f"(g[33]), "=f"(g[34]), "=f"(g[35]),
        "=f"(h[0]), "=f"(h[1]), "=f"(h[2]), "=f"(h[3]), "=f"(h[4]), "=f"(h[5]), "=f"(h[6]), "=f"(h[7]), "=f"(h[8]), "=f"(h[9]), "=f"(h[10]), "=f"(h[11]), "=f"(h[12]), "=f"(h[13]), "=f"(h[14]), "=f"(h[15]), "=f"(h[16]), "=f"(h[17]), "=f"(h[18]), "=f"(h[19]), "=f"(h[20]), "=f"(h[21]), "=f"(h[22]), "=f"(h[23]), "=f"(h[24]), "=f"(h[25]), "=f"(h[26]), "=f"(h[27]), "=f"(h[28]), "=f"(h[29]), "=f"(h[30]), "=f"(h[31]), "=f"(h[32]), "=f"(h[33]), "=f"(h[34]), "=f"(h[35])
      : "r"(w[0]), "r"(w[1]), "r"(w[2]), "r"(w[3]), "r"(w[4]), "r"(w[5]), "r"(w[6]), "r"(w[7]), "r"(w[8]), "r"(w[9]), "r"(w[10]), "r"(w[11]), "r"(w[12]), "r"(w[13]), "r"(w[14]), "r"(w[15]), "r"(w[16]), "r"(w[17]), "r"(w[18]), "r"(w[19]), "r"(w[20]), "r"(w[21]), "r"(w[22]), "r"(w[23]), "r"(w[24]), "r"(w[25]), "r"(w[26]), "r"(w[27]), "r"(w[28]), "r"(w[29]), "r"(w[30]), "r"(w[31]), "r"(w[32]), "r"(w[33]), "r"(w[34]), "r"(w[35]), "r"(w[36]), "r"(w[37]), "r"(w[38]), "r"(w[39]), "r"(dx), "l"(de), "l"(dh)
      : "memory");
  }
  static __device__ __forceinline__ void wait_g(float* g) {
    asm volatile("wgmma.wait_group.sync.aligned 1;\n"
      : "+f"(g[0]), "+f"(g[1]), "+f"(g[2]), "+f"(g[3]), "+f"(g[4]), "+f"(g[5]), "+f"(g[6]), "+f"(g[7]), "+f"(g[8]), "+f"(g[9]), "+f"(g[10]), "+f"(g[11]), "+f"(g[12]), "+f"(g[13]), "+f"(g[14]), "+f"(g[15]), "+f"(g[16]), "+f"(g[17]), "+f"(g[18]), "+f"(g[19]), "+f"(g[20]), "+f"(g[21]), "+f"(g[22]), "+f"(g[23]), "+f"(g[24]), "+f"(g[25]), "+f"(g[26]), "+f"(g[27]), "+f"(g[28]), "+f"(g[29]), "+f"(g[30]), "+f"(g[31]), "+f"(g[32]), "+f"(g[33]), "+f"(g[34]), "+f"(g[35])
      :: "memory");
  }
  static __device__ __forceinline__ void wait_h(float* h) {
    asm volatile("wgmma.wait_group.sync.aligned 0;\n"
      : "+f"(h[0]), "+f"(h[1]), "+f"(h[2]), "+f"(h[3]), "+f"(h[4]), "+f"(h[5]), "+f"(h[6]), "+f"(h[7]), "+f"(h[8]), "+f"(h[9]), "+f"(h[10]), "+f"(h[11]), "+f"(h[12]), "+f"(h[13]), "+f"(h[14]), "+f"(h[15]), "+f"(h[16]), "+f"(h[17]), "+f"(h[18]), "+f"(h[19]), "+f"(h[20]), "+f"(h[21]), "+f"(h[22]), "+f"(h[23]), "+f"(h[24]), "+f"(h[25]), "+f"(h[26]), "+f"(h[27]), "+f"(h[28]), "+f"(h[29]), "+f"(h[30]), "+f"(h[31]), "+f"(h[32]), "+f"(h[33]), "+f"(h[34]), "+f"(h[35])
      :: "memory");
  }
};
template<> struct TileMMA<10> {
  static __device__ __forceinline__ void issue(float* g, float* h, const uint32_t* w, uint32_t dx, uint64_t de, uint64_t dh, uint64_t dc) {
    asm volatile(
      "{\n.reg .b64 dx0, dx1, dx2, dx3;\n.reg .b32 l1, l2, l3, hx;\nmov.b32 hx, 0x40000040;\n"
      "add.u32 l1, %120, 2;\nadd.u32 l2, %120, 4;\nadd.u32 l3, %120, 6;\n"
      "mov.b64 dx0, {%120, hx};\nmov.b64 dx1, {l1, hx};\nmov.b64 dx2, {l2, hx};\nmov.b64 dx3, {l3, hx};\n"
      "wgmma.fence.sync.aligned;\n"
      "wgmma.mma_async.sync.aligned.m64n80k16.f32.bf16.bf16 {%0, %1, %2, %3, %4, %5, %6, %7, %8, %9, %10, %11, %12, %13, %14, %15, %16, %17, %18, %19, %20, %21, %22, %23, %24, %25, %26, %27, %28, %29, %30, %31, %32, %33, %34, %35, %36, %37, %38, %39}, {%116, %117, %118, %119}, %122, 0, 1, 1, 0;\n"
      "wgmma.mma_async.sync.aligned.m64n80k16.f32.bf16.bf16 {%0, %1, %2, %3, %4, %5, %6, %7, %8, %9, %10, %11, %12, %13, %14, %15, %16, %17, %18, %19, %20, %21, %22, %23, %24, %25, %26, %27, %28, %29, %30, %31, %32, %33, %34, %35, %36, %37, %38, %39}, {%96, %97, %98, %99}, %121, 1, 1, 1, 0;\n"
      "wgmma.mma_async.sync.aligned.m64n80k16.f32.bf16.bf16 {%0, %1, %2, %3, %4, %5, %6, %7, %8, %9, %10, %11, %12, %13, %14, %15, %16, %17, %18, %19, %20, %21, %22, %23, %24, %25, %26, %27, %28, %29, %30, %31, %32, %33, %34, %35, %36, %37, %38, %39}, {%80, %81, %82, %83}, dx0, 1, 1, 1, 0;\n"
      "wgmma.mma_async.sync.aligned.m64n80k16.f32.bf16.bf16 {%0, %1, %2, %3, %4, %5, %6, %7, %8, %9, %10, %11, %12, %13, %14, %15, %16, %17, %18, %19, %20, %21, %22, %23, %24, %25, %26, %27, %28, %29, %30, %31, %32, %33, %34, %35, %36, %37, %38, %39}, {%84, %85, %86, %87}, dx1, 1, 1, 1, 0;\n"
      "wgmma.mma_async.sync.aligned.m64n80k16.f32.bf16.bf16 {%0, %1, %2, %3, %4, %5, %6, %7, %8, %9, %10, %11, %12, %13, %14, %15, %16, %17, %18, %19, %20, %21, %22, %23, %24, %25, %26, %27, %28, %29, %30, %31, %32, %33, %34, %35, %36, %37, %38, %39}, {%88, %89, %90, %91}, dx2, 1, 1, 1, 0;\n"
      "wgmma.mma_async.sync.aligned.m64n80k16.f32.bf16.bf16 {%0, %1, %2, %3, %4, %5, %6, %7, %8, %9, %10, %11, %12, %13, %14, %15, %16, %17, %18, %19, %20, %21, %22, %23, %24, %25, %26, %27, %28, %29, %30, %31, %32, %33, %34, %35, %36, %37, %38, %39}, {%92, %93, %94, %95}, dx3, 1, 1, 1, 0;\n"
      "wgmma.commit_group.sync.aligned;\n"
      "wgmma.mma_async.sync.aligned.m64n80k16.f32.bf16.bf16 {%40, %41, %42, %43, %44, %45, %46, %47, %48, %49, %50, %51, %52, %53, %54, %55, %56, %57, %58, %59, %60, %61, %62, %63, %64, %65, %66, %67, %68, %69, %70, %71, %72, %73, %74, %75, %76, %77, %78, %79}, {%100, %101, %102, %103}, dx0, 0, 1, 1, 0;\n"
      "wgmma.mma_async.sync.aligned.m64n80k16.f32.bf16.bf16 {%40, %41, %42, %43, %44, %45, %46, %47, %48, %49, %50, %51, %52, %53, %54, %55, %56, %57, %58, %59, %60, %61, %62, %63, %64, %65, %66, %67, %68, %69, %70, %71, %72, %73, %74, %75, %76, %77, %78, %79}, {%104, %105, %106, %107}, dx1, 1, 1, 1, 0;\n"
      "wgmma.mma_async.sync.aligned.m64n80k16.f32.bf16.bf16 {%40, %41, %42, %43, %44, %45, %46, %47, %48, %49, %50, %51, %52, %53, %54, %55, %56, %57, %58, %59, %60, %61, %62, %63, %64, %65, %66, %67, %68, %69, %70, %71, %72, %73, %74, %75, %76, %77, %78, %79}, {%108, %109, %110, %111}, dx2, 1, 1, 1, 0;\n"
      "wgmma.mma_async.sync.aligned.m64n80k16.f32.bf16.bf16 {%40, %41, %42, %43, %44, %45, %46, %47, %48, %49, %50, %51, %52, %53, %54, %55, %56, %57, %58, %59, %60, %61, %62, %63, %64, %65, %66, %67, %68, %69, %70, %71, %72, %73, %74, %75, %76, %77, %78, %79}, {%112, %113, %114, %115}, dx3, 1, 1, 1, 0;\n"
      "wgmma.commit_group.sync.aligned;\n}\n"
      : "=f"(g[0]), "=f"(g[1]), "=f"(g[2]), "=f"(g[3]), "=f"(g[4]), "=f"(g[5]), "=f"(g[6]), "=f"(g[7]), "=f"(g[8]), "=f"(g[9]), "=f"(g[10]), "=f"(g[11]), "=f"(g[12]), "=f"(g[13]), "=f"(g[14]), "=f"(g[15]), "=f"(g[16]), "=f"(g[17]), "=f"(g[18]), "=f"(g[19]), "=f"(g[20]), "=f"(g[21]), "=f"(g[22]), "=f"(g[23]), "=f"(g[24]), "=f"(g[25]), "=f"(g[26]), "=f"(g[27]), "=f"(g[28]), "=f"(g[29]), "=f"(g[30]), "=f"(g[31]), "=f"(g[32]), "=f"(g[33]), "=f"(g[34]), "=f"(g[35]), "=f"(g[36]), "=f"(g[37]), "=f"(g[38]), "=f"(g[39]),
        "=f"(h[0]), "=f"(h[1]), "=f"(h[2]), "=f"(h[3]), "=f"(h[4]), "=f"(h[5]), "=f"(h[6]), "=f"(h[7]), "=f"(h[8]), "=f"(h[9]), "=f"(h[10]), "=f"(h[11]), "=f"(h[12]), "=f"(h[13]), "=f"(h[14]), "=f"(h[15]), "=f"(h[16]), "=f"(h[17]), "=f"(h[18]), "=f"(h[19]), "=f"(h[20]), "=f"(h[21]), "=f"(h[22]), "=f"(h[23]), "=f"(h[24]), "=f"(h[25]), "=f"(h[26]), "=f"(h[27]), "=f"(h[28]), "=f"(h[29]), "=f"(h[30]), "=f"(h[31]), "=f"(h[32]), "=f"(h[33]), "=f"(h[34]), "=f"(h[35]), "=f"(h[36]), "=f"(h[37]), "=f"(h[38]), "=f"(h[39])
      : "r"(w[0]), "r"(w[1]), "r"(w[2]), "r"(w[3]), "r"(w[4]), "r"(w[5]), "r"(w[6]), "r"(w[7]), "r"(w[8]), "r"(w[9]), "r"(w[10]), "r"(w[11]), "r"(w[12]), "r"(w[13]), "r"(w[14]), "r"(w[15]), "r"(w[16]), "r"(w[17]), "r"(w[18]), "r"(w[19]), "r"(w[20]), "r"(w[21]), "r"(w[22]), "r"(w[23]), "r"(w[24]), "r"(w[25]), "r"(w[26]), "r"(w[27]), "r"(w[28]), "r"(w[29]), "r"(w[30]), "r"(w[31]), "r"(w[32]), "r"(w[33]), "r"(w[34]), "r"(w[35]), "r"(w[36]), "r"(w[37]), "r"(w[38]), "r"(w[39]), "r"(dx), "l"(de), "l"(dh)
      : "memory");
  }
  static __device__ __forceinline__ void wait_g(float* g) {
    asm volatile("wgmma.wait_group.sync.aligned 1;\n"
      : "+f"(g[0]), "+f"(g[1]), "+f"(g[2]), "+f"(g[3]), "+f"(g[4]), "+f"(g[5]), "+f"(g[6]), "+f"(g[7]), "+f"(g[8]), "+f"(g[9]), "+f"(g[10]), "+f"(g[11]), "+f"(g[12]), "+f"(g[13]), "+f"(g[14]), "+f"(g[15]), "+f"(g[16]), "+f"(g[17]), "+f"(g[18]), "+f"(g[19]), "+f"(g[20]), "+f"(g[21]), "+f"(g[22]), "+f"(g[23]), "+f"(g[24]), "+f"(g[25]), "+f"(g[26]), "+f"(g[27]), "+f"(g[28]), "+f"(g[29]), "+f"(g[30]), "+f"(g[31]), "+f"(g[32]), "+f"(g[33]), "+f"(g[34]), "+f"(g[35]), "+f"(g[36]), "+f"(g[37]), "+f"(g[38]), "+f"(g[39])
      :: "memory");
  }
  static __device__ __forceinline__ void wait_h(float* h) {
    asm volatile("wgmma.wait_group.sync.aligned 0;\n"
      : "+f"(h[0]), "+f"(h[1]), "+f"(h[2]), "+f"(h[3]), "+f"(h[4]), "+f"(h[5]), "+f"(h[6]), "+f"(h[7]), "+f"(h[8]), "+f"(h[9]), "+f"(h[10]), "+f"(h[11]), "+f"(h[12]), "+f"(h[13]), "+f"(h[14]), "+f"(h[15]), "+f"(h[16]), "+f"(h[17]), "+f"(h[18]), "+f"(h[19]), "+f"(h[20]), "+f"(h[21]), "+f"(h[22]), "+f"(h[23]), "+f"(h[24]), "+f"(h[25]), "+f"(h[26]), "+f"(h[27]), "+f"(h[28]), "+f"(h[29]), "+f"(h[30]), "+f"(h[31]), "+f"(h[32]), "+f"(h[33]), "+f"(h[34]), "+f"(h[35]), "+f"(h[36]), "+f"(h[37]), "+f"(h[38]), "+f"(h[39])
      :: "memory");
  }
};
template<> struct TileMMA<11> {
  static __device__ __forceinline__ void issue(float* g, float* h, const uint32_t* w, uint32_t dx, uint64_t de, uint64_t dh, uint64_t dc) {
    asm volatile(
      "{\n.reg .b64 dx0, dx1, dx2, dx3;\n.reg .b32 l1, l2, l3, hx;\nmov.b32 hx, 0x40000040;\n"
      "add.u32 l1, %124, 2;\nadd.u32 l2, %124, 4;\nadd.u32 l3, %124, 6;\n"
      "mov.b64 dx0, {%124, hx};\nmov.b64 dx1, {l1, hx};\nmov.b64 dx2, {l2, hx};\nmov.b64 dx3, {l3, hx};\n"
      "wgmma.fence.sync.aligned;\n"
      "wgmma.mma_async.sync.aligned.m64n88k16.f32.bf16.bf16 {%0, %1, %2, %3, %4, %5, %6, %7, %8, %9, %10, %11, %12, %13, %14, %15, %16, %17, %18, %19, %20, %21, %22, %23, %24, %25, %26, %27, %28, %29, %30, %31, %32, %33, %34, %35, %36, %37, %38, %39, %40, %41, %42, %43}, {%120, %121, %122, %123}, %126, 0, 1, 1, 0;\n"
      "wgmma.mma_async.sync.aligned.m64n88k16.f32.bf16.bf16 {%0, %1, %2, %3, %4, %5, %6, %7, %8, %9, %10, %11, %12, %13, %14, %15, %16, %17, %18, %19, %20, %21, %22, %23, %24, %25, %26, %27, %28, %29, %30, %31, %32, %33, %34, %35, %36, %37, %38, %39, %40, %41, %42, %43}, %127, %125, 1, 1, 1, 0, 0;\n"
      "wgmma.mma_async.sync.aligned.m64n88k16.f32.bf16.bf16 {%0, %1, %2, %3, %4, %5, %6, %7, %8, %9, %10, %11, %12, %13, %14, %15, %16, %17, %18, %19, %20, %21, %22, %23, %24, %25, %26, %27, %28, %29, %30, %31, %32, %33, %34, %35, %36, %37, %38, %39, %40, %41, %42, %43}, {%88, %89, %90, %91}, dx0, 1, 1, 1, 0;\n"
      "wgmma.mma_async.sync.aligned.m64n88k16.f32.bf16.bf16 {%0, %1, %2, %3, %4, %5, %6, %7, %8, %9, %10, %11, %12, %13, %14, %15, %16, %17, %18, %19, %20, %21, %22, %23, %24, %25, %26, %27, %28, %29, %30, %31, %32, %33, %34, %35, %36, %37, %38, %39, %40, %41, %42, %43}, {%92, %93, %94, %95}, dx1, 1, 1, 1, 0;\n"
      "wgmma.mma_async.sync.aligned.m64n88k16.f32.bf16.bf16 {%0, %1, %2, %3, %4, %5, %6, %7, %8, %9, %10, %11, %12, %13, %14, %15, %16, %17, %18, %19, %20, %21, %22, %23, %24, %25, %26, %27, %28, %29, %30, %31, %32, %33, %34, %35, %36, %37, %38, %39, %40, %41, %42, %43}, {%96, %97, %98, %99}, dx2, 1, 1, 1, 0;\n"
      "wgmma.mma_async.sync.aligned.m64n88k16.f32.bf16.bf16 {%0, %1, %2, %3, %4, %5, %6, %7, %8, %9, %10, %11, %12, %13, %14, %15, %16, %17, %18, %19, %20, %21, %22, %23, %24, %25, %26, %27, %28, %29, %30, %31, %32, %33, %34, %35, %36, %37, %38, %39, %40, %41, %42, %43}, {%100, %101, %102, %103}, dx3, 1, 1, 1, 0;\n"
      "wgmma.commit_group.sync.aligned;\n"
      "wgmma.mma_async.sync.aligned.m64n88k16.f32.bf16.bf16 {%44, %45, %46, %47, %48, %49, %50, %51, %52, %53, %54, %55, %56, %57, %58, %59, %60, %61, %62, %63, %64, %65, %66, %67, %68, %69, %70, %71, %72, %73, %74, %75, %76, %77, %78, %79, %80, %81, %82, %83, %84, %85, %86, %87}, {%104, %105, %106, %107}, dx0, 0, 1, 1, 0;\n"
      "wgmma.mma_async.sync.aligned.m64n88k16.f32.bf16.bf16 {%44, %45, %46, %47, %48, %49, %50, %51, %52, %53, %54, %55, %56, %57, %58, %59, %60, %61, %62, %63, %64, %65, %66, %67, %68, %69, %70, %71, %72, %73, %74, %75, %76, %77, %78, %79, %80, %81, %82, %83, %84, %85, %86, %87}, {%108, %109, %110, %111}, dx1, 1, 1, 1, 0;\n"
      "wgmma.mma_async.sync.aligned.m64n88k16.f32.bf16.bf16 {%44, %45, %46, %47, %48, %49, %50, %51, %52, %53, %54, %55, %56, %57, %58, %59, %60, %61, %62, %63, %64, %65, %66, %67, %68, %69, %70, %71, %72, %73, %74, %75, %76, %77, %78, %79, %80, %81, %82, %83, %84, %85, %86, %87}, {%112, %113, %114, %115}, dx2, 1, 1, 1, 0;\n"
      "wgmma.mma_async.sync.aligned.m64n88k16.f32.bf16.bf16 {%44, %45, %46, %47, %48, %49, %50, %51, %52, %53, %54, %55, %56, %57, %58, %59, %60, %61, %62, %63, %64, %65, %66, %67, %68, %69, %70, %71, %72, %73, %74, %75, %76, %77, %78, %79, %80, %81, %82, %83, %84, %85, %86, %87}, {%116, %117, %118, %119}, dx3, 1, 1, 1, 0;\n"
      "wgmma.commit_group.sync.aligned;\n}\n"
      : "=f"(g[0]), "=f"(g[1]), "=f"(g[2]), "=f"(g[3]), "=f"(g[4]), "=f"(g[5]), "=f"(g[6]), "=f"(g[7]), "=f"(g[8]), "=f"(g[9]), "=f"(g[10]), "=f"(g[11]), "=f"(g[12]), "=f"(g[13]), "=f"(g[14]), "=f"(g[15]), "=f"(g[16]), "=f"(g[17]), "=f"(g[18]), "=f"(g[19]), "=f"(g[20]), "=f"(g[21]), "=f"(g[22]), "=f"(g[23]), "=f"(g[24]), "=f"(g[25]), "=f"(g[26]), "=f"(g[27]), "=f"(g[28]), "=f"(g[29]), "=f"(g[30]), "=f"(g[31]), "=f"(g[32]), "=f"(g[33]), "=f"(g[34]), "=f"(g[35]), "=f"(g[36]), "=f"(g[37]), "=f"(g[38]), "=f"(g[39]), "=f"(g[40]), "=f"(g[41]), "=f"(g[42]), "=f"(g[43]),
        "=f"(h[0]), "=f"(h[1]), "=f"(h[2]), "=f"(h[3]), "=f"(h[4]), "=f"(h[5]), "=f"(h[6]), "=f"(h[7]), "=f"(h[8]), "=f"(h[9]), "=f"(h[10]), "=f"(h[11]), "=f"(h[12]), "=f"(h[13]), "=f"(h[14]), "=f"(h[15]), "=f"(h[16]), "=f"(h[17]), "=f"(h[18]), "=f"(h[19]), "=f"(h[20]), "=f"(h[21]), "=f"(h[22]), "=f"(h[23]), "=f"(h[24]), "=f"(h[25]), "=f"(h[26]), "=f"(h[27]), "=f"(h[28]), "=f"(h[29]), "=f"(h[30]), "=f"(h[31]), "=f"(h[32]), "=f"(h[33]), "=f"(h[34]), "=f"(h[35]), "=f"(h[36]), "=f"(h[37]), "=f"(h[38]), "=f"(h[39]), "=f"(h[40]), "=f"(h[41]), "=f"(h[42]), "=f"(h[43])
      : "r"(w[0]), "r"(w[1]), "r"(w[2]), "r"(w[3]), "r"(w[4]), "r"(w[5]), "r"(w[6]), "r"(w[7]), "r"(w[8]), "r"(w[9]), "r"(w[10]), "r"(w[11]), "r"(w[12]), "r"(w[13]), "r"(w[14]), "r"(w[15]), "r"(w[20]), "r"(w[21]), "r"(w[22]), "r"(w[23]), "r"(w[24]), "r"(w[25]), "r"(w[26]), "r"(w[27]), "r"(w[28]), "r"(w[29]), "r"(w[30]), "r"(w[31]), "r"(w[32]), "r"(w[33]), "r"(w[34]), "r"(w[35]), "r"(w[36]), "r"(w[37]), "r"(w[38]), "r"(w[39]), "r"(dx), "l"(de), "l"(dh), "l"(dc)
      : "memory");
  }
  static __device__ __forceinline__ void wait_g(float* g) {
    asm volatile("wgmma.wait_group.sync.aligned 1;\n"
      : "+f"(g[0]), "+f"(g[1]), "+f"(g[2]), "+f"(g[3]), "+f"(g[4]), "+f"(g[5]), "+f"(g[6]), "+f"(g[7]), "+f"(g[8]), "+f"(g[9]), "+f"(g[10]), "+f"(g[11]), "+f"(g[12]), "+f"(g[13]), "+f"(g[14]), "+f"(g[15]), "+f"(g[16]), "+f"(g[17]), "+f"(g[18]), "+f"(g[19]), "+f"(g[20]), "+f"(g[21]), "+f"(g[22]), "+f"(g[23]), "+f"(g[24]), "+f"(g[25]), "+f"(g[26]), "+f"(g[27]), "+f"(g[28]), "+f"(g[29]), "+f"(g[30]), "+f"(g[31]), "+f"(g[32]), "+f"(g[33]), "+f"(g[34]), "+f"(g[35]), "+f"(g[36]), "+f"(g[37]), "+f"(g[38]), "+f"(g[39]), "+f"(g[40]), "+f"(g[41]), "+f"(g[42]), "+f"(g[43])
      :: "memory");
  }
  static __device__ __forceinline__ void wait_h(float* h) {
    asm volatile("wgmma.wait_group.sync.aligned 0;\n"
      : "+f"(h[0]), "+f"(h[1]), "+f"(h[2]), "+f"(h[3]), "+f"(h[4]), "+f"(h[5]), "+f"(h[6]), "+f"(h[7]), "+f"(h[8]), "+f"(h[9]), "+f"(h[10]), "+f"(h[11]), "+f"(h[12]), "+f"(h[13]), "+f"(h[14]), "+f"(h[15]), "+f"(h[16]), "+f"(h[17]), "+f"(h[18]), "+f"(h[19]), "+f"(h[20]), "+f"(h[21]), "+f"(h[22]), "+f"(h[23]), "+f"(h[24]), "+f"(h[25]), "+f"(h[26]), "+f"(h[27]), "+f"(h[28]), "+f"(h[29]), "+f"(h[30]), "+f"(h[31]), "+f"(h[32]), "+f"(h[33]), "+f"(h[34]), "+f"(h[35]), "+f"(h[36]), "+f"(h[37]), "+f"(h[38]), "+f"(h[39]), "+f"(h[40]), "+f"(h[41]), "+f"(h[42]), "+f"(h[43])
      :: "memory");
  }
};
__device__ __forceinline__ void node_mma(float* g, const uint32_t* w, uint64_t dx) {
    asm volatile(
      "{\n.reg .b64 dx1, dx2, dx3;\n"
      "add.s64 dx1, %48, 2;\nadd.s64 dx2, %48, 4;\nadd.s64 dx3, %48, 6;\n"
      "wgmma.fence.sync.aligned;\n"
      "wgmma.mma_async.sync.aligned.m64n64k16.f32.bf16.bf16 {%0, %1, %2, %3, %4, %5, %6, %7, %8, %9, %10, %11, %12, %13, %14, %15, %16, %17, %18, %19, %20, %21, %22, %23, %24, %25, %26, %27, %28, %29, %30, %31}, {%32, %33, %34, %35}, %48, 0, 1, 1, 0;\n"
      "wgmma.mma_async.sync.aligned.m64n64k16.f32.bf16.bf16 {%0, %1, %2, %3, %4, %5, %6, %7, %8, %9, %10, %11, %12, %13, %14, %15, %16, %17, %18, %19, %20, %21, %22, %23, %24, %25, %26, %27, %28, %29, %30, %31}, {%36, %37, %38, %39}, dx1, 1, 1, 1, 0;\n"
      "wgmma.mma_async.sync.aligned.m64n64k16.f32.bf16.bf16 {%0, %1, %2, %3, %4, %5, %6, %7, %8, %9, %10, %11, %12, %13, %14, %15, %16, %17, %18, %19, %20, %21, %22, %23, %24, %25, %26, %27, %28, %29, %30, %31}, {%40, %41, %42, %43}, dx2, 1, 1, 1, 0;\n"
      "wgmma.mma_async.sync.aligned.m64n64k16.f32.bf16.bf16 {%0, %1, %2, %3, %4, %5, %6, %7, %8, %9, %10, %11, %12, %13, %14, %15, %16, %17, %18, %19, %20, %21, %22, %23, %24, %25, %26, %27, %28, %29, %30, %31}, {%44, %45, %46, %47}, dx3, 1, 1, 1, 0;\n"
      "wgmma.commit_group.sync.aligned;\n}\n"
      : "=f"(g[0]), "=f"(g[1]), "=f"(g[2]), "=f"(g[3]), "=f"(g[4]), "=f"(g[5]), "=f"(g[6]), "=f"(g[7]), "=f"(g[8]), "=f"(g[9]), "=f"(g[10]), "=f"(g[11]), "=f"(g[12]), "=f"(g[13]), "=f"(g[14]), "=f"(g[15]), "=f"(g[16]), "=f"(g[17]), "=f"(g[18]), "=f"(g[19]), "=f"(g[20]), "=f"(g[21]), "=f"(g[22]), "=f"(g[23]), "=f"(g[24]), "=f"(g[25]), "=f"(g[26]), "=f"(g[27]), "=f"(g[28]), "=f"(g[29]), "=f"(g[30]), "=f"(g[31])
      : "r"(w[0]), "r"(w[1]), "r"(w[2]), "r"(w[3]), "r"(w[4]), "r"(w[5]), "r"(w[6]), "r"(w[7]), "r"(w[8]), "r"(w[9]), "r"(w[10]), "r"(w[11]), "r"(w[12]), "r"(w[13]), "r"(w[14]), "r"(w[15]), "l"(dx)
      : "memory");
}

__device__ __forceinline__ uint32_t smem_u32(const void* p) { return (uint32_t)__cvta_generic_to_shared(p); }
__device__ __forceinline__ float ex2f(float x) { float y; asm("ex2.approx.ftz.f32 %0, %1;" : "=f"(y) : "f"(x)); return y; }
__device__ __forceinline__ float rcpf(float x) { float y; asm("rcp.approx.ftz.f32 %0, %1;" : "=f"(y) : "f"(x)); return y; }
__device__ __forceinline__ uint32_t pack_bf16(float lo, float hi) {
    uint32_t r; asm("cvt.rn.bf16x2.f32 %0, %1, %2;" : "=r"(r) : "f"(hi), "f"(lo)); return r;
}
__device__ __forceinline__ float bf_lo(uint32_t v) { return __uint_as_float(v << 16); }
__device__ __forceinline__ float bf_hi(uint32_t v) { return __uint_as_float(v & 0xFFFF0000u); }
template<int STRIDE>
__device__ __forceinline__ void cp16i(uint32_t dst, const char* base, uint32_t idx) {
    asm volatile("{\n.reg .b64 a;\nmad.wide.u32 a, %2, %3, %1;\ncp.async.cg.shared.global [%0], [a], 16;\n}\n" :: "r"(dst), "l"(base), "r"(idx), "n"(STRIDE) : "memory");
}
__device__ __forceinline__ void cp16e(uint32_t dst, const char* base, uint32_t idx, uint64_t pol) {
    asm volatile("{\n.reg .b64 a;\nmad.wide.u32 a, %2, 32, %1;\ncp.async.cg.shared.global.L2::cache_hint [%0], [a], 16, %3;\n}\n" :: "r"(dst), "l"(base), "r"(idx), "l"(pol) : "memory");
}
template<int STRIDE>
__device__ __forceinline__ void cp16z(uint32_t dst, const char* base, uint32_t idx, int k, int n, uint64_t pol) {
    if (STRIDE == 32)
        asm volatile("{\n.reg .b64 a;\n.reg .pred p;\nsetp.ge.s32 p, %3, %4;\nmad.wide.u32 a, %2, 32, %1;\ncp.async.cg.shared.global.L2::cache_hint [%0], [a], 16, p, %5;\n}\n"
                     :: "r"(dst), "l"(base), "r"(idx), "r"(k), "r"(n), "l"(pol) : "memory");
    else
        asm volatile("{\n.reg .b64 a;\n.reg .pred p;\nsetp.ge.s32 p, %3, %4;\nmad.wide.u32 a, %2, 128, %1;\ncp.async.cg.shared.global [%0], [a], 16, p;\n}\n"
                     :: "r"(dst), "l"(base), "r"(idx), "r"(k), "r"(n) : "memory");
}
template<int HI, bool Z>
__device__ __forceinline__ void cpx(uint32_t hi, uint32_t dst, uint32_t p, uint32_t lo, int k, int n) {
    if (Z) asm volatile("{\n.reg .b32 l;\n.reg .b64 a;\n.reg .pred q;\nsetp.ge.s32 q, %5, %6;\ndp2a.lo.u32.u32 l, %1, %2, %3;\nmov.b64 a, {l, %0};\ncp.async.cg.shared.global [%4], [a], 16, q;\n}\n"
                        :: "r"(hi), "r"(p), "r"(HI ? 0x8000u : 0x80u), "r"(lo), "r"(dst), "r"(k), "r"(n) : "memory");
    else asm volatile("{\n.reg .b32 l;\n.reg .b64 a;\ndp2a.lo.u32.u32 l, %1, %2, %3;\nmov.b64 a, {l, %0};\ncp.async.cg.shared.global [%4], [a], 16;\n}\n"
                      :: "r"(hi), "r"(p), "r"(HI ? 0x8000u : 0x80u), "r"(lo), "r"(dst) : "memory");
}
template<bool Z>
__device__ __forceinline__ void cpe(uint32_t hi, uint32_t dst, uint32_t idx, uint32_t lo, int k, int n, uint64_t pol) {
    if (Z) asm volatile("{\n.reg .b32 l;\n.reg .b64 a;\n.reg .pred q;\nsetp.ge.s32 q, %5, %6;\nmad.lo.u32 l, %1, 32, %2;\nmov.b64 a, {l, %0};\ncp.async.cg.shared.global.L2::cache_hint [%3], [a], 16, q, %4;\n}\n"
                        :: "r"(hi), "r"(idx), "r"(lo), "r"(dst), "l"(pol), "r"(k), "r"(n) : "memory");
    else asm volatile("{\n.reg .b32 l;\n.reg .b64 a;\nmad.lo.u32 l, %1, 32, %2;\nmov.b64 a, {l, %0};\ncp.async.cg.shared.global.L2::cache_hint [%3], [a], 16, %4;\n}\n"
                      :: "r"(hi), "r"(idx), "r"(lo), "r"(dst), "l"(pol) : "memory");
}
__device__ __forceinline__ void cp_commit() { asm volatile("cp.async.commit_group;" ::: "memory"); }
template<int N> __device__ __forceinline__ void cp_wait() { asm volatile("cp.async.wait_group %0;" :: "n"(N) : "memory"); }
__device__ __forceinline__ void mbar_arrive(uint32_t bar) { asm volatile("mbarrier.arrive.shared.b64 _, [%0];" :: "r"(bar) : "memory"); }
__device__ __forceinline__ void mbar_cp_arrive(uint32_t bar) { asm volatile("cp.async.mbarrier.arrive.noinc.shared.b64 [%0];" :: "r"(bar) : "memory"); }
__device__ __forceinline__ void mbar_wait(uint32_t bar, uint32_t parity) {
    asm volatile("{\n.reg .pred p;\n.reg .u32 n;\nmbarrier.try_wait.parity.shared.b64 p, [%0], %1;\n@p bra DONE_%=;\nmov.u32 n, 0;\n"
                 "WAIT_%=:\nmbarrier.try_wait.parity.shared.b64 p, [%0], %1, 0x100000;\n@p bra DONE_%=;\n"
                 "add.u32 n, n, 1;\nsetp.lt.u32 p, n, 0x400000;\n@p bra WAIT_%=;\ntrap;\nDONE_%=:\n}\n"
                 :: "r"(bar), "r"(parity) : "memory");
}
__device__ __forceinline__ void mbar_wait_c(uint32_t bar, uint32_t parity) {
    asm volatile("{\n.reg .pred p;\nWAIT_%=:\nmbarrier.try_wait.parity.shared.b64 p, [%0], %1;\n@p bra DONE_%=;\nbra WAIT_%=;\nDONE_%=:\n}\n"
                 :: "r"(bar), "r"(parity) : "memory");
}
__device__ __forceinline__ void mbar_wait_h(uint32_t bar, uint32_t parity) {
    asm volatile("{\n.reg .pred p;\nWAIT_%=:\nmbarrier.try_wait.parity.shared.b64 p, [%0], %1, 0x100000;\n@p bra DONE_%=;\nbra WAIT_%=;\nDONE_%=:\n}\n"
                 :: "r"(bar), "r"(parity) : "memory");
}
__device__ __forceinline__ uint32_t lds32(uint32_t a) { uint32_t v; asm volatile("ld.shared.u32 %0, [%1];" : "=r"(v) : "r"(a) : "memory"); return v; }
__device__ __forceinline__ void sts32(uint32_t a, uint32_t v) { asm volatile("st.shared.u32 [%0], %1;" :: "r"(a), "r"(v) : "memory"); }
__device__ __forceinline__ uint2 lds64(uint32_t a) { uint2 v; asm volatile("ld.shared.v2.u32 {%0,%1}, [%2];" : "=r"(v.x), "=r"(v.y) : "r"(a) : "memory"); return v; }
__device__ __forceinline__ void sts64(uint32_t a, uint32_t x, uint32_t y) { asm volatile("st.shared.v2.u32 [%0], {%1,%2};" :: "r"(a), "r"(x), "r"(y) : "memory"); }
__device__ __forceinline__ uint4 lds128(uint32_t a) { uint4 v; asm volatile("ld.shared.v4.u32 {%0,%1,%2,%3}, [%4];" : "=r"(v.x), "=r"(v.y), "=r"(v.z), "=r"(v.w) : "r"(a) : "memory"); return v; }
__device__ __forceinline__ void sts128(uint32_t a, uint4 v) { asm volatile("st.shared.v4.u32 [%0], {%1,%2,%3,%4};" :: "r"(a), "r"(v.x), "r"(v.y), "r"(v.z), "r"(v.w) : "memory"); }
__device__ __forceinline__ void ldsm4t(uint32_t* v, uint32_t a) {
    asm volatile("ldmatrix.sync.aligned.m8n8.x4.trans.shared.b16 {%0,%1,%2,%3}, [%4];" : "=r"(v[0]), "=r"(v[1]), "=r"(v[2]), "=r"(v[3]) : "r"(a) : "memory");
}
__device__ __forceinline__ void stsm4t(uint32_t a, const uint32_t* v) {
    asm volatile("stmatrix.sync.aligned.m8n8.x4.trans.shared.b16 [%0], {%1,%2,%3,%4};" :: "r"(a), "r"(v[0]), "r"(v[1]), "r"(v[2]), "r"(v[3]) : "memory");
}
__device__ __forceinline__ int atoms_inc(uint32_t a) { int v; asm volatile("atom.shared.add.u32 %0, [%1], 1;" : "=r"(v) : "r"(a) : "memory"); return v; }
__device__ __forceinline__ float tanhf_a(float x) { float y; asm("tanh.approx.f32 %0, %1;" : "=f"(y) : "f"(x)); return y; }
__device__ __forceinline__ const char* as_pair(const void* p, uint32_t scratch) {
    const char* r;
    asm volatile("st.shared.u64 [%1], %2;\nld.volatile.shared.u64 %0, [%1];" : "=l"(r) : "r"(scratch), "l"(p) : "memory");
    return r;
}
__device__ __forceinline__ void ld_unit(uint4& v, const char* p, bool ok) {
    asm volatile("{\n.reg .pred q;\nsetp.ne.u32 q, %5, 0;\n@q ld.relaxed.gpu.global.v4.u32 {%0,%1,%2,%3}, [%4];\n}"
                 : "+r"(v.x), "+r"(v.y), "+r"(v.z), "+r"(v.w) : "l"(p), "r"((uint32_t)ok) : "memory");
}
__device__ __forceinline__ void ld_unit(uint2& v, const char* p, bool ok) {
    asm volatile("{\n.reg .pred q;\nsetp.ne.u32 q, %3, 0;\n@q ld.relaxed.gpu.global.v2.u32 {%0,%1}, [%2];\n}"
                 : "+r"(v.x), "+r"(v.y) : "l"(p), "r"((uint32_t)ok) : "memory");
}
#define ELECT "{\n.reg .pred p;\nelect.sync _|p, 0xffffffff;\n@p "
__device__ __forceinline__ void w_init(uint32_t bar, int n) { asm volatile(ELECT "mbarrier.init.shared.b64 [%0], %1;\n}" :: "r"(bar), "r"(n) : "memory"); }
__device__ __forceinline__ void w_expect(uint32_t bar, uint32_t bytes) { asm volatile(ELECT "mbarrier.arrive.expect_tx.shared.b64 _, [%0], %1;\n}" :: "r"(bar), "r"(bytes) : "memory"); }
__device__ __forceinline__ void w_ld(uint32_t dst, const void* src, int bytes, uint32_t bar) {
    asm volatile(ELECT "cp.async.bulk.shared::cluster.global.mbarrier::complete_tx::bytes [%0], [%1], %2, [%3];\n}" :: "r"(dst), "l"(src), "r"(bytes), "r"(bar) : "memory");
}
__device__ __forceinline__ void w_box_ld(uint32_t dst, const CUtensorMap* tm, int row, uint32_t bar) {
    asm volatile(ELECT "cp.async.bulk.tensor.2d.shared::cluster.global.mbarrier::complete_tx::bytes [%0], [%1, {%3, %4}], [%2];\n}"
        :: "r"(dst), "l"((uint64_t)tm), "r"(bar), "r"(0), "r"(row) : "memory");
}
__device__ __forceinline__ void w_st(void* dst, uint32_t src, int bytes) {
    asm volatile(ELECT "cp.async.bulk.global.shared::cta.bulk_group [%0], [%1], %2;\n}" :: "l"(dst), "r"(src), "r"(bytes) : "memory");
}
__device__ __forceinline__ void w_box_st(const CUtensorMap* tm, int col, uint32_t src) {
    asm volatile(ELECT "cp.async.bulk.tensor.2d.global.shared::cta.bulk_group [%0, {%2, %3}], [%1];\n}" :: "l"((uint64_t)tm), "r"(src), "r"(col), "r"(0) : "memory");
}
__device__ __forceinline__ void w_sent(unsigned* p, uint32_t src) {
    asm volatile(ELECT "cp.reduce.async.bulk.global.shared::cta.bulk_group.add.u32 [%0], [%1], 16;\n}" :: "l"(p), "r"(src) : "memory");
}
__device__ __forceinline__ void w_inc(unsigned* p) { asm volatile(ELECT "red.relaxed.gpu.global.add.u32 [%0], 1;\n}" :: "l"(p) : "memory"); }
__device__ __forceinline__ void w_hint(unsigned* p, uint32_t all) {
    #pragma unroll 1
    for (int i = 0; i < 4096; i++) {
        uint32_t v; asm volatile("ld.relaxed.gpu.global.u32 %0, [%1];" : "=r"(v) : "l"(p) : "memory");
        if (__all_sync(~0u, (int)(v - all) >= 0)) break;
    }
}

__device__ __forceinline__ void finish(uint4& a, const uint4& xu, const uint4& xv) {
    asm("{\n.reg .b32 z;\nfma.rn.relu.bf16x2 z, %0, %3, %1;\nadd.rn.bf16x2 %0, z, %2;\n}" : "+r"(a.x) : "r"(xu.x), "r"(xv.x), "r"(0x3F803F80u));
    asm("{\n.reg .b32 z;\nfma.rn.relu.bf16x2 z, %0, %3, %1;\nadd.rn.bf16x2 %0, z, %2;\n}" : "+r"(a.y) : "r"(xu.y), "r"(xv.y), "r"(0x3F803F80u));
    asm("{\n.reg .b32 z;\nfma.rn.relu.bf16x2 z, %0, %3, %1;\nadd.rn.bf16x2 %0, z, %2;\n}" : "+r"(a.z) : "r"(xu.z), "r"(xv.z), "r"(0x3F803F80u));
    asm("{\n.reg .b32 z;\nfma.rn.relu.bf16x2 z, %0, %3, %1;\nadd.rn.bf16x2 %0, z, %2;\n}" : "+r"(a.w) : "r"(xu.w), "r"(xv.w), "r"(0x3F803F80u));
}

constexpr float EPS2 = 2e-6f;
constexpr float TAU = 2.5e-5f;

constexpr uint32_t TAU_BITS = 0x3A103000u;
template<int NP>
__device__ __forceinline__ bool epi_fast(const float* g, const float* h, float m2, float tau, float& n0, float& d0, float& n1, float& d1, float& dmin)
{
    constexpr int JC = NP >= 6 ? NP - 3 : NP - 2;
    bool ok;
    #pragma unroll
    for (int j = 0; j < NP; j++) {
        float t0 = tanhf_a(g[4*j+0]), t1 = tanhf_a(g[4*j+1]), t2 = tanhf_a(g[4*j+2]), t3 = tanhf_a(g[4*j+3]);
        auto add_d = [&]() {
            if (j == 0) { d0 = t0 + (2.f * (JC + 1) + EPS2); d1 = t2 + (2.f * (JC + 1) + EPS2); } else { d0 += t0; d1 += t2; }
            d0 += t1; d1 += t3;
        };
        if (j <= JC) add_d();
        if (j == 0) { n0 = fmaf(t0, h[0], h[0]); n1 = fmaf(t2, h[2], h[2]); }
        t0 += 1.f; t2 += 1.f;
        if (j == NP - 1) { t1 = fmaf(t1, m2, m2); t3 = fmaf(t3, m2, m2); } else { t1 += 1.f; t3 += 1.f; }
        if (j > JC) add_d();
        if (j > 0) { n0 = fmaf(t0, h[4*j], n0); n1 = fmaf(t2, h[4*j+2], n1); }
        n0 = fmaf(t1, h[4*j+1], n0); n1 = fmaf(t3, h[4*j+3], n1);
        if (j == JC) { dmin = fminf(d0, d1); ok = dmin >= tau; }
    }
    return ok;
}

__device__ __noinline__ void slow_bin(const __nv_bfloat16* x, const __nv_bfloat16* ea, const int* src, const int* dst,
                                      const __nv_bfloat16* wa, const __nv_bfloat16* wb, const __nv_bfloat16* wc,
                                      const __nv_bfloat16* wu, const __nv_bfloat16* wv, __nv_bfloat16* out,
                                      int E, int node0, int nn, int nthr)
{
    const int tid = threadIdx.x, lane = tid & 31;
    for (int i = tid; i < nn * 128; i += nthr) g_slow[(size_t)node0 * 128 + i] = 0.f;
    asm volatile("bar.sync 1, %0;" :: "r"(nthr) : "memory");
    for (int e0 = (tid >> 5) * 32; e0 < E; e0 += nthr) {
        int d = (e0 + lane < E) ? dst[e0 + lane] - node0 : -1;
        unsigned m = __ballot_sync(~0u, d >= 0 && d < nn);
        while (m) {
            int l = __ffs(m) - 1; m &= m - 1;
            int e = e0 + l, n = node0 + __shfl_sync(~0u, d, l), s = src[e];
            float g0 = 0, g1 = 0, h0 = 0, h1 = 0;
            for (int k = 0; k < 64; k++) {
                float xs = __bfloat162float(x[(size_t)s * 64 + k]), xd = __bfloat162float(x[(size_t)n * 64 + k]);
                uint32_t b2 = *(const uint32_t*)(wb + k * 64 + 2 * lane), v2 = *(const uint32_t*)(wv + k * 64 + 2 * lane);
                uint32_t a2 = *(const uint32_t*)(wa + k * 64 + 2 * lane);
                g0 = fmaf(xs, bf_lo(b2), fmaf(xd, bf_lo(a2), g0)); g1 = fmaf(xs, bf_hi(b2), fmaf(xd, bf_hi(a2), g1));
                h0 = fmaf(xs, bf_lo(v2), h0); h1 = fmaf(xs, bf_hi(v2), h1);
            }
            for (int k = 0; k < 16; k++) {
                float ev = __bfloat162float(ea[(size_t)e * 16 + k]);
                uint32_t c2 = *(const uint32_t*)(wc + k * 64 + 2 * lane);
                g0 = fmaf(ev, bf_lo(c2), g0); g1 = fmaf(ev, bf_hi(c2), g1);
            }
            float s0 = rcpf(1.f + ex2f(-LOG2E * g0)), s1 = rcpf(1.f + ex2f(-LOG2E * g1));
            float* acc = g_slow + (size_t)n * 128 + 4 * lane;
            atomicAdd(acc + 0, s0 * h0); atomicAdd(acc + 1, s0);
            atomicAdd(acc + 2, s1 * h1); atomicAdd(acc + 3, s1);
        }
    }
    __threadfence();
    asm volatile("bar.sync 1, %0;" :: "r"(nthr) : "memory");
    for (int i = tid; i < nn * 32; i += nthr) {
        int n = node0 + (i >> 5), cp = i & 31;
        float4 a = __ldcg((const float4*)(g_slow + (size_t)n * 128 + 4 * cp));
        float u0 = 0, u1 = 0;
        for (int k = 0; k < 64; k++) {
            float xd = __bfloat162float(x[(size_t)n * 64 + k]);
            uint32_t w2 = *(const uint32_t*)(wu + k * 64 + 2 * cp);
            u0 = fmaf(xd, bf_lo(w2), u0); u1 = fmaf(xd, bf_hi(w2), u1);
        }
        uint32_t xv = *(const uint32_t*)(x + (size_t)n * 64 + 2 * cp);
        float z0 = u0 + a.x / (a.y + 1e-6f), z1 = u1 + a.z / (a.w + 1e-6f);
        *(uint32_t*)(out + (size_t)n * 64 + 2 * cp) = pack_bf16(bf_lo(xv) + fmaxf(z0, 0.f), bf_hi(xv) + fmaxf(z1, 0.f));
    }
}

__global__ void __launch_bounds__(256) slow_kernel(const __nv_bfloat16* x, const __nv_bfloat16* ea, const int* src, const int* dst,
        const __nv_bfloat16* wa, const __nv_bfloat16* wb, const __nv_bfloat16* wc, const __nv_bfloat16* wu, const __nv_bfloat16* wv,
        __nv_bfloat16* out, int N, int E, int npb)
{
    int node0 = blockIdx.x * npb;
    slow_bin(x, ea, src, dst, wa, wb, wc, wu, wv, out, E, node0, max(0, min(npb, N - node0)), 256);
}

constexpr int XS_BYTES = NPMAX * 1024;
constexpr int ES_BYTES = NPMAX * 256;
constexpr int SM_XS = 0;
constexpr int SM_XU = SM_XS + 3 * NSTAGE * XS_BYTES;
constexpr int SM_TAB = SM_XU + NPB_MAX * 128;
constexpr int SM_ES = SM_TAB + NPB_MAX * 128;
constexpr int SM_WC = SM_ES + 3 * NSTAGE * ES_BYTES;
constexpr int SM_OH = SM_WC + 2048;
constexpr int SM_EID = SM_OH + 128;
constexpr int SM_SRC = SM_EID + SLOT_CAP * 4;
constexpr int SM_TINFO = SM_SRC + SLOT_CAP * 2;
constexpr int SM_MISC = SM_TINFO + TILE_CAP * 32;
constexpr int SM_CLAIM = SM_MISC + 32 * 4;
constexpr int STG = 272;
constexpr int SM_BARS = SM_CLAIM + 32 * 4;
constexpr int SM_ABAR = SM_BARS + 6 * STG;
constexpr int SM_GBAR = SM_ABAR + 16 * 8;
constexpr int SMEM_BYTES = SM_GBAR + (GD + 1) * 8;
constexpr int SM_P2 = 0, SM_P1 = P2B + 256;
constexpr int SM_L1 = SM_P1 + P1B + 128;
constexpr int SM_DEG = SM_L1 + 256;
constexpr int SM_CLS = SM_DEG + 512 * 4;
constexpr int SM_HIST = SM_CLS + NCLS * 4;
constexpr int SM_XLIST = SM_HIST + NB_MAX * 4;
constexpr int SM_SORT = SM_XLIST + 8;
constexpr int SM_SDEG = SM_SORT + NPB_MAX * 4;
constexpr int SM_PAIR = SM_SDEG + NPB_MAX * 2;
constexpr int SM_ENT = SM_ES + 1024;
constexpr int SM_H1 = SM_P1 + HB, SM_H2 = SM_P1;
constexpr int SM_IDX = SM_EID;
constexpr int SM_WR = SM_TAB;
static_assert(TILE_CAP <= 128 && TR >= 2 && SM_ES % 256 == 0 && NSTAGE == 2 && SM_BARS % 16 == 0 && SM_TINFO % 16 == 0 && SM_EID % 128 == 0 && SM_TAB % 1024 == 0 && SM_XU % 1024 == 0 && SM_TINFO % 8 == 0 && SM_OH % 16 == 0 && SM_XLIST % 8 == 0 && SM_PAIR % 8 == 0, "align");
static_assert(SM_P1 % 128 == 0 && P1B + HB <= SM_SRC - SM_EID && 2 * HB <= P1B && SM_H1 + 5 * 128 * 16 <= SM_XU && NB_MAX * (CE / 4) <= 6 * 384 && NB_MAX * 4 <= 5 * 128 && NB_MIN * 4 >= 3 * 128 && SM_PAIR + 128 * 8 <= SM_XU && CH_MAX * 4 <= SM_SRC - SM_EID && SM_DEG >= 3 << 14, "alias");
static_assert(KM == 4 && CE == 64 && SMEM_BYTES <= 232448, "smem");
constexpr uint32_t C_BRK = 16  , C_CONT = 32, C_MORE = 64;
constexpr uint32_t ONE_F = 0x3F800000u;
constexpr int NONE = NPB_MAX - 1;
__host__ __device__ constexpr uint32_t tab_at(uint32_t n) { return (n >> 2) * 512 + (n & 3) * 32 + ((n >> 2) & 1) * 16; }

__device__ __forceinline__ bool unpad(uint32_t w1, int np, float ga, float gb, float& d0, float& d1, int& dv) {
    const int pad = (w1 >> 8) & 31;
    dv = 2 * np - 1 - pad + (w1 >= ONE_F);
    float t0 = TAU * 2 * np, t1 = t0;
    if (pad) {
        t0 = fmaxf(t0, d0 * (1.f / 1024)); t1 = fmaxf(t1, d1 * (1.f / 1024));
        asm volatile("tanh.approx.f32 %0, %0;\ntanh.approx.f32 %1, %1;" : "+f"(ga), "+f"(gb));
        d0 -= pad * (1.f + ga); d1 -= pad * (1.f + gb);
    }
    if (dv == 0) { d0 = d1 = EPS2; t0 = t1 = 0.f; }
    return d0 < t0 || d1 < t1;
}
constexpr int SM_COPY = SM_XU + tab_at(NPB_MAX - 4) - 16;
__device__ __forceinline__ void exact_quad(const float4 g, const float4 h, int k, int dv, float4& r) {
    const float e0 = 2.f * rcpf(1.f + ex2f(-2.f * LOG2E * g.x)), e1 = 2.f * rcpf(1.f + ex2f(-2.f * LOG2E * g.y));
    const float e2 = 2.f * rcpf(1.f + ex2f(-2.f * LOG2E * g.z)), e3 = 2.f * rcpf(1.f + ex2f(-2.f * LOG2E * g.w));
    if (k < dv) { r.y += e0; r.x = fmaf(e0, h.x, r.x); r.w += e2; r.z = fmaf(e2, h.z, r.z); }
    if (k + 1 < dv) { r.y += e1; r.x = fmaf(e1, h.y, r.x); r.w += e3; r.z = fmaf(e3, h.w, r.z); }
}
__device__ __forceinline__ float4 ldsf4(uint32_t a) { const uint4 v = lds128(a); return make_float4(__uint_as_float(v.x), __uint_as_float(v.y), __uint_as_float(v.z), __uint_as_float(v.w)); }
__device__ __noinline__ float4 exact_1(uint32_t sa, uint32_t l16)
{
    __syncwarp();
    const float4 g = ldsf4(sa + l16), h = ldsf4(sa + NPMAX * 16 + l16);
    float4 r = make_float4(0.f, 0.f, 0.f, 0.f);
    exact_quad(g, h, l16 >> 3, lds32(sa + 496), r);
    __syncwarp();
    sts128(sa + l16, make_uint4(__float_as_uint(r.x), __float_as_uint(r.y), __float_as_uint(r.z), __float_as_uint(r.w)));
    __syncwarp();
    r = make_float4(0.f, EPS2, 0.f, EPS2);
    #pragma unroll
    for (int j = 0; j < NPMAX; j++) { const float4 v = ldsf4(sa + j * 16); r.x += v.x; r.y += v.y; r.z += v.z; r.w += v.w; }
    __syncwarp();
    sts32(sa + (SM_MISC + 12 - SM_COPY), 0);
    return r;
}
__device__ __noinline__ float4* exact_copy() { return g_copy + (blockIdx.x * 12 + (threadIdx.x >> 5)) * (64 * NPMAX) + (threadIdx.x & 31); }
__device__ __noinline__ float4 exact_all(const float4* gh, int np, int dv)
{
    float4 r = make_float4(0.f, EPS2, 0.f, EPS2);
    #pragma unroll 1
    for (int j = 0; j < np; j++, gh += 32) exact_quad(gh[0], gh[32 * NPMAX], 2 * j, dv, r);
    return r;
}
template<int NP>
__device__ __forceinline__ float4 epi_exact(const float* g, const float* h, uint32_t bad, bool on, int dv, uint32_t sa, uint32_t l16) {
    uint32_t old = 1;
    if ((bad & (bad - 1)) == 0) asm volatile(ELECT "atom.shared.exch.b32 %0, [%1], 1;\n}" : "+r"(old) : "r"(sa + (SM_MISC + 12 - SM_COPY)) : "memory");
    if (__any_sync(~0u, old == 0)) {
        #pragma unroll
        for (int i = 0; i < 2 * NP; i++) {
            const float* v = i < NP ? g + 4 * i : h + 4 * (i - NP);
            asm volatile("{\n.reg .pred p;\nsetp.ne.u32 p, %5, 0;\n@p st.shared.v4.f32 [%0], {%1,%2,%3,%4};\n}"
                         :: "r"(sa + (i < NP ? i : NPMAX + i - NP) * 16), "f"(v[0]), "f"(v[1]), "f"(v[2]), "f"(v[3]), "r"((uint32_t)on) : "memory");
        }
        asm volatile("{\n.reg .pred p;\nsetp.ne.u32 p, %2, 0;\n@p st.shared.u32 [%0], %1;\n}" :: "r"(sa + 496), "r"(dv), "r"((uint32_t)on) : "memory");
        return exact_1(sa, l16);
    }
    float4* gh = exact_copy();
    #pragma unroll
    for (int i = 0; i < 2 * NP; i++) {
        const float* v = i < NP ? g + 4 * i : h + 4 * (i - NP);
        asm volatile("st.global.v4.f32 [%0], {%1,%2,%3,%4};" :: "l"(gh + (i < NP ? i : NPMAX + i - NP) * 32), "f"(v[0]), "f"(v[1]), "f"(v[2]), "f"(v[3]) : "memory");
    }
    return exact_all(gh, NP, dv);
}
__device__ __forceinline__ uint32_t row_bytes(uint32_t o) { return (o & 0xFE00) | ((o << 2) & 0x180); }

__device__ __noinline__ int balance(int step, char* gs, uint32_t id, int ng, int npb)
{
    extern __shared__ __align__(1024) uint8_t smem[];
    const uint32_t sb = smem_u32(smem), lane = threadIdx.x & 31, b = blockIdx.x, r4 = lane >> 3;
    const uint32_t tw = ((lane & 1) << 4) | ((lane & 6) << 6), ti = sb + SM_TINFO + r4 * 8, st = sb + SM_MISC + 48;
    uint32_t now; asm volatile("mov.u32 %0, %%globaltimer_lo;" : "=r"(now));
    auto put = [&](uint32_t a, uint32_t v) { if (lane == 0) asm volatile("st.relaxed.gpu.global.v2.u32 [%0], {%1, %2};" :: "l"(gs + a), "r"(v), "r"(id) : "memory"); };
    auto get = [&](uint32_t a) {
        uint2 v;
        #pragma unroll 1
        for (uint32_t n = 0; ; n++) {
            asm volatile("ld.acquire.gpu.global.v2.u32 {%0, %1}, [%2];" : "=r"(v.x), "=r"(v.y) : "l"(gs + a) : "memory");
            if (__all_sync(~0u, v.y == id)) break;
            if (n > (1u << 22)) __trap();
        }
        return v.x;
    };
    int gn = ng;
    if (step < 0) {
        if (BAL && step == -1) {
            const uint32_t e = lds32(sb + SM_TINFO + (3 * R1 + 3) * 32);
            if ((e & 0xFFFF) >= KM * 64 && ((e >> 20) & 127) < 2 && ((lds32(sb + SM_TINFO + (ng - KM) * 32 + 4) >> 16) & 15) <= 8 && lds32(sb + SM_MISC + 24) == 0) {
                #pragma unroll 1
                for (int j = 0; j < KM; j++) {
                    const uint32_t ta = (ng - 1 - j) * 32, s0 = lds32(sb + SM_TINFO + ta) & 0xFFFF;
                    const uint2 e = lds64(ti + ta);
                    char* p = gs + G_P + (b * KM + j) * GRP_B;
                    const uint32_t ro = sb + ((e.y & 0xFFFF) ^ tw);
                    *(uint4*)(p + lane * 16) = lds128(ro + SM_TAB);
                    *(uint4*)(p + 512 + lane * 16) = lds128(ro + SM_XU);
                    *(uint2*)(p + 1024 + lane * 8) = lds64(sb + SM_EID + s0 * 4 + lane * 8);
                    *(uint32_t*)(p + 1280 + lane * 4) = lds32(sb + SM_SRC + s0 * 2 + lane * 4);
                    *(uint2*)(p + 1408 + r4 * 8) = make_uint2(e.x >> 27 ? e.x - s0 : e.x, e.y);
                }
                uint32_t c = 0;
                #pragma unroll 1
                for (int g = 3 * R1 + 3 + lane; g < ng; g += 32) c += 93 + ((lds32(sb + SM_TINFO + g * 32 + 4) >> 16) & 15) * 42;
                sts32(st, (__reduce_add_sync(~0u, c) * 595) >> 10);
                asm volatile("fence.acq_rel.gpu;" ::: "memory");
                __syncwarp();
                return 1;
            }
        }
        put(G_F + b * 8, (now << 6) & ~511u);
    } else if (step == R2) {
        uint2 v[5];
        #pragma unroll 1
        for (uint32_t n = 0; ; n++) {
            bool ok = true;
            #pragma unroll
            for (int i = 0; i < 5; i++) asm volatile("ld.relaxed.gpu.global.v2.u32 {%0, %1}, [%2];" : "=r"(v[i].x), "=r"(v[i].y) : "l"(gs + G_F + min(lane + 32 * i, gridDim.x - 1) * 8) : "memory");
            #pragma unroll
            for (int i = 0; i < 5; i++) ok &= v[i].y == id;
            if (__all_sync(~0u, ok)) break;
            if (n > (1u << 22)) __trap();
        }
        const uint32_t ref = __shfl_sync(~0u, v[0].x, 0) - 0x80000000u, key = ((lds32(st) - ref) & ~511u) | b;
        uint32_t c = 0;
        #pragma unroll
        for (int i = 0; i < 5; i++) if (lane + 32 * i < gridDim.x && (v[i].x & 256)) c += 0x10000 + ((((v[i].x - ref) & ~511u) | (lane + 32 * i)) < key);
        c = __reduce_add_sync(~0u, c);
        const uint32_t kf = key | (ng % 3 == 0 ? 256 : 0);
        put(G_R + (c & 0xFFFF) * 8, kf);
        sts64(st, kf, (c >> 16) - 1 - (c & 0xFFFF));
        __syncwarp();
        return gn;
    } else {
        const uint32_t pk = get(G_R + lds32(st + 4) * 8);
        const uint32_t key = lds32(st);
        const int df = (int)(pk >> 9) - (int)(key >> 9), m = min((abs(df) * 8 + 175) / 350, (df < 0 ? pk : key) & 256 ? 3 : KM);
        gn += df < 0 ? -m : m;
        #pragma unroll 1
        for (int i0 = 0; i0 < gn - ng; i0 += 2) {
            uint4 ra[2], ru[2]; uint2 le[2], e[2]; uint32_t ls[2];
            #pragma unroll
            for (int i = 0; i < 2; i++) {
                const char* p = gs + G_P + ((pk & 255) * KM + i0 + i) * GRP_B;
                ra[i] = __ldcg((const uint4*)(p + lane * 16)); ru[i] = __ldcg((const uint4*)(p + 512 + lane * 16));
                le[i] = __ldcg((const uint2*)(p + 1024 + lane * 8)); e[i] = __ldcg((const uint2*)(p + 1408 + r4 * 8));
                ls[i] = __ldcg((const uint32_t*)(p + 1280 + lane * 4));
            }
            #pragma unroll
            for (int i = 0; i < 2; i++) {
                const int j = (m - 1 - i0 - i) & 3;
                const bool some = (e[i].y & 0xFFFF) != tab_at(NONE);
                const uint32_t row = some ? lds32(ti + (i0 + i) * 32 + 4) & 0xFFFF : tab_at(NONE);
                if (some) { sts128(sb + (row ^ tw) + SM_TAB, ra[i]); sts128(sb + (row ^ tw) + SM_XU, ru[i]); }
                sts64(sb + SM_EID + (i0 + i) * 256 + lane * 8, le[i].x, le[i].y);
                sts32(sb + SM_SRC + (i0 + i) * 128 + lane * 4, ls[i]);
                sts32(sb + SM_MISC + 64 + j * 16 + r4 * 4, (pk & 255) * npb * 128 + row_bytes(e[i].y & 0xFFFF));
                sts64(ti + (ng + j) * 32, ((e[i].x & 0xF800FFFFu) + (i0 + i) * 64) | (((e[i].y >> 16) & 15) > 5 ? 14u << 16 : 13u << 16), (e[i].y & 0xFFFF0000u) | row);
            }
        }
        __syncwarp();
        sts32(sb + SM_TINFO + gn * 32 + lane * 4, lane & 1 ? tab_at(NONE) : 0);
        sts32(sb + SM_MISC + 16, gn);
    }
    sts32(sb + SM_MISC + 28, gn);
    __syncwarp();
    if (lane == 0) mbar_arrive(sb + SM_ABAR + 32);
    return step < 0 ? 0 : gn;
}
__device__ __forceinline__ uint32_t bin_bits(uint32_t b) { return (1u << (b & 7)) | ((b < 48 ? 0x100u : 0x400u) << (b >> 3)); }
__device__ __forceinline__ void place(uint32_t sbase, uint32_t slot, uint32_t v, uint32_t eb) {
    asm volatile("{\n.reg .pred p;\nsetp.lt.u32 p, %0, %5;\n@p st.shared.u32 [%1], %2;\n@p st.shared.u16 [%3], %4;\n}"
                 :: "r"(slot), "r"(sbase + SM_EID + slot * 4), "r"(eb + (v >> 19)), "r"(sbase + SM_SRC + slot * 2), "r"(v), "n"(SLOT_CAP) : "memory");
}
__device__ __forceinline__ uint64_t desc_sw128(uint32_t a) {
    return (uint64_t)((a & 0x3FFFF) >> 4) | ((uint64_t)1 << 16) | ((uint64_t)64 << 32) | ((uint64_t)1 << 62);
}

template<bool LO32>
__global__ void __launch_bounds__(THREADS, 1)
gcn_kernel(const int* __restrict__ dst, unsigned* gbar, char* gs, const int* __restrict__ src, int E, int ch, int N, int npb, uint32_t magic,
           const __nv_bfloat16* __restrict__ x, const __nv_bfloat16* __restrict__ ea,
           const __nv_bfloat16* __restrict__ wa, const __nv_bfloat16* __restrict__ wb, const __nv_bfloat16* __restrict__ wc,
           const __nv_bfloat16* __restrict__ wu, const __nv_bfloat16* __restrict__ wv,
           __nv_bfloat16* out, int4 wrow, const __grid_constant__ CUtensorMap tm1, const __grid_constant__ CUtensorMap tm2,
           const __grid_constant__ CUtensorMap tmw, const __grid_constant__ CUtensorMap tmx)
{
    extern __shared__ __align__(1024) uint8_t smem[];
    int* cls = (int*)(smem + SM_CLS);
    int* misc = (int*)(smem + SM_MISC);
    WG0(); WS(0); CG(0);
    const uint32_t sbase = smem_u32(smem);
    const int tid = threadIdx.x, lane = tid & 31;
    const int b = blockIdx.x, nb = gridDim.x;
    const int cnt = max(0, min(ch, E - b * ch));
    const int node0 = b * npb;
    uint32_t tag = 0;
    if (tid < 384) asm volatile("ld.relaxed.gpu.global.u32 %0, [%1];" : "=r"(tag) : "l"(gbar) : "memory");
    auto dst_ld = [&](int v, uint32_t n) {
        const uint32_t off = v * (THREADS * 4) + tid * 4;
        asm volatile("{\n.reg .pred q;\nsetp.lt.u32 q, %2, %3;\n@q cp.async.cg.shared.global [%0], [%1], 16;\n}"
                     :: "r"(sbase + SM_IDX + off * 4), "l"(dst + (uint32_t)(b * ch + off)), "r"(off), "r"(n) : "memory");
    };
    dst_ld(0, min(cnt, 384 * 4));
    const int warp = (int)__reduce_max_sync(~0u, (unsigned)tid >> 5);
    const uint32_t su = __reduce_or_sync(~0u, sbase);
    if (warp >= 12) {
        const int v = warp & 3;
        const uint32_t a1 = su + SM_ABAR + (v == 0 ? 80 : v == 1 ? 120 : v == 2 ? 32 : 40);
        w_init(su + SM_ABAR + v * 8, 1); w_init(a1, 1);
        w_expect(su + SM_ABAR + v * 8, v < 3 ? min(max(cnt * 4 - v * 8192, 0), 8192) : 4 * 8192 + 2048);
        if (v < 2) w_expect(a1, v == 0 ? nb * (CE * 2) : nb * 64);
        asm volatile("fence.mbarrier_init.release.cluster;" ::: "memory");
        dst_ld(0, cnt);
    }
    #pragma unroll
    for (int v = 0; v < EPT / 4; v++) {
        if (v) {
            uint32_t c0, c1; asm volatile("mov.u32 %0, %%clock;" : "=r"(c0)); do { asm volatile("mov.u32 %0, %%clock;" : "=r"(c1)); } while (__all_sync(~0u, c1 - c0 < PD));
            dst_ld(v, cnt);
        }
        cp_commit();
    }
    if (warp == 15) {
        w_box_ld(su + SM_WR, &tmw, wrow.x, su + SM_ABAR + 24); w_box_ld(su + SM_WR + 8192, &tmw, wrow.y, su + SM_ABAR + 24);
        w_box_ld(su + SM_WR + 16384, &tmw, wrow.z, su + SM_ABAR + 24); w_ld(su + SM_WR + 24576, wc, 2048, su + SM_ABAR + 24);
        w_box_ld(su + SM_WR + 40960, &tmw, wrow.w, su + SM_ABAR + 24);
    }
    const int wg = warp >> 2, w = warp & 3;
    const int q = lane >> 2, t = lane & 3;
    const int nn = max(0, min(npb, N - node0));
    if (sbase & 1023) __trap();

    sts32(sbase + SM_DEG + tid * 4, tid < NPB_MAX ? 0 : 0x80000000u);
    if (tid < NCLS + NB_MAX) cls[tid] = tid < NCLS ? 0 : ((tid - NCLS) * 20) & 63;
    else if (warp == 8) sts32(sbase + SM_OH + lane * 4, t != (q >> 1) ? 0u : 0x00003F00u);
    else if (warp == 11) misc[lane] = lane == 5 ? TILE_CAP - TILE_X : lane == 8 || lane == 3;
    if (warp == 14) sts32(sbase + SM_TINFO + 96 * 32 + lane * 4, lane & 1 ? tab_at(NONE) : 0);
    if (warp == 15) sts32(sbase + SM_CLAIM + lane * 4, lane == 0 ? 3 * 32 : 0x40000000);
    if (tid == 0) sts32(sbase + SM_XLIST, tag);
    tag = (tag & 1) | 2;
    if (wg < 3) {
        const uint32_t d0 = ((NPB_MAX + ((2 * lane) & 15) + 16 * (b & 1)) * 4 | (tag << 14)) * 0x10001u, d1 = d0 + 0x40004u, d2 = tag << 16;
        #pragma unroll 1
        for (int i = tid; i < (P1B + 384) / 16; i += 384) {
            sts128(sbase + SM_P1 + i * 16, make_uint4(d0, d0, d1, i == P1B / 16 + 11 ? 0x80000000u | (tag << 14) : d1));
            sts128(sbase + SM_P2 + i * 16, make_uint4(d2, d2, d2, d2)); sts128(sbase + SM_P2 + P1B - 128 + i * 16, make_uint4(d2, d2, d2, d2));
        }
    }
    WS(1);
    __syncthreads();
    if (wg == 3) tag = lds32(sbase + SM_P2) >> 16;
    uint32_t all = 0;
    if (wg == 3) all = (lds32(sbase + SM_XLIST) + 1) * nb;
    if (tid == 128) {
        asm volatile("prefetch.tensormap [%0];" :: "l"((uint64_t)&tm1) : "memory");
        asm volatile("prefetch.tensormap [%0];" :: "l"((uint64_t)&tm2) : "memory");
        asm volatile("prefetch.tensormap [%0];" :: "l"((uint64_t)&tmx) : "memory");
    }
    const uint32_t m4 = __reduce_or_sync(~0u, -4 * npb);
    uint32_t ent[EPT];
    #pragma unroll
    for (int v = 0; v < EPT / 4; v++) {
        if (v == 0) cp_wait<2>(); else if (v == 1) cp_wait<1>(); else cp_wait<0>();
        if (v == 0 && wg == 2 && w < 3) {
            const int n = min(cnt * 4 - w * 8192, 8192);
            if (n > 0) w_ld(su + SM_XU + w * 8192, src + b * ch + w * 2048, n, su + SM_ABAR + w * 8);
        }
        const uint32_t off = v * (THREADS * 4) + tid * 4;
        if (off < (uint32_t)cnt) {
            const uint4 u = lds128(sbase + SM_IDX + off * 4);
            uint32_t dv[4] = {u.x, u.y, u.z, u.w}, ps[4], ck[4];
            uint32_t* en = ent + 4 * v;
            #pragma unroll
            for (int k = 0; k < 4; k++) {
                dv[k] = min(dv[k], (uint32_t)(nb * npb - 1));
                ps[k] = __umulhi(dv[k], magic);
                asm volatile("atom.shared.add.u32 %0, [%1], 0x10001;" : "=r"(ck[k]) : "r"(sbase + SM_HIST + ps[k] * 4) : "memory");
            }
            #pragma unroll
            for (int k = 0; k < 4; k++) {
                dv[k] = ps[k] * m4 + (dv[k] * 4 + (tag << 14));
                en[k] = (ck[k] & 63) + ps[k] * CE;
            }
            if (__builtin_expect(max(max(ck[0], ck[1]), max(ck[2], ck[3])) >= CE << 16, 0)) {
                auto step = [&]() {
                    uint32_t e = en[0];
                    const uint32_t d = dv[0];
                    if (ck[0] >= CE << 16) {
                        uint32_t j; asm volatile("atom.shared.inc.u32 %0, [%1], 0x7fffffff;" : "=r"(j) : "r"(sbase + SM_MISC + 8) : "memory");
                        j = min(j + (j >= 15), 63u);
                        sts32(sbase + SM_L1 + j * 4, d | ((j < 63 ? e / CE : 255u) << 16));
                        e = NB_MAX * CE + j;
                    }
                    en[0] = en[1]; en[1] = en[2]; en[2] = en[3]; en[3] = e;
                    dv[0] = dv[1]; dv[1] = dv[2]; dv[2] = dv[3]; dv[3] = d;
                    ck[0] = ck[1]; ck[1] = ck[2]; ck[2] = ck[3];
                };
                if (v == 2) { step(); step(); step(); step(); }
                else {
                    #pragma unroll 1
                    for (int k = 0; k < 4; k++) step();
                }
            }
            #pragma unroll
            for (int k = 0; k < 4; k++)
                asm volatile("st.shared.u16 [%0], %1;" :: "r"(sbase + SM_P1 + en[k] * 2), "r"(dv[k]) : "memory");
        }
    }
    if (warp == 15) {
        #pragma unroll
        for (int v = 0; v < EPT / 4; v++) sts128(sbase + SM_ENT + v * 512 + lane * 16, make_uint4(ent[4*v], ent[4*v+1], ent[4*v+2], ent[4*v+3]));
    }
    asm volatile("fence.proxy.async.shared::cta;" ::: "memory");
    WS(5);
    __syncthreads();
    if (warp == 15) {
        w_inc(gbar + 1);
        const uint32_t n = __reduce_or_sync(~0u, lds32(su + SM_MISC + 8));
        if (__builtin_expect(n > 15, 0)) {
            const uint2 r = lds64(su + SM_L1 + lane * 8);
            uint32_t m = lane < 8 ? 0 : (r.x >> 24 ? 0 : bin_bits(r.x >> 16)) | (r.y >> 24 ? 0 : bin_bits(r.y >> 16));
            m = n > 62 ? 0x7FFF3FFFu : __reduce_or_sync(~0u, m);
            sts32(su + SM_L1 + 60, m | 0x80000000u | (tag << 14));
            asm volatile("fence.proxy.async.shared::cta;" ::: "memory");
            __syncwarp();
        }
        w_st(gs + G_H1 + b * 64, su + SM_L1, 64);
        w_box_st(&tm1, b * (CE / 2), su + SM_P1);
        w_st(gs + G_L + b * 512, su + SM_L1, 256);
        asm volatile("cp.async.bulk.commit_group;" ::: "memory");
    } else {
        mbar_wait_c(su + SM_ABAR, 0);
        auto put = [&](uint32_t off, const uint32_t* uu) {
            if (off < (uint32_t)cnt) {
                const uint4 sv = lds128(sbase + SM_XU + off * 4);
                const uint32_t ss[4] = {sv.x, sv.y, sv.z, sv.w};
                #pragma unroll
                for (int k = 0; k < 4; k++) sts32(sbase + SM_P2 + uu[k] * 4, (ss[k] & 0xFFFF) | (((off + k) << 19) + (tag << 16)));
            }
        };
        #pragma unroll
        for (int v = 0; v < EPT / 4; v++) { if (v) mbar_wait_c(su + SM_ABAR + v * 8, 0); put(v * (THREADS * 4) + tid * 4, ent + 4 * v); }
        if (wg == 3) {
            const uint4 e = lds128(sbase + SM_ENT + w * 512 + lane * 16);
            const uint32_t uu[4] = {e.x, e.y, e.z, e.w};
            put(w * (THREADS * 4) + (480 + lane) * 4, uu);
        }
        asm volatile("fence.proxy.async.shared::cta;" ::: "memory");
        WS(7);
        __syncwarp();
        asm volatile("bar.arrive 12, 512;" ::: "memory");
    }
    WS(8);

    const int ngroups = (nn + 3) >> 2;
    if (warp < 12) {
        asm volatile("setmaxnreg.inc.sync.aligned.u32 152;");
        const uint32_t ab = su + SM_ABAR;
        uint32_t wf[40], wn[16];
        const uint32_t mo = sbase + (8 * (lane >> 4) + (lane & 7)) * 128 + (((2 * w + ((lane >> 3) & 1)) ^ (lane & 7)) << 4);
        const uint32_t wca = __shfl_sync(~0u, sbase + SM_WC + (16 * w + q) * 32 + t * 4 + ((q >> 2) << 4), lane), l16 = __shfl_sync(~0u, (lane & 15) * 16, lane);
        mbar_wait_c(ab + 24, 0);
        {
            #pragma unroll
            for (int ks = 0; ks < 4; ks++) { ldsm4t(wf + 4 * ks, mo + SM_WR + ks * 2048); ldsm4t(wf + 20 + 4 * ks, mo + SM_WR + 8192 + ks * 2048); ldsm4t(wn + 4 * ks, mo + SM_WR + 16384 + ks * 2048); }
            auto half = [](uint32_t& v) { asm("mul.rn.bf16x2 %0, %0, %1;" : "+r"(v) : "r"(0x3F003F00u)); };
            uint32_t z = 0;
            #pragma unroll
            for (int i = 0; i < 16; i++) { half(wf[i]); z ^= wf[i]; }
            sts32(sbase + SM_ES + lane * 4, z);
            if (wg == 2) {
                uint32_t f[4];
                ldsm4t(f, (mo ^ ((lane & 7) << 4)) + SM_WR + 24576);
                half(f[0]); half(f[1]); half(f[2]); half(f[3]);
                sts32(wca, f[0]); sts32(wca + 256, f[1]); sts32(wca ^ 16, f[2]); sts32((wca ^ 16) + 256, f[3]);
                asm volatile("fence.proxy.async.shared::cta;" ::: "memory");
            }
        }
        const uint64_t wcd = __reduce_or_sync(~0u, (((sbase + SM_WC) & 0x3FFFF) >> 4) | (8u << 16)) | EDHI;
        const uint32_t bar0 = __reduce_or_sync(~0u, sbase + SM_BARS + wg * 2 * STG);
        const uint32_t xd0 = __reduce_or_sync(~0u, (((sbase + SM_XS + wg * NSTAGE * XS_BYTES) & 0x3FFFF) >> 4) | (1u << 16));
        const uint32_t ed0 = __reduce_or_sync(~0u, (((sbase + SM_ES + wg * NSTAGE * ES_BYTES) & 0x3FFFF) >> 4) | (8u << 16));
        const uint64_t ohd = __reduce_or_sync(~0u, ((sbase + SM_OH) & 0x3FFFF) >> 4);
        const uint32_t tabx = __reduce_or_sync(~0u, sbase + SM_TAB + w * 128);
        const uint32_t bars = __reduce_or_sync(~0u, 2 * bar0 + STG), xds = __reduce_or_sync(~0u, 2 * xd0 + XS_BYTES / 16), eds = __reduce_or_sync(~0u, 2 * ed0 + ES_BYTES / 16);
        const uint32_t xuo = __reduce_or_sync(~0u, sbase + SM_XU + wg * 16384);
        { const uint2 z = lds64(sbase + SM_OH + 8); wf[38] = z.x; wf[39] = z.y; }
        WS(9);
        constexpr int NU = 6;
        const uint32_t dm = ((NPB_MAX + lane) * 4 | (tag << 14)) * 0x10001u;
        const uint32_t db = sbase + SM_DEG - (tag << 14);
        const char* const g1 = gs + (uint32_t)(b * (P1B + P2B) + tid * 8);
        int rk[NU][4];
        uint32_t spins = 0;
        {
            uint2 r1[NU];
            mbar_wait_c(ab + 80, 0);
            WS(2);
            #pragma unroll
            for (int i = 0; i < NU; i++) {
                r1[i] = make_uint2(dm, dm);
                if (NB_MIN * 16 >= 384 * (i + 1) || tid + 384 * i < nb * 16) r1[i] = lds64(sbase + SM_IDX + (tid + 384 * i) * 8);
            }
            #pragma unroll 1
            while (true) {
                uint32_t bad = 0;
                #pragma unroll
                for (int i = 0; i < NU; i++) bad |= r1[i].y ^ dm;
                if (__builtin_expect(!__any_sync(~0u, bad & 0xC000), 1)) break;
                #pragma unroll
                for (int i = 0; i < NU; i++) ld_unit(r1[i], g1 + 384 * 8 * i, (r1[i].y ^ dm) & 0xC000);
                if (++spins > (1u << 22)) break;
            }
            WS(3);
            #pragma unroll
            for (int i = 0; i < NU; i++) {
                rk[i][0] = r1[i].x & 0xFFFF; rk[i][1] = r1[i].x >> 16; rk[i][2] = r1[i].y & 0xFFFF; rk[i][3] = r1[i].y >> 16;
                #pragma unroll
                for (int k = 0; k < 4; k++) asm volatile("red.shared.add.u32 [%0], 1;" :: "r"(db + min((uint32_t)rk[i][k], NPB_MAX * 4 + (tag << 14))) : "memory");
            }
        }
        WS(10);
        asm volatile("bar.sync 11, 512;" ::: "memory");
        int mycls = 0, mycr = 0, dg = lds32(sbase + SM_DEG + tid * 4);
        if (tid < nn) {
            mycls = NCLS - 1 - (dg <= 40 ? dg : min(41 + ((dg - 41) >> 3), NCLS - 1)); mycr = atomicAdd(&cls[mycls], 1);
        }
        int s0 = 0;
        if (__builtin_expect(dg > 40, 0)) s0 = max(SLOT_CAP - ((dg + 1) & ~1) - atomicAdd(&misc[6], (dg + 1) & ~1), 0);
        asm volatile("bar.sync 1, 384;" ::: "memory");
        WS(12);
        {
            const uint2 c = lds64(sbase + SM_CLS + lane * 8);
            const int v0 = c.x * (lane > 11 ? ((64 - 2 * lane) << 16) + 1 : 1), v1 = c.y * (lane >= 11 ? ((62 - 2 * lane) << 16) + 1 : 1);
            int inc = v0 + v1;
            #pragma unroll
            for (int o = 1; o < 32; o <<= 1) { int y = __shfl_up_sync(~0u, inc, o); if (lane >= o) inc += y; }
            const int e0 = __shfl_sync(~0u, inc - v0 - v1, mycls >> 1), e1 = __shfl_sync(~0u, inc - v1, mycls >> 1);
            const int e = (mycls & 1) ? e1 : e0;
            if (tid < nn) {
                if (dg <= 40) s0 = min((e >> 16) + mycr * ((dg + 1) & ~1), SLOT_CAP - 40);
                sts32(sbase + SM_DEG + tid * 4, s0);
            }
            const uint32_t pos = tid < nn ? (e & 0xFFFF) + mycr : tid;
            sts32(sbase + SM_SORT + pos * 4, tid < nn ? (uint32_t)tid | ((uint32_t)s0 << 16) : NONE);
            asm volatile("st.shared.u16 [%0], %1;" :: "r"(sbase + SM_SDEG + pos * 2), "r"(min(dg, 65535)) : "memory");
            if (tid == 383) { misc[4] = (nn - c.y + 3) >> 2; if ((inc >> 16) + misc[6] > SLOT_CAP - 40) misc[1] = 1; }
        }
        asm volatile("bar.sync 1, 384;" ::: "memory");
        WS(13);
        const uint32_t sv = lds32(sbase + SM_SORT + tid * 4);
        const uint2 d4 = lds64(sbase + SM_SDEG + (tid >> 2) * 8);
        const uint32_t slow = lds32(sbase + SM_MISC + 4);
        #pragma unroll
        for (int i = 0; i < NU; i++) {
            #pragma unroll
            for (int k = 0; k < 4; k++) rk[i][k] = atoms_inc(db + rk[i][k]);
        }
        if (__reduce_or_sync(~0u, slow) == 0) {
            const uint32_t nd = sv & 0xFFFF;
            const int g = tid >> 2;
            dg = ((t & 2 ? d4.y : d4.x) >> (16 * (t & 1))) & 0xFFFF;
            const uint32_t hi2 = __vmaxu2(d4.x, d4.y), lo2 = __vminu2(d4.x, d4.y);
            const int mx = max(hi2 >> 16, hi2 & 0xFFFF), mn = min(lo2 >> 16, lo2 & 0xFFFF);
            int left = (mx + 1) >> 1;
            int tl = g, nx = ngroups + 4 + g, nt = left > NPMAX ? 2 : 1;
            const bool odd = left > 2 * NPMAX || (nt == 2 && nx >= TILE_CAP - TILE_X);
            if (__builtin_expect(__any_sync(~0u, odd), 0)) {
                if (odd) nt = (left + NPMAX - 1) / NPMAX;
                if (odd && t == 0) { asm volatile("atom.shared.add.u32 %0, [%1], %2;" : "=r"(nx) : "r"(sbase + SM_MISC + 20), "r"(nt - 1) : "memory"); if (nx + nt - 1 > TILE_CAP) misc[1] = 1; }
                nx = __shfl_sync(~0u, nx, lane & ~3);
                if (odd && nx + nt - 1 > TILE_CAP) left = 0;
            }
            const uint32_t w0 = tab_at(nd);
            if (g >= ngroups + 4) tl = ngroups;
            uint32_t cont = 0;
            int done = 0;
            bool act = true;
            do {
                int np = nt <= 2 ? (left + nt - 1) >> (nt - 1) : (left + nt - 1) / nt;
                left -= np; nt = max(nt - 1, 1);
                if (np) np = max(np, NPMIN);
                const int dv = min(max(dg - done, 0), 2 * np);
                uint32_t code = (uint32_t)np | cont | (left > 0 ? C_MORE : 0u);
                const bool gen = mn - done < 2 * np - (np == NPMIN ? 1 : 2);
                if (np == 0) code = 0;
                const uint32_t w1 = code | (dv == 2 * np ? 0x8000u : (2 * np - 1 - dv) << 8);
                if (act) *(uint2*)(smem + SM_TINFO + tl * 32 + t * 8) = make_uint2((dv ? (sv >> 16) + done : 0) | ((gen ? (np > 8 ? 15 : np > 5 ? 14 : 13) : np) << 16) | ((left > 0 ? nx : g >= ngroups - (KM + 3)) << 20) | ((uint32_t)dv << 27), w0 | (np == 0 ? 0u : w1 << 16));
                tl = nx++; cont = C_CONT; done += 2 * np; act = left > 0;
            } while (__any_sync(~0u, act));
        }
        __syncwarp();
        asm volatile("bar.arrive 4, 512;" ::: "memory");
        WS(14);
        wf[16] = lds32(wca); wf[17] = lds32(wca + 256); wf[18] = lds32(wca ^ 16); wf[19] = lds32((wca ^ 16) + 256);
        #pragma unroll
        for (int pc = 0; pc < 3; pc++) {
            uint4 r2[2];
            mbar_wait_c(ab + pc * 8, 1);
            if (pc == 0) WS(4); if (pc == 2) WS(16);
            #pragma unroll
            for (int k = 0; k < 2; k++) {
                r2[k] = lds128(sbase + SM_P2 + (tid + 384 * (2 * pc + k)) * 16);
                if (rk[2 * pc + k][0] < 0) r2[k].w = tag << 16;
            }
            while (__builtin_expect(__any_sync(~0u, ((r2[0].w ^ (tag << 16)) | (r2[1].w ^ (tag << 16))) & 0x30000), 0)) {
                #pragma unroll
                for (int k = 0; k < 2; k++)
                    ld_unit(r2[k], g1 + (uint32_t)(tid * 8) + (P1B + 384 * 16 * (2 * pc + k)), (r2[k].w ^ (tag << 16)) & 0x30000);
                if (++spins > (1u << 22)) break;
            }
            #pragma unroll
            for (int k = 0; k < 2; k++) {
                const int i = 2 * pc + k;
                const uint32_t eb = ((tid >> 4) + 24 * i) * ch;
                place(sbase, rk[i][0], r2[k].x, eb); place(sbase, rk[i][1], r2[k].y, eb); place(sbase, rk[i][2], r2[k].z, eb); place(sbase, rk[i][3], r2[k].w, eb);
            }
        }
        WGD();
        __syncwarp();
        asm volatile("bar.arrive 3, 480;" ::: "memory");
        float g[4 * NPMAX], h[4 * NPMAX];
        float4 cyr = make_float4(0.f, 0.f, 0.f, 0.f);
        WS(15); CG(1);
        mbar_wait_c(ab + 88 + wg * 8, 0);
        auto pack = [&](uint32_t* v, const float* u) {
            #pragma unroll
            for (int i = 0; i < 16; i++) v[i] = pack_bf16(u[2*i], u[2*i+1]);
        };
        auto rows_st = [&](uint32_t p, const uint32_t* v) {
            #pragma unroll
            for (int i = 0; i < 4; i++) stsm4t(p + i * 2048, v + 4 * i);
        };
        {
            const uint64_t d0 = desc_sw128(xuo), d1 = d0 + 512;
            const uint32_t mr = sbase + wg * 16384 + w * 128 + (tab_at(8 * (lane >> 4) + (lane & 7)) ^ ((lane & 8) << 1));
            uint32_t v[16];
            node_mma(g, wn, d0); node_mma(h, wn, d1);
            TileMMA<8>::wait_g(g);
            pack(v, g); rows_st(mr + SM_TAB, v);
            TileMMA<8>::wait_h(h);
            #pragma unroll
            for (int ks = 0; ks < 4; ks++) ldsm4t(wn + 4 * ks, mo + SM_WR + 40960 + ks * 2048);
            node_mma(g, wn, d0);
            if (wg == 2) asm volatile("bar.sync 5, 384;" ::: "memory"); else asm volatile("bar.arrive 5, 384;" ::: "memory");
            pack(v, h); rows_st(mr + SM_TAB + 8192, v);
            node_mma(h, wn, d1);
            __syncwarp();
            if (lane == 0) mbar_arrive(sbase + SM_ABAR + 112);
            TileMMA<8>::wait_g(g);
            pack(v, g);
            asm volatile("bar.sync %0, 128;" :: "r"(8 + wg) : "memory");
            rows_st(mr + SM_XU, v);
            TileMMA<8>::wait_h(h);
            pack(v, h);
            asm volatile("bar.sync %0, 128;" :: "r"(8 + wg) : "memory");
            rows_st(mr + SM_XU + 8192, v);
            __syncwarp();
            if (lane == 0) mbar_arrive(sbase + SM_ABAR + 72);
            mbar_wait_c(ab + 112, 0);
            __syncwarp();
            if (__builtin_expect(__reduce_or_sync(~0u, misc[1]) != 0, 0)) { slow_bin(x, ea, src, dst, wa, wb, wc, wu, wv, out, E, node0, nn, 384); asm volatile("exit;"); }
            WS(6);
        }
        uint32_t bar = bar0, xd = xd0, ed = ed0, ph = 0;
        float pn0 = 0.f, pd0 = 1.f, pn1 = 0.f, pd1 = 1.f;
        uint4 rc;
        rc.x = lds32(sbase + SM_TINFO + wg * 32 + ((lane >> 1) & 3) * 8 + 4);
        uint32_t code = __reduce_or_sync(~0u, rc.x >> 16);
        rc.x = (rc.x & 0xFFFF) ^ ((lane & 8) << 1);
        uint32_t pst = tabx + tab_at(NONE);
        auto fetch_a = [&]() {
            asm volatile("ldmatrix.sync.aligned.m8n8.x2.trans.shared.b16 {%0,%1}, [%2];" : "=r"(wf[36]), "=r"(wf[37]) : "r"(tabx + rc.x) : "memory");
        };
        auto emit = [&]() {
            asm volatile("stmatrix.sync.aligned.m8n8.x1.trans.shared.b16 [%0], {%1};" :: "r"(pst), "r"(pack_bf16(pn0 * rcpf(pd0), pn1 * rcpf(pd1))) : "memory");
        };
        auto carry = [&]() {
            if (rc.z & C_CONT) { pn0 += cyr.x; pd0 += cyr.y; pn1 += cyr.z; pd1 += cyr.w; }
            if (rc.z & C_MORE) { cyr = make_float4(pn0, pd0 - EPS2, pn1, pd1 - EPS2); pn0 = pn1 = 0.f; pst = tabx + tab_at(NONE); }
        };
        fetch_a();
        while (true) {
            switch (code & 15) {
                default: goto finished;
#define TILE(P) { \
                    bool ok; float dmin; \
                    do { \
                        mbar_wait_c(bar, ph); \
                        TileMMA<P>::issue(g, h, wf, xd, ed | EDHI, ohd, wcd); \
                        const uint32_t eb = bar + 8; \
                        ph ^= bar != bar0; bar = bars - bar; xd = xds - xd; ed = eds - ed; \
                          \
                        asm volatile("{\n.reg .pred p;\nsetp.eq.u32 p, %0, 77;\n@p trap;\n}" :: "r"(xds) : "memory"); \
                        emit(); rc = lds128(eb + 8 + l16); \
                        TileMMA<P>::wait_g(g); fetch_a(); TileMMA<P>::wait_h(h); \
                        mbar_arrive(eb); \
                        asm volatile("add.u32 %0, %1, %2;" : "=r"(pst) : "r"(rc.y), "r"(tabx)); \
                        ok = epi_fast<P>(g, h, __uint_as_float(rc.z), __uint_as_float(rc.w), pn0, pd0, pn1, pd1, dmin); \
                    } while (__all_sync(~0u, ok)); \
                    code = __reduce_or_sync(~0u, rc.w); \
                    if (__builtin_expect(__any_sync(~0u, ((rc.z & 0x1F00) != 0) | (dmin < TAU * 2 * P)), 0)) { \
                        int dv; \
                        const bool on = unpad(rc.z, P, g[4 * P - 4], g[4 * P - 2], pd0, pd1, dv); \
                        const uint32_t bad = __ballot_sync(~0u, on); \
                        if (__builtin_expect(bad != 0, 0)) { \
                            const float4 r = epi_exact<P>(g, h, bad, on, dv, su + SM_COPY, l16); \
                            if (on) { pn0 = r.x; pd0 = r.y; pn1 = r.z; pd1 = r.w; } \
                        } \
                    } \
                    if (code & C_BRK) { carry(); if (P != 11 && (code & 15) == P) goto L##P; } \
                    if (P == 11) {         \
                        wf[16] = lds32(wca); wf[17] = lds32(wca + 256); wf[18] = lds32(wca ^ 16); wf[19] = lds32((wca ^ 16) + 256); \
                    } }
#define CASE(P, UP, DN) case P: L##P: TILE(P) \
                    if (P > NPMIN && (code & 15) == P - 1) goto L##DN; \
                    if ((code & 15) == UP) goto L##UP; \
                    break;
                CASE(11, 11, 10) CASE(10, 11, 9) CASE(9, 10, 8) CASE(8, 9, 7) CASE(7, 8, 6) CASE(6, 7, 5) CASE(5, 6, 5)
#undef CASE
#undef TILE
            }
        }
finished:
        emit();
        __syncwarp();
        if (lane == 0) mbar_arrive(sbase + SM_ABAR + 48 + wg * 8);
    } else {
        asm volatile("setmaxnreg.dec.sync.aligned.u32 56;");
        auto x_ld = [&](int i0, int i1) {
            #pragma unroll
            for (int i = i0; i < i1; i++) w_box_ld(su + SM_XU + i * 8192, &tmx, node0 + i * 64, su + SM_ABAR + 88 + (i >> 1) * 8);
        };
        if (w < 3) {
            #pragma unroll
            for (int i = 0; i < 2; i++) { w_init(su + SM_BARS + (w * 2 + i) * STG, 64); w_init(su + SM_BARS + (w * 2 + i) * STG + 8, 128); }
            w_init(su + SM_ABAR + 48 + w * 8, 4);
            w_init(su + (w == 0 ? SM_GBAR + 99 * 8 : w == 1 ? SM_ABAR + 72 : SM_ABAR + 112), w == 0 ? 32 : 12);
        } else {
            #pragma unroll
            for (int i = 0; i < 4; i++) { w_init(su + SM_ABAR + (i < 3 ? 88 + i * 8 : 40), 1); w_expect(su + SM_ABAR + (i < 3 ? 88 + i * 8 : 40), i < 3 ? 16384 : nb * 64); }
            asm volatile("fence.mbarrier_init.release.cluster;" ::: "memory");
            w_hint(gbar + 1, all);
            asm volatile("cp.async.bulk.wait_group.read 0;" ::: "memory");
            WS(2);
            w_ld(su + SM_IDX, gs + b * (P1B + P2B), nb * (CE * 2), su + SM_ABAR + 80);
            w_ld(su + SM_H1, gs + G_H1, nb * 64, su + SM_ABAR + 120);
            asm volatile("bar.sync 12, 512;" ::: "memory");
            w_box_st(&tm2, P1B / 4 + b * CE, su + SM_P2);
            w_st(gs + G_H2 + b * 64, su + SM_P2 + P2B, 64);
            w_st(gs + G_L + b * 512 + 256, su + SM_P2 + P2B, 256);
            w_sent(gbar + 4, su + SM_MISC + 32);
            asm volatile("cp.async.bulk.commit_group;" ::: "memory");
        }
        const uint32_t ab = su + SM_ABAR;
        uint32_t todo = 0;
        const uint32_t mb = (lane & 3) == 3 ? bin_bits(b) : ~0u;
        WS(12);
        mbar_wait_c(ab + 120, 0);
        WS(13);
        {
            uint4 r[5];
            #pragma unroll
            for (int i = 0; i < 5; i++) r[i] = lds128(sbase + SM_H1 + (tid - 384 + 128 * i) * 16);
            #pragma unroll
            for (int i = 0; i < 5; i++) {
                const uint32_t bb = b << 16;
                const uint32_t m = min(min(r[i].x ^ bb, r[i].y ^ bb), min(r[i].z ^ bb, r[i].w ^ bb)) >> 16;
                if ((m == 0) | (((r[i].w ^ (tag << 14)) & 0xC000) != 0) | ((~r[i].w & mb) == 0)) todo |= 1 << i;
            }
            todo &= tid - 384 + 512 < nb * 4 ? 31 : tid - 384 + 384 < nb * 4 ? 15 : 7;
        }
        #pragma unroll 1
        for (int put = 0; put < 2; put++) {
            uint32_t any = __reduce_or_sync(~0u, todo), m = 0, u = 0;
            #pragma unroll 1
            while (any | m) {
                uint4 r = make_uint4(0, 0, 0, 0), r2 = r;
                uint32_t s, go, gd;
                bool on;
                if (__builtin_expect(m == 0, 1)) {
                    const uint32_t i = __ffs(any) - 1;
                    any &= any - 1; u = tid - 384 + 128 * i; on = (todo >> i) & 1;
                    r = lds128(sbase + SM_H1 + u * 16); r2 = lds128(sbase + SM_H2 + u * 16);
                    s = u >> 2; go = G_H1 + u * 16; gd = HB;
                } else {
                    s = ((u & ~31) + __ffs(m) - 1) >> 2; m &= m - 1; on = lane < 12;
                    go = G_L + s * 512 + 64 + lane * 16; gd = 256;
                }
                #pragma unroll 1
                for (int n = 0; n < (1 << 22); n++) {
                    const bool b1 = on && ((r.w >> 14) & 3) != tag, b2 = on && put && ((r2.w >> 16) & 3) != tag;
                    if (__builtin_expect(!__any_sync(~0u, b1 | b2), 1)) break;
                    ld_unit(r, gs + go, b1); ld_unit(r2, gs + go + gd, b2);
                }
                if (gd == HB) m = __ballot_sync(~0u, on && (~r.w & mb) == 0);
                if (on && r.w >> 16 == 255) sts32(sbase + SM_MISC + 4, 1);
                const uint32_t e[4] = {r.x, r.y, r.z, r.w}, v[4] = {r2.x, r2.y, r2.z, r2.w};
                uint32_t slot[4];
                #pragma unroll
                for (int k = 0; k < 4; k++) slot[k] = atoms_inc(sbase + SM_DEG + (on && e[k] >> 16 == (uint32_t)b ? (e[k] & 0x3FFF) : (NPB_MAX + lane) * 4));
                if (put) {
                    #pragma unroll
                    for (int k = 0; k < 4; k++) place(sbase, slot[k], v[k], s * ch);
                }
            }
            if (put == 0) {
                WS(4);
                asm volatile("bar.arrive 11, 512;" ::: "memory");
                if (w == 3) {
                    x_ld(0, 1);
                    w_expect(su + SM_ABAR, 12288); w_expect(su + SM_ABAR + 8, 12288); w_expect(su + SM_ABAR + 16, nb * (CE * 4) - 24576);
                    w_hint(gbar + 4, all);
                    asm volatile("cp.async.bulk.wait_group.read 0;" ::: "memory");
                    WS(3);
                    const char* g2 = gs + b * (P1B + P2B) + P1B;
                    w_ld(su + SM_P2, g2, 12288, su + SM_ABAR);
                    w_ld(su + SM_P2 + 12288, g2 + 12288, 12288, su + SM_ABAR + 8);
                    w_ld(su + SM_P2 + 24576, g2 + 24576, nb * (CE * 4) - 24576, su + SM_ABAR + 16);
                    w_ld(su + SM_H2, gs + G_H2, nb * 64, su + SM_ABAR + 40);
                    x_ld(1, 2);
                    mbar_wait_c(ab, 1);
                    x_ld(2, 6);
                } else {
                    #pragma unroll 11
                    for (int i = 0; i < 33; i++) w_init(su + SM_GBAR + (w * 33 + i) * 8, 32);
                    w_init(su + SM_GBAR + GD * 8, 32);
                }
                asm volatile("bar.sync 4, 512;" ::: "memory");
                mbar_wait_c(ab + 40, 0);
            }
        }
        __syncwarp();
        WS(10);
        WGD();
        const uint32_t scr = sbase + SM_PAIR + (tid & 127) * 8;
        const int r4 = lane >> 3, c8 = lane & 7;
        const uint32_t sb = su;
        const uint32_t tk = ((c8 & 1) << 4) | ((c8 >> 1) << 7);
        if (w < 3) {
            const char* gx = as_pair((const char*)x + c8 * 16, scr);
            const char* ge = as_pair((const char*)ea + (lane & 1) * 16, scr);
            const uint32_t gx0 = (uint32_t)(uint64_t)gx, ge0 = (uint32_t)(uint64_t)ge, hi = (uint64_t)gx >> 32, he = (uint64_t)ge >> 32;
            const int s = (lane >> 1) & 3;
            const uint32_t xs0 = sb + SM_XS + w * NSTAGE * XS_BYTES;
            const uint32_t es0 = sb + SM_ES + w * NSTAGE * ES_BYTES + r4 * 64 + (((lane ^ (r4 >> 1)) & 1) << 4) + (s >> 1) * 256 + (s & 1) * 32;
            const uint32_t bars = sb + SM_BARS + w * 2 * STG;
            const uint32_t xoffA = (2 * r4) * 128 + ((c8 ^ (2 * r4)) << 4);
            uint64_t pol;
            asm volatile("createpolicy.fractional.L2::evict_first.b64 %0, 1.0;" : "=l"(pol));
            asm volatile("bar.sync 6, 128;" ::: "memory");
            WS(15);
            uint32_t ph = 1, cur = w;
            uint32_t hist = GD * 0x010101u;
            auto done3 = [&]() { uint32_t v = (hist >> 16) & 0xFF; asm("" : "+r"(v)); mbar_arrive(sb + SM_GBAR + v * 8); };
            const bool go = __reduce_or_sync(~0u, misc[1] == 0 && nn > 0);
            const uint32_t ra = __shfl_sync(~0u, (lane & 15) * 16 + 32, lane), k15 = __shfl_sync(~0u, 15 | (lane & 1) << 7, lane), ca = SM_CLAIM + min(lane, 30) * 4, pa = sb + SM_TINFO + r4 * 8;
            const uint32_t pb = sb + SM_TINFO + s * 8 + 4, pc = sb + SM_TINFO + (lane & 3) * 8 + 6, xl = (lane & 8) << 1, xs = ra & 16;
            auto row_of = [&](uint32_t o) { uint32_t v; asm volatile("ld.shared.u16 %0, [%1];" : "=r"(v) : "r"(pb + o) : "memory"); return v; };
            auto code_of = [&](uint32_t o) { uint32_t v; asm volatile("ld.shared.s16 %0, [%1];" : "=r"(v) : "r"(pc + o) : "memory"); return v; };
            uint32_t pw = lds32(pa + w * 32), pt = __reduce_or_sync(~0u, pw), cont = 1;
            uint4 rc = make_uint4(0, row_of(w * 32) ^ xs, code_of(w * 32) & (ONE_F | 0x1FFFu), 0);
            const uint32_t se0 = sb + SM_EID + s * 4, brs = 2 * bars + STG;
            uint32_t br = bars, da = xs0 + xoffA, de = es0, ue = ES_BYTES;
            #pragma unroll 1
            while (go) {
                uint32_t se, sx;
                asm("dp2a.lo.u32.u32 %0, %1, 4, %2;" : "=r"(se) : "r"(pw), "r"(se0));
                asm("dp2a.lo.u32.u32 %0, %1, 2, %2;" : "=r"(sx) : "r"(pw), "r"(sb + SM_SRC));
                const int dv = pw >> 27;
                const uint32_t db = da ^ 0x90;
                const uint32_t sel = (pt >> 16) & 15, nf = (pt >> 15) & (127 << 5), nx = nf == 32 ? 0u : nf;
                uint32_t g;
                auto claim = [&]() { asm volatile("atom.shared.add.u32 %0, [%1], %2;" : "=r"(g) : "r"(ca + (nx == 0 ? sb : sb + 4)), "r"(ra) : "memory"); };
                if (sel == 0) break;
                if ((cont & 1) | (nf ^ nx)) {
                    if (cont & 1) asm volatile("bar.sync 3, 480;" ::: "memory");
                    if (nf != nx) mbar_wait_c(sb + SM_ABAR + 32, 0);
                }
                switch (sel) {
#define CASE(L, P, GEN) case L: { \
                        uint32_t oe[(P + 1) / 2], o[P]; \
                        _Pragma("unroll") for (int j = 0; j < (P + 1) / 2; j++) oe[j] = lds32(se + j * 16); \
                        _Pragma("unroll") for (int j = 0; j < P; j++) o[j] = lds32(sx + j * 4); \
                        mbar_wait_h(br + 8, ph); \
                        _Pragma("unroll") for (int j = 0; j < (P + 1) / 2; j++) \
                            if (LO32) { if (!GEN && 2 * j + 2 < P) cpe<false>(he, de + j * 512, oe[j], ge0, 0, 0, pol); \
                                else if (2 * j + 1 < NPMAX || s < 2) cpe<true>(he, de + j * 512, oe[j], ge0, 4 * j + s, dv, pol); } \
                            else if (!GEN && 2 * j + 2 < P) cp16e(de + j * 512, ge, oe[j], pol); else if (2 * j + 1 < NPMAX || s < 2) cp16z<32>(de + j * 512, ge, oe[j], 4 * j + s, dv, pol); \
                        _Pragma("unroll") for (int j = 0; j < P - 1; j++) { \
                            if (LO32) { cpx<0, GEN>(hi, da + j * 1024, o[j], gx0, 2 * j, dv); cpx<1, GEN>(hi, db + j * 1024, o[j], gx0, 2 * j + 1, dv); } \
                            else if (GEN) { cp16z<128>(da + j * 1024, gx, o[j] & 0xFFFFu, 2 * j, dv, 0); cp16z<128>(db + j * 1024, gx, o[j] >> 16, 2 * j + 1, dv, 0); } \
                            else { cp16i<128>(da + j * 1024, gx, o[j] & 0xFFFFu); cp16i<128>(db + j * 1024, gx, o[j] >> 16); } } \
                        if (LO32) { cpx<0, true>(hi, da + (P - 1) * 1024, o[P - 1], gx0, 2 * P - 2, dv); cpx<1, true>(hi, db + (P - 1) * 1024, o[P - 1], gx0, 2 * P - 1, dv); } \
                        else { cp16z<128>(da + (P - 1) * 1024, gx, o[P - 1] & 0xFFFFu, 2 * P - 2, dv, 0); cp16z<128>(db + (P - 1) * 1024, gx, o[P - 1] >> 16, 2 * P - 1, dv, 0); } \
                    } break;
                    CASE(11, 11, false) CASE(6, 6, false) CASE(7, 7, false) CASE(8, 8, false) CASE(9, 9, false) CASE(10, 10, false)
                    CASE(15, NPMAX, true) CASE(14, 8, true) default: CASE(13, 5, true)
#undef CASE
                }
                claim();
                mbar_cp_arrive(br);
                done3();
                g = __reduce_min_sync(~0u, g);
                {
                    const uint32_t o = nx == 0 ? g : nx;
                    pw = lds32(pa + o);
                    const uint32_t ya = row_of(o), yb = code_of(o);
                    pt = __reduce_or_sync(~0u, pw);
                    const uint32_t brk = (cont | nx) > 1 ? C_BRK : 0u;
                    rc.x = ya ^ xl;
                    const uint32_t lv = brk | ((sel + (15 - NPMAX)) & 16) | (((pt >> 16) & 15) ^ sel);
                    rc.w = (yb & k15) | (lv ? 0x70000000u | brk : TAU_BITS);
                    asm volatile("st.shared.v4.u32 [%2], {%3, %0, %1, %4};\nxor.b32 %0, %5, %6;\nand.b32 %1, %7, %8;"
                                 : "+r"(rc.y), "+r"(rc.z) : "r"(br + ra - 16), "r"(rc.x), "r"(rc.w), "r"(ya), "r"(xs), "r"(yb), "n"(ONE_F | 0x1FFFu) : "memory");
                    cont = nx;
                }
                mbar_arrive(br);
                hist = (hist << 8) | (nx == 0 ? cur : (uint32_t)GD);
                cur = nx == 0 ? g >> 5 : cur;
                da += ue * 4; de += ue; ue = -ue;
                ph ^= br != bars; br = brs - br;
            }
            if (cont & 1) asm volatile("bar.sync 3, 480;" ::: "memory");
            if (go) {
                mbar_wait(sb + SM_ABAR + 32, 0);
                const int g0 = 3 * max((misc[7] + 2) / 3 - TR, 0) + w;
                uint32_t ro[TR], gb[TR]; uint4 xv[TR], xu[TR]; char* op[TR];
                const int gz = misc[4];
                #pragma unroll
                for (int k = 0; k < TR; k++) {
                    uint32_t nd;
                    asm volatile("ld.shared.u16 %0, [%1];" : "=r"(nd) : "r"(pa + (g0 + 3 * k) * 32 + 4) : "memory");
                    uint32_t rb = node0 * 128 + row_bytes(nd);
                    if (g0 + 3 * k >= ngroups) rb = misc[16 + ((g0 + 3 * k - ngroups) & 3) * 4 + r4];
                    if (nd == tab_at(NONE)) rb = 0;
                    xv[k] = __ldg((const uint4*)(gx + rb));
                    op[k] = nd == tab_at(NONE) ? nullptr : (char*)out + rb + c8 * 16;
                    ro[k] = sb + (nd ^ tk);
                    xu[k] = lds128(ro[k] + SM_XU);
                    gb[k] = __reduce_or_sync(~0u, g0 + 3 * k < gz ? sb + SM_GBAR + (g0 + 3 * k) * 8 : 0u);
                }
                #pragma unroll 1
                for (int k = 0; k < 3; k++) {
                    mbar_wait(k < 2 ? br + 8 : sb + SM_ABAR + 48 + w * 8, k < 2 ? ph : 0);
                    done3(); hist <<= 8;
                    ph ^= br != bars; br = brs - br;
                }
                #pragma unroll
                for (int k = 0; k < TR; k++) {
                    uint4 a = make_uint4(0, 0, 0, 0);
                    if (gb[k]) { mbar_wait(gb[k], 0); a = lds128(ro[k] + SM_TAB); }
                    finish(a, xu[k], xv[k]);
                    if (op[k]) *(uint4*)op[k] = a;
                }
            }
            cp_wait<0>();
        } else {
            const int r4 = (lane >> 1) & 3, c8 = (lane >> 3) * 2 + (lane & 1);
            const uint32_t tk = ((c8 & 1) << 4) | ((c8 >> 1) << 7);
            const char* gx = as_pair((const char*)x + (size_t)node0 * 128 + c8 * 16, scr);
            const char* ob = as_pair((const char*)out + (size_t)node0 * 128 + c8 * 16, scr);
            asm volatile("bar.sync 6, 128;" ::: "memory");
            WS(15);
            if (b == 0 && lane == 0) asm volatile("red.relaxed.gpu.global.add.u32 [%0], 1;" :: "l"(gbar) : "memory");
            if (misc[1] == 0) mbar_wait(sb + SM_ABAR + 72, 0);
            if (npb <= NPB_MAX - 4) sts32(sb + SM_MISC + 12, 0);
            int rounds = misc[1] ? 0 : max((ngroups + 2) / 3 - TR, 0);
            const int gz = misc[4];
            int fast = __reduce_min_sync(~0u, min(rounds, gz / 3));
            const uint32_t wl = SM_TINFO + r4 * 8 + 4;
            uint32_t ko = sb;
            auto row_at = [&](uint32_t a) { uint32_t n; asm volatile("ld.shared.u16 %0, [%1];" : "=r"(n) : "r"(a) : "memory"); return n; };
            auto fetch = [&](uint32_t n, uint4& v) {
                asm volatile("{\n.reg .b64 p;\ncvt.u64.u32 p, %5;\nadd.u64 p, p, %4;\nld.global.nc.L1::no_allocate.v4.u32 {%0,%1,%2,%3}, [p];\n}"
                             : "=r"(v.x), "=r"(v.y), "=r"(v.z), "=r"(v.w) : "l"(gx), "r"(n));
            };
            auto store = [&](uint32_t n, const uint4& a) {
                asm volatile("{\n.reg .b64 p;\ncvt.u64.u32 p, %1;\nadd.u64 p, p, %0;\nst.global.v4.u32 [p], {%2,%3,%4,%5};\n}" :: "l"(ob), "r"(n), "r"(a.x), "r"(a.y), "r"(a.z), "r"(a.w) : "memory");
            };
            const uint32_t tw = __shfl_sync(~0u, tk, lane);
            int step = fast > R3 + PMIN && gz == ngroups ? -1 : -2, k = 0;
            #pragma unroll 1
            do {
                const int gn = __reduce_max_sync(~0u, balance(step, gs, all, ngroups, npb));
                if (step == R3) fast = rounds = (gn + 2) / 3 - TR;
                const bool pub = step < 0 && gn;
                step = gn == 0 || step == R3 ? fast - 1 : step < 0 ? R2 : R3;
                const uint32_t lim = step == fast - 1 ? ~0u : (ngroups - (KM + 3)) * 32;
                if (fast == 0) break;
                uint32_t n0[3], o0[3]; uint4 x0[3];
                #pragma unroll
                for (int r = 0; r < 3; r++) { const uint32_t v = row_at(wl + ko + r * 32); n0[r] = row_bytes(v); o0[r] = v ^ tw; fetch(n0[r], x0[r]); }
                #pragma unroll 1
                for (; k <= step; k++) {
                    const uint32_t wn = k < step ? ko + 96 : ko, gbar = sb + SM_GBAR + k * 24;
                    uint4 xu[3], a[3]; uint32_t v[3], ok;
                    #pragma unroll
                    for (int r = 0; r < 3; r++) { xu[r] = lds128(sb + o0[r] + SM_XU); v[r] = row_at(wl + wn + r * 32); }
#define TRY(o) "mbarrier.try_wait.parity.shared.b64 p, [%1 + " o "], 0, 4000;\n@p bra A_%=;\n"
#define NEXT(o) TRY(o) TRY(o) TRY(o) "bra B_%=;\n"
                    asm volatile("{\n.reg .pred p, q, r;\n.reg .b32 c, n;\nmov.u32 n, 0;\n"
                                 "A_%=:\nmbarrier.test_wait.parity.shared.b64 p, [%1], 0;\nmbarrier.test_wait.parity.shared.b64 q, [%1 + 8], 0;\nmbarrier.test_wait.parity.shared.b64 r, [%1 + 16], 0;\n"
                                 "@!r bra W2_%=;\n@!q bra W1_%=;\n@p bra D_%=;\n"
                                 NEXT("0") "W1_%=:\n" NEXT("8") "W2_%=:\n" NEXT("16")
                                 "B_%=:\nld.volatile.shared.u32 c, [%2];\nadd.u32 n, n, 1;\nsetp.gt.u32 q, n, 0x100000;\n@q trap;\nsetp.le.u32 q, c, %3;\n@q bra A_%=;\n"
                                 "D_%=:\nselp.u32 %0, 1, 0, p;\n}" : "=r"(ok) : "r"(gbar), "r"(sb + SM_CLAIM), "r"(lim) : "memory");
#undef NEXT
#undef TRY
                    if (!ok) break;
                    #pragma unroll
                    for (int r = 0; r < 3; r++) a[r] = lds128(sb + o0[r] + SM_TAB);
                    #pragma unroll
                    for (int r = 0; r < 3; r++) {
                        finish(a[r], xu[r], x0[r]);
                        const uint32_t nd = n0[r];
                        n0[r] = row_bytes(v[r]); o0[r] = v[r] ^ tw;
                        fetch(n0[r], x0[r]);
                        store(nd, a[r]);
                    }
                    ko += 96;
                    if (pub && k == R1) {
                        uint32_t now; asm volatile("mov.u32 %0, %%globaltimer_lo;" : "=r"(now));
                        now = __reduce_max_sync(~0u, (((now + lds32(sb + SM_MISC + 48)) << 6) & ~511u) | 256);
                        sts32(sb + SM_MISC + 48, now);
                        asm volatile(ELECT "st.relaxed.gpu.global.v2.u32 [%0], {%1, %2};\n}" :: "l"(gs + G_F + b * 8), "r"(now), "r"(all) : "memory");
                    }
                }
                if (k <= R1) step = -2;
            } while (k < fast);
            #pragma unroll 1
            for (int g = 3 * fast; g < 3 * rounds; g++) {
                const uint32_t v = row_at(sb + SM_TINFO + r4 * 8 + 4 + g * 32), nd = row_bytes(v), ro = sb + (v ^ tw);
                uint4 xv, a = make_uint4(0, 0, 0, 0);
                fetch(nd, xv);
                if (g < gz) { mbar_wait(sb + SM_GBAR + g * 8, 0); a = lds128(ro + SM_TAB); }
                finish(a, lds128(ro + SM_XU), xv);
                store(nd, a);
            }
        }
    }
    WS(17); WG1(); CG(2);
}

}

extern "C" void kernel_launch(void* const* d_in, const int* in_sizes, int n_in, void* d_out, int out_size) {
    const __nv_bfloat16* x = (const __nv_bfloat16*)d_in[0];
    const __nv_bfloat16* ea = (const __nv_bfloat16*)d_in[1];
    const int* src = (const int*)d_in[2];
    const int* dst = (const int*)d_in[3];
    const __nv_bfloat16* wa = (const __nv_bfloat16*)d_in[4];
    const __nv_bfloat16* wb = (const __nv_bfloat16*)d_in[5];
    const __nv_bfloat16* wc = (const __nv_bfloat16*)d_in[6];
    const __nv_bfloat16* wu = (const __nv_bfloat16*)d_in[7];
    const __nv_bfloat16* wv = (const __nv_bfloat16*)d_in[8];
    __nv_bfloat16* out = (__nv_bfloat16*)d_out;
    int N = in_sizes[0] / 64, E = in_sizes[2];
    static int sms = 0;
    static CUtensorMap tm1, tm2, tmw, tmx;
    static bool tm_ok = false;
    static void* gp = nullptr; static void* gb = nullptr;
    typedef CUresult (*EncFn)(CUtensorMap*, CUtensorMapDataType, cuuint32_t, void*, const cuuint64_t*, const cuuint64_t*, const cuuint32_t*,
                              const cuuint32_t*, CUtensorMapInterleave, CUtensorMapSwizzle, CUtensorMapL2promotion, CUtensorMapFloatOOBfill);
    static void* fn = nullptr;
    auto enc = [&](CUtensorMap* tm, const void* base, cuuint64_t cols, cuuint64_t rows, cuuint32_t bc, cuuint32_t br, CUtensorMapSwizzle sw) {
        cuuint64_t g2[2] = {cols, rows}, gs[1] = {cols * 4};
        cuuint32_t b2[2] = {bc, br}, es[2] = {1, 1};
        return ((EncFn)fn)(tm, CU_TENSOR_MAP_DATA_TYPE_UINT32, 2, (void*)base, g2, gs, b2, es, CU_TENSOR_MAP_INTERLEAVE_NONE, sw,
                           CU_TENSOR_MAP_L2_PROMOTION_NONE, CU_TENSOR_MAP_FLOAT_OOB_FILL_NONE) == CUDA_SUCCESS;
    };
    if (!sms) {
        cudaDeviceGetAttribute(&sms, cudaDevAttrMultiProcessorCount, 0);
        cudaDriverEntryPointQueryResult qr;
        cudaGetDriverEntryPoint("cuTensorMapEncodeTiled", &fn, cudaEnableDefault, &qr);
        cudaGetSymbolAddress(&gp, g_str); cudaGetSymbolAddress(&gb, g_bar);
        if (fn && gp && gb) {
            const cuuint32_t rows = sms < NB_MAX ? sms : NB_MAX;
            tm_ok = enc(&tm1, gp, (P1B + P2B) / 4, NB_MAX, CE / 2, rows, CU_TENSOR_MAP_SWIZZLE_NONE) && enc(&tm2, gp, (P1B + P2B) / 4, NB_MAX, CE, rows, CU_TENSOR_MAP_SWIZZLE_NONE);
        }
        cudaFuncSetAttribute(gcn_kernel<true>, cudaFuncAttributeMaxDynamicSharedMemorySize, SMEM_LAUNCH);
        cudaFuncSetAttribute(gcn_kernel<false>, cudaFuncAttributeMaxDynamicSharedMemorySize, SMEM_LAUNCH);
    }
    int nb = sms < NB_MAX ? sms : NB_MAX;
    int npb = (N + nb - 1) / nb;
    int ch = (((E + nb - 1) / nb) + 3) & ~3;
    const uintptr_t wp[4] = {(uintptr_t)wb, (uintptr_t)wv, (uintptr_t)wa, (uintptr_t)wu};
    uintptr_t wlo = wp[0], whi = wp[0], wal = 0;
    for (int i = 0; i < 4; i++) { wlo = wp[i] < wlo ? wp[i] : wlo; whi = wp[i] > whi ? wp[i] : whi; wal |= wp[i] - wp[0]; }
    bool ok = tm_ok && nb >= NB_MIN && npb < NPB_MAX && ch <= CH_MAX && !(E & 3) && N <= 65535 && npb >= 2 && !(wal & 127) && (whi - wlo) >> 7 < (1u << 30) &&
              !(((uintptr_t)src | (uintptr_t)dst | (uintptr_t)x | (uintptr_t)wb | (uintptr_t)wc) & 15);
    ok = ok && enc(&tmw, (const void*)wlo, 32, ((whi - wlo) >> 7) + 64, 32, 64, CU_TENSOR_MAP_SWIZZLE_128B) && enc(&tmx, x, 32, N, 32, 64, CU_TENSOR_MAP_SWIZZLE_128B);
    if (!ok) {
        int g = 1024, p = (N + g - 1) / g;
        slow_kernel<<<g, 256>>>(x, ea, src, dst, wa, wb, wc, wu, wv, out, N, E, p < 1 ? 1 : p);
        return;
    }
    int4 wrow = make_int4((int)((wp[0] - wlo) >> 7), (int)((wp[1] - wlo) >> 7), (int)((wp[2] - wlo) >> 7), (int)((wp[3] - wlo) >> 7));
    uint32_t magic = (uint32_t)((1ull << 32) / (uint32_t)npb) + 1u;
    void* args[] = {&dst, &gb, &gp, &src, &E, &ch, &N, &npb, &magic, &x, &ea, &wa, &wb, &wc, &wu, &wv, &out, &wrow, &tm1, &tm2, &tmw, &tmx};
    const bool lo32 = ((uintptr_t)x >> 32) == (((uintptr_t)x + (size_t)N * 128 - 1) >> 32) && ((uintptr_t)ea >> 32) == (((uintptr_t)ea + (size_t)E * 32 - 1) >> 32);
    cudaLaunchCooperativeKernel(lo32 && !FORCE64 ? (const void*)gcn_kernel<true> : (const void*)gcn_kernel<false>, dim3(nb), dim3(THREADS), args, SMEM_LAUNCH, cudaStreamPerThread);
}
```

```cpp
#include <cuda_runtime.h>
#include <cuda.h>
#include <cuda_bf16.h>
#include <stdint.h>

namespace {

constexpr int N_MAX = 65536;
constexpr int NPMAX = 11;
constexpr int NPMIN = 5;
constexpr int THREADS = 512;
constexpr int EPT = 12;
constexpr int CH_MAX = THREADS * EPT;
constexpr int NB_MAX = 134, NB_MIN = 120;
constexpr int CE = 64;
constexpr int P1B = NB_MAX * CE * 2;
constexpr int P2B = NB_MAX * CE * 4;
constexpr int HB = NB_MAX * 64;
constexpr int G_H1 = NB_MAX * (P1B + P2B), G_H2 = G_H1 + HB, G_L = G_H2 + HB, G_F = G_L + NB_MAX * 512;
constexpr int KM = 4, GRP_B = 1536, G_R = G_F + 2048, G_P = G_R + 2048, G_END = G_P + NB_MAX * KM * GRP_B;
#define BAL 1
#define TRIES 12
#define PMIN 8
constexpr int R1 = 9, R2 = 11, R3 = 14;
constexpr int GD = 100;
constexpr int NPB_MAX = 384;
constexpr int SLOT_CAP = 6784;
constexpr int TILE_CAP = 123;
constexpr int TILE_X = 8;
constexpr int NCLS = 64;
constexpr int NSTAGE = 2;
constexpr int PD = 300;
constexpr int TR = 2;
constexpr float LOG2E = 1.4426950408889634f;

__device__ __align__(256) uint4 g_str[G_END / 16];
__device__ __align__(128) unsigned g_bar[8];
__device__ float g_slow[N_MAX * 128];
__device__ float4 g_copy[NB_MAX * 384 * 2 * NPMAX];

#define WS(k)
#define WGD()
#define WG0()
#define WG1()
#define CG(k)
#define SMEM_LAUNCH SMEM_BYTES
#define FORCE64 0
#define EDHI ((16ull << 32) | (3ull << 62))
template<int NP> struct TileMMA;
template<> struct TileMMA<5> {
  static __device__ __forceinline__ void issue(float* g, float* h, const uint32_t* w, uint32_t dx, uint64_t de, uint64_t dh, uint64_t dc) {
    asm volatile(
      "{\n.reg .b64 dx0, dx1, dx2, dx3;\n.reg .b32 l1, l2, l3, hx;\nmov.b32 hx, 0x40000040;\n"
      "add.u32 l1, %80, 2;\nadd.u32 l2, %80, 4;\nadd.u32 l3, %80, 6;\n"
      "mov.b64 dx0, {%80, hx};\nmov.b64 dx1, {l1, hx};\nmov.b64 dx2, {l2, hx};\nmov.b64 dx3, {l3, hx};\n"
      "wgmma.fence.sync.aligned;\n"
      "wgmma.mma_async.sync.aligned.m64n40k16.f32.bf16.bf16 {%0, %1, %2, %3, %4, %5, %6, %7, %8, %9, %10, %11, %12, %13, %14, %15, %16, %17, %18, %19}, {%76, %77, %78, %79}, %82, 0, 1, 1, 0;\n"
      "wgmma.mma_async.sync.aligned.m64n40k16.f32.bf16.bf16 {%0, %1, %2, %3, %4, %5, %6, %7, %8, %9, %10, %11, %12, %13, %14, %15, %16, %17, %18, %19}, {%56, %57, %58, %59}, %81, 1, 1, 1, 0;\n"
      "wgmma.mma_async.sync.aligned.m64n40k16.f32.bf16.bf16 {%0, %1, %2, %3, %4, %5, %6, %7, %8, %9, %10, %11, %12, %13, %14, %15, %16, %17, %18, %19}, {%40, %41, %42, %43}, dx0, 1, 1, 1, 0;\n"
      "wgmma.mma_async.sync.aligned.m64n40k16.f32.bf16.bf16 {%0, %1, %2, %3, %4, %5, %6, %7, %8, %9, %10, %11, %12, %13, %14, %15, %16, %17, %18, %19}, {%44, %45, %46, %47}, dx1, 1, 1, 1, 0;\n"
      "wgmma.mma_async.sync.aligned.m64n40k16.f32.bf16.bf16 {%0, %1, %2, %3, %4, %5, %6, %7, %8, %9, %10, %11, %12, %13, %14, %15, %16, %17, %18, %19}, {%48, %49, %50, %51}, dx2, 1, 1, 1, 0;\n"
      "wgmma.mma_async.sync.aligned.m64n40k16.f32.bf16.bf16 {%0, %1, %2, %3, %4, %5, %6, %7, %8, %9, %10, %11, %12, %13, %14, %15, %16, %17, %18, %19}, {%52, %53, %54, %55}, dx3, 1, 1, 1, 0;\n"
      "wgmma.commit_group.sync.aligned;\n"
      "wgmma.mma_async.sync.aligned.m64n40k16.f32.bf16.bf16 {%20, %21, %22, %23, %24, %25, %26, %27, %28, %29, %30, %31, %32, %33, %34, %35, %36, %37, %38, %39}, {%60, %61, %62, %63}, dx0, 0, 1, 1, 0;\n"
      "wgmma.mma_async.sync.aligned.m64n40k16.f32.bf16.bf16 {%20, %21, %22, %23, %24, %25, %26, %27, %28, %29, %30, %31, %32, %33, %34, %35, %36, %37, %38, %39}, {%64, %65, %66, %67}, dx1, 1, 1, 1, 0;\n"
      "wgmma.mma_async.sync.aligned.m64n40k16.f32.bf16.bf16 {%20, %21, %22, %23, %24, %25, %26, %27, %28, %29, %30, %31, %32, %33, %34, %35, %36, %37, %38, %39}, {%68, %69, %70, %71}, dx2, 1, 1, 1, 0;\n"
      "wgmma.mma_async.sync.aligned.m64n40k16.f32.bf16.bf16 {%20, %21, %22, %23, %24, %25, %26, %27, %28, %29, %30, %31, %32, %33, %34, %35, %36, %37, %38, %39}, {%72, %73, %74, %75}, dx3, 1, 1, 1, 0;\n"
      "wgmma.commit_group.sync.aligned;\n}\n"
      : "=f"(g[0]), "=f"(g[1]), "=f"(g[2]), "=f"(g[3]), "=f"(g[4]), "=f"(g[5]), "=f"(g[6]), "=f"(g[7]), "=f"(g[8]), "=f"(g[9]), "=f"(g[10]), "=f"(g[11]), "=f"(g[12]), "=f"(g[13]), "=f"(g[14]), "=f"(g[15]), "=f"(g[16]), "=f"(g[17]), "=f"(g[18]), "=f"(g[19]),
        "=f"(h[0]), "=f"(h[1]), "=f"(h[2]), "=f"(h[3]), "=f"(h[4]), "=f"(h[5]), "=f"(h[6]), "=f"(h[7]), "=f"(h[8]), "=f"(h[9]), "=f"(h[10]), "=f"(h[11]), "=f"(h[12]), "=f"(h[13]), "=f"(h[14]), "=f"(h[15]), "=f"(h[16]), "=f"(h[17]), "=f"(h[18]), "=f"(h[19])
      : "r"(w[0]), "r"(w[1]), "r"(w[2]), "r"(w[3]), "r"(w[4]), "r"(w[5]), "r"(w[6]), "r"(w[7]), "r"(w[8]), "r"(w[9]), "r"(w[10]), "r"(w[11]), "r"(w[12]), "r"(w[13]), "r"(w[14]), "r"(w[15]), "r"(w[16]), "r"(w[17]), "r"(w[18]), "r"(w[19]), "r"(w[20]), "r"(w[21]), "r"(w[22]), "r"(w[23]), "r"(w[24]), "r"(w[25]), "r"(w[26]), "r"(w[27]), "r"(w[28]), "r"(w[29]), "r"(w[30]), "r"(w[31]), "r"(w[32]), "r"(w[33]), "r"(w[34]), "r"(w[35]), "r"(w[36]), "r"(w[37]), "r"(w[38]), "r"(w[39]), "r"(dx), "l"(de), "l"(dh)
      : "memory");
  }
  static __device__ __forceinline__ void wait_g(float* g) {
    asm volatile("wgmma.wait_group.sync.aligned 1;\n"
      : "+f"(g[0]), "+f"(g[1]), "+f"(g[2]), "+f"(g[3]), "+f"(g[4]), "+f"(g[5]), "+f"(g[6]), "+f"(g[7]), "+f"(g[8]), "+f"(g[9]), "+f"(g[10]), "+f"(g[11]), "+f"(g[12]), "+f"(g[13]), "+f"(g[14]), "+f"(g[15]), "+f"(g[16]), "+f"(g[17]), "+f"(g[18]), "+f"(g[19])
      :: "memory");
  }
  static __device__ __forceinline__ void wait_h(float* h) {
    asm volatile("wgmma.wait_group.sync.aligned 0;\n"
      : "+f"(h[0]), "+f"(h[1]), "+f"(h[2]), "+f"(h[3]), "+f"(h[4]), "+f"(h[5]), "+f"(h[6]), "+f"(h[7]), "+f"(h[8]), "+f"(h[9]), "+f"(h[10]), "+f"(h[11]), "+f"(h[12]), "+f"(h[13]), "+f"(h[14]), "+f"(h[15]), "+f"(h[16]), "+f"(h[17]), "+f"(h[18]), "+f"(h[19])
      :: "memory");
  }
};
template<> struct TileMMA<6> {
  static __device__ __forceinline__ void issue(float* g, float* h, const uint32_t* w, uint32_t dx, uint64_t de, uint64_t dh, uint64_t dc) {
    asm volatile(
      "{\n.reg .b64 dx0, dx1, dx2, dx3;\n.reg .b32 l1, l2, l3, hx;\nmov.b32 hx, 0x40000040;\n"
      "add.u32 l1, %88, 2;\nadd.u32 l2, %88, 4;\nadd.u32 l3, %88, 6;\n"
      "mov.b64 dx0, {%88, hx};\nmov.b64 dx1, {l1, hx};\nmov.b64 dx2, {l2, hx};\nmov.b64 dx3, {l3, hx};\n"
      "wgmma.fence.sync.aligned;\n"
      "wgmma.mma_async.sync.aligned.m64n48k16.f32.bf16.bf16 {%0, %1, %2, %3, %4, %5, %6, %7, %8, %9, %10, %11, %12, %13, %14, %15, %16, %17, %18, %19, %20, %21, %22, %23}, {%84, %85, %86, %87}, %90, 0, 1, 1, 0;\n"
      "wgmma.mma_async.sync.aligned.m64n48k16.f32.bf16.bf16 {%0, %1, %2, %3, %4, %5, %6, %7, %8, %9, %10, %11, %12, %13, %14, %15, %16, %17, %18, %19, %20, %21, %22, %23}, {%64, %65, %66, %67}, %89, 1, 1, 1, 0;\n"
      "wgmma.mma_async.sync.aligned.m64n48k16.f32.bf16.bf16 {%0, %1, %2, %3, %4, %5, %6, %7, %8, %9, %10, %11, %12, %13, %14, %15, %16, %17, %18, %19, %20, %21, %22, %23}, {%48, %49, %50, %51}, dx0, 1, 1, 1, 0;\n"
      "wgmma.mma_async.sync.aligned.m64n48k16.f32.bf16.bf16 {%0, %1, %2, %3, %4, %5, %6, %7, %8, %9, %10, %11, %12, %13, %14, %15, %16, %17, %18, %19, %20, %21, %22, %23}, {%52, %53, %54, %55}, dx1, 1, 1, 1, 0;\n"
      "wgmma.mma_async.sync.aligned.m64n48k16.f32.bf16.bf16 {%0, %1, %2, %3, %4, %5, %6, %7, %8, %9, %10, %11, %12, %13, %14, %15, %16, %17, %18, %19, %20, %21, %22, %23}, {%56, %57, %58, %59}, dx2, 1, 1, 1, 0;\n"
      "wgmma.mma_async.sync.aligned.m64n48k16.f32.bf16.bf16 {%0, %1, %2, %3, %4, %5, %6, %7, %8, %9, %10, %11, %12, %13, %14, %15, %16, %17, %18, %19, %20, %21, %22, %23}, {%60, %61, %62, %63}, dx3, 1, 1, 1, 0;\n"
      "wgmma.commit_group.sync.aligned;\n"
      "wgmma.mma_async.sync.aligned.m64n48k16.f32.bf16.bf16 {%24, %25, %26, %27, %28, %29, %30, %31, %32, %33, %34, %35, %36, %37, %38, %39, %40, %41, %42, %43, %44, %45, %46, %47}, {%68, %69, %70, %71}, dx0, 0, 1, 1, 0;\n"
      "wgmma.mma_async.sync.aligned.m64n48k16.f32.bf16.bf16 {%24, %25, %26, %27, %28, %29, %30, %31, %32, %33, %34, %35, %36, %37, %38, %39, %40, %41, %42, %43, %44, %45, %46, %47}, {%72, %73, %74, %75}, dx1, 1, 1, 1, 0;\n"
      "wgmma.mma_async.sync.aligned.m64n48k16.f32.bf16.bf16 {%24, %25, %26, %27, %28, %29, %30, %31, %32, %33, %34, %35, %36, %37, %38, %39, %40, %41, %42, %43, %44, %45, %46, %47}, {%76, %77, %78, %79}, dx2, 1, 1, 1, 0;\n"
      "wgmma.mma_async.sync.aligned.m64n48k16.f32.bf16.bf16 {%24, %25, %26, %27, %28, %29, %30, %31, %32, %33, %34, %35, %36, %37, %38, %39, %40, %41, %42, %43, %44, %45, %46, %47}, {%80, %81, %82, %83}, dx3, 1, 1, 1, 0;\n"
      "wgmma.commit_group.sync.aligned;\n}\n"
      : "=f"(g[0]), "=f"(g[1]), "=f"(g[2]), "=f"(g[3]), "=f"(g[4]), "=f"(g[5]), "=f"(g[6]), "=f"(g[7]), "=f"(g[8]), "=f"(g[9]), "=f"(g[10]), "=f"(g[11]), "=f"(g[12]), "=f"(g[13]), "=f"(g[14]), "=f"(g[15]), "=f"(g[16]), "=f"(g[17]), "=f"(g[18]), "=f"(g[19]), "=f"(g[20]), "=f"(g[21]), "=f"(g[22]), "=f"(g[23]),
        "=f"(h[0]), "=f"(h[1]), "=f"(h[2]), "=f"(h[3]), "=f"(h[4]), "=f"(h[5]), "=f"(h[6]), "=f"(h[7]), "=f"(h[8]), "=f"(h[9]), "=f"(h[10]), "=f"(h[11]), "=f"(h[12]), "=f"(h[13]), "=f"(h[14]), "=f"(h[15]), "=f"(h[16]), "=f"(h[17]), "=f"(h[18]), "=f"(h[19]), "=f"(h[20]), "=f"(h[21]), "=f"(h[22]), "=f"(h[23])
      : "r"(w[0]), "r"(w[1]), "r"(w[2]), "r"(w[3]), "r"(w[4]), "r"(w[5]), "r"(w[6]), "r"(w[7]), "r"(w[8]), "r"(w[9]), "r"(w[10]), "r"(w[11]), "r"(w[12]), "r"(w[13]), "r"(w[14]), "r"(w[15]), "r"(w[16]), "r"(w[17]), "r"(w[18]), "r"(w[19]), "r"(w[20]), "r"(w[21]), "r"(w[22]), "r"(w[23]), "r"(w[24]), "r"(w[25]), "r"(w[26]), "r"(w[27]), "r"(w[28]), "r"(w[29]), "r"(w[30]), "r"(w[31]), "r"(w[32]), "r"(w[33]), "r"(w[34]), "r"(w[35]), "r"(w[36]), "r"(w[37]), "r"(w[38]), "r"(w[39]), "r"(dx), "l"(de), "l"(dh)
      : "memory");
  }
  static __device__ __forceinline__ void wait_g(float* g) {
    asm volatile("wgmma.wait_group.sync.aligned 1;\n"
      : "+f"(g[0]), "+f"(g[1]), "+f"(g[2]), "+f"(g[3]), "+f"(g[4]), "+f"(g[5]), "+f"(g[6]), "+f"(g[7]), "+f"(g[8]), "+f"(g[9]), "+f"(g[10]), "+f"(g[11]), "+f"(g[12]), "+f"(g[13]), "+f"(g[14]), "+f"(g[15]), "+f"(g[16]), "+f"(g[17]), "+f"(g[18]), "+f"(g[19]), "+f"(g[20]), "+f"(g[21]), "+f"(g[22]), "+f"(g[23])
      :: "memory");
  }
  static __device__ __forceinline__ void wait_h(float* h) {
    asm volatile("wgmma.wait_group.sync.aligned 0;\n"
      : "+f"(h[0]), "+f"(h[1]), "+f"(h[2]), "+f"(h[3]), "+f"(h[4]), "+f"(h[5]), "+f"(h[6]), "+f"(h[7]), "+f"(h[8]), "+f"(h[9]), "+f"(h[10]), "+f"(h[11]), "+f"(h[12]), "+f"(h[13]), "+f"(h[14]), "+f"(h[15]), "+f"(h[16]), "+f"(h[17]), "+f"(h[18]), "+f"(h[19]), "+f"(h[20]), "+f"(h[21]), "+f"(h[22]), "+f"(h[23])
      :: "memory");
  }
};
template<> struct TileMMA<7> {
  static __device__ __forceinline__ void issue(float* g, float* h, const uint32_t* w, uint32_t dx, uint64_t de, uint64_t dh, uint64_t dc) {
    asm volatile(
      "{\n.reg .b64 dx0, dx1, dx2, dx3;\n.reg .b32 l1, l2, l3, hx;\nmov.b32 hx, 0x40000040;\n"
      "add.u32 l1, %96, 2;\nadd.u32 l2, %96, 4;\nadd.u32 l3, %96, 6;\n"
      "mov.b64 dx0, {%96, hx};\nmov.b64 dx1, {l1, hx};\nmov.b64 dx2, {l2, hx};\nmov.b64 dx3, {l3, hx};\n"
      "wgmma.fence.sync.aligned;\n"
      "wgmma.mma_async.sync.aligned.m64n56k16.f32.bf16.bf16 {%0, %1, %2, %3, %4, %5, %6, %7, %8, %9, %10, %11, %12, %13, %14, %15, %16, %17, %18, %19, %20, %21, %22, %23, %24, %25, %26, %27}, {%92, %93, %94, %95}, %98, 0, 1, 1, 0;\n"
      "wgmma.mma_async.sync.aligned.m64n56k16.f32.bf16.bf16 {%0, %1, %2, %3, %4, %5, %6, %7, %8, %9, %10, %11, %12, %13, %14, %15, %16, %17, %18, %19, %20, %21, %22, %23, %24, %25, %26, %27}, {%72, %73, %74, %75}, %97, 1, 1, 1, 0;\n"
      "wgmma.mma_async.sync.aligned.m64n56k16.f32.bf16.bf16 {%0, %1, %2, %3, %4, %5, %6, %7, %8, %9, %10, %11, %12, %13, %14, %15, %16, %17, %18, %19, %20, %21, %22, %23, %24, %25, %26, %27}, {%56, %57, %58, %59}, dx0, 1, 1, 1, 0;\n"
      "wgmma.mma_async.sync.aligned.m64n56k16.f32.bf16.bf16 {%0, %1, %2, %3, %4, %5, %6, %7, %8, %9, %10, %11, %12, %13, %14, %15, %16, %17, %18, %19, %20, %21, %22, %23, %24, %25, %26, %27}, {%60, %61, %62, %63}, dx1, 1, 1, 1, 0;\n"
      "wgmma.mma_async.sync.aligned.m64n56k16.f32.bf16.bf16 {%0, %1, %2, %3, %4, %5, %6, %7, %8, %9, %10, %11, %12, %13, %14, %15, %16, %17, %18, %19, %20, %21, %22, %23, %24, %25, %26, %27}, {%64, %65, %66, %67}, dx2, 1, 1, 1, 0;\n"
      "wgmma.mma_async.sync.aligned.m64n56k16.f32.bf16.bf16 {%0, %1, %2, %3, %4, %5, %6, %7, %8, %9, %10, %11, %12, %13, %14, %15, %16, %17, %18, %19, %20, %21, %22, %23, %24, %25, %26, %27}, {%68, %69, %70, %71}, dx3, 1, 1, 1, 0;\n"
      "wgmma.commit_group.sync.aligned;\n"
      "wgmma.mma_async.sync.aligned.m64n56k16.f32.bf16.bf16 {%28, %29, %30, %31, %32, %33, %34, %35, %36, %37, %38, %39, %40, %41, %42, %43, %44, %45, %46, %47, %48, %49, %50, %51, %52, %53, %54, %55}, {%76, %77, %78, %79}, dx0, 0, 1, 1, 0;\n"
      "wgmma.mma_async.sync.aligned.m64n56k16.f32.bf16.bf16 {%28, %29, %30, %31, %32, %33, %34, %35, %36, %37, %38, %39, %40, %41, %42, %43, %44, %45, %46, %47, %48, %49, %50, %51, %52, %53, %54, %55}, {%80, %81, %82, %83}, dx1, 1, 1, 1, 0;\n"
      "wgmma.mma_async.sync.aligned.m64n56k16.f32.bf16.bf16 {%28, %29, %30, %31, %32, %33, %34, %35, %36, %37, %38, %39, %40, %41, %42, %43, %44, %45, %46, %47, %48, %49, %50, %51, %52, %53, %54, %55}, {%84, %85, %86, %87}, dx2, 1, 1, 1, 0;\n"
      "wgmma.mma_async.sync.aligned.m64n56k16.f32.bf16.bf16 {%28, %29, %30, %31, %32, %33, %34, %35, %36, %37, %38, %39, %40, %41, %42, %43, %44, %45, %46, %47, %48, %49, %50, %51, %52, %53, %54, %55}, {%88, %89, %90, %91}, dx3, 1, 1, 1, 0;\n"
      "wgmma.commit_group.sync.aligned;\n}\n"
      : "=f"(g[0]), "=f"(g[1]), "=f"(g[2]), "=f"(g[3]), "=f"(g[4]), "=f"(g[5]), "=f"(g[6]), "=f"(g[7]), "=f"(g[8]), "=f"(g[9]), "=f"(g[10]), "=f"(g[11]), "=f"(g[12]), "=f"(g[13]), "=f"(g[14]), "=f"(g[15]), "=f"(g[16]), "=f"(g[17]), "=f"(g[18]), "=f"(g[19]), "=f"(g[20]), "=f"(g[21]), "=f"(g[22]), "=f"(g[23]), "=f"(g[24]), "=f"(g[25]), "=f"(g[26]), "=f"(g[27]),
        "=f"(h[0]), "=f"(h[1]), "=f"(h[2]), "=f"(h[3]), "=f"(h[4]), "=f"(h[5]), "=f"(h[6]), "=f"(h[7]), "=f"(h[8]), "=f"(h[9]), "=f"(h[10]), "=f"(h[11]), "=f"(h[12]), "=f"(h[13]), "=f"(h[14]), "=f"(h[15]), "=f"(h[16]), "=f"(h[17]), "=f"(h[18]), "=f"(h[19]), "=f"(h[20]), "=f"(h[21]), "=f"(h[22]), "=f"(h[23]), "=f"(h[24]), "=f"(h[25]), "=f"(h[26]), "=f"(h[27])
      : "r"(w[0]), "r"(w[1]), "r"(w[2]), "r"(w[3]), "r"(w[4]), "r"(w[5]), "r"(w[6]), "r"(w[7]), "r"(w[8]), "r"(w[9]), "r"(w[10]), "r"(w[11]), "r"(w[12]), "r"(w[13]), "r"(w[14]), "r"(w[15]), "r"(w[16]), "r"(w[17]), "r"(w[18]), "r"(w[19]), "r"(w[20]), "r"(w[21]), "r"(w[22]), "r"(w[23]), "r"(w[24]), "r"(w[25]), "r"(w[26]), "r"(w[27]), "r"(w[28]), "r"(w[29]), "r"(w[30]), "r"(w[31]), "r"(w[32]), "r"(w[33]), "r"(w[34]), "r"(w[35]), "r"(w[36]), "r"(w[37]), "r"(w[38]), "r"(w[39]), "r"(dx), "l"(de), "l"(dh)
      : "memory");
  }
  static __device__ __forceinline__ void wait_g(float* g) {
    asm volatile("wgmma.wait_group.sync.aligned 1;\n"
      : "+f"(g[0]), "+f"(g[1]), "+f"(g[2]), "+f"(g[3]), "+f"(g[4]), "+f"(g[5]), "+f"(g[6]), "+f"(g[7]), "+f"(g[8]), "+f"(g[9]), "+f"(g[10]), "+f"(g[11]), "+f"(g[12]), "+f"(g[13]), "+f"(g[14]), "+f"(g[15]), "+f"(g[16]), "+f"(g[17]), "+f"(g[18]), "+f"(g[19]), "+f"(g[20]), "+f"(g[21]), "+f"(g[22]), "+f"(g[23]), "+f"(g[24]), "+f"(g[25]), "+f"(g[26]), "+f"(g[27])
      :: "memory");
  }
  static __device__ __forceinline__ void wait_h(float* h) {
    asm volatile("wgmma.wait_group.sync.aligned 0;\n"
      : "+f"(h[0]), "+f"(h[1]), "+f"(h[2]), "+f"(h[3]), "+f"(h[4]), "+f"(h[5]), "+f"(h[6]), "+f"(h[7]), "+f"(h[8]), "+f"(h[9]), "+f"(h[10]), "+f"(h[11]), "+f"(h[12]), "+f"(h[13]), "+f"(h[14]), "+f"(h[15]), "+f"(h[16]), "+f"(h[17]), "+f"(h[18]), "+f"(h[19]), "+f"(h[20]), "+f"(h[21]), "+f"(h[22]), "+f"(h[23]), "+f"(h[24]), "+f"(h[25]), "+f"(h[26]), "+f"(h[27])
      :: "memory");
  }
};
template<> struct TileMMA<8> {
  static __device__ __forceinline__ void issue(float* g, float* h, const uint32_t* w, uint32_t dx, uint64_t de, uint64_t dh, uint64_t dc) {
    asm volatile(
      "{\n.reg .b64 dx0, dx1, dx2, dx3;\n.reg .b32 l1, l2, l3, hx;\nmov.b32 hx, 0x40000040;\n"
      "add.u32 l1, %104, 2;\nadd.u32 l2, %104, 4;\nadd.u32 l3, %104, 6;\n"
      "mov.b64 dx0, {%104, hx};\nmov.b64 dx1, {l1, hx};\nmov.b64 dx2, {l2, hx};\nmov.b64 dx3, {l3, hx};\n"
      "wgmma.fence.sync.aligned;\n"
      "wgmma.mma_async.sync.aligned.m64n64k16.f32.bf16.bf16 {%0, %1, %2, %3, %4, %5, %6, %7, %8, %9, %10, %11, %12, %13, %14, %15, %16, %17, %18, %19, %20, %21, %22, %23, %24, %25, %26, %27, %28, %29, %30, %31}, {%100, %101, %102, %103}, %106, 0, 1, 1, 0;\n"
      "wgmma.mma_async.sync.aligned.m64n64k16.f32.bf16.bf16 {%0, %1, %2, %3, %4, %5, %6, %7, %8, %9, %10, %11, %12, %13, %14, %15, %16, %17, %18, %19, %20, %21, %22, %23, %24, %25, %26, %27, %28, %29, %30, %31}, {%80, %81, %82, %83}, %105, 1, 1, 1, 0;\n"
      "wgmma.mma_async.sync.aligned.m64n64k16.f32.bf16.bf16 {%0, %1, %2, %3, %4, %5, %6, %7, %8, %9, %10, %11, %12, %13, %14, %15, %16, %17, %18, %19, %20, %21, %22, %23, %24, %25, %26, %27, %28, %29, %30, %31}, {%64, %65, %66, %67}, dx0, 1, 1, 1, 0;\n"
      "wgmma.mma_async.sync.aligned.m64n64k16.f32.bf16.bf16 {%0, %1, %2, %3, %4, %5, %6, %7, %8, %9, %10, %11, %12, %13, %14, %15, %16, %17, %18, %19, %20, %21, %22, %23, %24, %25, %26, %27, %28, %29, %30, %31}, {%68, %69, %70, %71}, dx1, 1, 1, 1, 0;\n"
      "wgmma.mma_async.sync.aligned.m64n64k16.f32.bf16.bf16 {%0, %1, %2, %3, %4, %5, %6, %7, %8, %9, %10, %11, %12, %13, %14, %15, %16, %17, %18, %19, %20, %21, %22, %23, %24, %25, %26, %27, %28, %29, %30, %31}, {%72, %73, %74, %75}, dx2, 1, 1, 1, 0;\n"
      "wgmma.mma_async.sync.aligned.m64n64k16.f32.bf16.bf16 {%0, %1, %2, %3, %4, %5, %6, %7, %8, %9, %10, %11, %12, %13, %14, %15, %16, %17, %18, %19, %20, %21, %22, %23, %24, %25, %26, %27, %28, %29, %30, %31}, {%76, %77, %78, %79}, dx3, 1, 1, 1, 0;\n"
      "wgmma.commit_group.sync.aligned;\n"
      "wgmma.mma_async.sync.aligned.m64n64k16.f32.bf16.bf16 {%32, %33, %34, %35, %36, %37, %38, %39, %40, %41, %42, %43, %44, %45, %46, %47, %48, %49, %50, %51, %52, %53, %54, %55, %56, %57, %58, %59, %60, %61, %62, %63}, {%84, %85, %86, %87}, dx0, 0, 1, 1, 0;\n"
      "wgmma.mma_async.sync.aligned.m64n64k16.f32.bf16.bf16 {%32, %33, %34, %35, %36, %37, %38, %39, %40, %41, %42, %43, %44, %45, %46, %47, %48, %49, %50, %51, %52, %53, %54, %55, %56, %57, %58, %59, %60, %61, %62, %63}, {%88, %89, %90, %91}, dx1, 1, 1, 1, 0;\n"
      "wgmma.mma_async.sync.aligned.m64n64k16.f32.bf16.bf16 {%32, %33, %34, %35, %36, %37, %38, %39, %40, %41, %42, %43, %44, %45, %46, %47, %48, %49, %50, %51, %52, %53, %54, %55, %56, %57, %58, %59, %60, %61, %62, %63}, {%92, %93, %94, %95}, dx2, 1, 1, 1, 0;\n"
      "wgmma.mma_async.sync.aligned.m64n64k16.f32.bf16.bf16 {%32, %33, %34, %35, %36, %37, %38, %39, %40, %41, %42, %43, %44, %45, %46, %47, %48, %49, %50, %51, %52, %53, %54, %55, %56, %57, %58, %59, %60, %61, %62, %63}, {%96, %97, %98, %99}, dx3, 1, 1, 1, 0;\n"
      "wgmma.commit_group.sync.aligned;\n}\n"
      : "=f"(g[0]), "=f"(g[1]), "=f"(g[2]), "=f"(g[3]), "=f"(g[4]), "=f"(g[5]), "=f"(g[6]), "=f"(g[7]), "=f"(g[8]), "=f"(g[9]), "=f"(g[10]), "=f"(g[11]), "=f"(g[12]), "=f"(g[13]), "=f"(g[14]), "=f"(g[15]), "=f"(g[16]), "=f"(g[17]), "=f"(g[18]), "=f"(g[19]), "=f"(g[20]), "=f"(g[21]), "=f"(g[22]), "=f"(g[23]), "=f"(g[24]), "=f"(g[25]), "=f"(g[26]), "=f"(g[27]), "=f"(g[28]), "=f"(g[29]), "=f"(g[30]), "=f"(g[31]),
        "=f"(h[0]), "=f"(h[1]), "=f"(h[2]), "=f"(h[3]), "=f"(h[4]), "=f"(h[5]), "=f"(h[6]), "=f"(h[7]), "=f"(h[8]), "=f"(h[9]), "=f"(h[10]), "=f"(h[11]), "=f"(h[12]), "=f"(h[13]), "=f"(h[14]), "=f"(h[15]), "=f"(h[16]), "=f"(h[17]), "=f"(h[18]), "=f"(h[19]), "=f"(h[20]), "=f"(h[21]), "=f"(h[22]), "=f"(h[23]), "=f"(h[24]), "=f"(h[25]), "=f"(h[26]), "=f"(h[27]), "=f"(h[28]), "=f"(h[29]), "=f"(h[30]), "=f"(h[31])
      : "r"(w[0]), "r"(w[1]), "r"(w[2]), "r"(w[3]), "r"(w[4]), "r"(w[5]), "r"(w[6]), "r"(w[7]), "r"(w[8]), "r"(w[9]), "r"(w[10]), "r"(w[11]), "r"(w[12]), "r"(w[13]), "r"(w[14]), "r"(w[15]), "r"(w[16]), "r"(w[17]), "r"(w[18]), "r"(w[19]), "r"(w[20]), "r"(w[21]), "r"(w[22]), "r"(w[23]), "r"(w[24]), "r"(w[25]), "r"(w[26]), "r"(w[27]), "r"(w[28]), "r"(w[29]), "r"(w[30]), "r"(w[31]), "r"(w[32]), "r"(w[33]), "r"(w[34]), "r"(w[35]), "r"(w[36]), "r"(w[37]), "r"(w[38]), "r"(w[39]), "r"(dx), "l"(de), "l"(dh)
      : "memory");
  }
  static __device__ __forceinline__ void wait_g(float* g) {
    asm volatile("wgmma.wait_group.sync.aligned 1;\n"
      : "+f"(g[0]), "+f"(g[1]), "+f"(g[2]), "+f"(g[3]), "+f"(g[4]), "+f"(g[5]), "+f"(g[6]), "+f"(g[7]), "+f"(g[8]), "+f"(g[9]), "+f"(g[10]), "+f"(g[11]), "+f"(g[12]), "+f"(g[13]), "+f"(g[14]), "+f"(g[15]), "+f"(g[16]), "+f"(g[17]), "+f"(g[18]), "+f"(g[19]), "+f"(g[20]), "+f"(g[21]), "+f"(g[22]), "+f"(g[23]), "+f"(g[24]), "+f"(g[25]), "+f"(g[26]), "+f"(g[27]), "+f"(g[28]), "+f"(g[29]), "+f"(g[30]), "+f"(g[31])
      :: "memory");
  }
  static __device__ __forceinline__ void wait_h(float* h) {
    asm volatile("wgmma.wait_group.sync.aligned 0;\n"
      : "+f"(h[0]), "+f"(h[1]), "+f"(h[2]), "+f"(h[3]), "+f"(h[4]), "+f"(h[5]), "+f"(h[6]), "+f"(h[7]), "+f"(h[8]), "+f"(h[9]), "+f"(h[10]), "+f"(h[11]), "+f"(h[12]), "+f"(h[13]), "+f"(h[14]), "+f"(h[15]), "+f"(h[16]), "+f"(h[17]), "+f"(h[18]), "+f"(h[19]), "+f"(h[20]), "+f"(h[21]), "+f"(h[22]), "+f"(h[23]), "+f"(h[24]), "+f"(h[25]), "+f"(h[26]), "+f"(h[27]), "+f"(h[28]), "+f"(h[29]), "+f"(h[30]), "+f"(h[31])
      :: "memory");
  }
};
template<> struct TileMMA<9> {
  static __device__ __forceinline__ void issue(float* g, float* h, const uint32_t* w, uint32_t dx, uint64_t de, uint64_t dh, uint64_t dc) {
    asm volatile(
      "{\n.reg .b64 dx0, dx1, dx2, dx3;\n.reg .b32 l1, l2, l3, hx;\nmov.b32 hx, 0x40000040;\n"
      "add.u32 l1, %112, 2;\nadd.u32 l2, %112, 4;\nadd.u32 l3, %112, 6;\n"
      "mov.b64 dx0, {%112, hx};\nmov.b64 dx1, {l1, hx};\nmov.b64 dx2, {l2, hx};\nmov.b64 dx3, {l3, hx};\n"
      "wgmma.fence.sync.aligned;\n"
      "wgmma.mma_async.sync.aligned.m64n72k16.f32.bf16.bf16 {%0, %1, %2, %3, %4, %5, %6, %7, %8, %9, %10, %11, %12, %13, %14, %15, %16, %17, %18, %19, %20, %21, %22, %23, %24, %25, %26, %27, %28, %29, %30, %31, %32, %33, %34, %35}, {%108, %109, %110, %111}, %114, 0, 1, 1, 0;\n"
      "wgmma.mma_async.sync.aligned.m64n72k16.f32.bf16.bf16 {%0, %1, %2, %3, %4, %5, %6, %7, %8, %9, %10, %11, %12, %13, %14, %15, %16, %17, %18, %19, %20, %21, %22, %23, %24, %25, %26, %27, %28, %29, %30, %31, %32, %33, %34, %35}, {%88, %89, %90, %91}, %113, 1, 1, 1, 0;\n"
      "wgmma.mma_async.sync.aligned.m64n72k16.f32.bf16.bf16 {%0, %1, %2, %3, %4, %5, %6, %7, %8, %9, %10, %11, %12, %13, %14, %15, %16, %17, %18, %19, %20, %21, %22, %23, %24, %25, %26, %27, %28, %29, %30, %31, %32, %33, %34, %35}, {%72, %73, %74, %75}, dx0, 1, 1, 1, 0;\n"
      "wgmma.mma_async.sync.aligned.m64n72k16.f32.bf16.bf16 {%0, %1, %2, %3, %4, %5, %6, %7, %8, %9, %10, %11, %12, %13, %14, %15, %16, %17, %18, %19, %20, %21, %22, %23, %24, %25, %26, %27, %28, %29, %30, %31, %32, %33, %34, %35}, {%76, %77, %78, %79}, dx1, 1, 1, 1, 0;\n"
      "wgmma.mma_async.sync.aligned.m64n72k16.f32.bf16.bf16 {%0, %1, %2, %3, %4, %5, %6, %7, %8, %9, %10, %11, %12, %13, %14, %15, %16, %17, %18, %19, %20, %21, %22, %23, %24, %25, %26, %27, %28, %29, %30, %31, %32, %33, %34, %35}, {%80, %81, %82, %83}, dx2, 1, 1, 1, 0;\n"
      "wgmma.mma_async.sync.aligned.m64n72k16.f32.bf16.bf16 {%0, %1, %2, %3, %4, %5, %6, %7, %8, %9, %10, %11, %12, %13, %14, %15, %16, %17, %18, %19, %20, %21, %22, %23, %24, %25, %26, %27, %28, %29, %30, %31, %32, %33, %34, %35}, {%84, %85, %86, %87}, dx3, 1, 1, 1, 0;\n"
      "wgmma.commit_group.sync.aligned;\n"
      "wgmma.mma_async.sync.aligned.m64n72k16.f32.bf16.bf16 {%36, %37, %38, %39, %40, %41, %42, %43, %44, %45, %46, %47, %48, %49, %50, %51, %52, %53, %54, %55, %56, %57, %58, %59, %60, %61, %62, %63, %64, %65, %66, %67, %68, %69, %70, %71}, {%92, %93, %94, %95}, dx0, 0, 1, 1, 0;\n"
      "wgmma.mma_async.sync.aligned.m64n72k16.f32.bf16.bf16 {%36, %37, %38, %39, %40, %41, %42, %43, %44, %45, %46, %47, %48, %49, %50, %51, %52, %53, %54, %55, %56, %57, %58, %59, %60, %61, %62, %63, %64, %65, %66, %67, %68, %69, %70, %71}, {%96, %97, %98, %99}, dx1, 1, 1, 1, 0;\n"
      "wgmma.mma_async.sync.aligned.m64n72k16.f32.bf16.bf16 {%36, %37, %38, %39, %40, %41, %42, %43, %44, %45, %46, %47, %48, %49, %50, %51, %52, %53, %54, %55, %56, %57, %58, %59, %60, %61, %62, %63, %64, %65, %66, %67, %68, %69, %70, %71}, {%100, %101, %102, %103}, dx2, 1, 1, 1, 0;\n"
      "wgmma.mma_async.sync.aligned.m64n72k16.f32.bf16.bf16 {%36, %37, %38, %39, %40, %41, %42, %43, %44, %45, %46, %47, %48, %49, %50, %51, %52, %53, %54, %55, %56, %57, %58, %59, %60, %61, %62, %63, %64, %65, %66, %67, %68, %69, %70, %71}, {%104, %105, %106, %107}, dx3, 1, 1, 1, 0;\n"
      "wgmma.commit_group.sync.aligned;\n}\n"
      : "=f"(g[0]), "=f"(g[1]), "=f"(g[2]), "=f"(g[3]), "=f"(g[4]), "=f"(g[5]), "=f"(g[6]), "=f"(g[7]), "=f"(g[8]), "=f"(g[9]), "=f"(g[10]), "=f"(g[11]), "=f"(g[12]), "=f"(g[13]), "=f"(g[14]), "=f"(g[15]), "=f"(g[16]), "=f"(g[17]), "=f"(g[18]), "=f"(g[19]), "=f"(g[20]), "=f"(g[21]), "=f"(g[22]), "=f"(g[23]), "=f"(g[24]), "=f"(g[25]), "=f"(g[26]), "=f"(g[27]), "=f"(g[28]), "=f"(g[29]), "=f"(g[30]), "=f"(g[31]), "=f"(g[32]), "=f"(g[33]), "=f"(g[34]), "=f"(g[35]),
        "=f"(h[0]), "=f"(h[1]), "=f"(h[2]), "=f"(h[3]), "=f"(h[4]), "=f"(h[5]), "=f"(h[6]), "=f"(h[7]), "=f"(h[8]), "=f"(h[9]), "=f"(h[10]), "=f"(h[11]), "=f"(h[12]), "=f"(h[13]), "=f"(h[14]), "=f"(h[15]), "=f"(h[16]), "=f"(h[17]), "=f"(h[18]), "=f"(h[19]), "=f"(h[20]), "=f"(h[21]), "=f"(h[22]), "=f"(h[23]), "=f"(h[24]), "=f"(h[25]), "=f"(h[26]), "=f"(h[27]), "=f"(h[28]), "=f"(h[29]), "=f"(h[30]), "=f"(h[31]), "=f"(h[32]), "=f"(h[33]), "=f"(h[34]), "=f"(h[35])
      : "r"(w[0]), "r"(w[1]), "r"(w[2]), "r"(w[3]), "r"(w[4]), "r"(w[5]), "r"(w[6]), "r"(w[7]), "r"(w[8]), "r"(w[9]), "r"(w[10]), "r"(w[11]), "r"(w[12]), "r"(w[13]), "r"(w[14]), "r"(w[15]), "r"(w[16]), "r"(w[17]), "r"(w[18]), "r"(w[19]), "r"(w[20]), "r"(w[21]), "r"(w[22]), "r"(w[23]), "r"(w[24]), "r"(w[25]), "r"(w[26]), "r"(w[27]), "r"(w[28]), "r"(w[29]), "r"(w[30]), "r"(w[31]), "r"(w[32]), "r"(w[33]), "r"(w[34]), "r"(w[35]), "r"(w[36]), "r"(w[37]), "r"(w[38]), "r"(w[39]), "r"(dx), "l"(de), "l"(dh)
      : "memory");
  }
  static __device__ __forceinline__ void wait_g(float* g) {
    asm volatile("wgmma.wait_group.sync.aligned 1;\n"
      : "+f"(g[0]), "+f"(g[1]), "+f"(g[2]), "+f"(g[3]), "+f"(g[4]), "+f"(g[5]), "+f"(g[6]), "+f"(g[7]), "+f"(g[8]), "+f"(g[9]), "+f"(g[10]), "+f"(g[11]), "+f"(g[12]), "+f"(g[13]), "+f"(g[14]), "+f"(g[15]), "+f"(g[16]), "+f"(g[17]), "+f"(g[18]), "+f"(g[19]), "+f"(g[20]), "+f"(g[21]), "+f"(g[22]), "+f"(g[23]), "+f"(g[24]), "+f"(g[25]), "+f"(g[26]), "+f"(g[27]), "+f"(g[28]), "+f"(g[29]), "+f"(g[30]), "+f"(g[31]), "+f"(g[32]), "+f"(g[33]), "+f"(g[34]), "+f"(g[35])
      :: "memory");
  }
  static __device__ __forceinline__ void wait_h(float* h) {
    asm volatile("wgmma.wait_group.sync.aligned 0;\n"
      : "+f"(h[0]), "+f"(h[1]), "+f"(h[2]), "+f"(h[3]), "+f"(h[4]), "+f"(h[5]), "+f"(h[6]), "+f"(h[7]), "+f"(h[8]), "+f"(h[9]), "+f"(h[10]), "+f"(h[11]), "+f"(h[12]), "+f"(h[13]), "+f"(h[14]), "+f"(h[15]), "+f"(h[16]), "+f"(h[17]), "+f"(h[18]), "+f"(h[19]), "+f"(h[20]), "+f"(h[21]), "+f"(h[22]), "+f"(h[23]), "+f"(h[24]), "+f"(h[25]), "+f"(h[26]), "+f"(h[27]), "+f"(h[28]), "+f"(h[29]), "+f"(h[30]), "+f"(h[31]), "+f"(h[32]), "+f"(h[33]), "+f"(h[34]), "+f"(h[35])
      :: "memory");
  }
};
template<> struct TileMMA<10> {
  static __device__ __forceinline__ void issue(float* g, float* h, const uint32_t* w, uint32_t dx, uint64_t de, uint64_t dh, uint64_t dc) {
    asm volatile(
      "{\n.reg .b64 dx0, dx1, dx2, dx3;\n.reg .b32 l1, l2, l3, hx;\nmov.b32 hx, 0x40000040;\n"
      "add.u32 l1, %120, 2;\nadd.u32 l2, %120, 4;\nadd.u32 l3, %120, 6;\n"
      "mov.b64 dx0, {%120, hx};\nmov.b64 dx1, {l1, hx};\nmov.b64 dx2, {l2, hx};\nmov.b64 dx3, {l3, hx};\n"
      "wgmma.fence.sync.aligned;\n"
      "wgmma.mma_async.sync.aligned.m64n80k16.f32.bf16.bf16 {%0, %1, %2, %3, %4, %5, %6, %7, %8, %9, %10, %11, %12, %13, %14, %15, %16, %17, %18, %19, %20, %21, %22, %23, %24, %25, %26, %27, %28, %29, %30, %31, %32, %33, %34, %35, %36, %37, %38, %39}, {%116, %117, %118, %119}, %122, 0, 1, 1, 0;\n"
      "wgmma.mma_async.sync.aligned.m64n80k16.f32.bf16.bf16 {%0, %1, %2, %3, %4, %5, %6, %7, %8, %9, %10, %11, %12, %13, %14, %15, %16, %17, %18, %19, %20, %21, %22, %23, %24, %25, %26, %27, %28, %29, %30, %31, %32, %33, %34, %35, %36, %37, %38, %39}, {%96, %97, %98, %99}, %121, 1, 1, 1, 0;\n"
      "wgmma.mma_async.sync.aligned.m64n80k16.f32.bf16.bf16 {%0, %1, %2, %3, %4, %5, %6, %7, %8, %9, %10, %11, %12, %13, %14, %15, %16, %17, %18, %19, %20, %21, %22, %23, %24, %25, %26, %27, %28, %29, %30, %31, %32, %33, %34, %35, %36, %37, %38, %39}, {%80, %81, %82, %83}, dx0, 1, 1, 1, 0;\n"
      "wgmma.mma_async.sync.aligned.m64n80k16.f32.bf16.bf16 {%0, %1, %2, %3, %4, %5, %6, %7, %8, %9, %10, %11, %12, %13, %14, %15, %16, %17, %18, %19, %20, %21, %22, %23, %24, %25, %26, %27, %28, %29, %30, %31, %32, %33, %34, %35, %36, %37, %38, %39}, {%84, %85, %86, %87}, dx1, 1, 1, 1, 0;\n"
      "wgmma.mma_async.sync.aligned.m64n80k16.f32.bf16.bf16 {%0, %1, %2, %3, %4, %5, %6, %7, %8, %9, %10, %11, %12, %13, %14, %15, %16, %17, %18, %19, %20, %21, %22, %23, %24, %25, %26, %27, %28, %29, %30, %31, %32, %33, %34, %35, %36, %37, %38, %39}, {%88, %89, %90, %91}, dx2, 1, 1, 1, 0;\n"
      "wgmma.mma_async.sync.aligned.m64n80k16.f32.bf16.bf16 {%0, %1, %2, %3, %4, %5, %6, %7, %8, %9, %10, %11, %12, %13, %14, %15, %16, %17, %18, %19, %20, %21, %22, %23, %24, %25, %26, %27, %28, %29, %30, %31, %32, %33, %34, %35, %36, %37, %38, %39}, {%92, %93, %94, %95}, dx3, 1, 1, 1, 0;\n"
      "wgmma.commit_group.sync.aligned;\n"
      "wgmma.mma_async.sync.aligned.m64n80k16.f32.bf16.bf16 {%40, %41, %42, %43, %44, %45, %46, %47, %48, %49, %50, %51, %52, %53, %54, %55, %56, %57, %58, %59, %60, %61, %62, %63, %64, %65, %66, %67, %68, %69, %70, %71, %72, %73, %74, %75, %76, %77, %78, %79}, {%100, %101, %102, %103}, dx0, 0, 1, 1, 0;\n"
      "wgmma.mma_async.sync.aligned.m64n80k16.f32.bf16.bf16 {%40, %41, %42, %43, %44, %45, %46, %47, %48, %49, %50, %51, %52, %53, %54, %55, %56, %57, %58, %59, %60, %61, %62, %63, %64, %65, %66, %67, %68, %69, %70, %71, %72, %73, %74, %75, %76, %77, %78, %79}, {%104, %105, %106, %107}, dx1, 1, 1, 1, 0;\n"
      "wgmma.mma_async.sync.aligned.m64n80k16.f32.bf16.bf16 {%40, %41, %42, %43, %44, %45, %46, %47, %48, %49, %50, %51, %52, %53, %54, %55, %56, %57, %58, %59, %60, %61, %62, %63, %64, %65, %66, %67, %68, %69, %70, %71, %72, %73, %74, %75, %76, %77, %78, %79}, {%108, %109, %110, %111}, dx2, 1, 1, 1, 0;\n"
      "wgmma.mma_async.sync.aligned.m64n80k16.f32.bf16.bf16 {%40, %41, %42, %43, %44, %45, %46, %47, %48, %49, %50, %51, %52, %53, %54, %55, %56, %57, %58, %59, %60, %61, %62, %63, %64, %65, %66, %67, %68, %69, %70, %71, %72, %73, %74, %75, %76, %77, %78, %79}, {%112, %113, %114, %115}, dx3, 1, 1, 1, 0;\n"
      "wgmma.commit_group.sync.aligned;\n}\n"
      : "=f"(g[0]), "=f"(g[1]), "=f"(g[2]), "=f"(g[3]), "=f"(g[4]), "=f"(g[5]), "=f"(g[6]), "=f"(g[7]), "=f"(g[8]), "=f"(g[9]), "=f"(g[10]), "=f"(g[11]), "=f"(g[12]), "=f"(g[13]), "=f"(g[14]), "=f"(g[15]), "=f"(g[16]), "=f"(g[17]), "=f"(g[18]), "=f"(g[19]), "=f"(g[20]), "=f"(g[21]), "=f"(g[22]), "=f"(g[23]), "=f"(g[24]), "=f"(g[25]), "=f"(g[26]), "=f"(g[27]), "=f"(g[28]), "=f"(g[29]), "=f"(g[30]), "=f"(g[31]), "=f"(g[32]), "=f"(g[33]), "=f"(g[34]), "=f"(g[35]), "=f"(g[36]), "=f"(g[37]), "=f"(g[38]), "=f"(g[39]),
        "=f"(h[0]), "=f"(h[1]), "=f"(h[2]), "=f"(h[3]), "=f"(h[4]), "=f"(h[5]), "=f"(h[6]), "=f"(h[7]), "=f"(h[8]), "=f"(h[9]), "=f"(h[10]), "=f"(h[11]), "=f"(h[12]), "=f"(h[13]), "=f"(h[14]), "=f"(h[15]), "=f"(h[16]), "=f"(h[17]), "=f"(h[18]), "=f"(h[19]), "=f"(h[20]), "=f"(h[21]), "=f"(h[22]), "=f"(h[23]), "=f"(h[24]), "=f"(h[25]), "=f"(h[26]), "=f"(h[27]), "=f"(h[28]), "=f"(h[29]), "=f"(h[30]), "=f"(h[31]), "=f"(h[32]), "=f"(h[33]), "=f"(h[34]), "=f"(h[35]), "=f"(h[36]), "=f"(h[37]), "=f"(h[38]), "=f"(h[39])
      : "r"(w[0]), "r"(w[1]), "r"(w[2]), "r"(w[3]), "r"(w[4]), "r"(w[5]), "r"(w[6]), "r"(w[7]), "r"(w[8]), "r"(w[9]), "r"(w[10]), "r"(w[11]), "r"(w[12]), "r"(w[13]), "r"(w[14]), "r"(w[15]), "r"(w[16]), "r"(w[17]), "r"(w[18]), "r"(w[19]), "r"(w[20]), "r"(w[21]), "r"(w[22]), "r"(w[23]), "r"(w[24]), "r"(w[25]), "r"(w[26]), "r"(w[27]), "r"(w[28]), "r"(w[29]), "r"(w[30]), "r"(w[31]), "r"(w[32]), "r"(w[33]), "r"(w[34]), "r"(w[35]), "r"(w[36]), "r"(w[37]), "r"(w[38]), "r"(w[39]), "r"(dx), "l"(de), "l"(dh)
      : "memory");
  }
  static __device__ __forceinline__ void wait_g(float* g) {
    asm volatile("wgmma.wait_group.sync.aligned 1;\n"
      : "+f"(g[0]), "+f"(g[1]), "+f"(g[2]), "+f"(g[3]), "+f"(g[4]), "+f"(g[5]), "+f"(g[6]), "+f"(g[7]), "+f"(g[8]), "+f"(g[9]), "+f"(g[10]), "+f"(g[11]), "+f"(g[12]), "+f"(g[13]), "+f"(g[14]), "+f"(g[15]), "+f"(g[16]), "+f"(g[17]), "+f"(g[18]), "+f"(g[19]), "+f"(g[20]), "+f"(g[21]), "+f"(g[22]), "+f"(g[23]), "+f"(g[24]), "+f"(g[25]), "+f"(g[26]), "+f"(g[27]), "+f"(g[28]), "+f"(g[29]), "+f"(g[30]), "+f"(g[31]), "+f"(g[32]), "+f"(g[33]), "+f"(g[34]), "+f"(g[35]), "+f"(g[36]), "+f"(g[37]), "+f"(g[38]), "+f"(g[39])
      :: "memory");
  }
  static __device__ __forceinline__ void wait_h(float* h) {
    asm volatile("wgmma.wait_group.sync.aligned 0;\n"
      : "+f"(h[0]), "+f"(h[1]), "+f"(h[2]), "+f"(h[3]), "+f"(h[4]), "+f"(h[5]), "+f"(h[6]), "+f"(h[7]), "+f"(h[8]), "+f"(h[9]), "+f"(h[10]), "+f"(h[11]), "+f"(h[12]), "+f"(h[13]), "+f"(h[14]), "+f"(h[15]), "+f"(h[16]), "+f"(h[17]), "+f"(h[18]), "+f"(h[19]), "+f"(h[20]), "+f"(h[21]), "+f"(h[22]), "+f"(h[23]), "+f"(h[24]), "+f"(h[25]), "+f"(h[26]), "+f"(h[27]), "+f"(h[28]), "+f"(h[29]), "+f"(h[30]), "+f"(h[31]), "+f"(h[32]), "+f"(h[33]), "+f"(h[34]), "+f"(h[35]), "+f"(h[36]), "+f"(h[37]), "+f"(h[38]), "+f"(h[39])
      :: "memory");
  }
};
template<> struct TileMMA<11> {
  static __device__ __forceinline__ void issue(float* g, float* h, const uint32_t* w, uint32_t dx, uint64_t de, uint64_t dh, uint64_t dc) {
    asm volatile(
      "{\n.reg .b64 dx0, dx1, dx2, dx3;\n.reg .b32 l1, l2, l3, hx;\nmov.b32 hx, 0x40000040;\n"
      "add.u32 l1, %124, 2;\nadd.u32 l2, %124, 4;\nadd.u32 l3, %124, 6;\n"
      "mov.b64 dx0, {%124, hx};\nmov.b64 dx1, {l1, hx};\nmov.b64 dx2, {l2, hx};\nmov.b64 dx3, {l3, hx};\n"
      "wgmma.fence.sync.aligned;\n"
      "wgmma.mma_async.sync.aligned.m64n88k16.f32.bf16.bf16 {%0, %1, %2, %3, %4, %5, %6, %7, %8, %9, %10, %11, %12, %13, %14, %15, %16, %17, %18, %19, %20, %21, %22, %23, %24, %25, %26, %27, %28, %29, %30, %31, %32, %33, %34, %35, %36, %37, %38, %39, %40, %41, %42, %43}, {%120, %121, %122, %123}, %126, 0, 1, 1, 0;\n"
      "wgmma.mma_async.sync.aligned.m64n88k16.f32.bf16.bf16 {%0, %1, %2, %3, %4, %5, %6, %7, %8, %9, %10, %11, %12, %13, %14, %15, %16, %17, %18, %19, %20, %21, %22, %23, %24, %25, %26, %27, %28, %29, %30, %31, %32, %33, %34, %35, %36, %37, %38, %39, %40, %41, %42, %43}, %127, %125, 1, 1, 1, 0, 0;\n"
      "wgmma.mma_async.sync.aligned.m64n88k16.f32.bf16.bf16 {%0, %1, %2, %3, %4, %5, %6, %7, %8, %9, %10, %11, %12, %13, %14, %15, %16, %17, %18, %19, %20, %21, %22, %23, %24, %25, %26, %27, %28, %29, %30, %31, %32, %33, %34, %35, %36, %37, %38, %39, %40, %41, %42, %43}, {%88, %89, %90, %91}, dx0, 1, 1, 1, 0;\n"
      "wgmma.mma_async.sync.aligned.m64n88k16.f32.bf16.bf16 {%0, %1, %2, %3, %4, %5, %6, %7, %8, %9, %10, %11, %12, %13, %14, %15, %16, %17, %18, %19, %20, %21, %22, %23, %24, %25, %26, %27, %28, %29, %30, %31, %32, %33, %34, %35, %36, %37, %38, %39, %40, %41, %42, %43}, {%92, %93, %94, %95}, dx1, 1, 1, 1, 0;\n"
      "wgmma.mma_async.sync.aligned.m64n88k16.f32.bf16.bf16 {%0, %1, %2, %3, %4, %5, %6, %7, %8, %9, %10, %11, %12, %13, %14, %15, %16, %17, %18, %19, %20, %21, %22, %23, %24, %25, %26, %27, %28, %29, %30, %31, %32, %33, %34, %35, %36, %37, %38, %39, %40, %41, %42, %43}, {%96, %97, %98, %99}, dx2, 1, 1, 1, 0;\n"
      "wgmma.mma_async.sync.aligned.m64n88k16.f32.bf16.bf16 {%0, %1, %2, %3, %4, %5, %6, %7, %8, %9, %10, %11, %12, %13, %14, %15, %16, %17, %18, %19, %20, %21, %22, %23, %24, %25, %26, %27, %28, %29, %30, %31, %32, %33, %34, %35, %36, %37, %38, %39, %40, %41, %42, %43}, {%100, %101, %102, %103}, dx3, 1, 1, 1, 0;\n"
      "wgmma.commit_group.sync.aligned;\n"
      "wgmma.mma_async.sync.aligned.m64n88k16.f32.bf16.bf16 {%44, %45, %46, %47, %48, %49, %50, %51, %52, %53, %54, %55, %56, %57, %58, %59, %60, %61, %62, %63, %64, %65, %66, %67, %68, %69, %70, %71, %72, %73, %74, %75, %76, %77, %78, %79, %80, %81, %82, %83, %84, %85, %86, %87}, {%104, %105, %106, %107}, dx0, 0, 1, 1, 0;\n"
      "wgmma.mma_async.sync.aligned.m64n88k16.f32.bf16.bf16 {%44, %45, %46, %47, %48, %49, %50, %51, %52, %53, %54, %55, %56, %57, %58, %59, %60, %61, %62, %63, %64, %65, %66, %67, %68, %69, %70, %71, %72, %73, %74, %75, %76, %77, %78, %79, %80, %81, %82, %83, %84, %85, %86, %87}, {%108, %109, %110, %111}, dx1, 1, 1, 1, 0;\n"
      "wgmma.mma_async.sync.aligned.m64n88k16.f32.bf16.bf16 {%44, %45, %46, %47, %48, %49, %50, %51, %52, %53, %54, %55, %56, %57, %58, %59, %60, %61, %62, %63, %64, %65, %66, %67, %68, %69, %70, %71, %72, %73, %74, %75, %76, %77, %78, %79, %80, %81, %82, %83, %84, %85, %86, %87}, {%112, %113, %114, %115}, dx2, 1, 1, 1, 0;\n"
      "wgmma.mma_async.sync.aligned.m64n88k16.f32.bf16.bf16 {%44, %45, %46, %47, %48, %49, %50, %51, %52, %53, %54, %55, %56, %57, %58, %59, %60, %61, %62, %63, %64, %65, %66, %67, %68, %69, %70, %71, %72, %73, %74, %75, %76, %77, %78, %79, %80, %81, %82, %83, %84, %85, %86, %87}, {%116, %117, %118, %119}, dx3, 1, 1, 1, 0;\n"
      "wgmma.commit_group.sync.aligned;\n}\n"
      : "=f"(g[0]), "=f"(g[1]), "=f"(g[2]), "=f"(g[3]), "=f"(g[4]), "=f"(g[5]), "=f"(g[6]), "=f"(g[7]), "=f"(g[8]), "=f"(g[9]), "=f"(g[10]), "=f"(g[11]), "=f"(g[12]), "=f"(g[13]), "=f"(g[14]), "=f"(g[15]), "=f"(g[16]), "=f"(g[17]), "=f"(g[18]), "=f"(g[19]), "=f"(g[20]), "=f"(g[21]), "=f"(g[22]), "=f"(g[23]), "=f"(g[24]), "=f"(g[25]), "=f"(g[26]), "=f"(g[27]), "=f"(g[28]), "=f"(g[29]), "=f"(g[30]), "=f"(g[31]), "=f"(g[32]), "=f"(g[33]), "=f"(g[34]), "=f"(g[35]), "=f"(g[36]), "=f"(g[37]), "=f"(g[38]), "=f"(g[39]), "=f"(g[40]), "=f"(g[41]), "=f"(g[42]), "=f"(g[43]),
        "=f"(h[0]), "=f"(h[1]), "=f"(h[2]), "=f"(h[3]), "=f"(h[4]), "=f"(h[5]), "=f"(h[6]), "=f"(h[7]), "=f"(h[8]), "=f"(h[9]), "=f"(h[10]), "=f"(h[11]), "=f"(h[12]), "=f"(h[13]), "=f"(h[14]), "=f"(h[15]), "=f"(h[16]), "=f"(h[17]), "=f"(h[18]), "=f"(h[19]), "=f"(h[20]), "=f"(h[21]), "=f"(h[22]), "=f"(h[23]), "=f"(h[24]), "=f"(h[25]), "=f"(h[26]), "=f"(h[27]), "=f"(h[28]), "=f"(h[29]), "=f"(h[30]), "=f"(h[31]), "=f"(h[32]), "=f"(h[33]), "=f"(h[34]), "=f"(h[35]), "=f"(h[36]), "=f"(h[37]), "=f"(h[38]), "=f"(h[39]), "=f"(h[40]), "=f"(h[41]), "=f"(h[42]), "=f"(h[43])
      : "r"(w[0]), "r"(w[1]), "r"(w[2]), "r"(w[3]), "r"(w[4]), "r"(w[5]), "r"(w[6]), "r"(w[7]), "r"(w[8]), "r"(w[9]), "r"(w[10]), "r"(w[11]), "r"(w[12]), "r"(w[13]), "r"(w[14]), "r"(w[15]), "r"(w[20]), "r"(w[21]), "r"(w[22]), "r"(w[23]), "r"(w[24]), "r"(w[25]), "r"(w[26]), "r"(w[27]), "r"(w[28]), "r"(w[29]), "r"(w[30]), "r"(w[31]), "r"(w[32]), "r"(w[33]), "r"(w[34]), "r"(w[35]), "r"(w[36]), "r"(w[37]), "r"(w[38]), "r"(w[39]), "r"(dx), "l"(de), "l"(dh), "l"(dc)
      : "memory");
  }
  static __device__ __forceinline__ void wait_g(float* g) {
    asm volatile("wgmma.wait_group.sync.aligned 1;\n"
      : "+f"(g[0]), "+f"(g[1]), "+f"(g[2]), "+f"(g[3]), "+f"(g[4]), "+f"(g[5]), "+f"(g[6]), "+f"(g[7]), "+f"(g[8]), "+f"(g[9]), "+f"(g[10]), "+f"(g[11]), "+f"(g[12]), "+f"(g[13]), "+f"(g[14]), "+f"(g[15]), "+f"(g[16]), "+f"(g[17]), "+f"(g[18]), "+f"(g[19]), "+f"(g[20]), "+f"(g[21]), "+f"(g[22]), "+f"(g[23]), "+f"(g[24]), "+f"(g[25]), "+f"(g[26]), "+f"(g[27]), "+f"(g[28]), "+f"(g[29]), "+f"(g[30]), "+f"(g[31]), "+f"(g[32]), "+f"(g[33]), "+f"(g[34]), "+f"(g[35]), "+f"(g[36]), "+f"(g[37]), "+f"(g[38]), "+f"(g[39]), "+f"(g[40]), "+f"(g[41]), "+f"(g[42]), "+f"(g[43])
      :: "memory");
  }
  static __device__ __forceinline__ void wait_h(float* h) {
    asm volatile("wgmma.wait_group.sync.aligned 0;\n"
      : "+f"(h[0]), "+f"(h[1]), "+f"(h[2]), "+f"(h[3]), "+f"(h[4]), "+f"(h[5]), "+f"(h[6]), "+f"(h[7]), "+f"(h[8]), "+f"(h[9]), "+f"(h[10]), "+f"(h[11]), "+f"(h[12]), "+f"(h[13]), "+f"(h[14]), "+f"(h[15]), "+f"(h[16]), "+f"(h[17]), "+f"(h[18]), "+f"(h[19]), "+f"(h[20]), "+f"(h[21]), "+f"(h[22]), "+f"(h[23]), "+f"(h[24]), "+f"(h[25]), "+f"(h[26]), "+f"(h[27]), "+f"(h[28]), "+f"(h[29]), "+f"(h[30]), "+f"(h[31]), "+f"(h[32]), "+f"(h[33]), "+f"(h[34]), "+f"(h[35]), "+f"(h[36]), "+f"(h[37]), "+f"(h[38]), "+f"(h[39]), "+f"(h[40]), "+f"(h[41]), "+f"(h[42]), "+f"(h[43])
      :: "memory");
  }
};
__device__ __forceinline__ void node_mma(float* g, const uint32_t* w, uint64_t dx) {
    asm volatile(
      "{\n.reg .b64 dx1, dx2, dx3;\n"
      "add.s64 dx1, %48, 2;\nadd.s64 dx2, %48, 4;\nadd.s64 dx3, %48, 6;\n"
      "wgmma.fence.sync.aligned;\n"
      "wgmma.mma_async.sync.aligned.m64n64k16.f32.bf16.bf16 {%0, %1, %2, %3, %4, %5, %6, %7, %8, %9, %10, %11, %12, %13, %14, %15, %16, %17, %18, %19, %20, %21, %22, %23, %24, %25, %26, %27, %28, %29, %30, %31}, {%32, %33, %34, %35}, %48, 0, 1, 1, 0;\n"
      "wgmma.mma_async.sync.aligned.m64n64k16.f32.bf16.bf16 {%0, %1, %2, %3, %4, %5, %6, %7, %8, %9, %10, %11, %12, %13, %14, %15, %16, %17, %18, %19, %20, %21, %22, %23, %24, %25, %26, %27, %28, %29, %30, %31}, {%36, %37, %38, %39}, dx1, 1, 1, 1, 0;\n"
      "wgmma.mma_async.sync.aligned.m64n64k16.f32.bf16.bf16 {%0, %1, %2, %3, %4, %5, %6, %7, %8, %9, %10, %11, %12, %13, %14, %15, %16, %17, %18, %19, %20, %21, %22, %23, %24, %25, %26, %27, %28, %29, %30, %31}, {%40, %41, %42, %43}, dx2, 1, 1, 1, 0;\n"
      "wgmma.mma_async.sync.aligned.m64n64k16.f32.bf16.bf16 {%0, %1, %2, %3, %4, %5, %6, %7, %8, %9, %10, %11, %12, %13, %14, %15, %16, %17, %18, %19, %20, %21, %22, %23, %24, %25, %26, %27, %28, %29, %30, %31}, {%44, %45, %46, %47}, dx3, 1, 1, 1, 0;\n"
      "wgmma.commit_group.sync.aligned;\n}\n"
      : "=f"(g[0]), "=f"(g[1]), "=f"(g[2]), "=f"(g[3]), "=f"(g[4]), "=f"(g[5]), "=f"(g[6]), "=f"(g[7]), "=f"(g[8]), "=f"(g[9]), "=f"(g[10]), "=f"(g[11]), "=f"(g[12]), "=f"(g[13]), "=f"(g[14]), "=f"(g[15]), "=f"(g[16]), "=f"(g[17]), "=f"(g[18]), "=f"(g[19]), "=f"(g[20]), "=f"(g[21]), "=f"(g[22]), "=f"(g[23]), "=f"(g[24]), "=f"(g[25]), "=f"(g[26]), "=f"(g[27]), "=f"(g[28]), "=f"(g[29]), "=f"(g[30]), "=f"(g[31])
      : "r"(w[0]), "r"(w[1]), "r"(w[2]), "r"(w[3]), "r"(w[4]), "r"(w[5]), "r"(w[6]), "r"(w[7]), "r"(w[8]), "r"(w[9]), "r"(w[10]), "r"(w[11]), "r"(w[12]), "r"(w[13]), "r"(w[14]), "r"(w[15]), "l"(dx)
      : "memory");
}

__device__ __forceinline__ uint32_t smem_u32(const void* p) { return (uint32_t)__cvta_generic_to_shared(p); }
__device__ __forceinline__ float ex2f(float x) { float y; asm("ex2.approx.ftz.f32 %0, %1;" : "=f"(y) : "f"(x)); return y; }
__device__ __forceinline__ float rcpf(float x) { float y; asm("rcp.approx.ftz.f32 %0, %1;" : "=f"(y) : "f"(x)); return y; }
__device__ __forceinline__ uint32_t pack_bf16(float lo, float hi) {
    uint32_t r; asm("cvt.rn.bf16x2.f32 %0, %1, %2;" : "=r"(r) : "f"(hi), "f"(lo)); return r;
}
__device__ __forceinline__ float bf_lo(uint32_t v) { return __uint_as_float(v << 16); }
__device__ __forceinline__ float bf_hi(uint32_t v) { return __uint_as_float(v & 0xFFFF0000u); }
template<int STRIDE>
__device__ __forceinline__ void cp16i(uint32_t dst, const char* base, uint32_t idx) {
    asm volatile("{\n.reg .b64 a;\nmad.wide.u32 a, %2, %3, %1;\ncp.async.cg.shared.global [%0], [a], 16;\n}\n" :: "r"(dst), "l"(base), "r"(idx), "n"(STRIDE) : "memory");
}
__device__ __forceinline__ void cp16e(uint32_t dst, const char* base, uint32_t idx, uint64_t pol) {
    asm volatile("{\n.reg .b64 a;\nmad.wide.u32 a, %2, 32, %1;\ncp.async.cg.shared.global.L2::cache_hint [%0], [a], 16, %3;\n}\n" :: "r"(dst), "l"(base), "r"(idx), "l"(pol) : "memory");
}
template<int STRIDE>
__device__ __forceinline__ void cp16z(uint32_t dst, const char* base, uint32_t idx, int k, int n, uint64_t pol) {
    if (STRIDE == 32)
        asm volatile("{\n.reg .b64 a;\n.reg .pred p;\nsetp.ge.s32 p, %3, %4;\nmad.wide.u32 a, %2, 32, %1;\ncp.async.cg.shared.global.L2::cache_hint [%0], [a], 16, p, %5;\n}\n"
                     :: "r"(dst), "l"(base), "r"(idx), "r"(k), "r"(n), "l"(pol) : "memory");
    else
        asm volatile("{\n.reg .b64 a;\n.reg .pred p;\nsetp.ge.s32 p, %3, %4;\nmad.wide.u32 a, %2, 128, %1;\ncp.async.cg.shared.global [%0], [a], 16, p;\n}\n"
                     :: "r"(dst), "l"(base), "r"(idx), "r"(k), "r"(n) : "memory");
}
template<int HI, bool Z>
__device__ __forceinline__ void cpx(uint32_t hi, uint32_t dst, uint32_t p, uint32_t lo, int k, int n) {
    if (Z) asm volatile("{\n.reg .b32 l;\n.reg .b64 a;\n.reg .pred q;\nsetp.ge.s32 q, %5, %6;\ndp2a.lo.u32.u32 l, %1, %2, %3;\nmov.b64 a, {l, %0};\ncp.async.cg.shared.global [%4], [a], 16, q;\n}\n"
                        :: "r"(hi), "r"(p), "r"(HI ? 0x8000u : 0x80u), "r"(lo), "r"(dst), "r"(k), "r"(n) : "memory");
    else asm volatile("{\n.reg .b32 l;\n.reg .b64 a;\ndp2a.lo.u32.u32 l, %1, %2, %3;\nmov.b64 a, {l, %0};\ncp.async.cg.shared.global [%4], [a], 16;\n}\n"
                      :: "r"(hi), "r"(p), "r"(HI ? 0x8000u : 0x80u), "r"(lo), "r"(dst) : "memory");
}
template<bool Z>
__device__ __forceinline__ void cpe(uint32_t hi, uint32_t dst, uint32_t idx, uint32_t lo, int k, int n, uint64_t pol) {
    if (Z) asm volatile("{\n.reg .b32 l;\n.reg .b64 a;\n.reg .pred q;\nsetp.ge.s32 q, %5, %6;\nmad.lo.u32 l, %1, 32, %2;\nmov.b64 a, {l, %0};\ncp.async.cg.shared.global.L2::cache_hint [%3], [a], 16, q, %4;\n}\n"
                        :: "r"(hi), "r"(idx), "r"(lo), "r"(dst), "l"(pol), "r"(k), "r"(n) : "memory");
    else asm volatile("{\n.reg .b32 l;\n.reg .b64 a;\nmad.lo.u32 l, %1, 32, %2;\nmov.b64 a, {l, %0};\ncp.async.cg.shared.global.L2::cache_hint [%3], [a], 16, %4;\n}\n"
                      :: "r"(hi), "r"(idx), "r"(lo), "r"(dst), "l"(pol) : "memory");
}
__device__ __forceinline__ void cp_commit() { asm volatile("cp.async.commit_group;" ::: "memory"); }
template<int N> __device__ __forceinline__ void cp_wait() { asm volatile("cp.async.wait_group %0;" :: "n"(N) : "memory"); }
__device__ __forceinline__ void mbar_arrive(uint32_t bar) { asm volatile("mbarrier.arrive.shared.b64 _, [%0];" :: "r"(bar) : "memory"); }
__device__ __forceinline__ void mbar_cp_arrive(uint32_t bar) { asm volatile("cp.async.mbarrier.arrive.noinc.shared.b64 [%0];" :: "r"(bar) : "memory"); }
__device__ __forceinline__ void mbar_wait(uint32_t bar, uint32_t parity) {
    asm volatile("{\n.reg .pred p;\n.reg .u32 n;\nmbarrier.try_wait.parity.shared.b64 p, [%0], %1;\n@p bra DONE_%=;\nmov.u32 n, 0;\n"
                 "WAIT_%=:\nmbarrier.try_wait.parity.shared.b64 p, [%0], %1, 0x100000;\n@p bra DONE_%=;\n"
                 "add.u32 n, n, 1;\nsetp.lt.u32 p, n, 0x400000;\n@p bra WAIT_%=;\ntrap;\nDONE_%=:\n}\n"
                 :: "r"(bar), "r"(parity) : "memory");
}
__device__ __forceinline__ void mbar_wait_c(uint32_t bar, uint32_t parity) {
    asm volatile("{\n.reg .pred p;\nWAIT_%=:\nmbarrier.try_wait.parity.shared.b64 p, [%0], %1;\n@p bra DONE_%=;\nbra WAIT_%=;\nDONE_%=:\n}\n"
                 :: "r"(bar), "r"(parity) : "memory");
}
__device__ __forceinline__ void mbar_wait_h(uint32_t bar, uint32_t parity) {
    asm volatile("{\n.reg .pred p;\nWAIT_%=:\nmbarrier.try_wait.parity.shared.b64 p, [%0], %1, 0x100000;\n@p bra DONE_%=;\nbra WAIT_%=;\nDONE_%=:\n}\n"
                 :: "r"(bar), "r"(parity) : "memory");
}
__device__ __forceinline__ uint32_t lds32(uint32_t a) { uint32_t v; asm volatile("ld.shared.u32 %0, [%1];" : "=r"(v) : "r"(a) : "memory"); return v; }
__device__ __forceinline__ void sts32(uint32_t a, uint32_t v) { asm volatile("st.shared.u32 [%0], %1;" :: "r"(a), "r"(v) : "memory"); }
__device__ __forceinline__ uint2 lds64(uint32_t a) { uint2 v; asm volatile("ld.shared.v2.u32 {%0,%1}, [%2];" : "=r"(v.x), "=r"(v.y) : "r"(a) : "memory"); return v; }
__device__ __forceinline__ void sts64(uint32_t a, uint32_t x, uint32_t y) { asm volatile("st.shared.v2.u32 [%0], {%1,%2};" :: "r"(a), "r"(x), "r"(y) : "memory"); }
__device__ __forceinline__ uint4 lds128(uint32_t a) { uint4 v; asm volatile("ld.shared.v4.u32 {%0,%1,%2,%3}, [%4];" : "=r"(v.x), "=r"(v.y), "=r"(v.z), "=r"(v.w) : "r"(a) : "memory"); return v; }
__device__ __forceinline__ void sts128(uint32_t a, uint4 v) { asm volatile("st.shared.v4.u32 [%0], {%1,%2,%3,%4};" :: "r"(a), "r"(v.x), "r"(v.y), "r"(v.z), "r"(v.w) : "memory"); }
__device__ __forceinline__ void ldsm4t(uint32_t* v, uint32_t a) {
    asm volatile("ldmatrix.sync.aligned.m8n8.x4.trans.shared.b16 {%0,%1,%2,%3}, [%4];" : "=r"(v[0]), "=r"(v[1]), "=r"(v[2]), "=r"(v[3]) : "r"(a) : "memory");
}
__device__ __forceinline__ void stsm4t(uint32_t a, const uint32_t* v) {
    asm volatile("stmatrix.sync.aligned.m8n8.x4.trans.shared.b16 [%0], {%1,%2,%3,%4};" :: "r"(a), "r"(v[0]), "r"(v[1]), "r"(v[2]), "r"(v[3]) : "memory");
}
__device__ __forceinline__ int atoms_inc(uint32_t a) { int v; asm volatile("atom.shared.add.u32 %0, [%1], 1;" : "=r"(v) : "r"(a) : "memory"); return v; }
__device__ __forceinline__ float tanhf_a(float x) { float y; asm("tanh.approx.f32 %0, %1;" : "=f"(y) : "f"(x)); return y; }
__device__ __forceinline__ const char* as_pair(const void* p, uint32_t scratch) {
    const char* r;
    asm volatile("st.shared.u64 [%1], %2;\nld.volatile.shared.u64 %0, [%1];" : "=l"(r) : "r"(scratch), "l"(p) : "memory");
    return r;
}
__device__ __forceinline__ void ld_unit(uint4& v, const char* p, bool ok) {
    asm volatile("{\n.reg .pred q;\nsetp.ne.u32 q, %5, 0;\n@q ld.relaxed.gpu.global.v4.u32 {%0,%1,%2,%3}, [%4];\n}"
                 : "+r"(v.x), "+r"(v.y), "+r"(v.z), "+r"(v.w) : "l"(p), "r"((uint32_t)ok) : "memory");
}
__device__ __forceinline__ void ld_unit(uint2& v, const char* p, bool ok) {
    asm volatile("{\n.reg .pred q;\nsetp.ne.u32 q, %3, 0;\n@q ld.relaxed.gpu.global.v2.u32 {%0,%1}, [%2];\n}"
                 : "+r"(v.x), "+r"(v.y) : "l"(p), "r"((uint32_t)ok) : "memory");
}
#define ELECT "{\n.reg .pred p;\nelect.sync _|p, 0xffffffff;\n@p "
__device__ __forceinline__ void w_init(uint32_t bar, int n) { asm volatile(ELECT "mbarrier.init.shared.b64 [%0], %1;\n}" :: "r"(bar), "r"(n) : "memory"); }
__device__ __forceinline__ void w_expect(uint32_t bar, uint32_t bytes) { asm volatile(ELECT "mbarrier.arrive.expect_tx.shared.b64 _, [%0], %1;\n}" :: "r"(bar), "r"(bytes) : "memory"); }
__device__ __forceinline__ void w_ld(uint32_t dst, const void* src, int bytes, uint32_t bar) {
    asm volatile(ELECT "cp.async.bulk.shared::cluster.global.mbarrier::complete_tx::bytes [%0], [%1], %2, [%3];\n}" :: "r"(dst), "l"(src), "r"(bytes), "r"(bar) : "memory");
}
__device__ __forceinline__ void w_box_ld(uint32_t dst, const CUtensorMap* tm, int row, uint32_t bar) {
    asm volatile(ELECT "cp.async.bulk.tensor.2d.shared::cluster.global.mbarrier::complete_tx::bytes [%0], [%1, {%3, %4}], [%2];\n}"
        :: "r"(dst), "l"((uint64_t)tm), "r"(bar), "r"(0), "r"(row) : "memory");
}
__device__ __forceinline__ void w_st(void* dst, uint32_t src, int bytes) {
    asm volatile(ELECT "cp.async.bulk.global.shared::cta.bulk_group [%0], [%1], %2;\n}" :: "l"(dst), "r"(src), "r"(bytes) : "memory");
}
__device__ __forceinline__ void w_box_st(const CUtensorMap* tm, int col, uint32_t src) {
    asm volatile(ELECT "cp.async.bulk.tensor.2d.global.shared::cta.bulk_group [%0, {%2, %3}], [%1];\n}" :: "l"((uint64_t)tm), "r"(src), "r"(col), "r"(0) : "memory");
}
__device__ __forceinline__ void w_sent(unsigned* p, uint32_t src) {
    asm volatile(ELECT "cp.reduce.async.bulk.global.shared::cta.bulk_group.add.u32 [%0], [%1], 16;\n}" :: "l"(p), "r"(src) : "memory");
}
__device__ __forceinline__ void w_inc(unsigned* p) { asm volatile(ELECT "red.relaxed.gpu.global.add.u32 [%0], 1;\n}" :: "l"(p) : "memory"); }
__device__ __forceinline__ void w_hint(unsigned* p, uint32_t all) {
    #pragma unroll 1
    for (int i = 0; i < 4096; i++) {
        uint32_t v; asm volatile("ld.relaxed.gpu.global.u32 %0, [%1];" : "=r"(v) : "l"(p) : "memory");
        if (__all_sync(~0u, (int)(v - all) >= 0)) break;
    }
}

__device__ __forceinline__ void finish(uint4& a, const uint4& xu, const uint4& xv) {
    asm("{\n.reg .b32 z;\nfma.rn.relu.bf16x2 z, %0, %3, %1;\nadd.rn.bf16x2 %0, z, %2;\n}" : "+r"(a.x) : "r"(xu.x), "r"(xv.x), "r"(0x3F803F80u));
    asm("{\n.reg .b32 z;\nfma.rn.relu.bf16x2 z, %0, %3, %1;\nadd.rn.bf16x2 %0, z, %2;\n}" : "+r"(a.y) : "r"(xu.y), "r"(xv.y), "r"(0x3F803F80u));
    asm("{\n.reg .b32 z;\nfma.rn.relu.bf16x2 z, %0, %3, %1;\nadd.rn.bf16x2 %0, z, %2;\n}" : "+r"(a.z) : "r"(xu.z), "r"(xv.z), "r"(0x3F803F80u));
    asm("{\n.reg .b32 z;\nfma.rn.relu.bf16x2 z, %0, %3, %1;\nadd.rn.bf16x2 %0, z, %2;\n}" : "+r"(a.w) : "r"(xu.w), "r"(xv.w), "r"(0x3F803F80u));
}

constexpr float EPS2 = 2e-6f;
constexpr float TAU = 2.5e-5f;

constexpr uint32_t TAU_BITS = 0x3A103000u;
template<int NP>
__device__ __forceinline__ bool epi_fast(const float* g, const float* h, float m2, float tau, float& n0, float& d0, float& n1, float& d1, float& dmin)
{
    constexpr int JC = NP >= 6 ? NP - 3 : NP - 2;
    bool ok;
    #pragma unroll
    for (int j = 0; j < NP; j++) {
        float t0 = tanhf_a(g[4*j+0]), t1 = tanhf_a(g[4*j+1]), t2 = tanhf_a(g[4*j+2]), t3 = tanhf_a(g[4*j+3]);
        auto add_d = [&]() {
            if (j == 0) { d0 = t0 + (2.f * (JC + 1) + EPS2); d1 = t2 + (2.f * (JC + 1) + EPS2); } else { d0 += t0; d1 += t2; }
            d0 += t1; d1 += t3;
        };
        if (j <= JC) add_d();
        if (j == 0) { n0 = fmaf(t0, h[0], h[0]); n1 = fmaf(t2, h[2], h[2]); }
        t0 += 1.f; t2 += 1.f;
        if (j == NP - 1) { t1 = fmaf(t1, m2, m2); t3 = fmaf(t3, m2, m2); } else { t1 += 1.f; t3 += 1.f; }
        if (j > JC) add_d();
        if (j > 0) { n0 = fmaf(t0, h[4*j], n0); n1 = fmaf(t2, h[4*j+2], n1); }
        n0 = fmaf(t1, h[4*j+1], n0); n1 = fmaf(t3, h[4*j+3], n1);
        if (j == JC) { dmin = fminf(d0, d1); ok = dmin >= tau; }
    }
    return ok;
}

__device__ __noinline__ void slow_bin(const __nv_bfloat16* x, const __nv_bfloat16* ea, const int* src, const int* dst,
                                      const __nv_bfloat16* wa, const __nv_bfloat16* wb, const __nv_bfloat16* wc,
                                      const __nv_bfloat16* wu, const __nv_bfloat16* wv, __nv_bfloat16* out,
                                      int E, int node0, int nn, int nthr)
{
    const int tid = threadIdx.x, lane = tid & 31;
    for (int i = tid; i < nn * 128; i += nthr) g_slow[(size_t)node0 * 128 + i] = 0.f;
    asm volatile("bar.sync 1, %0;" :: "r"(nthr) : "memory");
    for (int e0 = (tid >> 5) * 32; e0 < E; e0 += nthr) {
        int d = (e0 + lane < E) ? dst[e0 + lane] - node0 : -1;
        unsigned m = __ballot_sync(~0u, d >= 0 && d < nn);
        while (m) {
            int l = __ffs(m) - 1; m &= m - 1;
            int e = e0 + l, n = node0 + __shfl_sync(~0u, d, l), s = src[e];
            float g0 = 0, g1 = 0, h0 = 0, h1 = 0;
            for (int k = 0; k < 64; k++) {
                float xs = __bfloat162float(x[(size_t)s * 64 + k]), xd = __bfloat162float(x[(size_t)n * 64 + k]);
                uint32_t b2 = *(const uint32_t*)(wb + k * 64 + 2 * lane), v2 = *(const uint32_t*)(wv + k * 64 + 2 * lane);
                uint32_t a2 = *(const uint32_t*)(wa + k * 64 + 2 * lane);
                g0 = fmaf(xs, bf_lo(b2), fmaf(xd, bf_lo(a2), g0)); g1 = fmaf(xs, bf_hi(b2), fmaf(xd, bf_hi(a2), g1));
                h0 = fmaf(xs, bf_lo(v2), h0); h1 = fmaf(xs, bf_hi(v2), h1);
            }
            for (int k = 0; k < 16; k++) {
                float ev = __bfloat162float(ea[(size_t)e * 16 + k]);
                uint32_t c2 = *(const uint32_t*)(wc + k * 64 + 2 * lane);
                g0 = fmaf(ev, bf_lo(c2), g0); g1 = fmaf(ev, bf_hi(c2), g1);
            }
            float s0 = rcpf(1.f + ex2f(-LOG2E * g0)), s1 = rcpf(1.f + ex2f(-LOG2E * g1));
            float* acc = g_slow + (size_t)n * 128 + 4 * lane;
            atomicAdd(acc + 0, s0 * h0); atomicAdd(acc + 1, s0);
            atomicAdd(acc + 2, s1 * h1); atomicAdd(acc + 3, s1);
        }
    }
    __threadfence();
    asm volatile("bar.sync 1, %0;" :: "r"(nthr) : "memory");
    for (int i = tid; i < nn * 32; i += nthr) {
        int n = node0 + (i >> 5), cp = i & 31;
        float4 a = __ldcg((const float4*)(g_slow + (size_t)n * 128 + 4 * cp));
        float u0 = 0, u1 = 0;
        for (int k = 0; k < 64; k++) {
            float xd = __bfloat162float(x[(size_t)n * 64 + k]);
            uint32_t w2 = *(const uint32_t*)(wu + k * 64 + 2 * cp);
            u0 = fmaf(xd, bf_lo(w2), u0); u1 = fmaf(xd, bf_hi(w2), u1);
        }
        uint32_t xv = *(const uint32_t*)(x + (size_t)n * 64 + 2 * cp);
        float z0 = u0 + a.x / (a.y + 1e-6f), z1 = u1 + a.z / (a.w + 1e-6f);
        *(uint32_t*)(out + (size_t)n * 64 + 2 * cp) = pack_bf16(bf_lo(xv) + fmaxf(z0, 0.f), bf_hi(xv) + fmaxf(z1, 0.f));
    }
}

__global__ void __launch_bounds__(256) slow_kernel(const __nv_bfloat16* x, const __nv_bfloat16* ea, const int* src, const int* dst,
        const __nv_bfloat16* wa, const __nv_bfloat16* wb, const __nv_bfloat16* wc, const __nv_bfloat16* wu, const __nv_bfloat16* wv,
        __nv_bfloat16* out, int N, int E, int npb)
{
    int node0 = blockIdx.x * npb;
    slow_bin(x, ea, src, dst, wa, wb, wc, wu, wv, out, E, node0, max(0, min(npb, N - node0)), 256);
}

constexpr int XS_BYTES = NPMAX * 1024;
constexpr int ES_BYTES = NPMAX * 256;
constexpr int SM_XS = 0;
constexpr int SM_XU = SM_XS + 3 * NSTAGE * XS_BYTES;
constexpr int SM_TAB = SM_XU + NPB_MAX * 128;
constexpr int SM_ES = SM_TAB + NPB_MAX * 128;
constexpr int SM_WC = SM_ES + 3 * NSTAGE * ES_BYTES;
constexpr int SM_OH = SM_WC + 2048;
constexpr int SM_EID = SM_OH + 128;
constexpr int SM_SRC = SM_EID + SLOT_CAP * 4;
constexpr int SM_TINFO = SM_SRC + SLOT_CAP * 2;
constexpr int SM_MISC = SM_TINFO + TILE_CAP * 32;
constexpr int SM_CLAIM = SM_MISC + 32 * 4;
constexpr int STG = 272;
constexpr int SM_BARS = SM_CLAIM + 32 * 4;
constexpr int SM_ABAR = SM_BARS + 6 * STG;
constexpr int SM_GBAR = SM_ABAR + 16 * 8;
constexpr int SMEM_BYTES = SM_GBAR + (GD + 1) * 8;
constexpr int SM_P2 = 0, SM_P1 = P2B + 256;
constexpr int SM_L1 = SM_P1 + P1B + 128;
constexpr int SM_DEG = SM_L1 + 256;
constexpr int SM_CLS = SM_DEG + 512 * 4;
constexpr int SM_HIST = SM_CLS + NCLS * 4;
constexpr int SM_XLIST = SM_HIST + NB_MAX * 4;
constexpr int SM_SORT = SM_XLIST + 8;
constexpr int SM_SDEG = SM_SORT + NPB_MAX * 4;
constexpr int SM_PAIR = SM_SDEG + NPB_MAX * 2;
constexpr int SM_ENT = SM_ES + 1024;
constexpr int SM_H1 = SM_P1 + HB, SM_H2 = SM_P1;
constexpr int SM_IDX = SM_EID;
constexpr int SM_WR = SM_TAB;
static_assert(TILE_CAP <= 128 && TR >= 2 && SM_ES % 256 == 0 && NSTAGE == 2 && SM_BARS % 16 == 0 && SM_TINFO % 16 == 0 && SM_EID % 128 == 0 && SM_TAB % 1024 == 0 && SM_XU % 1024 == 0 && SM_TINFO % 8 == 0 && SM_OH % 16 == 0 && SM_XLIST % 8 == 0 && SM_PAIR % 8 == 0, "align");
static_assert(SM_P1 % 128 == 0 && P1B + HB <= SM_SRC - SM_EID && 2 * HB <= P1B && SM_H1 + 5 * 128 * 16 <= SM_XU && NB_MAX * (CE / 4) <= 6 * 384 && NB_MAX * 4 <= 5 * 128 && NB_MIN * 4 >= 3 * 128 && SM_PAIR + 128 * 8 <= SM_XU && CH_MAX * 4 <= SM_SRC - SM_EID && SM_DEG >= 3 << 14, "alias");
static_assert(KM == 4 && CE == 64 && SMEM_BYTES <= 232448, "smem");
constexpr uint32_t C_BRK = 16  , C_CONT = 32, C_MORE = 64;
constexpr uint32_t ONE_F = 0x3F800000u;
constexpr int NONE = NPB_MAX - 1;
__host__ __device__ constexpr uint32_t tab_at(uint32_t n) { return (n >> 2) * 512 + (n & 3) * 32 + ((n >> 2) & 1) * 16; }

__device__ __forceinline__ bool unpad(uint32_t w1, int np, float ga, float gb, float& d0, float& d1, int& dv) {
    const int pad = (w1 >> 8) & 31;
    dv = 2 * np - 1 - pad + (w1 >= ONE_F);
    float t0 = TAU * 2 * np, t1 = t0;
    if (pad) {
        t0 = fmaxf(t0, d0 * (1.f / 16384)); t1 = fmaxf(t1, d1 * (1.f / 16384));
        asm volatile("tanh.approx.f32 %0, %0;\ntanh.approx.f32 %1, %1;" : "+f"(ga), "+f"(gb));
        d0 -= pad * (1.f + ga); d1 -= pad * (1.f + gb);
    }
    if (dv == 0) { d0 = d1 = EPS2; t0 = t1 = 0.f; }
    return d0 < t0 || d1 < t1;
}
constexpr int SM_COPY = SM_XU + tab_at(NPB_MAX - 4) - 16;
__device__ __forceinline__ void exact_quad(const float4 g, const float4 h, int k, int dv, float4& r) {
    const float e0 = 2.f * rcpf(1.f + ex2f(-2.f * LOG2E * g.x)), e1 = 2.f * rcpf(1.f + ex2f(-2.f * LOG2E * g.y));
    const float e2 = 2.f * rcpf(1.f + ex2f(-2.f * LOG2E * g.z)), e3 = 2.f * rcpf(1.f + ex2f(-2.f * LOG2E * g.w));
    if (k < dv) { r.y += e0; r.x = fmaf(e0, h.x, r.x); r.w += e2; r.z = fmaf(e2, h.z, r.z); }
    if (k + 1 < dv) { r.y += e1; r.x = fmaf(e1, h.y, r.x); r.w += e3; r.z = fmaf(e3, h.w, r.z); }
}
__device__ __forceinline__ float4 ldsf4(uint32_t a) { const uint4 v = lds128(a); return make_float4(__uint_as_float(v.x), __uint_as_float(v.y), __uint_as_float(v.z), __uint_as_float(v.w)); }
__device__ __noinline__ float4 exact_1(uint32_t sa, uint32_t l16, int np, uint32_t own)
{
    const uint32_t n16 = np * 16, slot = (l16 >= n16) + (l16 >= 2 * n16);
    __syncwarp();
    const float4 g = ldsf4(sa + l16), h = ldsf4(sa + 240 + l16);
    float4 r = make_float4(0.f, 0.f, 0.f, 0.f);
    exact_quad(g, h, (l16 - slot * n16) >> 3, lds32(sa + 496 + slot * 4), r);
    __syncwarp();
    sts128(sa + l16, make_uint4(__float_as_uint(r.x), __float_as_uint(r.y), __float_as_uint(r.z), __float_as_uint(r.w)));
    __syncwarp();
    r = make_float4(0.f, EPS2, 0.f, EPS2);
    #pragma unroll
    for (int j = 0; j < NPMAX; j++) {
        const float4 v = ldsf4(own + j * 16);
        if (j < NPMIN || j < np) { r.x += v.x; r.y += v.y; r.z += v.z; r.w += v.w; }
    }
    __syncwarp();
    sts32(sa + (SM_MISC + 12 - SM_COPY), 0);
    return r;
}
__device__ __noinline__ float4* exact_copy() { return g_copy + (blockIdx.x * 12 + (threadIdx.x >> 5)) * (64 * NPMAX) + (threadIdx.x & 31); }
__device__ __noinline__ float4 exact_all(const float4* gh, int np, int dv)
{
    float4 r = make_float4(0.f, EPS2, 0.f, EPS2);
    #pragma unroll 1
    for (int j = 0; j < np; j++, gh += 32) exact_quad(gh[0], gh[32 * NPMAX], 2 * j, dv, r);
    return r;
}
template<int NP>
__device__ __forceinline__ float4 epi_exact(const float* g, const float* h, uint32_t bad, bool on, int dv, uint32_t sa, uint32_t l16) {
    uint32_t old = 1;
    const uint32_t b1 = bad & (bad - 1), b2 = b1 & (b1 - 1);
    uint32_t slot = 0;
    if (15 / NP > 1) {
        uint32_t lt; asm("mov.u32 %0, %%lanemask_lt;" : "=r"(lt));
        slot = on ? ((bad & lt) != 0) + ((b1 & lt) != 0) : 0;
    }
    const uint32_t own = sa + slot * (NP * 16);
    if ((15 / NP > 2 ? b2 & (b2 - 1) : 15 / NP > 1 ? b2 : b1) == 0) {
        #pragma unroll 1
        for (int n = 0; n < TRIES; n++) {
            asm volatile(ELECT "atom.shared.or.b32 %0, [%1], 1;\n}" : "+r"(old) : "r"(sa + (SM_MISC + 12 - SM_COPY)) : "memory");
            if (__any_sync(~0u, old != 1)) break;
        }
    }
    if (__any_sync(~0u, old == 0)) {
        #pragma unroll
        for (int i = 0; i < 2 * NP; i++) {
            const float* v = i < NP ? g + 4 * i : h + 4 * (i - NP);
            asm volatile("{\n.reg .pred p;\nsetp.ne.u32 p, %5, 0;\n@p st.shared.v4.f32 [%0], {%1,%2,%3,%4};\n}"
                         :: "r"(own + (i < NP ? i : 15 + i - NP) * 16), "f"(v[0]), "f"(v[1]), "f"(v[2]), "f"(v[3]), "r"((uint32_t)on) : "memory");
        }
        asm volatile("{\n.reg .pred p;\nsetp.ne.u32 p, %2, 0;\n@p st.shared.u32 [%0], %1;\n}" :: "r"(sa + 496 + slot * 4), "r"(dv), "r"((uint32_t)on) : "memory");
        return exact_1(sa, l16, NP, own);
    }
    float4* gh = exact_copy();
    #pragma unroll
    for (int i = 0; i < 2 * NP; i++) {
        const float* v = i < NP ? g + 4 * i : h + 4 * (i - NP);
        asm volatile("st.global.v4.f32 [%0], {%1,%2,%3,%4};" :: "l"(gh + (i < NP ? i : NPMAX + i - NP) * 32), "f"(v[0]), "f"(v[1]), "f"(v[2]), "f"(v[3]) : "memory");
    }
    return exact_all(gh, NP, dv);
}
__device__ __forceinline__ uint32_t row_bytes(uint32_t o) { return (o & 0xFE00) | ((o << 2) & 0x180); }

__device__ __noinline__ int balance(int step, char* gs, uint32_t id, int ng, int npb)
{
    extern __shared__ __align__(1024) uint8_t smem[];
    const uint32_t sb = smem_u32(smem), lane = threadIdx.x & 31, b = blockIdx.x, r4 = lane >> 3;
    const uint32_t tw = ((lane & 1) << 4) | ((lane & 6) << 6), ti = sb + SM_TINFO + r4 * 8, st = sb + SM_MISC + 48;
    uint32_t now; asm volatile("mov.u32 %0, %%globaltimer_lo;" : "=r"(now));
    auto put = [&](uint32_t a, uint32_t v) { if (lane == 0) asm volatile("st.relaxed.gpu.global.v2.u32 [%0], {%1, %2};" :: "l"(gs + a), "r"(v), "r"(id) : "memory"); };
    auto get = [&](uint32_t a) {
        uint2 v;
        #pragma unroll 1
        for (uint32_t n = 0; ; n++) {
            asm volatile("ld.acquire.gpu.global.v2.u32 {%0, %1}, [%2];" : "=r"(v.x), "=r"(v.y) : "l"(gs + a) : "memory");
            if (__all_sync(~0u, v.y == id)) break;
            if (n > (1u << 22)) __trap();
        }
        return v.x;
    };
    int gn = ng;
    if (step < 0) {
        if (BAL && step == -1) {
            const uint32_t e = lds32(sb + SM_TINFO + (3 * R1 + 3) * 32);
            if ((e & 0xFFFF) >= KM * 64 && ((e >> 20) & 127) < 2 && ((lds32(sb + SM_TINFO + (ng - KM) * 32 + 4) >> 16) & 15) <= 8 && lds32(sb + SM_MISC + 24) == 0) {
                #pragma unroll 1
                for (int j = 0; j < KM; j++) {
                    const uint32_t ta = (ng - 1 - j) * 32, s0 = lds32(sb + SM_TINFO + ta) & 0xFFFF;
                    const uint2 e = lds64(ti + ta);
                    char* p = gs + G_P + (b * KM + j) * GRP_B;
                    const uint32_t ro = sb + ((e.y & 0xFFFF) ^ tw);
                    *(uint4*)(p + lane * 16) = lds128(ro + SM_TAB);
                    *(uint4*)(p + 512 + lane * 16) = lds128(ro + SM_XU);
                    *(uint2*)(p + 1024 + lane * 8) = lds64(sb + SM_EID + s0 * 4 + lane * 8);
                    *(uint32_t*)(p + 1280 + lane * 4) = lds32(sb + SM_SRC + s0 * 2 + lane * 4);
                    *(uint2*)(p + 1408 + r4 * 8) = make_uint2(e.x >> 27 ? e.x - s0 : e.x, e.y);
                }
                uint32_t c = 0;
                #pragma unroll 1
                for (int g = 3 * R1 + 3 + lane; g < ng; g += 32) c += 93 + ((lds32(sb + SM_TINFO + g * 32 + 4) >> 16) & 15) * 42;
                sts32(st, (__reduce_add_sync(~0u, c) * 595) >> 10);
                asm volatile("fence.acq_rel.gpu;" ::: "memory");
                __syncwarp();
                return 1;
            }
        }
        put(G_F + b * 8, (now << 6) & ~511u);
    } else if (step == R2) {
        uint2 v[5];
        #pragma unroll 1
        for (uint32_t n = 0; ; n++) {
            bool ok = true;
            #pragma unroll
            for (int i = 0; i < 5; i++) asm volatile("ld.relaxed.gpu.global.v2.u32 {%0, %1}, [%2];" : "=r"(v[i].x), "=r"(v[i].y) : "l"(gs + G_F + min(lane + 32 * i, gridDim.x - 1) * 8) : "memory");
            #pragma unroll
            for (int i = 0; i < 5; i++) ok &= v[i].y == id;
            if (__all_sync(~0u, ok)) break;
            if (n > (1u << 22)) __trap();
        }
        const uint32_t ref = __shfl_sync(~0u, v[0].x, 0) - 0x80000000u, key = ((lds32(st) - ref) & ~511u) | b;
        uint32_t c = 0;
        #pragma unroll
        for (int i = 0; i < 5; i++) if (lane + 32 * i < gridDim.x && (v[i].x & 256)) c += 0x10000 + ((((v[i].x - ref) & ~511u) | (lane + 32 * i)) < key);
        c = __reduce_add_sync(~0u, c);
        const uint32_t kf = key | (ng % 3 == 0 ? 256 : 0);
        put(G_R + (c & 0xFFFF) * 8, kf);
        sts64(st, kf, (c >> 16) - 1 - (c & 0xFFFF));
        __syncwarp();
        return gn;
    } else {
        const uint32_t pk = get(G_R + lds32(st + 4) * 8);
        const uint32_t key = lds32(st);
        const int df = (int)(pk >> 9) - (int)(key >> 9), m = min((abs(df) * 8 + 175) / 350, (df < 0 ? pk : key) & 256 ? 3 : KM);
        gn += df < 0 ? -m : m;
        #pragma unroll 1
        for (int i0 = 0; i0 < gn - ng; i0 += 2) {
            uint4 ra[2], ru[2]; uint2 le[2], e[2]; uint32_t ls[2];
            #pragma unroll
            for (int i = 0; i < 2; i++) {
                const char* p = gs + G_P + ((pk & 255) * KM + i0 + i) * GRP_B;
                ra[i] = __ldcg((const uint4*)(p + lane * 16)); ru[i] = __ldcg((const uint4*)(p + 512 + lane * 16));
                le[i] = __ldcg((const uint2*)(p + 1024 + lane * 8)); e[i] = __ldcg((const uint2*)(p + 1408 + r4 * 8));
                ls[i] = __ldcg((const uint32_t*)(p + 1280 + lane * 4));
            }
            #pragma unroll
            for (int i = 0; i < 2; i++) {
                const int j = (m - 1 - i0 - i) & 3;
                const bool some = (e[i].y & 0xFFFF) != tab_at(NONE);
                const uint32_t row = some ? lds32(ti + (i0 + i) * 32 + 4) & 0xFFFF : tab_at(NONE);
                if (some) { sts128(sb + (row ^ tw) + SM_TAB, ra[i]); sts128(sb + (row ^ tw) + SM_XU, ru[i]); }
                sts64(sb + SM_EID + (i0 + i) * 256 + lane * 8, le[i].x, le[i].y);
                sts32(sb + SM_SRC + (i0 + i) * 128 + lane * 4, ls[i]);
                sts32(sb + SM_MISC + 64 + j * 16 + r4 * 4, (pk & 255) * npb * 128 + row_bytes(e[i].y & 0xFFFF));
                sts64(ti + (ng + j) * 32, ((e[i].x & 0xF800FFFFu) + (i0 + i) * 64) | (((e[i].y >> 16) & 15) > 5 ? 14u << 16 : 13u << 16), (e[i].y & 0xFFFF0000u) | row);
            }
        }
        __syncwarp();
        sts32(sb + SM_TINFO + gn * 32 + lane * 4, lane & 1 ? tab_at(NONE) : 0);
        sts32(sb + SM_MISC + 16, gn);
    }
    sts32(sb + SM_MISC + 28, gn);
    __syncwarp();
    if (lane == 0) mbar_arrive(sb + SM_ABAR + 32);
    return step < 0 ? 0 : gn;
}
__device__ __forceinline__ uint32_t bin_bits(uint32_t b) { return (1u << (b & 7)) | ((b < 48 ? 0x100u : 0x400u) << (b >> 3)); }
__device__ __forceinline__ void place(uint32_t sbase, uint32_t slot, uint32_t v, uint32_t eb) {
    asm volatile("{\n.reg .pred p;\nsetp.lt.u32 p, %0, %5;\n@p st.shared.u32 [%1], %2;\n@p st.shared.u16 [%3], %4;\n}"
                 :: "r"(slot), "r"(sbase + SM_EID + slot * 4), "r"(eb + (v >> 19)), "r"(sbase + SM_SRC + slot * 2), "r"(v), "n"(SLOT_CAP) : "memory");
}
__device__ __forceinline__ uint64_t desc_sw128(uint32_t a) {
    return (uint64_t)((a & 0x3FFFF) >> 4) | ((uint64_t)1 << 16) | ((uint64_t)64 << 32) | ((uint64_t)1 << 62);
}

template<bool LO32>
__global__ void __launch_bounds__(THREADS, 1)
gcn_kernel(const int* __restrict__ dst, unsigned* gbar, char* gs, const int* __restrict__ src, int E, int ch, int N, int npb, uint32_t magic,
           const __nv_bfloat16* __restrict__ x, const __nv_bfloat16* __restrict__ ea,
           const __nv_bfloat16* __restrict__ wa, const __nv_bfloat16* __restrict__ wb, const __nv_bfloat16* __restrict__ wc,
           const __nv_bfloat16* __restrict__ wu, const __nv_bfloat16* __restrict__ wv,
           __nv_bfloat16* out, int4 wrow, const __grid_constant__ CUtensorMap tm1, const __grid_constant__ CUtensorMap tm2,
           const __grid_constant__ CUtensorMap tmw, const __grid_constant__ CUtensorMap tmx)
{
    extern __shared__ __align__(1024) uint8_t smem[];
    int* cls = (int*)(smem + SM_CLS);
    int* misc = (int*)(smem + SM_MISC);
    WG0(); WS(0); CG(0);
    const uint32_t sbase = smem_u32(smem);
    const int tid = threadIdx.x, lane = tid & 31;
    const int b = blockIdx.x, nb = gridDim.x;
    const int cnt = max(0, min(ch, E - b * ch));
    const int node0 = b * npb;
    uint32_t tag = 0;
    if (tid < 384) asm volatile("ld.relaxed.gpu.global.u32 %0, [%1];" : "=r"(tag) : "l"(gbar) : "memory");
    auto dst_ld = [&](int v, uint32_t n) {
        const uint32_t off = v * (THREADS * 4) + tid * 4;
        asm volatile("{\n.reg .pred q;\nsetp.lt.u32 q, %2, %3;\n@q cp.async.cg.shared.global [%0], [%1], 16;\n}"
                     :: "r"(sbase + SM_IDX + off * 4), "l"(dst + (uint32_t)(b * ch + off)), "r"(off), "r"(n) : "memory");
    };
    dst_ld(0, min(cnt, 384 * 4));
    const int warp = (int)__reduce_max_sync(~0u, (unsigned)tid >> 5);
    const uint32_t su = __reduce_or_sync(~0u, sbase);
    if (warp >= 12) {
        const int v = warp & 3;
        const uint32_t a1 = su + SM_ABAR + (v == 0 ? 80 : v == 1 ? 120 : v == 2 ? 32 : 40);
        w_init(su + SM_ABAR + v * 8, 1); w_init(a1, 1);
        w_expect(su + SM_ABAR + v * 8, v < 3 ? min(max(cnt * 4 - v * 8192, 0), 8192) : 4 * 8192 + 2048);
        if (v < 2) w_expect(a1, v == 0 ? nb * (CE * 2) : nb * 64);
        asm volatile("fence.mbarrier_init.release.cluster;" ::: "memory");
        dst_ld(0, cnt);
    }
    #pragma unroll
    for (int v = 0; v < EPT / 4; v++) {
        if (v) {
            uint32_t c0, c1; asm volatile("mov.u32 %0, %%clock;" : "=r"(c0)); do { asm volatile("mov.u32 %0, %%clock;" : "=r"(c1)); } while (__all_sync(~0u, c1 - c0 < PD));
            dst_ld(v, cnt);
        }
        cp_commit();
    }
    if (warp == 15) {
        w_box_ld(su + SM_WR, &tmw, wrow.x, su + SM_ABAR + 24); w_box_ld(su + SM_WR + 8192, &tmw, wrow.y, su + SM_ABAR + 24);
        w_box_ld(su + SM_WR + 16384, &tmw, wrow.z, su + SM_ABAR + 24); w_ld(su + SM_WR + 24576, wc, 2048, su + SM_ABAR + 24);
        w_box_ld(su + SM_WR + 40960, &tmw, wrow.w, su + SM_ABAR + 24);
    }
    const int wg = warp >> 2, w = warp & 3;
    const int q = lane >> 2, t = lane & 3;
    const int nn = max(0, min(npb, N - node0));
    if (sbase & 1023) __trap();

    sts32(sbase + SM_DEG + tid * 4, tid < NPB_MAX ? 0 : 0x80000000u);
    if (tid < NCLS + NB_MAX) cls[tid] = tid < NCLS ? 0 : ((tid - NCLS) * 20) & 63;
    else if (warp == 8) sts32(sbase + SM_OH + lane * 4, t != (q >> 1) ? 0u : 0x00003F00u);
    else if (warp == 11) misc[lane] = lane == 5 ? TILE_CAP - TILE_X : lane == 3 ? 3 : lane == 8;
    if (warp == 14) sts32(sbase + SM_TINFO + 96 * 32 + lane * 4, lane & 1 ? tab_at(NONE) : 0);
    if (warp == 15) sts32(sbase + SM_CLAIM + lane * 4, lane == 0 ? 3 * 32 : 0x40000000);
    if (tid == 0) sts32(sbase + SM_XLIST, tag);
    tag = (tag & 1) | 2;
    if (wg < 3) {
        const uint32_t d0 = ((NPB_MAX + ((2 * lane) & 15) + 16 * (b & 1)) * 4 | (tag << 14)) * 0x10001u, d1 = d0 + 0x40004u, d2 = tag << 16;
        #pragma unroll 1
        for (int i = tid; i < (P1B + 384) / 16; i += 384) {
            sts128(sbase + SM_P1 + i * 16, make_uint4(d0, d0, d1, i == P1B / 16 + 11 ? 0x80000000u | (tag << 14) : d1));
            sts128(sbase + SM_P2 + i * 16, make_uint4(d2, d2, d2, d2)); sts128(sbase + SM_P2 + P1B - 128 + i * 16, make_uint4(d2, d2, d2, d2));
        }
    }
    WS(1);
    __syncthreads();
    if (wg == 3) tag = lds32(sbase + SM_P2) >> 16;
    uint32_t all = 0;
    if (wg == 3) all = (lds32(sbase + SM_XLIST) + 1) * nb;
    if (tid == 128) {
        asm volatile("prefetch.tensormap [%0];" :: "l"((uint64_t)&tm1) : "memory");
        asm volatile("prefetch.tensormap [%0];" :: "l"((uint64_t)&tm2) : "memory");
        asm volatile("prefetch.tensormap [%0];" :: "l"((uint64_t)&tmx) : "memory");
    }
    const uint32_t m4 = __reduce_or_sync(~0u, -4 * npb);
    uint32_t ent[EPT];
    #pragma unroll
    for (int v = 0; v < EPT / 4; v++) {
        if (v == 0) cp_wait<2>(); else if (v == 1) cp_wait<1>(); else cp_wait<0>();
        if (v == 0 && wg == 2 && w < 3) {
            const int n = min(cnt * 4 - w * 8192, 8192);
            if (n > 0) w_ld(su + SM_XU + w * 8192, src + b * ch + w * 2048, n, su + SM_ABAR + w * 8);
        }
        const uint32_t off = v * (THREADS * 4) + tid * 4;
        if (off < (uint32_t)cnt) {
            const uint4 u = lds128(sbase + SM_IDX + off * 4);
            uint32_t dv[4] = {u.x, u.y, u.z, u.w}, ps[4], ck[4];
            uint32_t* en = ent + 4 * v;
            #pragma unroll
            for (int k = 0; k < 4; k++) {
                dv[k] = min(dv[k], (uint32_t)(nb * npb - 1));
                ps[k] = __umulhi(dv[k], magic);
                asm volatile("atom.shared.add.u32 %0, [%1], 0x10001;" : "=r"(ck[k]) : "r"(sbase + SM_HIST + ps[k] * 4) : "memory");
            }
            #pragma unroll
            for (int k = 0; k < 4; k++) {
                dv[k] = ps[k] * m4 + (dv[k] * 4 + (tag << 14));
                en[k] = (ck[k] & 63) + ps[k] * CE;
            }
            if (__builtin_expect(max(max(ck[0], ck[1]), max(ck[2], ck[3])) >= CE << 16, 0)) {
                auto step = [&]() {
                    uint32_t e = en[0];
                    const uint32_t d = dv[0];
                    if (ck[0] >= CE << 16) {
                        uint32_t j; asm volatile("atom.shared.inc.u32 %0, [%1], 0x7fffffff;" : "=r"(j) : "r"(sbase + SM_MISC + 8) : "memory");
                        j = min(j + (j >= 15), 63u);
                        sts32(sbase + SM_L1 + j * 4, d | ((j < 63 ? e / CE : 255u) << 16));
                        e = NB_MAX * CE + j;
                    }
                    en[0] = en[1]; en[1] = en[2]; en[2] = en[3]; en[3] = e;
                    dv[0] = dv[1]; dv[1] = dv[2]; dv[2] = dv[3]; dv[3] = d;
                    ck[0] = ck[1]; ck[1] = ck[2]; ck[2] = ck[3];
                };
                if (v == 2) { step(); step(); step(); step(); }
                else {
                    #pragma unroll 1
                    for (int k = 0; k < 4; k++) step();
                }
            }
            #pragma unroll
            for (int k = 0; k < 4; k++)
                asm volatile("st.shared.u16 [%0], %1;" :: "r"(sbase + SM_P1 + en[k] * 2), "r"(dv[k]) : "memory");
        }
    }
    if (warp == 15) {
        #pragma unroll
        for (int v = 0; v < EPT / 4; v++) sts128(sbase + SM_ENT + v * 512 + lane * 16, make_uint4(ent[4*v], ent[4*v+1], ent[4*v+2], ent[4*v+3]));
    }
    asm volatile("fence.proxy.async.shared::cta;" ::: "memory");
    WS(5);
    __syncthreads();
    if (warp == 15) {
        w_inc(gbar + 1);
        const uint32_t n = __reduce_or_sync(~0u, lds32(su + SM_MISC + 8));
        if (__builtin_expect(n > 15, 0)) {
            const uint2 r = lds64(su + SM_L1 + lane * 8);
            uint32_t m = lane < 8 ? 0 : (r.x >> 24 ? 0 : bin_bits(r.x >> 16)) | (r.y >> 24 ? 0 : bin_bits(r.y >> 16));
            m = n > 62 ? 0x7FFF3FFFu : __reduce_or_sync(~0u, m);
            sts32(su + SM_L1 + 60, m | 0x80000000u | (tag << 14));
            asm volatile("fence.proxy.async.shared::cta;" ::: "memory");
            __syncwarp();
        }
        w_st(gs + G_H1 + b * 64, su + SM_L1, 64);
        w_box_st(&tm1, b * (CE / 2), su + SM_P1);
        w_st(gs + G_L + b * 512, su + SM_L1, 256);
        asm volatile("cp.async.bulk.commit_group;" ::: "memory");
    } else {
        mbar_wait_c(su + SM_ABAR, 0);
        auto put = [&](uint32_t off, const uint32_t* uu) {
            if (off < (uint32_t)cnt) {
                const uint4 sv = lds128(sbase + SM_XU + off * 4);
                const uint32_t ss[4] = {sv.x, sv.y, sv.z, sv.w};
                #pragma unroll
                for (int k = 0; k < 4; k++) sts32(sbase + SM_P2 + uu[k] * 4, (ss[k] & 0xFFFF) | (((off + k) << 19) + (tag << 16)));
            }
        };
        #pragma unroll
        for (int v = 0; v < EPT / 4; v++) { if (v) mbar_wait_c(su + SM_ABAR + v * 8, 0); put(v * (THREADS * 4) + tid * 4, ent + 4 * v); }
        if (wg == 3) {
            const uint4 e = lds128(sbase + SM_ENT + w * 512 + lane * 16);
            const uint32_t uu[4] = {e.x, e.y, e.z, e.w};
            put(w * (THREADS * 4) + (480 + lane) * 4, uu);
        }
        asm volatile("fence.proxy.async.shared::cta;" ::: "memory");
        WS(7);
        __syncwarp();
        asm volatile("bar.arrive 12, 512;" ::: "memory");
    }
    WS(8);

    const int ngroups = (nn + 3) >> 2;
    if (warp < 12) {
        asm volatile("setmaxnreg.inc.sync.aligned.u32 152;");
        const uint32_t ab = su + SM_ABAR;
        uint32_t wf[40], wn[16];
        const uint32_t mo = sbase + (8 * (lane >> 4) + (lane & 7)) * 128 + (((2 * w + ((lane >> 3) & 1)) ^ (lane & 7)) << 4);
        const uint32_t wca = __shfl_sync(~0u, sbase + SM_WC + (16 * w + q) * 32 + t * 4 + ((q >> 2) << 4), lane), l16 = __shfl_sync(~0u, (lane & 15) * 16, lane);
        mbar_wait_c(ab + 24, 0);
        {
            #pragma unroll
            for (int ks = 0; ks < 4; ks++) { ldsm4t(wf + 4 * ks, mo + SM_WR + ks * 2048); ldsm4t(wf + 20 + 4 * ks, mo + SM_WR + 8192 + ks * 2048); ldsm4t(wn + 4 * ks, mo + SM_WR + 16384 + ks * 2048); }
            auto half = [](uint32_t& v) { asm("mul.rn.bf16x2 %0, %0, %1;" : "+r"(v) : "r"(0x3F003F00u)); };
            uint32_t z = 0;
            #pragma unroll
            for (int i = 0; i < 16; i++) { half(wf[i]); z ^= wf[i]; }
            sts32(sbase + SM_ES + lane * 4, z);
            if (wg == 2) {
                uint32_t f[4];
                ldsm4t(f, (mo ^ ((lane & 7) << 4)) + SM_WR + 24576);
                half(f[0]); half(f[1]); half(f[2]); half(f[3]);
                sts32(wca, f[0]); sts32(wca + 256, f[1]); sts32(wca ^ 16, f[2]); sts32((wca ^ 16) + 256, f[3]);
                asm volatile("fence.proxy.async.shared::cta;" ::: "memory");
            }
        }
        const uint64_t wcd = __reduce_or_sync(~0u, (((sbase + SM_WC) & 0x3FFFF) >> 4) | (8u << 16)) | EDHI;
        const uint32_t bar0 = __reduce_or_sync(~0u, sbase + SM_BARS + wg * 2 * STG);
        const uint32_t xd0 = __reduce_or_sync(~0u, (((sbase + SM_XS + wg * NSTAGE * XS_BYTES) & 0x3FFFF) >> 4) | (1u << 16));
        const uint32_t ed0 = __reduce_or_sync(~0u, (((sbase + SM_ES + wg * NSTAGE * ES_BYTES) & 0x3FFFF) >> 4) | (8u << 16));
        const uint64_t ohd = __reduce_or_sync(~0u, ((sbase + SM_OH) & 0x3FFFF) >> 4);
        const uint32_t tabx = __reduce_or_sync(~0u, sbase + SM_TAB + w * 128);
        const uint32_t bars = __reduce_or_sync(~0u, 2 * bar0 + STG), xds = __reduce_or_sync(~0u, 2 * xd0 + XS_BYTES / 16), eds = __reduce_or_sync(~0u, 2 * ed0 + ES_BYTES / 16);
        const uint32_t xuo = __reduce_or_sync(~0u, sbase + SM_XU + wg * 16384);
        { const uint2 z = lds64(sbase + SM_OH + 8); wf[38] = z.x; wf[39] = z.y; }
        WS(9);
        constexpr int NU = 6;
        const uint32_t dm = ((NPB_MAX + lane) * 4 | (tag << 14)) * 0x10001u;
        const uint32_t db = sbase + SM_DEG - (tag << 14);
        const char* const g1 = gs + (uint32_t)(b * (P1B + P2B) + tid * 8);
        int rk[NU][4];
        uint32_t spins = 0;
        {
            uint2 r1[NU];
            mbar_wait_c(ab + 80, 0);
            WS(2);
            #pragma unroll
            for (int i = 0; i < NU; i++) {
                r1[i] = make_uint2(dm, dm);
                if (NB_MIN * 16 >= 384 * (i + 1) || tid + 384 * i < nb * 16) r1[i] = lds64(sbase + SM_IDX + (tid + 384 * i) * 8);
            }
            #pragma unroll 1
            while (true) {
                uint32_t bad = 0;
                #pragma unroll
                for (int i = 0; i < NU; i++) bad |= r1[i].y ^ dm;
                if (__builtin_expect(!__any_sync(~0u, bad & 0xC000), 1)) break;
                #pragma unroll
                for (int i = 0; i < NU; i++) ld_unit(r1[i], g1 + 384 * 8 * i, (r1[i].y ^ dm) & 0xC000);
                if (++spins > (1u << 22)) break;
            }
            WS(3);
            #pragma unroll
            for (int i = 0; i < NU; i++) {
                rk[i][0] = r1[i].x & 0xFFFF; rk[i][1] = r1[i].x >> 16; rk[i][2] = r1[i].y & 0xFFFF; rk[i][3] = r1[i].y >> 16;
                #pragma unroll
                for (int k = 0; k < 4; k++) asm volatile("red.shared.add.u32 [%0], 1;" :: "r"(db + min((uint32_t)rk[i][k], NPB_MAX * 4 + (tag << 14))) : "memory");
            }
        }
        WS(10);
        asm volatile("bar.sync 11, 512;" ::: "memory");
        int mycls = 0, mycr = 0, dg = lds32(sbase + SM_DEG + tid * 4);
        if (tid < nn) {
            mycls = NCLS - 1 - (dg <= 40 ? dg : min(41 + ((dg - 41) >> 3), NCLS - 1)); mycr = atomicAdd(&cls[mycls], 1);
        }
        int s0 = 0;
        if (__builtin_expect(dg > 40, 0)) s0 = max(SLOT_CAP - ((dg + 1) & ~1) - atomicAdd(&misc[6], (dg + 1) & ~1), 0);
        asm volatile("bar.sync 1, 384;" ::: "memory");
        WS(12);
        {
            const uint2 c = lds64(sbase + SM_CLS + lane * 8);
            const int v0 = c.x * (lane > 11 ? ((64 - 2 * lane) << 16) + 1 : 1), v1 = c.y * (lane >= 11 ? ((62 - 2 * lane) << 16) + 1 : 1);
            int inc = v0 + v1;
            #pragma unroll
            for (int o = 1; o < 32; o <<= 1) { int y = __shfl_up_sync(~0u, inc, o); if (lane >= o) inc += y; }
            const int e0 = __shfl_sync(~0u, inc - v0 - v1, mycls >> 1), e1 = __shfl_sync(~0u, inc - v1, mycls >> 1);
            const int e = (mycls & 1) ? e1 : e0;
            if (tid < nn) {
                if (dg <= 40) s0 = min((e >> 16) + mycr * ((dg + 1) & ~1), SLOT_CAP - 40);
                sts32(sbase + SM_DEG + tid * 4, s0);
            }
            const uint32_t pos = tid < nn ? (e & 0xFFFF) + mycr : tid;
            sts32(sbase + SM_SORT + pos * 4, tid < nn ? (uint32_t)tid | ((uint32_t)s0 << 16) : NONE);
            asm volatile("st.shared.u16 [%0], %1;" :: "r"(sbase + SM_SDEG + pos * 2), "r"(min(dg, 65535)) : "memory");
            if (tid == 383) { misc[4] = (nn - c.y + 3) >> 2; if ((inc >> 16) + misc[6] > SLOT_CAP - 40) misc[1] = 1; }
        }
        asm volatile("bar.sync 1, 384;" ::: "memory");
        WS(13);
        const uint32_t sv = lds32(sbase + SM_SORT + tid * 4);
        const uint2 d4 = lds64(sbase + SM_SDEG + (tid >> 2) * 8);
        const uint32_t slow = lds32(sbase + SM_MISC + 4);
        #pragma unroll
        for (int i = 0; i < NU; i++) {
            #pragma unroll
            for (int k = 0; k < 4; k++) rk[i][k] = atoms_inc(db + rk[i][k]);
        }
        if (__reduce_or_sync(~0u, slow) == 0) {
            const uint32_t nd = sv & 0xFFFF;
            const int g = tid >> 2;
            dg = ((t & 2 ? d4.y : d4.x) >> (16 * (t & 1))) & 0xFFFF;
            const uint32_t hi2 = __vmaxu2(d4.x, d4.y), lo2 = __vminu2(d4.x, d4.y);
            const int mx = max(hi2 >> 16, hi2 & 0xFFFF), mn = min(lo2 >> 16, lo2 & 0xFFFF);
            int left = (mx + 1) >> 1;
            int tl = g, nx = ngroups + 4 + g, nt = left > NPMAX ? 2 : 1;
            const bool odd = left > 2 * NPMAX || (nt == 2 && nx >= TILE_CAP - TILE_X);
            if (__builtin_expect(__any_sync(~0u, odd), 0)) {
                if (odd) nt = (left + NPMAX - 1) / NPMAX;
                if (odd && t == 0) { asm volatile("atom.shared.add.u32 %0, [%1], %2;" : "=r"(nx) : "r"(sbase + SM_MISC + 20), "r"(nt - 1) : "memory"); if (nx + nt - 1 > TILE_CAP) misc[1] = 1; }
                nx = __shfl_sync(~0u, nx, lane & ~3);
                if (odd && nx + nt - 1 > TILE_CAP) left = 0;
            }
            const uint32_t w0 = tab_at(nd);
            if (g >= ngroups + 4) tl = ngroups;
            uint32_t cont = 0;
            int done = 0;
            bool act = true;
            do {
                int np = nt <= 2 ? (left + nt - 1) >> (nt - 1) : (left + nt - 1) / nt;
                left -= np; nt = max(nt - 1, 1);
                if (np) np = max(np, NPMIN);
                const int dv = min(max(dg - done, 0), 2 * np);
                uint32_t code = (uint32_t)np | cont | (left > 0 ? C_MORE : 0u);
                const bool gen = mn - done < 2 * np - (np == NPMIN ? 1 : 2);
                if (np == 0) code = 0;
                const uint32_t w1 = code | (dv == 2 * np ? 0x8000u : (2 * np - 1 - dv) << 8);
                if (act) *(uint2*)(smem + SM_TINFO + tl * 32 + t * 8) = make_uint2((dv ? (sv >> 16) + done : 0) | ((gen ? (np > 8 ? 15 : np > 5 ? 14 : 13) : np) << 16) | ((left > 0 ? nx : g >= ngroups - (KM + 3)) << 20) | ((uint32_t)dv << 27), w0 | (np == 0 ? 0u : w1 << 16));
                tl = nx++; cont = C_CONT; done += 2 * np; act = left > 0;
            } while (__any_sync(~0u, act));
        }
        __syncwarp();
        asm volatile("bar.arrive 4, 512;" ::: "memory");
        WS(14);
        wf[16] = lds32(wca); wf[17] = lds32(wca + 256); wf[18] = lds32(wca ^ 16); wf[19] = lds32((wca ^ 16) + 256);
        #pragma unroll
        for (int pc = 0; pc < 3; pc++) {
            uint4 r2[2];
            mbar_wait_c(ab + pc * 8, 1);
            if (pc == 0) WS(4); if (pc == 2) WS(16);
            #pragma unroll
            for (int k = 0; k < 2; k++) {
                r2[k] = lds128(sbase + SM_P2 + (tid + 384 * (2 * pc + k)) * 16);
                if (rk[2 * pc + k][0] < 0) r2[k].w = tag << 16;
            }
            while (__builtin_expect(__any_sync(~0u, ((r2[0].w ^ (tag << 16)) | (r2[1].w ^ (tag << 16))) & 0x30000), 0)) {
                #pragma unroll
                for (int k = 0; k < 2; k++)
                    ld_unit(r2[k], g1 + (uint32_t)(tid * 8) + (P1B + 384 * 16 * (2 * pc + k)), (r2[k].w ^ (tag << 16)) & 0x30000);
                if (++spins > (1u << 22)) break;
            }
            #pragma unroll
            for (int k = 0; k < 2; k++) {
                const int i = 2 * pc + k;
                const uint32_t eb = ((tid >> 4) + 24 * i) * ch;
                place(sbase, rk[i][0], r2[k].x, eb); place(sbase, rk[i][1], r2[k].y, eb); place(sbase, rk[i][2], r2[k].z, eb); place(sbase, rk[i][3], r2[k].w, eb);
            }
        }
        WGD();
        __syncwarp();
        asm volatile("bar.arrive 3, 480;" ::: "memory");
        float g[4 * NPMAX], h[4 * NPMAX];
        float4 cyr = make_float4(0.f, 0.f, 0.f, 0.f);
        WS(15); CG(1);
        mbar_wait_c(ab + 88 + wg * 8, 0);
        auto pack = [&](uint32_t* v, const float* u) {
            #pragma unroll
            for (int i = 0; i < 16; i++) v[i] = pack_bf16(u[2*i], u[2*i+1]);
        };
        auto rows_st = [&](uint32_t p, const uint32_t* v) {
            #pragma unroll
            for (int i = 0; i < 4; i++) stsm4t(p + i * 2048, v + 4 * i);
        };
        {
            const uint64_t d0 = desc_sw128(xuo), d1 = d0 + 512;
            const uint32_t mr = sbase + wg * 16384 + w * 128 + (tab_at(8 * (lane >> 4) + (lane & 7)) ^ ((lane & 8) << 1));
            uint32_t v[16];
            node_mma(g, wn, d0); node_mma(h, wn, d1);
            TileMMA<8>::wait_g(g);
            pack(v, g); rows_st(mr + SM_TAB, v);
            TileMMA<8>::wait_h(h);
            #pragma unroll
            for (int ks = 0; ks < 4; ks++) ldsm4t(wn + 4 * ks, mo + SM_WR + 40960 + ks * 2048);
            node_mma(g, wn, d0);
            if (wg == 2) asm volatile("bar.sync 5, 384;" ::: "memory"); else asm volatile("bar.arrive 5, 384;" ::: "memory");
            pack(v, h); rows_st(mr + SM_TAB + 8192, v);
            node_mma(h, wn, d1);
            __syncwarp();
            if (lane == 0) mbar_arrive(sbase + SM_ABAR + 112);
            TileMMA<8>::wait_g(g);
            pack(v, g);
            asm volatile("bar.sync %0, 128;" :: "r"(8 + wg) : "memory");
            rows_st(mr + SM_XU, v);
            TileMMA<8>::wait_h(h);
            pack(v, h);
            asm volatile("bar.sync %0, 128;" :: "r"(8 + wg) : "memory");
            rows_st(mr + SM_XU + 8192, v);
            __syncwarp();
            if (lane == 0) mbar_arrive(sbase + SM_ABAR + 72);
            mbar_wait_c(ab + 112, 0);
            __syncwarp();
            if (__builtin_expect(__reduce_or_sync(~0u, misc[1]) != 0, 0)) { slow_bin(x, ea, src, dst, wa, wb, wc, wu, wv, out, E, node0, nn, 384); asm volatile("exit;"); }
            WS(6);
        }
        uint32_t bar = bar0, xd = xd0, ed = ed0, ph = 0;
        float pn0 = 0.f, pd0 = 1.f, pn1 = 0.f, pd1 = 1.f;
        uint4 rc;
        rc.x = lds32(sbase + SM_TINFO + wg * 32 + ((lane >> 1) & 3) * 8 + 4);
        uint32_t code = __reduce_or_sync(~0u, rc.x >> 16);
        rc.x = (rc.x & 0xFFFF) ^ ((lane & 8) << 1);
        uint32_t pst = tabx + tab_at(NONE);
        auto fetch_a = [&]() {
            asm volatile("ldmatrix.sync.aligned.m8n8.x2.trans.shared.b16 {%0,%1}, [%2];" : "=r"(wf[36]), "=r"(wf[37]) : "r"(tabx + rc.x) : "memory");
        };
        auto emit = [&]() {
            asm volatile("stmatrix.sync.aligned.m8n8.x1.trans.shared.b16 [%0], {%1};" :: "r"(pst), "r"(pack_bf16(pn0 * rcpf(pd0), pn1 * rcpf(pd1))) : "memory");
        };
        auto carry = [&]() {
            if (rc.z & C_CONT) { pn0 += cyr.x; pd0 += cyr.y; pn1 += cyr.z; pd1 += cyr.w; }
            if (rc.z & C_MORE) { cyr = make_float4(pn0, pd0 - EPS2, pn1, pd1 - EPS2); pn0 = pn1 = 0.f; pst = tabx + tab_at(NONE); }
        };
        fetch_a();
        while (true) {
            switch (code & 15) {
                default: goto finished;
#define TILE(P) { \
                    bool ok; float dmin; \
                    do { \
                        mbar_wait_c(bar, ph); \
                        TileMMA<P>::issue(g, h, wf, xd, ed | EDHI, ohd, wcd); \
                        const uint32_t eb = bar + 8; \
                        ph ^= bar != bar0; bar = bars - bar; xd = xds - xd; ed = eds - ed; \
                          \
                        asm volatile("{\n.reg .pred p;\nsetp.eq.u32 p, %0, 77;\n@p trap;\n}" :: "r"(xds) : "memory"); \
                        emit(); rc = lds128(eb + 8 + l16); \
                        TileMMA<P>::wait_g(g); fetch_a(); TileMMA<P>::wait_h(h); \
                        mbar_arrive(eb); \
                        asm volatile("add.u32 %0, %1, %2;" : "=r"(pst) : "r"(rc.y), "r"(tabx)); \
                        ok = epi_fast<P>(g, h, __uint_as_float(rc.z), __uint_as_float(rc.w), pn0, pd0, pn1, pd1, dmin); \
                    } while (__all_sync(~0u, ok)); \
                    code = __reduce_or_sync(~0u, rc.w); \
                    if (__builtin_expect(__any_sync(~0u, ((rc.z & 0x1F00) != 0) | (dmin < TAU * 2 * P)), 0)) { \
                        int dv; \
                        const bool on = unpad(rc.z, P, g[4 * P - 4], g[4 * P - 2], pd0, pd1, dv); \
                        const uint32_t bad = __ballot_sync(~0u, on); \
                        if (__builtin_expect(bad != 0, 0)) { \
                            const float4 r = epi_exact<P>(g, h, bad, on, dv, su + SM_COPY, l16); \
                            if (on) { pn0 = r.x; pd0 = r.y; pn1 = r.z; pd1 = r.w; } \
                        } \
                    } \
                    if (code & C_BRK) { carry(); if (P != 11 && (code & 15) == P) goto L##P; } \
                    if (P == 11) {         \
                        wf[16] = lds32(wca); wf[17] = lds32(wca + 256); wf[18] = lds32(wca ^ 16); wf[19] = lds32((wca ^ 16) + 256); \
                    } }
#define CASE(P, UP, DN) case P: L##P: TILE(P) \
                    if (P > NPMIN && (code & 15) == P - 1) goto L##DN; \
                    if ((code & 15) == UP) goto L##UP; \
                    break;
                CASE(11, 11, 10) CASE(10, 11, 9) CASE(9, 10, 8) CASE(8, 9, 7) CASE(7, 8, 6) CASE(6, 7, 5) CASE(5, 6, 5)
#undef CASE
#undef TILE
            }
        }
finished:
        emit();
        __syncwarp();
        if (lane == 0) mbar_arrive(sbase + SM_ABAR + 48 + wg * 8);
    } else {
        asm volatile("setmaxnreg.dec.sync.aligned.u32 56;");
        auto x_ld = [&](int i0, int i1) {
            #pragma unroll
            for (int i = i0; i < i1; i++) w_box_ld(su + SM_XU + i * 8192, &tmx, node0 + i * 64, su + SM_ABAR + 88 + (i >> 1) * 8);
        };
        if (w < 3) {
            #pragma unroll
            for (int i = 0; i < 2; i++) { w_init(su + SM_BARS + (w * 2 + i) * STG, 64); w_init(su + SM_BARS + (w * 2 + i) * STG + 8, 128); }
            w_init(su + SM_ABAR + 48 + w * 8, 4);
            w_init(su + (w == 0 ? SM_GBAR + 99 * 8 : w == 1 ? SM_ABAR + 72 : SM_ABAR + 112), w == 0 ? 32 : 12);
        } else {
            #pragma unroll
            for (int i = 0; i < 4; i++) { w_init(su + SM_ABAR + (i < 3 ? 88 + i * 8 : 40), 1); w_expect(su + SM_ABAR + (i < 3 ? 88 + i * 8 : 40), i < 3 ? 16384 : nb * 64); }
            asm volatile("fence.mbarrier_init.release.cluster;" ::: "memory");
            w_hint(gbar + 1, all);
            asm volatile("cp.async.bulk.wait_group.read 0;" ::: "memory");
            WS(2);
            w_ld(su + SM_IDX, gs + b * (P1B + P2B), nb * (CE * 2), su + SM_ABAR + 80);
            w_ld(su + SM_H1, gs + G_H1, nb * 64, su + SM_ABAR + 120);
            asm volatile("bar.sync 12, 512;" ::: "memory");
            w_box_st(&tm2, P1B / 4 + b * CE, su + SM_P2);
            w_st(gs + G_H2 + b * 64, su + SM_P2 + P2B, 64);
            w_st(gs + G_L + b * 512 + 256, su + SM_P2 + P2B, 256);
            w_sent(gbar + 4, su + SM_MISC + 32);
            asm volatile("cp.async.bulk.commit_group;" ::: "memory");
        }
        const uint32_t ab = su + SM_ABAR;
        uint32_t todo = 0;
        const uint32_t mb = (lane & 3) == 3 ? bin_bits(b) : ~0u;
        WS(12);
        mbar_wait_c(ab + 120, 0);
        WS(13);
        {
            uint4 r[5];
            #pragma unroll
            for (int i = 0; i < 5; i++) r[i] = lds128(sbase + SM_H1 + (tid - 384 + 128 * i) * 16);
            #pragma unroll
            for (int i = 0; i < 5; i++) {
                const uint32_t bb = b << 16;
                const uint32_t m = min(min(r[i].x ^ bb, r[i].y ^ bb), min(r[i].z ^ bb, r[i].w ^ bb)) >> 16;
                if ((m == 0) | (((r[i].w ^ (tag << 14)) & 0xC000) != 0) | ((~r[i].w & mb) == 0)) todo |= 1 << i;
            }
            todo &= tid - 384 + 512 < nb * 4 ? 31 : tid - 384 + 384 < nb * 4 ? 15 : 7;
        }
        #pragma unroll 1
        for (int put = 0; put < 2; put++) {
            uint32_t any = __reduce_or_sync(~0u, todo), m = 0, u = 0;
            #pragma unroll 1
            while (any | m) {
                uint4 r = make_uint4(0, 0, 0, 0), r2 = r;
                uint32_t s, go, gd;
                bool on;
                if (__builtin_expect(m == 0, 1)) {
                    const uint32_t i = __ffs(any) - 1;
                    any &= any - 1; u = tid - 384 + 128 * i; on = (todo >> i) & 1;
                    r = lds128(sbase + SM_H1 + u * 16); r2 = lds128(sbase + SM_H2 + u * 16);
                    s = u >> 2; go = G_H1 + u * 16; gd = HB;
                } else {
                    s = ((u & ~31) + __ffs(m) - 1) >> 2; m &= m - 1; on = lane < 12;
                    go = G_L + s * 512 + 64 + lane * 16; gd = 256;
                }
                #pragma unroll 1
                for (int n = 0; n < (1 << 22); n++) {
                    const bool b1 = on && ((r.w >> 14) & 3) != tag, b2 = on && put && ((r2.w >> 16) & 3) != tag;
                    if (__builtin_expect(!__any_sync(~0u, b1 | b2), 1)) break;
                    ld_unit(r, gs + go, b1); ld_unit(r2, gs + go + gd, b2);
                }
                if (gd == HB) m = __ballot_sync(~0u, on && (~r.w & mb) == 0);
                if (on && r.w >> 16 == 255) sts32(sbase + SM_MISC + 4, 1);
                const uint32_t e[4] = {r.x, r.y, r.z, r.w}, v[4] = {r2.x, r2.y, r2.z, r2.w};
                uint32_t slot[4];
                #pragma unroll
                for (int k = 0; k < 4; k++) slot[k] = atoms_inc(sbase + SM_DEG + (on && e[k] >> 16 == (uint32_t)b ? (e[k] & 0x3FFF) : (NPB_MAX + lane) * 4));
                if (put) {
                    #pragma unroll
                    for (int k = 0; k < 4; k++) place(sbase, slot[k], v[k], s * ch);
                }
            }
            if (put == 0) {
                WS(4);
                asm volatile("bar.arrive 11, 512;" ::: "memory");
                if (w == 3) {
                    x_ld(0, 1);
                    w_expect(su + SM_ABAR, 12288); w_expect(su + SM_ABAR + 8, 12288); w_expect(su + SM_ABAR + 16, nb * (CE * 4) - 24576);
                    w_hint(gbar + 4, all);
                    asm volatile("cp.async.bulk.wait_group.read 0;" ::: "memory");
                    WS(3);
                    const char* g2 = gs + b * (P1B + P2B) + P1B;
                    w_ld(su + SM_P2, g2, 12288, su + SM_ABAR);
                    w_ld(su + SM_P2 + 12288, g2 + 12288, 12288, su + SM_ABAR + 8);
                    w_ld(su + SM_P2 + 24576, g2 + 24576, nb * (CE * 4) - 24576, su + SM_ABAR + 16);
                    w_ld(su + SM_H2, gs + G_H2, nb * 64, su + SM_ABAR + 40);
                    x_ld(1, 2);
                    mbar_wait_c(ab, 1);
                    x_ld(2, 6);
                } else {
                    #pragma unroll 11
                    for (int i = 0; i < 33; i++) w_init(su + SM_GBAR + (w * 33 + i) * 8, 32);
                    w_init(su + SM_GBAR + GD * 8, 32);
                }
                asm volatile("bar.sync 4, 512;" ::: "memory");
                mbar_wait_c(ab + 40, 0);
            }
        }
        __syncwarp();
        WS(10);
        WGD();
        const uint32_t scr = sbase + SM_PAIR + (tid & 127) * 8;
        const int r4 = lane >> 3, c8 = lane & 7;
        const uint32_t sb = su;
        const uint32_t tk = ((c8 & 1) << 4) | ((c8 >> 1) << 7);
        if (w < 3) {
            const char* gx = as_pair((const char*)x + c8 * 16, scr);
            const char* ge = as_pair((const char*)ea + (lane & 1) * 16, scr);
            const uint32_t gx0 = (uint32_t)(uint64_t)gx, ge0 = (uint32_t)(uint64_t)ge, hi = (uint64_t)gx >> 32, he = (uint64_t)ge >> 32;
            const int s = (lane >> 1) & 3;
            const uint32_t xs0 = sb + SM_XS + w * NSTAGE * XS_BYTES;
            const uint32_t es0 = sb + SM_ES + w * NSTAGE * ES_BYTES + r4 * 64 + (((lane ^ (r4 >> 1)) & 1) << 4) + (s >> 1) * 256 + (s & 1) * 32;
            const uint32_t bars = sb + SM_BARS + w * 2 * STG;
            const uint32_t xoffA = (2 * r4) * 128 + ((c8 ^ (2 * r4)) << 4);
            uint64_t pol;
            asm volatile("createpolicy.fractional.L2::evict_first.b64 %0, 1.0;" : "=l"(pol));
            asm volatile("bar.sync 6, 128;" ::: "memory");
            WS(15);
            uint32_t ph = 1, cur = w;
            uint32_t hist = GD * 0x010101u;
            auto done3 = [&]() { uint32_t v = (hist >> 16) & 0xFF; asm("" : "+r"(v)); mbar_arrive(sb + SM_GBAR + v * 8); };
            const bool go = __reduce_or_sync(~0u, misc[1] == 0 && nn > 0);
            const uint32_t ra = __shfl_sync(~0u, (lane & 15) * 16 + 32, lane), k15 = __shfl_sync(~0u, 15 | (lane & 1) << 7, lane), ca = SM_CLAIM + min(lane, 30) * 4, pa = sb + SM_TINFO + r4 * 8;
            const uint32_t pb = sb + SM_TINFO + s * 8 + 4, pc = sb + SM_TINFO + (lane & 3) * 8 + 6, xl = (lane & 8) << 1, xs = ra & 16;
            auto row_of = [&](uint32_t o) { uint32_t v; asm volatile("ld.shared.u16 %0, [%1];" : "=r"(v) : "r"(pb + o) : "memory"); return v; };
            auto code_of = [&](uint32_t o) { uint32_t v; asm volatile("ld.shared.s16 %0, [%1];" : "=r"(v) : "r"(pc + o) : "memory"); return v; };
            uint32_t pw = lds32(pa + w * 32), pt = __reduce_or_sync(~0u, pw), cont = 1;
            uint4 rc = make_uint4(0, row_of(w * 32) ^ xs, code_of(w * 32) & (ONE_F | 0x1FFFu), 0);
            const uint32_t se0 = sb + SM_EID + s * 4, brs = 2 * bars + STG;
            uint32_t br = bars, da = xs0 + xoffA, de = es0, ue = ES_BYTES;
            #pragma unroll 1
            while (go) {
                uint32_t se, sx;
                asm("dp2a.lo.u32.u32 %0, %1, 4, %2;" : "=r"(se) : "r"(pw), "r"(se0));
                asm("dp2a.lo.u32.u32 %0, %1, 2, %2;" : "=r"(sx) : "r"(pw), "r"(sb + SM_SRC));
                const int dv = pw >> 27;
                const uint32_t db = da ^ 0x90;
                const uint32_t sel = (pt >> 16) & 15, nf = (pt >> 15) & (127 << 5), nx = nf == 32 ? 0u : nf;
                uint32_t g;
                auto claim = [&]() { asm volatile("atom.shared.add.u32 %0, [%1], %2;" : "=r"(g) : "r"(ca + (nx == 0 ? sb : sb + 4)), "r"(ra) : "memory"); };
                if (sel == 0) break;
                if ((cont & 1) | (nf ^ nx)) {
                    if (cont & 1) asm volatile("bar.sync 3, 480;" ::: "memory");
                    if (nf != nx) mbar_wait_c(sb + SM_ABAR + 32, 0);
                }
                switch (sel) {
#define CASE(L, P, GEN) case L: { \
                        uint32_t oe[(P + 1) / 2], o[P]; \
                        _Pragma("unroll") for (int j = 0; j < (P + 1) / 2; j++) oe[j] = lds32(se + j * 16); \
                        _Pragma("unroll") for (int j = 0; j < P; j++) o[j] = lds32(sx + j * 4); \
                        mbar_wait_h(br + 8, ph); \
                        _Pragma("unroll") for (int j = 0; j < (P + 1) / 2; j++) \
                            if (LO32) { if (!GEN && 2 * j + 2 < P) cpe<false>(he, de + j * 512, oe[j], ge0, 0, 0, pol); \
                                else if (2 * j + 1 < NPMAX || s < 2) cpe<true>(he, de + j * 512, oe[j], ge0, 4 * j + s, dv, pol); } \
                            else if (!GEN && 2 * j + 2 < P) cp16e(de + j * 512, ge, oe[j], pol); else if (2 * j + 1 < NPMAX || s < 2) cp16z<32>(de + j * 512, ge, oe[j], 4 * j + s, dv, pol); \
                        _Pragma("unroll") for (int j = 0; j < P - 1; j++) { \
                            if (LO32) { cpx<0, GEN>(hi, da + j * 1024, o[j], gx0, 2 * j, dv); cpx<1, GEN>(hi, db + j * 1024, o[j], gx0, 2 * j + 1, dv); } \
                            else if (GEN) { cp16z<128>(da + j * 1024, gx, o[j] & 0xFFFFu, 2 * j, dv, 0); cp16z<128>(db + j * 1024, gx, o[j] >> 16, 2 * j + 1, dv, 0); } \
                            else { cp16i<128>(da + j * 1024, gx, o[j] & 0xFFFFu); cp16i<128>(db + j * 1024, gx, o[j] >> 16); } } \
                        if (LO32) { cpx<0, true>(hi, da + (P - 1) * 1024, o[P - 1], gx0, 2 * P - 2, dv); cpx<1, true>(hi, db + (P - 1) * 1024, o[P - 1], gx0, 2 * P - 1, dv); } \
                        else { cp16z<128>(da + (P - 1) * 1024, gx, o[P - 1] & 0xFFFFu, 2 * P - 2, dv, 0); cp16z<128>(db + (P - 1) * 1024, gx, o[P - 1] >> 16, 2 * P - 1, dv, 0); } \
                    } break;
                    CASE(11, 11, false) CASE(6, 6, false) CASE(7, 7, false) CASE(8, 8, false) CASE(9, 9, false) CASE(10, 10, false)
                    CASE(15, NPMAX, true) CASE(14, 8, true) default: CASE(13, 5, true)
#undef CASE
                }
                claim();
                mbar_cp_arrive(br);
                done3();
                g = __reduce_min_sync(~0u, g);
                {
                    const uint32_t o = nx == 0 ? g : nx;
                    pw = lds32(pa + o);
                    const uint32_t ya = row_of(o), yb = code_of(o);
                    pt = __reduce_or_sync(~0u, pw);
                    const uint32_t brk = (cont | nx) > 1 ? C_BRK : 0u;
                    rc.x = ya ^ xl;
                    const uint32_t lv = brk | ((sel + (15 - NPMAX)) & 16) | (((pt >> 16) & 15) ^ sel);
                    rc.w = (yb & k15) | (lv ? 0x70000000u | brk : TAU_BITS);
                    asm volatile("st.shared.v4.u32 [%2], {%3, %0, %1, %4};\nxor.b32 %0, %5, %6;\nand.b32 %1, %7, %8;"
                                 : "+r"(rc.y), "+r"(rc.z) : "r"(br + ra - 16), "r"(rc.x), "r"(rc.w), "r"(ya), "r"(xs), "r"(yb), "n"(ONE_F | 0x1FFFu) : "memory");
                    cont = nx;
                }
                mbar_arrive(br);
                hist = (hist << 8) | (nx == 0 ? cur : (uint32_t)GD);
                cur = nx == 0 ? g >> 5 : cur;
                da += ue * 4; de += ue; ue = -ue;
                ph ^= br != bars; br = brs - br;
            }
            if (cont & 1) asm volatile("bar.sync 3, 480;" ::: "memory");
            if (go) {
                mbar_wait(sb + SM_ABAR + 32, 0);
                const int g0 = 3 * max((misc[7] + 2) / 3 - TR, 0) + w;
                uint32_t ro[TR], gb[TR]; uint4 xv[TR], xu[TR]; char* op[TR];
                const int gz = misc[4];
                #pragma unroll
                for (int k = 0; k < TR; k++) {
                    uint32_t nd;
                    asm volatile("ld.shared.u16 %0, [%1];" : "=r"(nd) : "r"(pa + (g0 + 3 * k) * 32 + 4) : "memory");
                    uint32_t rb = node0 * 128 + row_bytes(nd);
                    if (g0 + 3 * k >= ngroups) rb = misc[16 + ((g0 + 3 * k - ngroups) & 3) * 4 + r4];
                    if (nd == tab_at(NONE)) rb = 0;
                    xv[k] = __ldg((const uint4*)(gx + rb));
                    op[k] = nd == tab_at(NONE) ? nullptr : (char*)out + rb + c8 * 16;
                    ro[k] = sb + (nd ^ tk);
                    xu[k] = lds128(ro[k] + SM_XU);
                    gb[k] = __reduce_or_sync(~0u, g0 + 3 * k < gz ? sb + SM_GBAR + (g0 + 3 * k) * 8 : 0u);
                }
                #pragma unroll 1
                for (int k = 0; k < 3; k++) {
                    mbar_wait(k < 2 ? br + 8 : sb + SM_ABAR + 48 + w * 8, k < 2 ? ph : 0);
                    done3(); hist <<= 8;
                    ph ^= br != bars; br = brs - br;
                }
                #pragma unroll
                for (int k = 0; k < TR; k++) {
                    uint4 a = make_uint4(0, 0, 0, 0);
                    if (gb[k]) { mbar_wait(gb[k], 0); a = lds128(ro[k] + SM_TAB); }
                    finish(a, xu[k], xv[k]);
                    if (op[k]) *(uint4*)op[k] = a;
                }
            }
            cp_wait<0>();
        } else {
            const int r4 = (lane >> 1) & 3, c8 = (lane >> 3) * 2 + (lane & 1);
            const uint32_t tk = ((c8 & 1) << 4) | ((c8 >> 1) << 7);
            const char* gx = as_pair((const char*)x + (size_t)node0 * 128 + c8 * 16, scr);
            const char* ob = as_pair((const char*)out + (size_t)node0 * 128 + c8 * 16, scr);
            asm volatile("bar.sync 6, 128;" ::: "memory");
            WS(15);
            if (b == 0 && lane == 0) asm volatile("red.relaxed.gpu.global.add.u32 [%0], 1;" :: "l"(gbar) : "memory");
            if (misc[1] == 0) mbar_wait(sb + SM_ABAR + 72, 0);
            if (npb <= NPB_MAX - 4) sts32(sb + SM_MISC + 12, 0);
            int rounds = misc[1] ? 0 : max((ngroups + 2) / 3 - TR, 0);
            const int gz = misc[4];
            int fast = __reduce_min_sync(~0u, min(rounds, gz / 3));
            const uint32_t wl = SM_TINFO + r4 * 8 + 4;
            uint32_t ko = sb;
            auto row_at = [&](uint32_t a) { uint32_t n; asm volatile("ld.shared.u16 %0, [%1];" : "=r"(n) : "r"(a) : "memory"); return n; };
            auto fetch = [&](uint32_t n, uint4& v) {
                asm volatile("{\n.reg .b64 p;\ncvt.u64.u32 p, %5;\nadd.u64 p, p, %4;\nld.global.nc.L1::no_allocate.v4.u32 {%0,%1,%2,%3}, [p];\n}"
                             : "=r"(v.x), "=r"(v.y), "=r"(v.z), "=r"(v.w) : "l"(gx), "r"(n));
            };
            auto store = [&](uint32_t n, const uint4& a) {
                asm volatile("{\n.reg .b64 p;\ncvt.u64.u32 p, %1;\nadd.u64 p, p, %0;\nst.global.v4.u32 [p], {%2,%3,%4,%5};\n}" :: "l"(ob), "r"(n), "r"(a.x), "r"(a.y), "r"(a.z), "r"(a.w) : "memory");
            };
            const uint32_t tw = __shfl_sync(~0u, tk, lane);
            int step = fast > R3 + PMIN && gz == ngroups ? -1 : -2, k = 0;
            #pragma unroll 1
            do {
                const int gn = __reduce_max_sync(~0u, balance(step, gs, all, ngroups, npb));
                if (step == R3) fast = rounds = (gn + 2) / 3 - TR;
                const bool pub = step < 0 && gn;
                step = gn == 0 || step == R3 ? fast - 1 : step < 0 ? R2 : R3;
                const uint32_t lim = step == fast - 1 ? ~0u : (ngroups - (KM + 3)) * 32;
                if (fast == 0) break;
                uint32_t n0[3], o0[3]; uint4 x0[3];
                #pragma unroll
                for (int r = 0; r < 3; r++) { const uint32_t v = row_at(wl + ko + r * 32); n0[r] = row_bytes(v); o0[r] = v ^ tw; fetch(n0[r], x0[r]); }
                #pragma unroll 1
                for (; k <= step; k++) {
                    const uint32_t wn = k < step ? ko + 96 : ko, gbar = sb + SM_GBAR + k * 24;
                    uint4 xu[3], a[3]; uint32_t v[3], ok;
                    #pragma unroll
                    for (int r = 0; r < 3; r++) { xu[r] = lds128(sb + o0[r] + SM_XU); v[r] = row_at(wl + wn + r * 32); }
#define TRY(o) "mbarrier.try_wait.parity.shared.b64 p, [%1 + " o "], 0, 4000;\n@p bra A_%=;\n"
#define NEXT(o) TRY(o) TRY(o) TRY(o) "bra B_%=;\n"
                    asm volatile("{\n.reg .pred p, q, r;\n.reg .b32 c, n;\nmov.u32 n, 0;\n"
                                 "A_%=:\nmbarrier.test_wait.parity.shared.b64 p, [%1], 0;\nmbarrier.test_wait.parity.shared.b64 q, [%1 + 8], 0;\nmbarrier.test_wait.parity.shared.b64 r, [%1 + 16], 0;\n"
                                 "@!r bra W2_%=;\n@!q bra W1_%=;\n@p bra D_%=;\n"
                                 NEXT("0") "W1_%=:\n" NEXT("8") "W2_%=:\n" NEXT("16")
                                 "B_%=:\nld.volatile.shared.u32 c, [%2];\nadd.u32 n, n, 1;\nsetp.gt.u32 q, n, 0x100000;\n@q trap;\nsetp.le.u32 q, c, %3;\n@q bra A_%=;\n"
                                 "D_%=:\nselp.u32 %0, 1, 0, p;\n}" : "=r"(ok) : "r"(gbar), "r"(sb + SM_CLAIM), "r"(lim) : "memory");
#undef NEXT
#undef TRY
                    if (!ok) break;
                    #pragma unroll
                    for (int r = 0; r < 3; r++) a[r] = lds128(sb + o0[r] + SM_TAB);
                    #pragma unroll
                    for (int r = 0; r < 3; r++) {
                        finish(a[r], xu[r], x0[r]);
                        const uint32_t nd = n0[r];
                        n0[r] = row_bytes(v[r]); o0[r] = v[r] ^ tw;
                        fetch(n0[r], x0[r]);
                        store(nd, a[r]);
                    }
                    ko += 96;
                    if (pub && k == R1) {
                        uint32_t now; asm volatile("mov.u32 %0, %%globaltimer_lo;" : "=r"(now));
                        now = __reduce_max_sync(~0u, (((now + lds32(sb + SM_MISC + 48)) << 6) & ~511u) | 256);
                        sts32(sb + SM_MISC + 48, now);
                        asm volatile(ELECT "st.relaxed.gpu.global.v2.u32 [%0], {%1, %2};\n}" :: "l"(gs + G_F + b * 8), "r"(now), "r"(all) : "memory");
                    }
                }
                if (k <= R1) step = -2;
            } while (k < fast);
            #pragma unroll 1
            for (int g = 3 * fast; g < 3 * rounds; g++) {
                const uint32_t v = row_at(sb + SM_TINFO + r4 * 8 + 4 + g * 32), nd = row_bytes(v), ro = sb + (v ^ tw);
                uint4 xv, a = make_uint4(0, 0, 0, 0);
                fetch(nd, xv);
                if (g < gz) { mbar_wait(sb + SM_GBAR + g * 8, 0); a = lds128(ro + SM_TAB); }
                finish(a, lds128(ro + SM_XU), xv);
                store(nd, a);
            }
        }
    }
    WS(17); WG1(); CG(2);
}

}

extern "C" void kernel_launch(void* const* d_in, const int* in_sizes, int n_in, void* d_out, int out_size) {
    const __nv_bfloat16* x = (const __nv_bfloat16*)d_in[0];
    const __nv_bfloat16* ea = (const __nv_bfloat16*)d_in[1];
    const int* src = (const int*)d_in[2];
    const int* dst = (const int*)d_in[3];
    const __nv_bfloat16* wa = (const __nv_bfloat16*)d_in[4];
    const __nv_bfloat16* wb = (const __nv_bfloat16*)d_in[5];
    const __nv_bfloat16* wc = (const __nv_bfloat16*)d_in[6];
    const __nv_bfloat16* wu = (const __nv_bfloat16*)d_in[7];
    const __nv_bfloat16* wv = (const __nv_bfloat16*)d_in[8];
    __nv_bfloat16* out = (__nv_bfloat16*)d_out;
    int N = in_sizes[0] / 64, E = in_sizes[2];
    static int sms = 0;
    static CUtensorMap tm1, tm2, tmw, tmx;
    static bool tm_ok = false;
    static void* gp = nullptr; static void* gb = nullptr;
    typedef CUresult (*EncFn)(CUtensorMap*, CUtensorMapDataType, cuuint32_t, void*, const cuuint64_t*, const cuuint64_t*, const cuuint32_t*,
                              const cuuint32_t*, CUtensorMapInterleave, CUtensorMapSwizzle, CUtensorMapL2promotion, CUtensorMapFloatOOBfill);
    static void* fn = nullptr;
    auto enc = [&](CUtensorMap* tm, const void* base, cuuint64_t cols, cuuint64_t rows, cuuint32_t bc, cuuint32_t br, CUtensorMapSwizzle sw) {
        cuuint64_t g2[2] = {cols, rows}, gs[1] = {cols * 4};
        cuuint32_t b2[2] = {bc, br}, es[2] = {1, 1};
        return ((EncFn)fn)(tm, CU_TENSOR_MAP_DATA_TYPE_UINT32, 2, (void*)base, g2, gs, b2, es, CU_TENSOR_MAP_INTERLEAVE_NONE, sw,
                           CU_TENSOR_MAP_L2_PROMOTION_NONE, CU_TENSOR_MAP_FLOAT_OOB_FILL_NONE) == CUDA_SUCCESS;
    };
    if (!sms) {
        cudaDeviceGetAttribute(&sms, cudaDevAttrMultiProcessorCount, 0);
        cudaDriverEntryPointQueryResult qr;
        cudaGetDriverEntryPoint("cuTensorMapEncodeTiled", &fn, cudaEnableDefault, &qr);
        cudaGetSymbolAddress(&gp, g_str); cudaGetSymbolAddress(&gb, g_bar);
        if (fn && gp && gb) {
            const cuuint32_t rows = sms < NB_MAX ? sms : NB_MAX;
            tm_ok = enc(&tm1, gp, (P1B + P2B) / 4, NB_MAX, CE / 2, rows, CU_TENSOR_MAP_SWIZZLE_NONE) && enc(&tm2, gp, (P1B + P2B) / 4, NB_MAX, CE, rows, CU_TENSOR_MAP_SWIZZLE_NONE);
        }
        cudaFuncSetAttribute(gcn_kernel<true>, cudaFuncAttributeMaxDynamicSharedMemorySize, SMEM_LAUNCH);
        cudaFuncSetAttribute(gcn_kernel<false>, cudaFuncAttributeMaxDynamicSharedMemorySize, SMEM_LAUNCH);
    }
    int nb = sms < NB_MAX ? sms : NB_MAX;
    int npb = (N + nb - 1) / nb;
    int ch = (((E + nb - 1) / nb) + 3) & ~3;
    const uintptr_t wp[4] = {(uintptr_t)wb, (uintptr_t)wv, (uintptr_t)wa, (uintptr_t)wu};
    uintptr_t wlo = wp[0], whi = wp[0], wal = 0;
    for (int i = 0; i < 4; i++) { wlo = wp[i] < wlo ? wp[i] : wlo; whi = wp[i] > whi ? wp[i] : whi; wal |= wp[i] - wp[0]; }
    bool ok = tm_ok && nb >= NB_MIN && npb < NPB_MAX && ch <= CH_MAX && !(E & 3) && N <= 65535 && npb >= 2 && !(wal & 127) && (whi - wlo) >> 7 < (1u << 30) &&
              !(((uintptr_t)src | (uintptr_t)dst | (uintptr_t)x | (uintptr_t)wb | (uintptr_t)wc) & 15);
    ok = ok && enc(&tmw, (const void*)wlo, 32, ((whi - wlo) >> 7) + 64, 32, 64, CU_TENSOR_MAP_SWIZZLE_128B) && enc(&tmx, x, 32, N, 32, 64, CU_TENSOR_MAP_SWIZZLE_128B);
    if (!ok) {
        int g = 1024, p = (N + g - 1) / g;
        slow_kernel<<<g, 256>>>(x, ea, src, dst, wa, wb, wc, wu, wv, out, N, E, p < 1 ? 1 : p);
        return;
    }
    int4 wrow = make_int4((int)((wp[0] - wlo) >> 7), (int)((wp[1] - wlo) >> 7), (int)((wp[2] - wlo) >> 7), (int)((wp[3] - wlo) >> 7));
    uint32_t magic = (uint32_t)((1ull << 32) / (uint32_t)npb) + 1u;
    void* args[] = {&dst, &gb, &gp, &src, &E, &ch, &N, &npb, &magic, &x, &ea, &wa, &wb, &wc, &wu, &wv, &out, &wrow, &tm1, &tm2, &tmw, &tmx};
    const bool lo32 = ((uintptr_t)x >> 32) == (((uintptr_t)x + (size_t)N * 128 - 1) >> 32) && ((uintptr_t)ea >> 32) == (((uintptr_t)ea + (size_t)E * 32 - 1) >> 32);
    cudaLaunchCooperativeKernel(lo32 && !FORCE64 ? (const void*)gcn_kernel<true> : (const void*)gcn_kernel<false>, dim3(nb), dim3(THREADS), args, SMEM_LAUNCH, cudaStreamPerThread);
}
```

```cpp
#include <cuda_runtime.h>
#include <cuda.h>
#include <cuda_bf16.h>
#include <stdint.h>

namespace {

constexpr int N_MAX = 65536;
constexpr int NPMAX = 11;
constexpr int NPMIN = 5;
constexpr int THREADS = 512;
constexpr int EPT = 12;
constexpr int CH_MAX = THREADS * EPT;
constexpr int NB_MAX = 134, NB_MIN = 120;
constexpr int CE = 64;
constexpr int P1B = NB_MAX * CE * 2;
constexpr int P2B = NB_MAX * CE * 4;
constexpr int HB = NB_MAX * 64;
constexpr int G_H1 = NB_MAX * (P1B + P2B), G_H2 = G_H1 + HB, G_L = G_H2 + HB, G_F = G_L + NB_MAX * 512;
constexpr int KM = 4, GRP_B = 1536, G_R = G_F + 2048, G_P = G_R + 2048, G_END = G_P + NB_MAX * KM * GRP_B;
#define BAL 1
#define PMIN 8
constexpr int R1 = 9, R2 = 11, R3 = 14;
constexpr int GD = 100;
constexpr int NPB_MAX = 384;
constexpr int SLOT_CAP = 6784;
constexpr int TILE_CAP = 123;
constexpr int TILE_X = 8;
constexpr int NCLS = 64;
constexpr int NSTAGE = 2;
constexpr int PD = 300;
constexpr int TR = 2;
constexpr float LOG2E = 1.4426950408889634f;

__device__ __align__(256) uint4 g_str[G_END / 16];
__device__ __align__(128) unsigned g_bar[8];
__device__ float g_slow[N_MAX * 128];
__device__ float4 g_copy[NB_MAX * 384 * 2 * NPMAX];

#define WS(k)
#define WGD()
#define WG0()
#define WG1()
#define CG(k)
#define SMEM_LAUNCH SMEM_BYTES
#define FORCE64 0
#define EDHI ((16ull << 32) | (3ull << 62))
template<int NP> struct TileMMA;
template<> struct TileMMA<5> {
  static __device__ __forceinline__ void issue(float* g, float* h, const uint32_t* w, uint32_t dx, uint64_t de, uint64_t dh, uint64_t dc) {
    asm volatile(
      "{\n.reg .b64 dx0, dx1, dx2, dx3;\n.reg .b32 l1, l2, l3, hx;\nmov.b32 hx, 0x40000040;\n"
      "add.u32 l1, %80, 2;\nadd.u32 l2, %80, 4;\nadd.u32 l3, %80, 6;\n"
      "mov.b64 dx0, {%80, hx};\nmov.b64 dx1, {l1, hx};\nmov.b64 dx2, {l2, hx};\nmov.b64 dx3, {l3, hx};\n"
      "wgmma.fence.sync.aligned;\n"
      "wgmma.mma_async.sync.aligned.m64n40k16.f32.bf16.bf16 {%0, %1, %2, %3, %4, %5, %6, %7, %8, %9, %10, %11, %12, %13, %14, %15, %16, %17, %18, %19}, {%76, %77, %78, %79}, %82, 0, 1, 1, 0;\n"
      "wgmma.mma_async.sync.aligned.m64n40k16.f32.bf16.bf16 {%0, %1, %2, %3, %4, %5, %6, %7, %8, %9, %10, %11, %12, %13, %14, %15, %16, %17, %18, %19}, {%56, %57, %58, %59}, %81, 1, 1, 1, 0;\n"
      "wgmma.mma_async.sync.aligned.m64n40k16.f32.bf16.bf16 {%0, %1, %2, %3, %4, %5, %6, %7, %8, %9, %10, %11, %12, %13, %14, %15, %16, %17, %18, %19}, {%40, %41, %42, %43}, dx0, 1, 1, 1, 0;\n"
      "wgmma.mma_async.sync.aligned.m64n40k16.f32.bf16.bf16 {%0, %1, %2, %3, %4, %5, %6, %7, %8, %9, %10, %11, %12, %13, %14, %15, %16, %17, %18, %19}, {%44, %45, %46, %47}, dx1, 1, 1, 1, 0;\n"
      "wgmma.mma_async.sync.aligned.m64n40k16.f32.bf16.bf16 {%0, %1, %2, %3, %4, %5, %6, %7, %8, %9, %10, %11, %12, %13, %14, %15, %16, %17, %18, %19}, {%48, %49, %50, %51}, dx2, 1, 1, 1, 0;\n"
      "wgmma.mma_async.sync.aligned.m64n40k16.f32.bf16.bf16 {%0, %1, %2, %3, %4, %5, %6, %7, %8, %9, %10, %11, %12, %13, %14, %15, %16, %17, %18, %19}, {%52, %53, %54, %55}, dx3, 1, 1, 1, 0;\n"
      "wgmma.commit_group.sync.aligned;\n"
      "wgmma.mma_async.sync.aligned.m64n40k16.f32.bf16.bf16 {%20, %21, %22, %23, %24, %25, %26, %27, %28, %29, %30, %31, %32, %33, %34, %35, %36, %37, %38, %39}, {%60, %61, %62, %63}, dx0, 0, 1, 1, 0;\n"
      "wgmma.mma_async.sync.aligned.m64n40k16.f32.bf16.bf16 {%20, %21, %22, %23, %24, %25, %26, %27, %28, %29, %30, %31, %32, %33, %34, %35, %36, %37, %38, %39}, {%64, %65, %66, %67}, dx1, 1, 1, 1, 0;\n"
      "wgmma.mma_async.sync.aligned.m64n40k16.f32.bf16.bf16 {%20, %21, %22, %23, %24, %25, %26, %27, %28, %29, %30, %31, %32, %33, %34, %35, %36, %37, %38, %39}, {%68, %69, %70, %71}, dx2, 1, 1, 1, 0;\n"
      "wgmma.mma_async.sync.aligned.m64n40k16.f32.bf16.bf16 {%20, %21, %22, %23, %24, %25, %26, %27, %28, %29, %30, %31, %32, %33, %34, %35, %36, %37, %38, %39}, {%72, %73, %74, %75}, dx3, 1, 1, 1, 0;\n"
      "wgmma.commit_group.sync.aligned;\n}\n"
      : "=f"(g[0]), "=f"(g[1]), "=f"(g[2]), "=f"(g[3]), "=f"(g[4]), "=f"(g[5]), "=f"(g[6]), "=f"(g[7]), "=f"(g[8]), "=f"(g[9]), "=f"(g[10]), "=f"(g[11]), "=f"(g[12]), "=f"(g[13]), "=f"(g[14]), "=f"(g[15]), "=f"(g[16]), "=f"(g[17]), "=f"(g[18]), "=f"(g[19]),
        "=f"(h[0]), "=f"(h[1]), "=f"(h[2]), "=f"(h[3]), "=f"(h[4]), "=f"(h[5]), "=f"(h[6]), "=f"(h[7]), "=f"(h[8]), "=f"(h[9]), "=f"(h[10]), "=f"(h[11]), "=f"(h[12]), "=f"(h[13]), "=f"(h[14]), "=f"(h[15]), "=f"(h[16]), "=f"(h[17]), "=f"(h[18]), "=f"(h[19])
      : "r"(w[0]), "r"(w[1]), "r"(w[2]), "r"(w[3]), "r"(w[4]), "r"(w[5]), "r"(w[6]), "r"(w[7]), "r"(w[8]), "r"(w[9]), "r"(w[10]), "r"(w[11]), "r"(w[12]), "r"(w[13]), "r"(w[14]), "r"(w[15]), "r"(w[16]), "r"(w[17]), "r"(w[18]), "r"(w[19]), "r"(w[20]), "r"(w[21]), "r"(w[22]), "r"(w[23]), "r"(w[24]), "r"(w[25]), "r"(w[26]), "r"(w[27]), "r"(w[28]), "r"(w[29]), "r"(w[30]), "r"(w[31]), "r"(w[32]), "r"(w[33]), "r"(w[34]), "r"(w[35]), "r"(w[36]), "r"(w[37]), "r"(w[38]), "r"(w[39]), "r"(dx), "l"(de), "l"(dh)
      : "memory");
  }
  static __device__ __forceinline__ void wait_g(float* g) {
    asm volatile("wgmma.wait_group.sync.aligned 1;\n"
      : "+f"(g[0]), "+f"(g[1]), "+f"(g[2]), "+f"(g[3]), "+f"(g[4]), "+f"(g[5]), "+f"(g[6]), "+f"(g[7]), "+f"(g[8]), "+f"(g[9]), "+f"(g[10]), "+f"(g[11]), "+f"(g[12]), "+f"(g[13]), "+f"(g[14]), "+f"(g[15]), "+f"(g[16]), "+f"(g[17]), "+f"(g[18]), "+f"(g[19])
      :: "memory");
  }
  static __device__ __forceinline__ void wait_h(float* h) {
    asm volatile("wgmma.wait_group.sync.aligned 0;\n"
      : "+f"(h[0]), "+f"(h[1]), "+f"(h[2]), "+f"(h[3]), "+f"(h[4]), "+f"(h[5]), "+f"(h[6]), "+f"(h[7]), "+f"(h[8]), "+f"(h[9]), "+f"(h[10]), "+f"(h[11]), "+f"(h[12]), "+f"(h[13]), "+f"(h[14]), "+f"(h[15]), "+f"(h[16]), "+f"(h[17]), "+f"(h[18]), "+f"(h[19])
      :: "memory");
  }
};
template<> struct TileMMA<6> {
  static __device__ __forceinline__ void issue(float* g, float* h, const uint32_t* w, uint32_t dx, uint64_t de, uint64_t dh, uint64_t dc) {
    asm volatile(
      "{\n.reg .b64 dx0, dx1, dx2, dx3;\n.reg .b32 l1, l2, l3, hx;\nmov.b32 hx, 0x40000040;\n"
      "add.u32 l1, %88, 2;\nadd.u32 l2, %88, 4;\nadd.u32 l3, %88, 6;\n"
      "mov.b64 dx0, {%88, hx};\nmov.b64 dx1, {l1, hx};\nmov.b64 dx2, {l2, hx};\nmov.b64 dx3, {l3, hx};\n"
      "wgmma.fence.sync.aligned;\n"
      "wgmma.mma_async.sync.aligned.m64n48k16.f32.bf16.bf16 {%0, %1, %2, %3, %4, %5, %6, %7, %8, %9, %10, %11, %12, %13, %14, %15, %16, %17, %18, %19, %20, %21, %22, %23}, {%84, %85, %86, %87}, %90, 0, 1, 1, 0;\n"
      "wgmma.mma_async.sync.aligned.m64n48k16.f32.bf16.bf16 {%0, %1, %2, %3, %4, %5, %6, %7, %8, %9, %10, %11, %12, %13, %14, %15, %16, %17, %18, %19, %20, %21, %22, %23}, {%64, %65, %66, %67}, %89, 1, 1, 1, 0;\n"
      "wgmma.mma_async.sync.aligned.m64n48k16.f32.bf16.bf16 {%0, %1, %2, %3, %4, %5, %6, %7, %8, %9, %10, %11, %12, %13, %14, %15, %16, %17, %18, %19, %20, %21, %22, %23}, {%48, %49, %50, %51}, dx0, 1, 1, 1, 0;\n"
      "wgmma.mma_async.sync.aligned.m64n48k16.f32.bf16.bf16 {%0, %1, %2, %3, %4, %5, %6, %7, %8, %9, %10, %11, %12, %13, %14, %15, %16, %17, %18, %19, %20, %21, %22, %23}, {%52, %53, %54, %55}, dx1, 1, 1, 1, 0;\n"
      "wgmma.mma_async.sync.aligned.m64n48k16.f32.bf16.bf16 {%0, %1, %2, %3, %4, %5, %6, %7, %8, %9, %10, %11, %12, %13, %14, %15, %16, %17, %18, %19, %20, %21, %22, %23}, {%56, %57, %58, %59}, dx2, 1, 1, 1, 0;\n"
      "wgmma.mma_async.sync.aligned.m64n48k16.f32.bf16.bf16 {%0, %1, %2, %3, %4, %5, %6, %7, %8, %9, %10, %11, %12, %13, %14, %15, %16, %17, %18, %19, %20, %21, %22, %23}, {%60, %61, %62, %63}, dx3, 1, 1, 1, 0;\n"
      "wgmma.commit_group.sync.aligned;\n"
      "wgmma.mma_async.sync.aligned.m64n48k16.f32.bf16.bf16 {%24, %25, %26, %27, %28, %29, %30, %31, %32, %33, %34, %35, %36, %37, %38, %39, %40, %41, %42, %43, %44, %45, %46, %47}, {%68, %69, %70, %71}, dx0, 0, 1, 1, 0;\n"
      "wgmma.mma_async.sync.aligned.m64n48k16.f32.bf16.bf16 {%24, %25, %26, %27, %28, %29, %30, %31, %32, %33, %34, %35, %36, %37, %38, %39, %40, %41, %42, %43, %44, %45, %46, %47}, {%72, %73, %74, %75}, dx1, 1, 1, 1, 0;\n"
      "wgmma.mma_async.sync.aligned.m64n48k16.f32.bf16.bf16 {%24, %25, %26, %27, %28, %29, %30, %31, %32, %33, %34, %35, %36, %37, %38, %39, %40, %41, %42, %43, %44, %45, %46, %47}, {%76, %77, %78, %79}, dx2, 1, 1, 1, 0;\n"
      "wgmma.mma_async.sync.aligned.m64n48k16.f32.bf16.bf16 {%24, %25, %26, %27, %28, %29, %30, %31, %32, %33, %34, %35, %36, %37, %38, %39, %40, %41, %42, %43, %44, %45, %46, %47}, {%80, %81, %82, %83}, dx3, 1, 1, 1, 0;\n"
      "wgmma.commit_group.sync.aligned;\n}\n"
      : "=f"(g[0]), "=f"(g[1]), "=f"(g[2]), "=f"(g[3]), "=f"(g[4]), "=f"(g[5]), "=f"(g[6]), "=f"(g[7]), "=f"(g[8]), "=f"(g[9]), "=f"(g[10]), "=f"(g[11]), "=f"(g[12]), "=f"(g[13]), "=f"(g[14]), "=f"(g[15]), "=f"(g[16]), "=f"(g[17]), "=f"(g[18]), "=f"(g[19]), "=f"(g[20]), "=f"(g[21]), "=f"(g[22]), "=f"(g[23]),
        "=f"(h[0]), "=f"(h[1]), "=f"(h[2]), "=f"(h[3]), "=f"(h[4]), "=f"(h[5]), "=f"(h[6]), "=f"(h[7]), "=f"(h[8]), "=f"(h[9]), "=f"(h[10]), "=f"(h[11]), "=f"(h[12]), "=f"(h[13]), "=f"(h[14]), "=f"(h[15]), "=f"(h[16]), "=f"(h[17]), "=f"(h[18]), "=f"(h[19]), "=f"(h[20]), "=f"(h[21]), "=f"(h[22]), "=f"(h[23])
      : "r"(w[0]), "r"(w[1]), "r"(w[2]), "r"(w[3]), "r"(w[4]), "r"(w[5]), "r"(w[6]), "r"(w[7]), "r"(w[8]), "r"(w[9]), "r"(w[10]), "r"(w[11]), "r"(w[12]), "r"(w[13]), "r"(w[14]), "r"(w[15]), "r"(w[16]), "r"(w[17]), "r"(w[18]), "r"(w[19]), "r"(w[20]), "r"(w[21]), "r"(w[22]), "r"(w[23]), "r"(w[24]), "r"(w[25]), "r"(w[26]), "r"(w[27]), "r"(w[28]), "r"(w[29]), "r"(w[30]), "r"(w[31]), "r"(w[32]), "r"(w[33]), "r"(w[34]), "r"(w[35]), "r"(w[36]), "r"(w[37]), "r"(w[38]), "r"(w[39]), "r"(dx), "l"(de), "l"(dh)
      : "memory");
  }
  static __device__ __forceinline__ void wait_g(float* g) {
    asm volatile("wgmma.wait_group.sync.aligned 1;\n"
      : "+f"(g[0]), "+f"(g[1]), "+f"(g[2]), "+f"(g[3]), "+f"(g[4]), "+f"(g[5]), "+f"(g[6]), "+f"(g[7]), "+f"(g[8]), "+f"(g[9]), "+f"(g[10]), "+f"(g[11]), "+f"(g[12]), "+f"(g[13]), "+f"(g[14]), "+f"(g[15]), "+f"(g[16]), "+f"(g[17]), "+f"(g[18]), "+f"(g[19]), "+f"(g[20]), "+f"(g[21]), "+f"(g[22]), "+f"(g[23])
      :: "memory");
  }
  static __device__ __forceinline__ void wait_h(float* h) {
    asm volatile("wgmma.wait_group.sync.aligned 0;\n"
      : "+f"(h[0]), "+f"(h[1]), "+f"(h[2]), "+f"(h[3]), "+f"(h[4]), "+f"(h[5]), "+f"(h[6]), "+f"(h[7]), "+f"(h[8]), "+f"(h[9]), "+f"(h[10]), "+f"(h[11]), "+f"(h[12]), "+f"(h[13]), "+f"(h[14]), "+f"(h[15]), "+f"(h[16]), "+f"(h[17]), "+f"(h[18]), "+f"(h[19]), "+f"(h[20]), "+f"(h[21]), "+f"(h[22]), "+f"(h[23])
      :: "memory");
  }
};
template<> struct TileMMA<7> {
  static __device__ __forceinline__ void issue(float* g, float* h, const uint32_t* w, uint32_t dx, uint64_t de, uint64_t dh, uint64_t dc) {
    asm volatile(
      "{\n.reg .b64 dx0, dx1, dx2, dx3;\n.reg .b32 l1, l2, l3, hx;\nmov.b32 hx, 0x40000040;\n"
      "add.u32 l1, %96, 2;\nadd.u32 l2, %96, 4;\nadd.u32 l3, %96, 6;\n"
      "mov.b64 dx0, {%96, hx};\nmov.b64 dx1, {l1, hx};\nmov.b64 dx2, {l2, hx};\nmov.b64 dx3, {l3, hx};\n"
      "wgmma.fence.sync.aligned;\n"
      "wgmma.mma_async.sync.aligned.m64n56k16.f32.bf16.bf16 {%0, %1, %2, %3, %4, %5, %6, %7, %8, %9, %10, %11, %12, %13, %14, %15, %16, %17, %18, %19, %20, %21, %22, %23, %24, %25, %26, %27}, {%92, %93, %94, %95}, %98, 0, 1, 1, 0;\n"
      "wgmma.mma_async.sync.aligned.m64n56k16.f32.bf16.bf16 {%0, %1, %2, %3, %4, %5, %6, %7, %8, %9, %10, %11, %12, %13, %14, %15, %16, %17, %18, %19, %20, %21, %22, %23, %24, %25, %26, %27}, {%72, %73, %74, %75}, %97, 1, 1, 1, 0;\n"
      "wgmma.mma_async.sync.aligned.m64n56k16.f32.bf16.bf16 {%0, %1, %2, %3, %4, %5, %6, %7, %8, %9, %10, %11, %12, %13, %14, %15, %16, %17, %18, %19, %20, %21, %22, %23, %24, %25, %26, %27}, {%56, %57, %58, %59}, dx0, 1, 1, 1, 0;\n"
      "wgmma.mma_async.sync.aligned.m64n56k16.f32.bf16.bf16 {%0, %1, %2, %3, %4, %5, %6, %7, %8, %9, %10, %11, %12, %13, %14, %15, %16, %17, %18, %19, %20, %21, %22, %23, %24, %25, %26, %27}, {%60, %61, %62, %63}, dx1, 1, 1, 1, 0;\n"
      "wgmma.mma_async.sync.aligned.m64n56k16.f32.bf16.bf16 {%0, %1, %2, %3, %4, %5, %6, %7, %8, %9, %10, %11, %12, %13, %14, %15, %16, %17, %18, %19, %20, %21, %22, %23, %24, %25, %26, %27}, {%64, %65, %66, %67}, dx2, 1, 1, 1, 0;\n"
      "wgmma.mma_async.sync.aligned.m64n56k16.f32.bf16.bf16 {%0, %1, %2, %3, %4, %5, %6, %7, %8, %9, %10, %11, %12, %13, %14, %15, %16, %17, %18, %19, %20, %21, %22, %23, %24, %25, %26, %27}, {%68, %69, %70, %71}, dx3, 1, 1, 1, 0;\n"
      "wgmma.commit_group.sync.aligned;\n"
      "wgmma.mma_async.sync.aligned.m64n56k16.f32.bf16.bf16 {%28, %29, %30, %31, %32, %33, %34, %35, %36, %37, %38, %39, %40, %41, %42, %43, %44, %45, %46, %47, %48, %49, %50, %51, %52, %53, %54, %55}, {%76, %77, %78, %79}, dx0, 0, 1, 1, 0;\n"
      "wgmma.mma_async.sync.aligned.m64n56k16.f32.bf16.bf16 {%28, %29, %30, %31, %32, %33, %34, %35, %36, %37, %38, %39, %40, %41, %42, %43, %44, %45, %46, %47, %48, %49, %50, %51, %52, %53, %54, %55}, {%80, %81, %82, %83}, dx1, 1, 1, 1, 0;\n"
      "wgmma.mma_async.sync.aligned.m64n56k16.f32.bf16.bf16 {%28, %29, %30, %31, %32, %33, %34, %35, %36, %37, %38, %39, %40, %41, %42, %43, %44, %45, %46, %47, %48, %49, %50, %51, %52, %53, %54, %55}, {%84, %85, %86, %87}, dx2, 1, 1, 1, 0;\n"
      "wgmma.mma_async.sync.aligned.m64n56k16.f32.bf16.bf16 {%28, %29, %30, %31, %32, %33, %34, %35, %36, %37, %38, %39, %40, %41, %42, %43, %44, %45, %46, %47, %48, %49, %50, %51, %52, %53, %54, %55}, {%88, %89, %90, %91}, dx3, 1, 1, 1, 0;\n"
      "wgmma.commit_group.sync.aligned;\n}\n"
      : "=f"(g[0]), "=f"(g[1]), "=f"(g[2]), "=f"(g[3]), "=f"(g[4]), "=f"(g[5]), "=f"(g[6]), "=f"(g[7]), "=f"(g[8]), "=f"(g[9]), "=f"(g[10]), "=f"(g[11]), "=f"(g[12]), "=f"(g[13]), "=f"(g[14]), "=f"(g[15]), "=f"(g[16]), "=f"(g[17]), "=f"(g[18]), "=f"(g[19]), "=f"(g[20]), "=f"(g[21]), "=f"(g[22]), "=f"(g[23]), "=f"(g[24]), "=f"(g[25]), "=f"(g[26]), "=f"(g[27]),
        "=f"(h[0]), "=f"(h[1]), "=f"(h[2]), "=f"(h[3]), "=f"(h[4]), "=f"(h[5]), "=f"(h[6]), "=f"(h[7]), "=f"(h[8]), "=f"(h[9]), "=f"(h[10]), "=f"(h[11]), "=f"(h[12]), "=f"(h[13]), "=f"(h[14]), "=f"(h[15]), "=f"(h[16]), "=f"(h[17]), "=f"(h[18]), "=f"(h[19]), "=f"(h[20]), "=f"(h[21]), "=f"(h[22]), "=f"(h[23]), "=f"(h[24]), "=f"(h[25]), "=f"(h[26]), "=f"(h[27])
      : "r"(w[0]), "r"(w[1]), "r"(w[2]), "r"(w[3]), "r"(w[4]), "r"(w[5]), "r"(w[6]), "r"(w[7]), "r"(w[8]), "r"(w[9]), "r"(w[10]), "r"(w[11]), "r"(w[12]), "r"(w[13]), "r"(w[14]), "r"(w[15]), "r"(w[16]), "r"(w[17]), "r"(w[18]), "r"(w[19]), "r"(w[20]), "r"(w[21]), "r"(w[22]), "r"(w[23]), "r"(w[24]), "r"(w[25]), "r"(w[26]), "r"(w[27]), "r"(w[28]), "r"(w[29]), "r"(w[30]), "r"(w[31]), "r"(w[32]), "r"(w[33]), "r"(w[34]), "r"(w[35]), "r"(w[36]), "r"(w[37]), "r"(w[38]), "r"(w[39]), "r"(dx), "l"(de), "l"(dh)
      : "memory");
  }
  static __device__ __forceinline__ void wait_g(float* g) {
    asm volatile("wgmma.wait_group.sync.aligned 1;\n"
      : "+f"(g[0]), "+f"(g[1]), "+f"(g[2]), "+f"(g[3]), "+f"(g[4]), "+f"(g[5]), "+f"(g[6]), "+f"(g[7]), "+f"(g[8]), "+f"(g[9]), "+f"(g[10]), "+f"(g[11]), "+f"(g[12]), "+f"(g[13]), "+f"(g[14]), "+f"(g[15]), "+f"(g[16]), "+f"(g[17]), "+f"(g[18]), "+f"(g[19]), "+f"(g[20]), "+f"(g[21]), "+f"(g[22]), "+f"(g[23]), "+f"(g[24]), "+f"(g[25]), "+f"(g[26]), "+f"(g[27])
      :: "memory");
  }
  static __device__ __forceinline__ void wait_h(float* h) {
    asm volatile("wgmma.wait_group.sync.aligned 0;\n"
      : "+f"(h[0]), "+f"(h[1]), "+f"(h[2]), "+f"(h[3]), "+f"(h[4]), "+f"(h[5]), "+f"(h[6]), "+f"(h[7]), "+f"(h[8]), "+f"(h[9]), "+f"(h[10]), "+f"(h[11]), "+f"(h[12]), "+f"(h[13]), "+f"(h[14]), "+f"(h[15]), "+f"(h[16]), "+f"(h[17]), "+f"(h[18]), "+f"(h[19]), "+f"(h[20]), "+f"(h[21]), "+f"(h[22]), "+f"(h[23]), "+f"(h[24]), "+f"(h[25]), "+f"(h[26]), "+f"(h[27])
      :: "memory");
  }
};
template<> struct TileMMA<8> {
  static __device__ __forceinline__ void issue(float* g, float* h, const uint32_t* w, uint32_t dx, uint64_t de, uint64_t dh, uint64_t dc) {
    asm volatile(
      "{\n.reg .b64 dx0, dx1, dx2, dx3;\n.reg .b32 l1, l2, l3, hx;\nmov.b32 hx, 0x40000040;\n"
      "add.u32 l1, %104, 2;\nadd.u32 l2, %104, 4;\nadd.u32 l3, %104, 6;\n"
      "mov.b64 dx0, {%104, hx};\nmov.b64 dx1, {l1, hx};\nmov.b64 dx2, {l2, hx};\nmov.b64 dx3, {l3, hx};\n"
      "wgmma.fence.sync.aligned;\n"
      "wgmma.mma_async.sync.aligned.m64n64k16.f32.bf16.bf16 {%0, %1, %2, %3, %4, %5, %6, %7, %8, %9, %10, %11, %12, %13, %14, %15, %16, %17, %18, %19, %20, %21, %22, %23, %24, %25, %26, %27, %28, %29, %30, %31}, {%100, %101, %102, %103}, %106, 0, 1, 1, 0;\n"
      "wgmma.mma_async.sync.aligned.m64n64k16.f32.bf16.bf16 {%0, %1, %2, %3, %4, %5, %6, %7, %8, %9, %10, %11, %12, %13, %14, %15, %16, %17, %18, %19, %20, %21, %22, %23, %24, %25, %26, %27, %28, %29, %30, %31}, {%80, %81, %82, %83}, %105, 1, 1, 1, 0;\n"
      "wgmma.mma_async.sync.aligned.m64n64k16.f32.bf16.bf16 {%0, %1, %2, %3, %4, %5, %6, %7, %8, %9, %10, %11, %12, %13, %14, %15, %16, %17, %18, %19, %20, %21, %22, %23, %24, %25, %26, %27, %28, %29, %30, %31}, {%64, %65, %66, %67}, dx0, 1, 1, 1, 0;\n"
      "wgmma.mma_async.sync.aligned.m64n64k16.f32.bf16.bf16 {%0, %1, %2, %3, %4, %5, %6, %7, %8, %9, %10, %11, %12, %13, %14, %15, %16, %17, %18, %19, %20, %21, %22, %23, %24, %25, %26, %27, %28, %29, %30, %31}, {%68, %69, %70, %71}, dx1, 1, 1, 1, 0;\n"
      "wgmma.mma_async.sync.aligned.m64n64k16.f32.bf16.bf16 {%0, %1, %2, %3, %4, %5, %6, %7, %8, %9, %10, %11, %12, %13, %14, %15, %16, %17, %18, %19, %20, %21, %22, %23, %24, %25, %26, %27, %28, %29, %30, %31}, {%72, %73, %74, %75}, dx2, 1, 1, 1, 0;\n"
      "wgmma.mma_async.sync.aligned.m64n64k16.f32.bf16.bf16 {%0, %1, %2, %3, %4, %5, %6, %7, %8, %9, %10, %11, %12, %13, %14, %15, %16, %17, %18, %19, %20, %21, %22, %23, %24, %25, %26, %27, %28, %29, %30, %31}, {%76, %77, %78, %79}, dx3, 1, 1, 1, 0;\n"
      "wgmma.commit_group.sync.aligned;\n"
      "wgmma.mma_async.sync.aligned.m64n64k16.f32.bf16.bf16 {%32, %33, %34, %35, %36, %37, %38, %39, %40, %41, %42, %43, %44, %45, %46, %47, %48, %49, %50, %51, %52, %53, %54, %55, %56, %57, %58, %59, %60, %61, %62, %63}, {%84, %85, %86, %87}, dx0, 0, 1, 1, 0;\n"
      "wgmma.mma_async.sync.aligned.m64n64k16.f32.bf16.bf16 {%32, %33, %34, %35, %36, %37, %38, %39, %40, %41, %42, %43, %44, %45, %46, %47, %48, %49, %50, %51, %52, %53, %54, %55, %56, %57, %58, %59, %60, %61, %62, %63}, {%88, %89, %90, %91}, dx1, 1, 1, 1, 0;\n"
      "wgmma.mma_async.sync.aligned.m64n64k16.f32.bf16.bf16 {%32, %33, %34, %35, %36, %37, %38, %39, %40, %41, %42, %43, %44, %45, %46, %47, %48, %49, %50, %51, %52, %53, %54, %55, %56, %57, %58, %59, %60, %61, %62, %63}, {%92, %93, %94, %95}, dx2, 1, 1, 1, 0;\n"
      "wgmma.mma_async.sync.aligned.m64n64k16.f32.bf16.bf16 {%32, %33, %34, %35, %36, %37, %38, %39, %40, %41, %42, %43, %44, %45, %46, %47, %48, %49, %50, %51, %52, %53, %54, %55, %56, %57, %58, %59, %60, %61, %62, %63}, {%96, %97, %98, %99}, dx3, 1, 1, 1, 0;\n"
      "wgmma.commit_group.sync.aligned;\n}\n"
      : "=f"(g[0]), "=f"(g[1]), "=f"(g[2]), "=f"(g[3]), "=f"(g[4]), "=f"(g[5]), "=f"(g[6]), "=f"(g[7]), "=f"(g[8]), "=f"(g[9]), "=f"(g[10]), "=f"(g[11]), "=f"(g[12]), "=f"(g[13]), "=f"(g[14]), "=f"(g[15]), "=f"(g[16]), "=f"(g[17]), "=f"(g[18]), "=f"(g[19]), "=f"(g[20]), "=f"(g[21]), "=f"(g[22]), "=f"(g[23]), "=f"(g[24]), "=f"(g[25]), "=f"(g[26]), "=f"(g[27]), "=f"(g[28]), "=f"(g[29]), "=f"(g[30]), "=f"(g[31]),
        "=f"(h[0]), "=f"(h[1]), "=f"(h[2]), "=f"(h[3]), "=f"(h[4]), "=f"(h[5]), "=f"(h[6]), "=f"(h[7]), "=f"(h[8]), "=f"(h[9]), "=f"(h[10]), "=f"(h[11]), "=f"(h[12]), "=f"(h[13]), "=f"(h[14]), "=f"(h[15]), "=f"(h[16]), "=f"(h[17]), "=f"(h[18]), "=f"(h[19]), "=f"(h[20]), "=f"(h[21]), "=f"(h[22]), "=f"(h[23]), "=f"(h[24]), "=f"(h[25]), "=f"(h[26]), "=f"(h[27]), "=f"(h[28]), "=f"(h[29]), "=f"(h[30]), "=f"(h[31])
      : "r"(w[0]), "r"(w[1]), "r"(w[2]), "r"(w[3]), "r"(w[4]), "r"(w[5]), "r"(w[6]), "r"(w[7]), "r"(w[8]), "r"(w[9]), "r"(w[10]), "r"(w[11]), "r"(w[12]), "r"(w[13]), "r"(w[14]), "r"(w[15]), "r"(w[16]), "r"(w[17]), "r"(w[18]), "r"(w[19]), "r"(w[20]), "r"(w[21]), "r"(w[22]), "r"(w[23]), "r"(w[24]), "r"(w[25]), "r"(w[26]), "r"(w[27]), "r"(w[28]), "r"(w[29]), "r"(w[30]), "r"(w[31]), "r"(w[32]), "r"(w[33]), "r"(w[34]), "r"(w[35]), "r"(w[36]), "r"(w[37]), "r"(w[38]), "r"(w[39]), "r"(dx), "l"(de), "l"(dh)
      : "memory");
  }
  static __device__ __forceinline__ void wait_g(float* g) {
    asm volatile("wgmma.wait_group.sync.aligned 1;\n"
      : "+f"(g[0]), "+f"(g[1]), "+f"(g[2]), "+f"(g[3]), "+f"(g[4]), "+f"(g[5]), "+f"(g[6]), "+f"(g[7]), "+f"(g[8]), "+f"(g[9]), "+f"(g[10]), "+f"(g[11]), "+f"(g[12]), "+f"(g[13]), "+f"(g[14]), "+f"(g[15]), "+f"(g[16]), "+f"(g[17]), "+f"(g[18]), "+f"(g[19]), "+f"(g[20]), "+f"(g[21]), "+f"(g[22]), "+f"(g[23]), "+f"(g[24]), "+f"(g[25]), "+f"(g[26]), "+f"(g[27]), "+f"(g[28]), "+f"(g[29]), "+f"(g[30]), "+f"(g[31])
      :: "memory");
  }
  static __device__ __forceinline__ void wait_h(float* h) {
    asm volatile("wgmma.wait_group.sync.aligned 0;\n"
      : "+f"(h[0]), "+f"(h[1]), "+f"(h[2]), "+f"(h[3]), "+f"(h[4]), "+f"(h[5]), "+f"(h[6]), "+f"(h[7]), "+f"(h[8]), "+f"(h[9]), "+f"(h[10]), "+f"(h[11]), "+f"(h[12]), "+f"(h[13]), "+f"(h[14]), "+f"(h[15]), "+f"(h[16]), "+f"(h[17]), "+f"(h[18]), "+f"(h[19]), "+f"(h[20]), "+f"(h[21]), "+f"(h[22]), "+f"(h[23]), "+f"(h[24]), "+f"(h[25]), "+f"(h[26]), "+f"(h[27]), "+f"(h[28]), "+f"(h[29]), "+f"(h[30]), "+f"(h[31])
      :: "memory");
  }
};
template<> struct TileMMA<9> {
  static __device__ __forceinline__ void issue(float* g, float* h, const uint32_t* w, uint32_t dx, uint64_t de, uint64_t dh, uint64_t dc) {
    asm volatile(
      "{\n.reg .b64 dx0, dx1, dx2, dx3;\n.reg .b32 l1, l2, l3, hx;\nmov.b32 hx, 0x40000040;\n"
      "add.u32 l1, %112, 2;\nadd.u32 l2, %112, 4;\nadd.u32 l3, %112, 6;\n"
      "mov.b64 dx0, {%112, hx};\nmov.b64 dx1, {l1, hx};\nmov.b64 dx2, {l2, hx};\nmov.b64 dx3, {l3, hx};\n"
      "wgmma.fence.sync.aligned;\n"
      "wgmma.mma_async.sync.aligned.m64n72k16.f32.bf16.bf16 {%0, %1, %2, %3, %4, %5, %6, %7, %8, %9, %10, %11, %12, %13, %14, %15, %16, %17, %18, %19, %20, %21, %22, %23, %24, %25, %26, %27, %28, %29, %30, %31, %32, %33, %34, %35}, {%108, %109, %110, %111}, %114, 0, 1, 1, 0;\n"
      "wgmma.mma_async.sync.aligned.m64n72k16.f32.bf16.bf16 {%0, %1, %2, %3, %4, %5, %6, %7, %8, %9, %10, %11, %12, %13, %14, %15, %16, %17, %18, %19, %20, %21, %22, %23, %24, %25, %26, %27, %28, %29, %30, %31, %32, %33, %34, %35}, {%88, %89, %90, %91}, %113, 1, 1, 1, 0;\n"
      "wgmma.mma_async.sync.aligned.m64n72k16.f32.bf16.bf16 {%0, %1, %2, %3, %4, %5, %6, %7, %8, %9, %10, %11, %12, %13, %14, %15, %16, %17, %18, %19, %20, %21, %22, %23, %24, %25, %26, %27, %28, %29, %30, %31, %32, %33, %34, %35}, {%72, %73, %74, %75}, dx0, 1, 1, 1, 0;\n"
      "wgmma.mma_async.sync.aligned.m64n72k16.f32.bf16.bf16 {%0, %1, %2, %3, %4, %5, %6, %7, %8, %9, %10, %11, %12, %13, %14, %15, %16, %17, %18, %19, %20, %21, %22, %23, %24, %25, %26, %27, %28, %29, %30, %31, %32, %33, %34, %35}, {%76, %77, %78, %79}, dx1, 1, 1, 1, 0;\n"
      "wgmma.mma_async.sync.aligned.m64n72k16.f32.bf16.bf16 {%0, %1, %2, %3, %4, %5, %6, %7, %8, %9, %10, %11, %12, %13, %14, %15, %16, %17, %18, %19, %20, %21, %22, %23, %24, %25, %26, %27, %28, %29, %30, %31, %32, %33, %34, %35}, {%80, %81, %82, %83}, dx2, 1, 1, 1, 0;\n"
      "wgmma.mma_async.sync.aligned.m64n72k16.f32.bf16.bf16 {%0, %1, %2, %3, %4, %5, %6, %7, %8, %9, %10, %11, %12, %13, %14, %15, %16, %17, %18, %19, %20, %21, %22, %23, %24, %25, %26, %27, %28, %29, %30, %31, %32, %33, %34, %35}, {%84, %85, %86, %87}, dx3, 1, 1, 1, 0;\n"
      "wgmma.commit_group.sync.aligned;\n"
      "wgmma.mma_async.sync.aligned.m64n72k16.f32.bf16.bf16 {%36, %37, %38, %39, %40, %41, %42, %43, %44, %45, %46, %47, %48, %49, %50, %51, %52, %53, %54, %55, %56, %57, %58, %59, %60, %61, %62, %63, %64, %65, %66, %67, %68, %69, %70, %71}, {%92, %93, %94, %95}, dx0, 0, 1, 1, 0;\n"
      "wgmma.mma_async.sync.aligned.m64n72k16.f32.bf16.bf16 {%36, %37, %38, %39, %40, %41, %42, %43, %44, %45, %46, %47, %48, %49, %50, %51, %52, %53, %54, %55, %56, %57, %58, %59, %60, %61, %62, %63, %64, %65, %66, %67, %68, %69, %70, %71}, {%96, %97, %98, %99}, dx1, 1, 1, 1, 0;\n"
      "wgmma.mma_async.sync.aligned.m64n72k16.f32.bf16.bf16 {%36, %37, %38, %39, %40, %41, %42, %43, %44, %45, %46, %47, %48, %49, %50, %51, %52, %53, %54, %55, %56, %57, %58, %59, %60, %61, %62, %63, %64, %65, %66, %67, %68, %69, %70, %71}, {%100, %101, %102, %103}, dx2, 1, 1, 1, 0;\n"
      "wgmma.mma_async.sync.aligned.m64n72k16.f32.bf16.bf16 {%36, %37, %38, %39, %40, %41, %42, %43, %44, %45, %46, %47, %48, %49, %50, %51, %52, %53, %54, %55, %56, %57, %58, %59, %60, %61, %62, %63, %64, %65, %66, %67, %68, %69, %70, %71}, {%104, %105, %106, %107}, dx3, 1, 1, 1, 0;\n"
      "wgmma.commit_group.sync.aligned;\n}\n"
      : "=f"(g[0]), "=f"(g[1]), "=f"(g[2]), "=f"(g[3]), "=f"(g[4]), "=f"(g[5]), "=f"(g[6]), "=f"(g[7]), "=f"(g[8]), "=f"(g[9]), "=f"(g[10]), "=f"(g[11]), "=f"(g[12]), "=f"(g[13]), "=f"(g[14]), "=f"(g[15]), "=f"(g[16]), "=f"(g[17]), "=f"(g[18]), "=f"(g[19]), "=f"(g[20]), "=f"(g[21]), "=f"(g[22]), "=f"(g[23]), "=f"(g[24]), "=f"(g[25]), "=f"(g[26]), "=f"(g[27]), "=f"(g[28]), "=f"(g[29]), "=f"(g[30]), "=f"(g[31]), "=f"(g[32]), "=f"(g[33]), "=f"(g[34]), "=f"(g[35]),
        "=f"(h[0]), "=f"(h[1]), "=f"(h[2]), "=f"(h[3]), "=f"(h[4]), "=f"(h[5]), "=f"(h[6]), "=f"(h[7]), "=f"(h[8]), "=f"(h[9]), "=f"(h[10]), "=f"(h[11]), "=f"(h[12]), "=f"(h[13]), "=f"(h[14]), "=f"(h[15]), "=f"(h[16]), "=f"(h[17]), "=f"(h[18]), "=f"(h[19]), "=f"(h[20]), "=f"(h[21]), "=f"(h[22]), "=f"(h[23]), "=f"(h[24]), "=f"(h[25]), "=f"(h[26]), "=f"(h[27]), "=f"(h[28]), "=f"(h[29]), "=f"(h[30]), "=f"(h[31]), "=f"(h[32]), "=f"(h[33]), "=f"(h[34]), "=f"(h[35])
      : "r"(w[0]), "r"(w[1]), "r"(w[2]), "r"(w[3]), "r"(w[4]), "r"(w[5]), "r"(w[6]), "r"(w[7]), "r"(w[8]), "r"(w[9]), "r"(w[10]), "r"(w[11]), "r"(w[12]), "r"(w[13]), "r"(w[14]), "r"(w[15]), "r"(w[16]), "r"(w[17]), "r"(w[18]), "r"(w[19]), "r"(w[20]), "r"(w[21]), "r"(w[22]), "r"(w[23]), "r"(w[24]), "r"(w[25]), "r"(w[26]), "r"(w[27]), "r"(w[28]), "r"(w[29]), "r"(w[30]), "r"(w[31]), "r"(w[32]), "r"(w[33]), "r"(w[34]), "r"(w[35]), "r"(w[36]), "r"(w[37]), "r"(w[38]), "r"(w[39]), "r"(dx), "l"(de), "l"(dh)
      : "memory");
  }
  static __device__ __forceinline__ void wait_g(float* g) {
    asm volatile("wgmma.wait_group.sync.aligned 1;\n"
      : "+f"(g[0]), "+f"(g[1]), "+f"(g[2]), "+f"(g[3]), "+f"(g[4]), "+f"(g[5]), "+f"(g[6]), "+f"(g[7]), "+f"(g[8]), "+f"(g[9]), "+f"(g[10]), "+f"(g[11]), "+f"(g[12]), "+f"(g[13]), "+f"(g[14]), "+f"(g[15]), "+f"(g[16]), "+f"(g[17]), "+f"(g[18]), "+f"(g[19]), "+f"(g[20]), "+f"(g[21]), "+f"(g[22]), "+f"(g[23]), "+f"(g[24]), "+f"(g[25]), "+f"(g[26]), "+f"(g[27]), "+f"(g[28]), "+f"(g[29]), "+f"(g[30]), "+f"(g[31]), "+f"(g[32]), "+f"(g[33]), "+f"(g[34]), "+f"(g[35])
      :: "memory");
  }
  static __device__ __forceinline__ void wait_h(float* h) {
    asm volatile("wgmma.wait_group.sync.aligned 0;\n"
      : "+f"(h[0]), "+f"(h[1]), "+f"(h[2]), "+f"(h[3]), "+f"(h[4]), "+f"(h[5]), "+f"(h[6]), "+f"(h[7]), "+f"(h[8]), "+f"(h[9]), "+f"(h[10]), "+f"(h[11]), "+f"(h[12]), "+f"(h[13]), "+f"(h[14]), "+f"(h[15]), "+f"(h[16]), "+f"(h[17]), "+f"(h[18]), "+f"(h[19]), "+f"(h[20]), "+f"(h[21]), "+f"(h[22]), "+f"(h[23]), "+f"(h[24]), "+f"(h[25]), "+f"(h[26]), "+f"(h[27]), "+f"(h[28]), "+f"(h[29]), "+f"(h[30]), "+f"(h[31]), "+f"(h[32]), "+f"(h[33]), "+f"(h[34]), "+f"(h[35])
      :: "memory");
  }
};
template<> struct TileMMA<10> {
  static __device__ __forceinline__ void issue(float* g, float* h, const uint32_t* w, uint32_t dx, uint64_t de, uint64_t dh, uint64_t dc) {
    asm volatile(
      "{\n.reg .b64 dx0, dx1, dx2, dx3;\n.reg .b32 l1, l2, l3, hx;\nmov.b32 hx, 0x40000040;\n"
      "add.u32 l1, %120, 2;\nadd.u32 l2, %120, 4;\nadd.u32 l3, %120, 6;\n"
      "mov.b64 dx0, {%120, hx};\nmov.b64 dx1, {l1, hx};\nmov.b64 dx2, {l2, hx};\nmov.b64 dx3, {l3, hx};\n"
      "wgmma.fence.sync.aligned;\n"
      "wgmma.mma_async.sync.aligned.m64n80k16.f32.bf16.bf16 {%0, %1, %2, %3, %4, %5, %6, %7, %8, %9, %10, %11, %12, %13, %14, %15, %16, %17, %18, %19, %20, %21, %22, %23, %24, %25, %26, %27, %28, %29, %30, %31, %32, %33, %34, %35, %36, %37, %38, %39}, {%116, %117, %118, %119}, %122, 0, 1, 1, 0;\n"
      "wgmma.mma_async.sync.aligned.m64n80k16.f32.bf16.bf16 {%0, %1, %2, %3, %4, %5, %6, %7, %8, %9, %10, %11, %12, %13, %14, %15, %16, %17, %18, %19, %20, %21, %22, %23, %24, %25, %26, %27, %28, %29, %30, %31, %32, %33, %34, %35, %36, %37, %38, %39}, {%96, %97, %98, %99}, %121, 1, 1, 1, 0;\n"
      "wgmma.mma_async.sync.aligned.m64n80k16.f32.bf16.bf16 {%0, %1, %2, %3, %4, %5, %6, %7, %8, %9, %10, %11, %12, %13, %14, %15, %16, %17, %18, %19, %20, %21, %22, %23, %24, %25, %26, %27, %28, %29, %30, %31, %32, %33, %34, %35, %36, %37, %38, %39}, {%80, %81, %82, %83}, dx0, 1, 1, 1, 0;\n"
      "wgmma.mma_async.sync.aligned.m64n80k16.f32.bf16.bf16 {%0, %1, %2, %3, %4, %5, %6, %7, %8, %9, %10, %11, %12, %13, %14, %15, %16, %17, %18, %19, %20, %21, %22, %23, %24, %25, %26, %27, %28, %29, %30, %31, %32, %33, %34, %35, %36, %37, %38, %39}, {%84, %85, %86, %87}, dx1, 1, 1, 1, 0;\n"
      "wgmma.mma_async.sync.aligned.m64n80k16.f32.bf16.bf16 {%0, %1, %2, %3, %4, %5, %6, %7, %8, %9, %10, %11, %12, %13, %14, %15, %16, %17, %18, %19, %20, %21, %22, %23, %24, %25, %26, %27, %28, %29, %30, %31, %32, %33, %34, %35, %36, %37, %38, %39}, {%88, %89, %90, %91}, dx2, 1, 1, 1, 0;\n"
      "wgmma.mma_async.sync.aligned.m64n80k16.f32.bf16.bf16 {%0, %1, %2, %3, %4, %5, %6, %7, %8, %9, %10, %11, %12, %13, %14, %15, %16, %17, %18, %19, %20, %21, %22, %23, %24, %25, %26, %27, %28, %29, %30, %31, %32, %33, %34, %35, %36, %37, %38, %39}, {%92, %93, %94, %95}, dx3, 1, 1, 1, 0;\n"
      "wgmma.commit_group.sync.aligned;\n"
      "wgmma.mma_async.sync.aligned.m64n80k16.f32.bf16.bf16 {%40, %41, %42, %43, %44, %45, %46, %47, %48, %49, %50, %51, %52, %53, %54, %55, %56, %57, %58, %59, %60, %61, %62, %63, %64, %65, %66, %67, %68, %69, %70, %71, %72, %73, %74, %75, %76, %77, %78, %79}, {%100, %101, %102, %103}, dx0, 0, 1, 1, 0;\n"
      "wgmma.mma_async.sync.aligned.m64n80k16.f32.bf16.bf16 {%40, %41, %42, %43, %44, %45, %46, %47, %48, %49, %50, %51, %52, %53, %54, %55, %56, %57, %58, %59, %60, %61, %62, %63, %64, %65, %66, %67, %68, %69, %70, %71, %72, %73, %74, %75, %76, %77, %78, %79}, {%104, %105, %106, %107}, dx1, 1, 1, 1, 0;\n"
      "wgmma.mma_async.sync.aligned.m64n80k16.f32.bf16.bf16 {%40, %41, %42, %43, %44, %45, %46, %47, %48, %49, %50, %51, %52, %53, %54, %55, %56, %57, %58, %59, %60, %61, %62, %63, %64, %65, %66, %67, %68, %69, %70, %71, %72, %73, %74, %75, %76, %77, %78, %79}, {%108, %109, %110, %111}, dx2, 1, 1, 1, 0;\n"
      "wgmma.mma_async.sync.aligned.m64n80k16.f32.bf16.bf16 {%40, %41, %42, %43, %44, %45, %46, %47, %48, %49, %50, %51, %52, %53, %54, %55, %56, %57, %58, %59, %60, %61, %62, %63, %64, %65, %66, %67, %68, %69, %70, %71, %72, %73, %74, %75, %76, %77, %78, %79}, {%112, %113, %114, %115}, dx3, 1, 1, 1, 0;\n"
      "wgmma.commit_group.sync.aligned;\n}\n"
      : "=f"(g[0]), "=f"(g[1]), "=f"(g[2]), "=f"(g[3]), "=f"(g[4]), "=f"(g[5]), "=f"(g[6]), "=f"(g[7]), "=f"(g[8]), "=f"(g[9]), "=f"(g[10]), "=f"(g[11]), "=f"(g[12]), "=f"(g[13]), "=f"(g[14]), "=f"(g[15]), "=f"(g[16]), "=f"(g[17]), "=f"(g[18]), "=f"(g[19]), "=f"(g[20]), "=f"(g[21]), "=f"(g[22]), "=f"(g[23]), "=f"(g[24]), "=f"(g[25]), "=f"(g[26]), "=f"(g[27]), "=f"(g[28]), "=f"(g[29]), "=f"(g[30]), "=f"(g[31]), "=f"(g[32]), "=f"(g[33]), "=f"(g[34]), "=f"(g[35]), "=f"(g[36]), "=f"(g[37]), "=f"(g[38]), "=f"(g[39]),
        "=f"(h[0]), "=f"(h[1]), "=f"(h[2]), "=f"(h[3]), "=f"(h[4]), "=f"(h[5]), "=f"(h[6]), "=f"(h[7]), "=f"(h[8]), "=f"(h[9]), "=f"(h[10]), "=f"(h[11]), "=f"(h[12]), "=f"(h[13]), "=f"(h[14]), "=f"(h[15]), "=f"(h[16]), "=f"(h[17]), "=f"(h[18]), "=f"(h[19]), "=f"(h[20]), "=f"(h[21]), "=f"(h[22]), "=f"(h[23]), "=f"(h[24]), "=f"(h[25]), "=f"(h[26]), "=f"(h[27]), "=f"(h[28]), "=f"(h[29]), "=f"(h[30]), "=f"(h[31]), "=f"(h[32]), "=f"(h[33]), "=f"(h[34]), "=f"(h[35]), "=f"(h[36]), "=f"(h[37]), "=f"(h[38]), "=f"(h[39])
      : "r"(w[0]), "r"(w[1]), "r"(w[2]), "r"(w[3]), "r"(w[4]), "r"(w[5]), "r"(w[6]), "r"(w[7]), "r"(w[8]), "r"(w[9]), "r"(w[10]), "r"(w[11]), "r"(w[12]), "r"(w[13]), "r"(w[14]), "r"(w[15]), "r"(w[16]), "r"(w[17]), "r"(w[18]), "r"(w[19]), "r"(w[20]), "r"(w[21]), "r"(w[22]), "r"(w[23]), "r"(w[24]), "r"(w[25]), "r"(w[26]), "r"(w[27]), "r"(w[28]), "r"(w[29]), "r"(w[30]), "r"(w[31]), "r"(w[32]), "r"(w[33]), "r"(w[34]), "r"(w[35]), "r"(w[36]), "r"(w[37]), "r"(w[38]), "r"(w[39]), "r"(dx), "l"(de), "l"(dh)
      : "memory");
  }
  static __device__ __forceinline__ void wait_g(float* g) {
    asm volatile("wgmma.wait_group.sync.aligned 1;\n"
      : "+f"(g[0]), "+f"(g[1]), "+f"(g[2]), "+f"(g[3]), "+f"(g[4]), "+f"(g[5]), "+f"(g[6]), "+f"(g[7]), "+f"(g[8]), "+f"(g[9]), "+f"(g[10]), "+f"(g[11]), "+f"(g[12]), "+f"(g[13]), "+f"(g[14]), "+f"(g[15]), "+f"(g[16]), "+f"(g[17]), "+f"(g[18]), "+f"(g[19]), "+f"(g[20]), "+f"(g[21]), "+f"(g[22]), "+f"(g[23]), "+f"(g[24]), "+f"(g[25]), "+f"(g[26]), "+f"(g[27]), "+f"(g[28]), "+f"(g[29]), "+f"(g[30]), "+f"(g[31]), "+f"(g[32]), "+f"(g[33]), "+f"(g[34]), "+f"(g[35]), "+f"(g[36]), "+f"(g[37]), "+f"(g[38]), "+f"(g[39])
      :: "memory");
  }
  static __device__ __forceinline__ void wait_h(float* h) {
    asm volatile("wgmma.wait_group.sync.aligned 0;\n"
      : "+f"(h[0]), "+f"(h[1]), "+f"(h[2]), "+f"(h[3]), "+f"(h[4]), "+f"(h[5]), "+f"(h[6]), "+f"(h[7]), "+f"(h[8]), "+f"(h[9]), "+f"(h[10]), "+f"(h[11]), "+f"(h[12]), "+f"(h[13]), "+f"(h[14]), "+f"(h[15]), "+f"(h[16]), "+f"(h[17]), "+f"(h[18]), "+f"(h[19]), "+f"(h[20]), "+f"(h[21]), "+f"(h[22]), "+f"(h[23]), "+f"(h[24]), "+f"(h[25]), "+f"(h[26]), "+f"(h[27]), "+f"(h[28]), "+f"(h[29]), "+f"(h[30]), "+f"(h[31]), "+f"(h[32]), "+f"(h[33]), "+f"(h[34]), "+f"(h[35]), "+f"(h[36]), "+f"(h[37]), "+f"(h[38]), "+f"(h[39])
      :: "memory");
  }
};
template<> struct TileMMA<11> {
  static __device__ __forceinline__ void issue(float* g, float* h, const uint32_t* w, uint32_t dx, uint64_t de, uint64_t dh, uint64_t dc) {
    asm volatile(
      "{\n.reg .b64 dx0, dx1, dx2, dx3;\n.reg .b32 l1, l2, l3, hx;\nmov.b32 hx, 0x40000040;\n"
      "add.u32 l1, %124, 2;\nadd.u32 l2, %124, 4;\nadd.u32 l3, %124, 6;\n"
      "mov.b64 dx0, {%124, hx};\nmov.b64 dx1, {l1, hx};\nmov.b64 dx2, {l2, hx};\nmov.b64 dx3, {l3, hx};\n"
      "wgmma.fence.sync.aligned;\n"
      "wgmma.mma_async.sync.aligned.m64n88k16.f32.bf16.bf16 {%0, %1, %2, %3, %4, %5, %6, %7, %8, %9, %10, %11, %12, %13, %14, %15, %16, %17, %18, %19, %20, %21, %22, %23, %24, %25, %26, %27, %28, %29, %30, %31, %32, %33, %34, %35, %36, %37, %38, %39, %40, %41, %42, %43}, {%120, %121, %122, %123}, %126, 0, 1, 1, 0;\n"
      "wgmma.mma_async.sync.aligned.m64n88k16.f32.bf16.bf16 {%0, %1, %2, %3, %4, %5, %6, %7, %8, %9, %10, %11, %12, %13, %14, %15, %16, %17, %18, %19, %20, %21, %22, %23, %24, %25, %26, %27, %28, %29, %30, %31, %32, %33, %34, %35, %36, %37, %38, %39, %40, %41, %42, %43}, %127, %125, 1, 1, 1, 0, 0;\n"
      "wgmma.mma_async.sync.aligned.m64n88k16.f32.bf16.bf16 {%0, %1, %2, %3, %4, %5, %6, %7, %8, %9, %10, %11, %12, %13, %14, %15, %16, %17, %18, %19, %20, %21, %22, %23, %24, %25, %26, %27, %28, %29, %30, %31, %32, %33, %34, %35, %36, %37, %38, %39, %40, %41, %42, %43}, {%88, %89, %90, %91}, dx0, 1, 1, 1, 0;\n"
      "wgmma.mma_async.sync.aligned.m64n88k16.f32.bf16.bf16 {%0, %1, %2, %3, %4, %5, %6, %7, %8, %9, %10, %11, %12, %13, %14, %15, %16, %17, %18, %19, %20, %21, %22, %23, %24, %25, %26, %27, %28, %29, %30, %31, %32, %33, %34, %35, %36, %37, %38, %39, %40, %41, %42, %43}, {%92, %93, %94, %95}, dx1, 1, 1, 1, 0;\n"
      "wgmma.mma_async.sync.aligned.m64n88k16.f32.bf16.bf16 {%0, %1, %2, %3, %4, %5, %6, %7, %8, %9, %10, %11, %12, %13, %14, %15, %16, %17, %18, %19, %20, %21, %22, %23, %24, %25, %26, %27, %28, %29, %30, %31, %32, %33, %34, %35, %36, %37, %38, %39, %40, %41, %42, %43}, {%96, %97, %98, %99}, dx2, 1, 1, 1, 0;\n"
      "wgmma.mma_async.sync.aligned.m64n88k16.f32.bf16.bf16 {%0, %1, %2, %3, %4, %5, %6, %7, %8, %9, %10, %11, %12, %13, %14, %15, %16, %17, %18, %19, %20, %21, %22, %23, %24, %25, %26, %27, %28, %29, %30, %31, %32, %33, %34, %35, %36, %37, %38, %39, %40, %41, %42, %43}, {%100, %101, %102, %103}, dx3, 1, 1, 1, 0;\n"
      "wgmma.commit_group.sync.aligned;\n"
      "wgmma.mma_async.sync.aligned.m64n88k16.f32.bf16.bf16 {%44, %45, %46, %47, %48, %49, %50, %51, %52, %53, %54, %55, %56, %57, %58, %59, %60, %61, %62, %63, %64, %65, %66, %67, %68, %69, %70, %71, %72, %73, %74, %75, %76, %77, %78, %79, %80, %81, %82, %83, %84, %85, %86, %87}, {%104, %105, %106, %107}, dx0, 0, 1, 1, 0;\n"
      "wgmma.mma_async.sync.aligned.m64n88k16.f32.bf16.bf16 {%44, %45, %46, %47, %48, %49, %50, %51, %52, %53, %54, %55, %56, %57, %58, %59, %60, %61, %62, %63, %64, %65, %66, %67, %68, %69, %70, %71, %72, %73, %74, %75, %76, %77, %78, %79, %80, %81, %82, %83, %84, %85, %86, %87}, {%108, %109, %110, %111}, dx1, 1, 1, 1, 0;\n"
      "wgmma.mma_async.sync.aligned.m64n88k16.f32.bf16.bf16 {%44, %45, %46, %47, %48, %49, %50, %51, %52, %53, %54, %55, %56, %57, %58, %59, %60, %61, %62, %63, %64, %65, %66, %67, %68, %69, %70, %71, %72, %73, %74, %75, %76, %77, %78, %79, %80, %81, %82, %83, %84, %85, %86, %87}, {%112, %113, %114, %115}, dx2, 1, 1, 1, 0;\n"
      "wgmma.mma_async.sync.aligned.m64n88k16.f32.bf16.bf16 {%44, %45, %46, %47, %48, %49, %50, %51, %52, %53, %54, %55, %56, %57, %58, %59, %60, %61, %62, %63, %64, %65, %66, %67, %68, %69, %70, %71, %72, %73, %74, %75, %76, %77, %78, %79, %80, %81, %82, %83, %84, %85, %86, %87}, {%116, %117, %118, %119}, dx3, 1, 1, 1, 0;\n"
      "wgmma.commit_group.sync.aligned;\n}\n"
      : "=f"(g[0]), "=f"(g[1]), "=f"(g[2]), "=f"(g[3]), "=f"(g[4]), "=f"(g[5]), "=f"(g[6]), "=f"(g[7]), "=f"(g[8]), "=f"(g[9]), "=f"(g[10]), "=f"(g[11]), "=f"(g[12]), "=f"(g[13]), "=f"(g[14]), "=f"(g[15]), "=f"(g[16]), "=f"(g[17]), "=f"(g[18]), "=f"(g[19]), "=f"(g[20]), "=f"(g[21]), "=f"(g[22]), "=f"(g[23]), "=f"(g[24]), "=f"(g[25]), "=f"(g[26]), "=f"(g[27]), "=f"(g[28]), "=f"(g[29]), "=f"(g[30]), "=f"(g[31]), "=f"(g[32]), "=f"(g[33]), "=f"(g[34]), "=f"(g[35]), "=f"(g[36]), "=f"(g[37]), "=f"(g[38]), "=f"(g[39]), "=f"(g[40]), "=f"(g[41]), "=f"(g[42]), "=f"(g[43]),
        "=f"(h[0]), "=f"(h[1]), "=f"(h[2]), "=f"(h[3]), "=f"(h[4]), "=f"(h[5]), "=f"(h[6]), "=f"(h[7]), "=f"(h[8]), "=f"(h[9]), "=f"(h[10]), "=f"(h[11]), "=f"(h[12]), "=f"(h[13]), "=f"(h[14]), "=f"(h[15]), "=f"(h[16]), "=f"(h[17]), "=f"(h[18]), "=f"(h[19]), "=f"(h[20]), "=f"(h[21]), "=f"(h[22]), "=f"(h[23]), "=f"(h[24]), "=f"(h[25]), "=f"(h[26]), "=f"(h[27]), "=f"(h[28]), "=f"(h[29]), "=f"(h[30]), "=f"(h[31]), "=f"(h[32]), "=f"(h[33]), "=f"(h[34]), "=f"(h[35]), "=f"(h[36]), "=f"(h[37]), "=f"(h[38]), "=f"(h[39]), "=f"(h[40]), "=f"(h[41]), "=f"(h[42]), "=f"(h[43])
      : "r"(w[0]), "r"(w[1]), "r"(w[2]), "r"(w[3]), "r"(w[4]), "r"(w[5]), "r"(w[6]), "r"(w[7]), "r"(w[8]), "r"(w[9]), "r"(w[10]), "r"(w[11]), "r"(w[12]), "r"(w[13]), "r"(w[14]), "r"(w[15]), "r"(w[20]), "r"(w[21]), "r"(w[22]), "r"(w[23]), "r"(w[24]), "r"(w[25]), "r"(w[26]), "r"(w[27]), "r"(w[28]), "r"(w[29]), "r"(w[30]), "r"(w[31]), "r"(w[32]), "r"(w[33]), "r"(w[34]), "r"(w[35]), "r"(w[36]), "r"(w[37]), "r"(w[38]), "r"(w[39]), "r"(dx), "l"(de), "l"(dh), "l"(dc)
      : "memory");
  }
  static __device__ __forceinline__ void wait_g(float* g) {
    asm volatile("wgmma.wait_group.sync.aligned 1;\n"
      : "+f"(g[0]), "+f"(g[1]), "+f"(g[2]), "+f"(g[3]), "+f"(g[4]), "+f"(g[5]), "+f"(g[6]), "+f"(g[7]), "+f"(g[8]), "+f"(g[9]), "+f"(g[10]), "+f"(g[11]), "+f"(g[12]), "+f"(g[13]), "+f"(g[14]), "+f"(g[15]), "+f"(g[16]), "+f"(g[17]), "+f"(g[18]), "+f"(g[19]), "+f"(g[20]), "+f"(g[21]), "+f"(g[22]), "+f"(g[23]), "+f"(g[24]), "+f"(g[25]), "+f"(g[26]), "+f"(g[27]), "+f"(g[28]), "+f"(g[29]), "+f"(g[30]), "+f"(g[31]), "+f"(g[32]), "+f"(g[33]), "+f"(g[34]), "+f"(g[35]), "+f"(g[36]), "+f"(g[37]), "+f"(g[38]), "+f"(g[39]), "+f"(g[40]), "+f"(g[41]), "+f"(g[42]), "+f"(g[43])
      :: "memory");
  }
  static __device__ __forceinline__ void wait_h(float* h) {
    asm volatile("wgmma.wait_group.sync.aligned 0;\n"
      : "+f"(h[0]), "+f"(h[1]), "+f"(h[2]), "+f"(h[3]), "+f"(h[4]), "+f"(h[5]), "+f"(h[6]), "+f"(h[7]), "+f"(h[8]), "+f"(h[9]), "+f"(h[10]), "+f"(h[11]), "+f"(h[12]), "+f"(h[13]), "+f"(h[14]), "+f"(h[15]), "+f"(h[16]), "+f"(h[17]), "+f"(h[18]), "+f"(h[19]), "+f"(h[20]), "+f"(h[21]), "+f"(h[22]), "+f"(h[23]), "+f"(h[24]), "+f"(h[25]), "+f"(h[26]), "+f"(h[27]), "+f"(h[28]), "+f"(h[29]), "+f"(h[30]), "+f"(h[31]), "+f"(h[32]), "+f"(h[33]), "+f"(h[34]), "+f"(h[35]), "+f"(h[36]), "+f"(h[37]), "+f"(h[38]), "+f"(h[39]), "+f"(h[40]), "+f"(h[41]), "+f"(h[42]), "+f"(h[43])
      :: "memory");
  }
};
__device__ __forceinline__ void node_mma(float* g, const uint32_t* w, uint64_t dx) {
    asm volatile(
      "{\n.reg .b64 dx1, dx2, dx3;\n"
      "add.s64 dx1, %48, 2;\nadd.s64 dx2, %48, 4;\nadd.s64 dx3, %48, 6;\n"
      "wgmma.fence.sync.aligned;\n"
      "wgmma.mma_async.sync.aligned.m64n64k16.f32.bf16.bf16 {%0, %1, %2, %3, %4, %5, %6, %7, %8, %9, %10, %11, %12, %13, %14, %15, %16, %17, %18, %19, %20, %21, %22, %23, %24, %25, %26, %27, %28, %29, %30, %31}, {%32, %33, %34, %35}, %48, 0, 1, 1, 0;\n"
      "wgmma.mma_async.sync.aligned.m64n64k16.f32.bf16.bf16 {%0, %1, %2, %3, %4, %5, %6, %7, %8, %9, %10, %11, %12, %13, %14, %15, %16, %17, %18, %19, %20, %21, %22, %23, %24, %25, %26, %27, %28, %29, %30, %31}, {%36, %37, %38, %39}, dx1, 1, 1, 1, 0;\n"
      "wgmma.mma_async.sync.aligned.m64n64k16.f32.bf16.bf16 {%0, %1, %2, %3, %4, %5, %6, %7, %8, %9, %10, %11, %12, %13, %14, %15, %16, %17, %18, %19, %20, %21, %22, %23, %24, %25, %26, %27, %28, %29, %30, %31}, {%40, %41, %42, %43}, dx2, 1, 1, 1, 0;\n"
      "wgmma.mma_async.sync.aligned.m64n64k16.f32.bf16.bf16 {%0, %1, %2, %3, %4, %5, %6, %7, %8, %9, %10, %11, %12, %13, %14, %15, %16, %17, %18, %19, %20, %21, %22, %23, %24, %25, %26, %27, %28, %29, %30, %31}, {%44, %45, %46, %47}, dx3, 1, 1, 1, 0;\n"
      "wgmma.commit_group.sync.aligned;\n}\n"
      : "=f"(g[0]), "=f"(g[1]), "=f"(g[2]), "=f"(g[3]), "=f"(g[4]), "=f"(g[5]), "=f"(g[6]), "=f"(g[7]), "=f"(g[8]), "=f"(g[9]), "=f"(g[10]), "=f"(g[11]), "=f"(g[12]), "=f"(g[13]), "=f"(g[14]), "=f"(g[15]), "=f"(g[16]), "=f"(g[17]), "=f"(g[18]), "=f"(g[19]), "=f"(g[20]), "=f"(g[21]), "=f"(g[22]), "=f"(g[23]), "=f"(g[24]), "=f"(g[25]), "=f"(g[26]), "=f"(g[27]), "=f"(g[28]), "=f"(g[29]), "=f"(g[30]), "=f"(g[31])
      : "r"(w[0]), "r"(w[1]), "r"(w[2]), "r"(w[3]), "r"(w[4]), "r"(w[5]), "r"(w[6]), "r"(w[7]), "r"(w[8]), "r"(w[9]), "r"(w[10]), "r"(w[11]), "r"(w[12]), "r"(w[13]), "r"(w[14]), "r"(w[15]), "l"(dx)
      : "memory");
}

__device__ __forceinline__ uint32_t smem_u32(const void* p) { return (uint32_t)__cvta_generic_to_shared(p); }
__device__ __forceinline__ float ex2f(float x) { float y; asm("ex2.approx.ftz.f32 %0, %1;" : "=f"(y) : "f"(x)); return y; }
__device__ __forceinline__ float rcpf(float x) { float y; asm("rcp.approx.ftz.f32 %0, %1;" : "=f"(y) : "f"(x)); return y; }
__device__ __forceinline__ uint32_t pack_bf16(float lo, float hi) {
    uint32_t r; asm("cvt.rn.bf16x2.f32 %0, %1, %2;" : "=r"(r) : "f"(hi), "f"(lo)); return r;
}
__device__ __forceinline__ float bf_lo(uint32_t v) { return __uint_as_float(v << 16); }
__device__ __forceinline__ float bf_hi(uint32_t v) { return __uint_as_float(v & 0xFFFF0000u); }
template<int STRIDE>
__device__ __forceinline__ void cp16i(uint32_t dst, const char* base, uint32_t idx) {
    asm volatile("{\n.reg .b64 a;\nmad.wide.u32 a, %2, %3, %1;\ncp.async.cg.shared.global [%0], [a], 16;\n}\n" :: "r"(dst), "l"(base), "r"(idx), "n"(STRIDE) : "memory");
}
__device__ __forceinline__ void cp16e(uint32_t dst, const char* base, uint32_t idx, uint64_t pol) {
    asm volatile("{\n.reg .b64 a;\nmad.wide.u32 a, %2, 32, %1;\ncp.async.cg.shared.global.L2::cache_hint [%0], [a], 16, %3;\n}\n" :: "r"(dst), "l"(base), "r"(idx), "l"(pol) : "memory");
}
template<int STRIDE>
__device__ __forceinline__ void cp16z(uint32_t dst, const char* base, uint32_t idx, int k, int n, uint64_t pol) {
    if (STRIDE == 32)
        asm volatile("{\n.reg .b64 a;\n.reg .pred p;\nsetp.ge.s32 p, %3, %4;\nmad.wide.u32 a, %2, 32, %1;\ncp.async.cg.shared.global.L2::cache_hint [%0], [a], 16, p, %5;\n}\n"
                     :: "r"(dst), "l"(base), "r"(idx), "r"(k), "r"(n), "l"(pol) : "memory");
    else
        asm volatile("{\n.reg .b64 a;\n.reg .pred p;\nsetp.ge.s32 p, %3, %4;\nmad.wide.u32 a, %2, 128, %1;\ncp.async.cg.shared.global [%0], [a], 16, p;\n}\n"
                     :: "r"(dst), "l"(base), "r"(idx), "r"(k), "r"(n) : "memory");
}
template<int HI, bool Z>
__device__ __forceinline__ void cpx(uint32_t hi, uint32_t dst, uint32_t p, uint32_t lo, int k, int n) {
    if (Z) asm volatile("{\n.reg .b32 l;\n.reg .b64 a;\n.reg .pred q;\nsetp.ge.s32 q, %5, %6;\ndp2a.lo.u32.u32 l, %1, %2, %3;\nmov.b64 a, {l, %0};\ncp.async.cg.shared.global [%4], [a], 16, q;\n}\n"
                        :: "r"(hi), "r"(p), "r"(HI ? 0x8000u : 0x80u), "r"(lo), "r"(dst), "r"(k), "r"(n) : "memory");
    else asm volatile("{\n.reg .b32 l;\n.reg .b64 a;\ndp2a.lo.u32.u32 l, %1, %2, %3;\nmov.b64 a, {l, %0};\ncp.async.cg.shared.global [%4], [a], 16;\n}\n"
                      :: "r"(hi), "r"(p), "r"(HI ? 0x8000u : 0x80u), "r"(lo), "r"(dst) : "memory");
}
template<bool Z>
__device__ __forceinline__ void cpe(uint32_t hi, uint32_t dst, uint32_t idx, uint32_t lo, int k, int n, uint64_t pol) {
    if (Z) asm volatile("{\n.reg .b32 l;\n.reg .b64 a;\n.reg .pred q;\nsetp.ge.s32 q, %5, %6;\nmad.lo.u32 l, %1, 32, %2;\nmov.b64 a, {l, %0};\ncp.async.cg.shared.global.L2::cache_hint [%3], [a], 16, q, %4;\n}\n"
                        :: "r"(hi), "r"(idx), "r"(lo), "r"(dst), "l"(pol), "r"(k), "r"(n) : "memory");
    else asm volatile("{\n.reg .b32 l;\n.reg .b64 a;\nmad.lo.u32 l, %1, 32, %2;\nmov.b64 a, {l, %0};\ncp.async.cg.shared.global.L2::cache_hint [%3], [a], 16, %4;\n}\n"
                      :: "r"(hi), "r"(idx), "r"(lo), "r"(dst), "l"(pol) : "memory");
}
__device__ __forceinline__ void cp_commit() { asm volatile("cp.async.commit_group;" ::: "memory"); }
template<int N> __device__ __forceinline__ void cp_wait() { asm volatile("cp.async.wait_group %0;" :: "n"(N) : "memory"); }
__device__ __forceinline__ void mbar_arrive(uint32_t bar) { asm volatile("mbarrier.arrive.shared.b64 _, [%0];" :: "r"(bar) : "memory"); }
__device__ __forceinline__ void mbar_cp_arrive(uint32_t bar) { asm volatile("cp.async.mbarrier.arrive.noinc.shared.b64 [%0];" :: "r"(bar) : "memory"); }
__device__ __forceinline__ void mbar_wait(uint32_t bar, uint32_t parity) {
    asm volatile("{\n.reg .pred p;\n.reg .u32 n;\nmbarrier.try_wait.parity.shared.b64 p, [%0], %1;\n@p bra DONE_%=;\nmov.u32 n, 0;\n"
                 "WAIT_%=:\nmbarrier.try_wait.parity.shared.b64 p, [%0], %1, 0x100000;\n@p bra DONE_%=;\n"
                 "add.u32 n, n, 1;\nsetp.lt.u32 p, n, 0x400000;\n@p bra WAIT_%=;\ntrap;\nDONE_%=:\n}\n"
                 :: "r"(bar), "r"(parity) : "memory");
}
__device__ __forceinline__ void mbar_wait_c(uint32_t bar, uint32_t parity) {
    asm volatile("{\n.reg .pred p;\nWAIT_%=:\nmbarrier.try_wait.parity.shared.b64 p, [%0], %1;\n@p bra DONE_%=;\nbra WAIT_%=;\nDONE_%=:\n}\n"
                 :: "r"(bar), "r"(parity) : "memory");
}
__device__ __forceinline__ void mbar_wait_h(uint32_t bar, uint32_t parity) {
    asm volatile("{\n.reg .pred p;\nWAIT_%=:\nmbarrier.try_wait.parity.shared.b64 p, [%0], %1, 0x100000;\n@p bra DONE_%=;\nbra WAIT_%=;\nDONE_%=:\n}\n"
                 :: "r"(bar), "r"(parity) : "memory");
}
__device__ __forceinline__ uint32_t lds32(uint32_t a) { uint32_t v; asm volatile("ld.shared.u32 %0, [%1];" : "=r"(v) : "r"(a) : "memory"); return v; }
__device__ __forceinline__ void sts32(uint32_t a, uint32_t v) { asm volatile("st.shared.u32 [%0], %1;" :: "r"(a), "r"(v) : "memory"); }
__device__ __forceinline__ uint2 lds64(uint32_t a) { uint2 v; asm volatile("ld.shared.v2.u32 {%0,%1}, [%2];" : "=r"(v.x), "=r"(v.y) : "r"(a) : "memory"); return v; }
__device__ __forceinline__ void sts64(uint32_t a, uint32_t x, uint32_t y) { asm volatile("st.shared.v2.u32 [%0], {%1,%2};" :: "r"(a), "r"(x), "r"(y) : "memory"); }
__device__ __forceinline__ uint4 lds128(uint32_t a) { uint4 v; asm volatile("ld.shared.v4.u32 {%0,%1,%2,%3}, [%4];" : "=r"(v.x), "=r"(v.y), "=r"(v.z), "=r"(v.w) : "r"(a) : "memory"); return v; }
__device__ __forceinline__ void sts128(uint32_t a, uint4 v) { asm volatile("st.shared.v4.u32 [%0], {%1,%2,%3,%4};" :: "r"(a), "r"(v.x), "r"(v.y), "r"(v.z), "r"(v.w) : "memory"); }
__device__ __forceinline__ void ldsm4t(uint32_t* v, uint32_t a) {
    asm volatile("ldmatrix.sync.aligned.m8n8.x4.trans.shared.b16 {%0,%1,%2,%3}, [%4];" : "=r"(v[0]), "=r"(v[1]), "=r"(v[2]), "=r"(v[3]) : "r"(a) : "memory");
}
__device__ __forceinline__ void stsm4t(uint32_t a, const uint32_t* v) {
    asm volatile("stmatrix.sync.aligned.m8n8.x4.trans.shared.b16 [%0], {%1,%2,%3,%4};" :: "r"(a), "r"(v[0]), "r"(v[1]), "r"(v[2]), "r"(v[3]) : "memory");
}
__device__ __forceinline__ int atoms_inc(uint32_t a) { int v; asm volatile("atom.shared.add.u32 %0, [%1], 1;" : "=r"(v) : "r"(a) : "memory"); return v; }
__device__ __forceinline__ float tanhf_a(float x) { float y; asm("tanh.approx.f32 %0, %1;" : "=f"(y) : "f"(x)); return y; }
__device__ __forceinline__ const char* as_pair(const void* p, uint32_t scratch) {
    const char* r;
    asm volatile("st.shared.u64 [%1], %2;\nld.volatile.shared.u64 %0, [%1];" : "=l"(r) : "r"(scratch), "l"(p) : "memory");
    return r;
}
__device__ __forceinline__ void ld_unit(uint4& v, const char* p, bool ok) {
    asm volatile("{\n.reg .pred q;\nsetp.ne.u32 q, %5, 0;\n@q ld.relaxed.gpu.global.v4.u32 {%0,%1,%2,%3}, [%4];\n}"
                 : "+r"(v.x), "+r"(v.y), "+r"(v.z), "+r"(v.w) : "l"(p), "r"((uint32_t)ok) : "memory");
}
__device__ __forceinline__ void ld_unit(uint2& v, const char* p, bool ok) {
    asm volatile("{\n.reg .pred q;\nsetp.ne.u32 q, %3, 0;\n@q ld.relaxed.gpu.global.v2.u32 {%0,%1}, [%2];\n}"
                 : "+r"(v.x), "+r"(v.y) : "l"(p), "r"((uint32_t)ok) : "memory");
}
#define ELECT "{\n.reg .pred p;\nelect.sync _|p, 0xffffffff;\n@p "
__device__ __forceinline__ void w_init(uint32_t bar, int n) { asm volatile(ELECT "mbarrier.init.shared.b64 [%0], %1;\n}" :: "r"(bar), "r"(n) : "memory"); }
__device__ __forceinline__ void w_expect(uint32_t bar, uint32_t bytes) { asm volatile(ELECT "mbarrier.arrive.expect_tx.shared.b64 _, [%0], %1;\n}" :: "r"(bar), "r"(bytes) : "memory"); }
__device__ __forceinline__ void w_ld(uint32_t dst, const void* src, int bytes, uint32_t bar) {
    asm volatile(ELECT "cp.async.bulk.shared::cluster.global.mbarrier::complete_tx::bytes [%0], [%1], %2, [%3];\n}" :: "r"(dst), "l"(src), "r"(bytes), "r"(bar) : "memory");
}
__device__ __forceinline__ void w_box_ld(uint32_t dst, const CUtensorMap* tm, int row, uint32_t bar) {
    asm volatile(ELECT "cp.async.bulk.tensor.2d.shared::cluster.global.mbarrier::complete_tx::bytes [%0], [%1, {%3, %4}], [%2];\n}"
        :: "r"(dst), "l"((uint64_t)tm), "r"(bar), "r"(0), "r"(row) : "memory");
}
__device__ __forceinline__ void w_st(void* dst, uint32_t src, int bytes) {
    asm volatile(ELECT "cp.async.bulk.global.shared::cta.bulk_group [%0], [%1], %2;\n}" :: "l"(dst), "r"(src), "r"(bytes) : "memory");
}
__device__ __forceinline__ void w_box_st(const CUtensorMap* tm, int col, uint32_t src) {
    asm volatile(ELECT "cp.async.bulk.tensor.2d.global.shared::cta.bulk_group [%0, {%2, %3}], [%1];\n}" :: "l"((uint64_t)tm), "r"(src), "r"(col), "r"(0) : "memory");
}
__device__ __forceinline__ void w_sent(unsigned* p, uint32_t src) {
    asm volatile(ELECT "cp.reduce.async.bulk.global.shared::cta.bulk_group.add.u32 [%0], [%1], 16;\n}" :: "l"(p), "r"(src) : "memory");
}
__device__ __forceinline__ void w_inc(unsigned* p) { asm volatile(ELECT "red.relaxed.gpu.global.add.u32 [%0], 1;\n}" :: "l"(p) : "memory"); }
__device__ __forceinline__ void w_hint(unsigned* p, uint32_t all) {
    #pragma unroll 1
    for (int i = 0; i < 4096; i++) {
        uint32_t v; asm volatile("ld.relaxed.gpu.global.u32 %0, [%1];" : "=r"(v) : "l"(p) : "memory");
        if (__all_sync(~0u, (int)(v - all) >= 0)) break;
    }
}

__device__ __forceinline__ void finish(uint4& a, const uint4& xu, const uint4& xv) {
    asm("{\n.reg .b32 z;\nfma.rn.relu.bf16x2 z, %0, %3, %1;\nadd.rn.bf16x2 %0, z, %2;\n}" : "+r"(a.x) : "r"(xu.x), "r"(xv.x), "r"(0x3F803F80u));
    asm("{\n.reg .b32 z;\nfma.rn.relu.bf16x2 z, %0, %3, %1;\nadd.rn.bf16x2 %0, z, %2;\n}" : "+r"(a.y) : "r"(xu.y), "r"(xv.y), "r"(0x3F803F80u));
    asm("{\n.reg .b32 z;\nfma.rn.relu.bf16x2 z, %0, %3, %1;\nadd.rn.bf16x2 %0, z, %2;\n}" : "+r"(a.z) : "r"(xu.z), "r"(xv.z), "r"(0x3F803F80u));
    asm("{\n.reg .b32 z;\nfma.rn.relu.bf16x2 z, %0, %3, %1;\nadd.rn.bf16x2 %0, z, %2;\n}" : "+r"(a.w) : "r"(xu.w), "r"(xv.w), "r"(0x3F803F80u));
}

constexpr float EPS2 = 2e-6f;
constexpr float TAU = 2.5e-5f;

constexpr uint32_t TAU_BITS = 0x3A103000u;
template<int NP>
__device__ __forceinline__ bool epi_fast(const float* g, const float* h, float m2, float tau, float& n0, float& d0, float& n1, float& d1, float& dmin)
{
    constexpr int JC = NP >= 6 ? NP - 3 : NP - 2;
    bool ok;
    #pragma unroll
    for (int j = 0; j < NP; j++) {
        float t0 = tanhf_a(g[4*j+0]), t1 = tanhf_a(g[4*j+1]), t2 = tanhf_a(g[4*j+2]), t3 = tanhf_a(g[4*j+3]);
        auto add_d = [&]() {
            if (j == 0) { d0 = t0 + (2.f * (JC + 1) + EPS2); d1 = t2 + (2.f * (JC + 1) + EPS2); } else { d0 += t0; d1 += t2; }
            d0 += t1; d1 += t3;
        };
        if (j <= JC) add_d();
        if (j == 0) { n0 = fmaf(t0, h[0], h[0]); n1 = fmaf(t2, h[2], h[2]); }
        t0 += 1.f; t2 += 1.f;
        if (j == NP - 1) { t1 = fmaf(t1, m2, m2); t3 = fmaf(t3, m2, m2); } else { t1 += 1.f; t3 += 1.f; }
        if (j > JC) add_d();
        if (j > 0) { n0 = fmaf(t0, h[4*j], n0); n1 = fmaf(t2, h[4*j+2], n1); }
        n0 = fmaf(t1, h[4*j+1], n0); n1 = fmaf(t3, h[4*j+3], n1);
        if (j == JC) { dmin = fminf(d0, d1); ok = dmin >= tau; }
    }
    return ok;
}

__device__ __noinline__ void slow_bin(const __nv_bfloat16* x, const __nv_bfloat16* ea, const int* src, const int* dst,
                                      const __nv_bfloat16* wa, const __nv_bfloat16* wb, const __nv_bfloat16* wc,
                                      const __nv_bfloat16* wu, const __nv_bfloat16* wv, __nv_bfloat16* out,
                                      int E, int node0, int nn, int nthr)
{
    const int tid = threadIdx.x, lane = tid & 31;
    for (int i = tid; i < nn * 128; i += nthr) g_slow[(size_t)node0 * 128 + i] = 0.f;
    asm volatile("bar.sync 1, %0;" :: "r"(nthr) : "memory");
    for (int e0 = (tid >> 5) * 32; e0 < E; e0 += nthr) {
        int d = (e0 + lane < E) ? dst[e0 + lane] - node0 : -1;
        unsigned m = __ballot_sync(~0u, d >= 0 && d < nn);
        while (m) {
            int l = __ffs(m) - 1; m &= m - 1;
            int e = e0 + l, n = node0 + __shfl_sync(~0u, d, l), s = src[e];
            float g0 = 0, g1 = 0, h0 = 0, h1 = 0;
            for (int k = 0; k < 64; k++) {
                float xs = __bfloat162float(x[(size_t)s * 64 + k]), xd = __bfloat162float(x[(size_t)n * 64 + k]);
                uint32_t b2 = *(const uint32_t*)(wb + k * 64 + 2 * lane), v2 = *(const uint32_t*)(wv + k * 64 + 2 * lane);
                uint32_t a2 = *(const uint32_t*)(wa + k * 64 + 2 * lane);
                g0 = fmaf(xs, bf_lo(b2), fmaf(xd, bf_lo(a2), g0)); g1 = fmaf(xs, bf_hi(b2), fmaf(xd, bf_hi(a2), g1));
                h0 = fmaf(xs, bf_lo(v2), h0); h1 = fmaf(xs, bf_hi(v2), h1);
            }
            for (int k = 0; k < 16; k++) {
                float ev = __bfloat162float(ea[(size_t)e * 16 + k]);
                uint32_t c2 = *(const uint32_t*)(wc + k * 64 + 2 * lane);
                g0 = fmaf(ev, bf_lo(c2), g0); g1 = fmaf(ev, bf_hi(c2), g1);
            }
            float s0 = rcpf(1.f + ex2f(-LOG2E * g0)), s1 = rcpf(1.f + ex2f(-LOG2E * g1));
            float* acc = g_slow + (size_t)n * 128 + 4 * lane;
            atomicAdd(acc + 0, s0 * h0); atomicAdd(acc + 1, s0);
            atomicAdd(acc + 2, s1 * h1); atomicAdd(acc + 3, s1);
        }
    }
    __threadfence();
    asm volatile("bar.sync 1, %0;" :: "r"(nthr) : "memory");
    for (int i = tid; i < nn * 32; i += nthr) {
        int n = node0 + (i >> 5), cp = i & 31;
        float4 a = __ldcg((const float4*)(g_slow + (size_t)n * 128 + 4 * cp));
        float u0 = 0, u1 = 0;
        for (int k = 0; k < 64; k++) {
            float xd = __bfloat162float(x[(size_t)n * 64 + k]);
            uint32_t w2 = *(const uint32_t*)(wu + k * 64 + 2 * cp);
            u0 = fmaf(xd, bf_lo(w2), u0); u1 = fmaf(xd, bf_hi(w2), u1);
        }
        uint32_t xv = *(const uint32_t*)(x + (size_t)n * 64 + 2 * cp);
        float z0 = u0 + a.x / (a.y + 1e-6f), z1 = u1 + a.z / (a.w + 1e-6f);
        *(uint32_t*)(out + (size_t)n * 64 + 2 * cp) = pack_bf16(bf_lo(xv) + fmaxf(z0, 0.f), bf_hi(xv) + fmaxf(z1, 0.f));
    }
}

__global__ void __launch_bounds__(256) slow_kernel(const __nv_bfloat16* x, const __nv_bfloat16* ea, const int* src, const int* dst,
        const __nv_bfloat16* wa, const __nv_bfloat16* wb, const __nv_bfloat16* wc, const __nv_bfloat16* wu, const __nv_bfloat16* wv,
        __nv_bfloat16* out, int N, int E, int npb)
{
    int node0 = blockIdx.x * npb;
    slow_bin(x, ea, src, dst, wa, wb, wc, wu, wv, out, E, node0, max(0, min(npb, N - node0)), 256);
}

constexpr int XS_BYTES = NPMAX * 1024;
constexpr int ES_BYTES = NPMAX * 256;
constexpr int SM_XS = 0;
constexpr int SM_XU = SM_XS + 3 * NSTAGE * XS_BYTES;
constexpr int SM_TAB = SM_XU + NPB_MAX * 128;
constexpr int SM_ES = SM_TAB + NPB_MAX * 128;
constexpr int SM_WC = SM_ES + 3 * NSTAGE * ES_BYTES;
constexpr int SM_OH = SM_WC + 2048;
constexpr int SM_EID = SM_OH + 128;
constexpr int SM_SRC = SM_EID + SLOT_CAP * 4;
constexpr int SM_TINFO = SM_SRC + SLOT_CAP * 2;
constexpr int SM_MISC = SM_TINFO + TILE_CAP * 32;
constexpr int SM_CLAIM = SM_MISC + 32 * 4;
constexpr int STG = 272;
constexpr int SM_BARS = SM_CLAIM + 32 * 4;
constexpr int SM_ABAR = SM_BARS + 6 * STG;
constexpr int SM_GBAR = SM_ABAR + 16 * 8;
constexpr int SMEM_BYTES = SM_GBAR + (GD + 1) * 8;
constexpr int SM_P2 = 0, SM_P1 = P2B + 256;
constexpr int SM_L1 = SM_P1 + P1B + 128;
constexpr int SM_DEG = SM_L1 + 256;
constexpr int SM_CLS = SM_DEG + 512 * 4;
constexpr int SM_HIST = SM_CLS + NCLS * 4;
constexpr int SM_XLIST = SM_HIST + NB_MAX * 4;
constexpr int SM_SORT = SM_XLIST + 8;
constexpr int SM_SDEG = SM_SORT + NPB_MAX * 4;
constexpr int SM_PAIR = SM_SDEG + NPB_MAX * 2;
constexpr int SM_ENT = SM_ES + 1024;
constexpr int SM_H1 = SM_P1 + HB, SM_H2 = SM_P1;
constexpr int SM_IDX = SM_EID;
constexpr int SM_WR = SM_TAB;
static_assert(TILE_CAP <= 128 && TR >= 2 && SM_ES % 256 == 0 && NSTAGE == 2 && SM_BARS % 16 == 0 && SM_TINFO % 16 == 0 && SM_EID % 128 == 0 && SM_TAB % 1024 == 0 && SM_XU % 1024 == 0 && SM_TINFO % 8 == 0 && SM_OH % 16 == 0 && SM_XLIST % 8 == 0 && SM_PAIR % 8 == 0, "align");
static_assert(SM_P1 % 128 == 0 && P1B + HB <= SM_SRC - SM_EID && 2 * HB <= P1B && SM_H1 + 5 * 128 * 16 <= SM_XU && NB_MAX * (CE / 4) <= 6 * 384 && NB_MAX * 4 <= 5 * 128 && NB_MIN * 4 >= 3 * 128 && SM_PAIR + 128 * 8 <= SM_XU && CH_MAX * 4 <= SM_SRC - SM_EID && SM_DEG >= 3 << 14, "alias");
static_assert(KM == 4 && CE == 64 && SMEM_BYTES <= 232448, "smem");
constexpr uint32_t C_BRK = 16  , C_CONT = 32, C_MORE = 64;
constexpr uint32_t ONE_F = 0x3F800000u;
constexpr int NONE = NPB_MAX - 1;
__host__ __device__ constexpr uint32_t tab_at(uint32_t n) { return (n >> 2) * 512 + (n & 3) * 32 + ((n >> 2) & 1) * 16; }

__device__ __forceinline__ bool unpad(uint32_t w1, int np, float ga, float gb, float& d0, float& d1, int& dv) {
    const int pad = (w1 >> 8) & 31;
    dv = 2 * np - 1 - pad + (w1 >= ONE_F);
    float t0 = TAU * 2 * np, t1 = t0;
    if (pad) {
        t0 = fmaxf(t0, d0 * (1.f / 16384)); t1 = fmaxf(t1, d1 * (1.f / 16384));
        asm volatile("tanh.approx.f32 %0, %0;\ntanh.approx.f32 %1, %1;" : "+f"(ga), "+f"(gb));
        d0 -= pad * (1.f + ga); d1 -= pad * (1.f + gb);
    }
    if (dv == 0) { d0 = d1 = EPS2; t0 = t1 = 0.f; }
    return d0 < t0 || d1 < t1;
}
constexpr int SM_COPY = SM_XU + tab_at(NPB_MAX - 4) - 16;
__device__ __forceinline__ void exact_quad(const float4 g, const float4 h, int k, int dv, float4& r) {
    const float e0 = 2.f * rcpf(1.f + ex2f(-2.f * LOG2E * g.x)), e1 = 2.f * rcpf(1.f + ex2f(-2.f * LOG2E * g.y));
    const float e2 = 2.f * rcpf(1.f + ex2f(-2.f * LOG2E * g.z)), e3 = 2.f * rcpf(1.f + ex2f(-2.f * LOG2E * g.w));
    if (k < dv) { r.y += e0; r.x = fmaf(e0, h.x, r.x); r.w += e2; r.z = fmaf(e2, h.z, r.z); }
    if (k + 1 < dv) { r.y += e1; r.x = fmaf(e1, h.y, r.x); r.w += e3; r.z = fmaf(e3, h.w, r.z); }
}
__device__ __forceinline__ float4 ldsf4(uint32_t a) { const uint4 v = lds128(a); return make_float4(__uint_as_float(v.x), __uint_as_float(v.y), __uint_as_float(v.z), __uint_as_float(v.w)); }
__device__ __noinline__ float4 exact_1(uint32_t sa, uint32_t l16, int np, uint32_t own)
{
    const uint32_t n16 = np * 16, slot = (l16 >= n16) + (l16 >= 2 * n16);
    __syncwarp();
    const float4 g = ldsf4(sa + l16), h = ldsf4(sa + 240 + l16);
    float4 r = make_float4(0.f, 0.f, 0.f, 0.f);
    exact_quad(g, h, (l16 - slot * n16) >> 3, lds32(sa + 496 + slot * 4), r);
    __syncwarp();
    sts128(sa + l16, make_uint4(__float_as_uint(r.x), __float_as_uint(r.y), __float_as_uint(r.z), __float_as_uint(r.w)));
    __syncwarp();
    r = make_float4(0.f, EPS2, 0.f, EPS2);
    #pragma unroll
    for (int j = 0; j < NPMAX; j++) {
        const float4 v = ldsf4(own + j * 16);
        if (j < NPMIN || j < np) { r.x += v.x; r.y += v.y; r.z += v.z; r.w += v.w; }
    }
    __syncwarp();
    sts32(sa + (SM_MISC + 12 - SM_COPY), 0);
    return r;
}
__device__ __noinline__ float4* exact_copy() { return g_copy + (blockIdx.x * 12 + (threadIdx.x >> 5)) * (64 * NPMAX) + (threadIdx.x & 31); }
__device__ __noinline__ float4 exact_all(const float4* gh, int np, int dv)
{
    float4 r = make_float4(0.f, EPS2, 0.f, EPS2);
    #pragma unroll 1
    for (int j = 0; j < np; j++, gh += 32) exact_quad(gh[0], gh[32 * NPMAX], 2 * j, dv, r);
    return r;
}
template<int NP>
__device__ __forceinline__ float4 epi_exact(const float* g, const float* h, uint32_t bad, bool on, int dv, uint32_t sa, uint32_t l16) {
    uint32_t old = 1;
    const uint32_t b1 = bad & (bad - 1), b2 = b1 & (b1 - 1);
    uint32_t slot = 0;
    if (15 / NP > 1) {
        uint32_t lt; asm("mov.u32 %0, %%lanemask_lt;" : "=r"(lt));
        slot = on ? ((bad & lt) != 0) + ((b1 & lt) != 0) : 0;
    }
    const uint32_t own = sa + slot * (NP * 16);
    if ((15 / NP > 2 ? b2 & (b2 - 1) : 15 / NP > 1 ? b2 : b1) == 0) {
        #pragma unroll 1
        for (int n = 0; n < 12; n++) {
            asm volatile(ELECT "atom.shared.or.b32 %0, [%1], 1;\n}" : "+r"(old) : "r"(sa + (SM_MISC + 12 - SM_COPY)) : "memory");
            if (__any_sync(~0u, old != 1)) break;
        }
    }
    if (__any_sync(~0u, old == 0)) {
        #pragma unroll
        for (int i = 0; i < 2 * NP; i++) {
            const float* v = i < NP ? g + 4 * i : h + 4 * (i - NP);
            asm volatile("{\n.reg .pred p;\nsetp.ne.u32 p, %5, 0;\n@p st.shared.v4.f32 [%0], {%1,%2,%3,%4};\n}"
                         :: "r"(own + (i < NP ? i : 15 + i - NP) * 16), "f"(v[0]), "f"(v[1]), "f"(v[2]), "f"(v[3]), "r"((uint32_t)on) : "memory");
        }
        asm volatile("{\n.reg .pred p;\nsetp.ne.u32 p, %2, 0;\n@p st.shared.u32 [%0], %1;\n}" :: "r"(sa + 496 + slot * 4), "r"(dv), "r"((uint32_t)on) : "memory");
        return exact_1(sa, l16, NP, own);
    }
    float4* gh = exact_copy();
    #pragma unroll
    for (int i = 0; i < 2 * NP; i++) {
        const float* v = i < NP ? g + 4 * i : h + 4 * (i - NP);
        asm volatile("st.global.v4.f32 [%0], {%1,%2,%3,%4};" :: "l"(gh + (i < NP ? i : NPMAX + i - NP) * 32), "f"(v[0]), "f"(v[1]), "f"(v[2]), "f"(v[3]) : "memory");
    }
    return exact_all(gh, NP, dv);
}
__device__ __forceinline__ uint32_t row_bytes(uint32_t o) { return (o & 0xFE00) | ((o << 2) & 0x180); }

__device__ __noinline__ int balance(int step, char* gs, uint32_t id, int ng, int npb)
{
    extern __shared__ __align__(1024) uint8_t smem[];
    const uint32_t sb = smem_u32(smem), lane = threadIdx.x & 31, b = blockIdx.x, r4 = lane >> 3;
    const uint32_t tw = ((lane & 1) << 4) | ((lane & 6) << 6), ti = sb + SM_TINFO + r4 * 8, st = sb + SM_MISC + 48;
    uint32_t now; asm volatile("mov.u32 %0, %%globaltimer_lo;" : "=r"(now));
    auto put = [&](uint32_t a, uint32_t v) { if (lane == 0) asm volatile("st.relaxed.gpu.global.v2.u32 [%0], {%1, %2};" :: "l"(gs + a), "r"(v), "r"(id) : "memory"); };
    auto get = [&](uint32_t a) {
        uint2 v;
        #pragma unroll 1
        for (uint32_t n = 0; ; n++) {
            asm volatile("ld.acquire.gpu.global.v2.u32 {%0, %1}, [%2];" : "=r"(v.x), "=r"(v.y) : "l"(gs + a) : "memory");
            if (__all_sync(~0u, v.y == id)) break;
            if (n > (1u << 22)) __trap();
        }
        return v.x;
    };
    int gn = ng;
    if (step < 0) {
        if (BAL && step == -1) {
            const uint32_t e = lds32(sb + SM_TINFO + (3 * R1 + 3) * 32);
            if ((e & 0xFFFF) >= KM * 64 && ((e >> 20) & 127) < 2 && ((lds32(sb + SM_TINFO + (ng - KM) * 32 + 4) >> 16) & 15) <= 8 && lds32(sb + SM_MISC + 24) == 0) {
                #pragma unroll 1
                for (int j = 0; j < KM; j++) {
                    const uint32_t ta = (ng - 1 - j) * 32, s0 = lds32(sb + SM_TINFO + ta) & 0xFFFF;
                    const uint2 e = lds64(ti + ta);
                    char* p = gs + G_P + (b * KM + j) * GRP_B;
                    const uint32_t ro = sb + ((e.y & 0xFFFF) ^ tw);
                    *(uint4*)(p + lane * 16) = lds128(ro + SM_TAB);
                    *(uint4*)(p + 512 + lane * 16) = lds128(ro + SM_XU);
                    *(uint2*)(p + 1024 + lane * 8) = lds64(sb + SM_EID + s0 * 4 + lane * 8);
                    *(uint32_t*)(p + 1280 + lane * 4) = lds32(sb + SM_SRC + s0 * 2 + lane * 4);
                    *(uint2*)(p + 1408 + r4 * 8) = make_uint2(e.x >> 27 ? e.x - s0 : e.x, e.y);
                }
                uint32_t c = 0;
                #pragma unroll 1
                for (int g = 3 * R1 + 3 + lane; g < ng; g += 32) c += 93 + ((lds32(sb + SM_TINFO + g * 32 + 4) >> 16) & 15) * 42;
                sts32(st, (__reduce_add_sync(~0u, c) * 595) >> 10);
                asm volatile("fence.acq_rel.gpu;" ::: "memory");
                __syncwarp();
                return 1;
            }
        }
        put(G_F + b * 8, (now << 6) & ~511u);
    } else if (step == R2) {
        uint2 v[5];
        #pragma unroll 1
        for (uint32_t n = 0; ; n++) {
            bool ok = true;
            #pragma unroll
            for (int i = 0; i < 5; i++) asm volatile("ld.relaxed.gpu.global.v2.u32 {%0, %1}, [%2];" : "=r"(v[i].x), "=r"(v[i].y) : "l"(gs + G_F + min(lane + 32 * i, gridDim.x - 1) * 8) : "memory");
            #pragma unroll
            for (int i = 0; i < 5; i++) ok &= v[i].y == id;
            if (__all_sync(~0u, ok)) break;
            if (n > (1u << 22)) __trap();
        }
        const uint32_t ref = __shfl_sync(~0u, v[0].x, 0) - 0x80000000u, key = ((lds32(st) - ref) & ~511u) | b;
        uint32_t c = 0;
        #pragma unroll
        for (int i = 0; i < 5; i++) if (lane + 32 * i < gridDim.x && (v[i].x & 256)) c += 0x10000 + ((((v[i].x - ref) & ~511u) | (lane + 32 * i)) < key);
        c = __reduce_add_sync(~0u, c);
        const uint32_t kf = key | (ng % 3 == 0 ? 256 : 0);
        put(G_R + (c & 0xFFFF) * 8, kf);
        sts64(st, kf, (c >> 16) - 1 - (c & 0xFFFF));
        __syncwarp();
        return gn;
    } else {
        const uint32_t pk = get(G_R + lds32(st + 4) * 8);
        const uint32_t key = lds32(st);
        const int df = (int)(pk >> 9) - (int)(key >> 9), m = min((abs(df) * 8 + 175) / 350, (df < 0 ? pk : key) & 256 ? 3 : KM);
        gn += df < 0 ? -m : m;
        #pragma unroll 1
        for (int i0 = 0; i0 < gn - ng; i0 += 2) {
            uint4 ra[2], ru[2]; uint2 le[2], e[2]; uint32_t ls[2];
            #pragma unroll
            for (int i = 0; i < 2; i++) {
                const char* p = gs + G_P + ((pk & 255) * KM + i0 + i) * GRP_B;
                ra[i] = __ldcg((const uint4*)(p + lane * 16)); ru[i] = __ldcg((const uint4*)(p + 512 + lane * 16));
                le[i] = __ldcg((const uint2*)(p + 1024 + lane * 8)); e[i] = __ldcg((const uint2*)(p + 1408 + r4 * 8));
                ls[i] = __ldcg((const uint32_t*)(p + 1280 + lane * 4));
            }
            #pragma unroll
            for (int i = 0; i < 2; i++) {
                const int j = (m - 1 - i0 - i) & 3;
                const bool some = (e[i].y & 0xFFFF) != tab_at(NONE);
                const uint32_t row = some ? lds32(ti + (i0 + i) * 32 + 4) & 0xFFFF : tab_at(NONE);
                if (some) { sts128(sb + (row ^ tw) + SM_TAB, ra[i]); sts128(sb + (row ^ tw) + SM_XU, ru[i]); }
                sts64(sb + SM_EID + (i0 + i) * 256 + lane * 8, le[i].x, le[i].y);
                sts32(sb + SM_SRC + (i0 + i) * 128 + lane * 4, ls[i]);
                sts32(sb + SM_MISC + 64 + j * 16 + r4 * 4, (pk & 255) * npb * 128 + row_bytes(e[i].y & 0xFFFF));
                sts64(ti + (ng + j) * 32, ((e[i].x & 0xF800FFFFu) + (i0 + i) * 64) | (((e[i].y >> 16) & 15) > 5 ? 14u << 16 : 13u << 16), (e[i].y & 0xFFFF0000u) | row);
            }
        }
        __syncwarp();
        sts32(sb + SM_TINFO + gn * 32 + lane * 4, lane & 1 ? tab_at(NONE) : 0);
        sts32(sb + SM_MISC + 16, gn);
    }
    sts32(sb + SM_MISC + 28, gn);
    __syncwarp();
    if (lane == 0) mbar_arrive(sb + SM_ABAR + 32);
    return step < 0 ? 0 : gn;
}
__device__ __forceinline__ uint32_t bin_bits(uint32_t b) { return (1u << (b & 7)) | ((b < 48 ? 0x100u : 0x400u) << (b >> 3)); }
__device__ __forceinline__ void place(uint32_t sbase, uint32_t slot, uint32_t v, uint32_t eb) {
    asm volatile("{\n.reg .pred p;\nsetp.lt.u32 p, %0, %5;\n@p st.shared.u32 [%1], %2;\n@p st.shared.u16 [%3], %4;\n}"
                 :: "r"(slot), "r"(sbase + SM_EID + slot * 4), "r"(eb + (v >> 19)), "r"(sbase + SM_SRC + slot * 2), "r"(v), "n"(SLOT_CAP) : "memory");
}
__device__ __forceinline__ uint64_t desc_sw128(uint32_t a) {
    return (uint64_t)((a & 0x3FFFF) >> 4) | ((uint64_t)1 << 16) | ((uint64_t)64 << 32) | ((uint64_t)1 << 62);
}

template<bool LO32>
__global__ void __launch_bounds__(THREADS, 1)
gcn_kernel(const int* __restrict__ dst, unsigned* gbar, char* gs, const int* __restrict__ src, int E, int ch, int N, int npb, uint32_t magic,
           const __nv_bfloat16* __restrict__ x, const __nv_bfloat16* __restrict__ ea,
           const __nv_bfloat16* __restrict__ wa, const __nv_bfloat16* __restrict__ wb, const __nv_bfloat16* __restrict__ wc,
           const __nv_bfloat16* __restrict__ wu, const __nv_bfloat16* __restrict__ wv,
           __nv_bfloat16* out, int4 wrow, const __grid_constant__ CUtensorMap tm1, const __grid_constant__ CUtensorMap tm2,
           const __grid_constant__ CUtensorMap tmw, const __grid_constant__ CUtensorMap tmx)
{
    extern __shared__ __align__(1024) uint8_t smem[];
    int* cls = (int*)(smem + SM_CLS);
    int* misc = (int*)(smem + SM_MISC);
    WG0(); WS(0); CG(0);
    const uint32_t sbase = smem_u32(smem);
    const int tid = threadIdx.x, lane = tid & 31;
    const int b = blockIdx.x, nb = gridDim.x;
    const int cnt = max(0, min(ch, E - b * ch));
    const int node0 = b * npb;
    uint32_t tag = 0;
    if (tid < 384) asm volatile("ld.relaxed.gpu.global.u32 %0, [%1];" : "=r"(tag) : "l"(gbar) : "memory");
    auto dst_ld = [&](int v, uint32_t n) {
        const uint32_t off = v * (THREADS * 4) + tid * 4;
        asm volatile("{\n.reg .pred q;\nsetp.lt.u32 q, %2, %3;\n@q cp.async.cg.shared.global [%0], [%1], 16;\n}"
                     :: "r"(sbase + SM_IDX + off * 4), "l"(dst + (uint32_t)(b * ch + off)), "r"(off), "r"(n) : "memory");
    };
    dst_ld(0, min(cnt, 384 * 4));
    const int warp = (int)__reduce_max_sync(~0u, (unsigned)tid >> 5);
    const uint32_t su = __reduce_or_sync(~0u, sbase);
    if (warp >= 12) {
        const int v = warp & 3;
        const uint32_t a1 = su + SM_ABAR + (v == 0 ? 80 : v == 1 ? 120 : v == 2 ? 32 : 40);
        w_init(su + SM_ABAR + v * 8, 1); w_init(a1, 1);
        w_expect(su + SM_ABAR + v * 8, v < 3 ? min(max(cnt * 4 - v * 8192, 0), 8192) : 4 * 8192 + 2048);
        if (v < 2) w_expect(a1, v == 0 ? nb * (CE * 2) : nb * 64);
        asm volatile("fence.mbarrier_init.release.cluster;" ::: "memory");
        dst_ld(0, cnt);
    }
    #pragma unroll
    for (int v = 0; v < EPT / 4; v++) {
        if (v) {
            uint32_t c0, c1; asm volatile("mov.u32 %0, %%clock;" : "=r"(c0)); do { asm volatile("mov.u32 %0, %%clock;" : "=r"(c1)); } while (__all_sync(~0u, c1 - c0 < PD));
            dst_ld(v, cnt);
        }
        cp_commit();
    }
    if (warp == 15) {
        w_box_ld(su + SM_WR, &tmw, wrow.x, su + SM_ABAR + 24); w_box_ld(su + SM_WR + 8192, &tmw, wrow.y, su + SM_ABAR + 24);
        w_box_ld(su + SM_WR + 16384, &tmw, wrow.z, su + SM_ABAR + 24); w_ld(su + SM_WR + 24576, wc, 2048, su + SM_ABAR + 24);
        w_box_ld(su + SM_WR + 40960, &tmw, wrow.w, su + SM_ABAR + 24);
    }
    const int wg = warp >> 2, w = warp & 3;
    const int q = lane >> 2, t = lane & 3;
    const int nn = max(0, min(npb, N - node0));
    if (sbase & 1023) __trap();

    sts32(sbase + SM_DEG + tid * 4, tid < NPB_MAX ? 0 : 0x80000000u);
    if (tid < NCLS + NB_MAX) cls[tid] = tid < NCLS ? 0 : ((tid - NCLS) * 20) & 63;
    else if (warp == 8) sts32(sbase + SM_OH + lane * 4, t != (q >> 1) ? 0u : 0x00003F00u);
    else if (warp == 11) misc[lane] = lane == 5 ? TILE_CAP - TILE_X : lane == 3 ? 3 : lane == 8;
    if (warp == 14) sts32(sbase + SM_TINFO + 96 * 32 + lane * 4, lane & 1 ? tab_at(NONE) : 0);
    if (warp == 15) sts32(sbase + SM_CLAIM + lane * 4, lane == 0 ? 3 * 32 : 0x40000000);
    if (tid == 0) sts32(sbase + SM_XLIST, tag);
    tag = (tag & 1) | 2;
    if (wg < 3) {
        const uint32_t d0 = ((NPB_MAX + ((2 * lane) & 15) + 16 * (b & 1)) * 4 | (tag << 14)) * 0x10001u, d1 = d0 + 0x40004u, d2 = tag << 16;
        #pragma unroll 1
        for (int i = tid; i < (P1B + 384) / 16; i += 384) {
            sts128(sbase + SM_P1 + i * 16, make_uint4(d0, d0, d1, i == P1B / 16 + 11 ? 0x80000000u | (tag << 14) : d1));
            sts128(sbase + SM_P2 + i * 16, make_uint4(d2, d2, d2, d2)); sts128(sbase + SM_P2 + P1B - 128 + i * 16, make_uint4(d2, d2, d2, d2));
        }
    }
    WS(1);
    __syncthreads();
    if (wg == 3) tag = lds32(sbase + SM_P2) >> 16;
    uint32_t all = 0;
    if (wg == 3) all = (lds32(sbase + SM_XLIST) + 1) * nb;
    if (tid == 128) {
        asm volatile("prefetch.tensormap [%0];" :: "l"((uint64_t)&tm1) : "memory");
        asm volatile("prefetch.tensormap [%0];" :: "l"((uint64_t)&tm2) : "memory");
        asm volatile("prefetch.tensormap [%0];" :: "l"((uint64_t)&tmx) : "memory");
    }
    const uint32_t m4 = __reduce_or_sync(~0u, -4 * npb);
    uint32_t ent[EPT];
    #pragma unroll
    for (int v = 0; v < EPT / 4; v++) {
        if (v == 0) cp_wait<2>(); else if (v == 1) cp_wait<1>(); else cp_wait<0>();
        if (v == 0 && wg == 2 && w < 3) {
            const int n = min(cnt * 4 - w * 8192, 8192);
            if (n > 0) w_ld(su + SM_XU + w * 8192, src + b * ch + w * 2048, n, su + SM_ABAR + w * 8);
        }
        const uint32_t off = v * (THREADS * 4) + tid * 4;
        if (off < (uint32_t)cnt) {
            const uint4 u = lds128(sbase + SM_IDX + off * 4);
            uint32_t dv[4] = {u.x, u.y, u.z, u.w}, ps[4], ck[4];
            uint32_t* en = ent + 4 * v;
            #pragma unroll
            for (int k = 0; k < 4; k++) {
                dv[k] = min(dv[k], (uint32_t)(nb * npb - 1));
                ps[k] = __umulhi(dv[k], magic);
                asm volatile("atom.shared.add.u32 %0, [%1], 0x10001;" : "=r"(ck[k]) : "r"(sbase + SM_HIST + ps[k] * 4) : "memory");
            }
            #pragma unroll
            for (int k = 0; k < 4; k++) {
                dv[k] = ps[k] * m4 + (dv[k] * 4 + (tag << 14));
                en[k] = (ck[k] & 63) + ps[k] * CE;
            }
            if (__builtin_expect(max(max(ck[0], ck[1]), max(ck[2], ck[3])) >= CE << 16, 0)) {
                auto step = [&]() {
                    uint32_t e = en[0];
                    const uint32_t d = dv[0];
                    if (ck[0] >= CE << 16) {
                        uint32_t j; asm volatile("atom.shared.inc.u32 %0, [%1], 0x7fffffff;" : "=r"(j) : "r"(sbase + SM_MISC + 8) : "memory");
                        j = min(j + (j >= 15), 63u);
                        sts32(sbase + SM_L1 + j * 4, d | ((j < 63 ? e / CE : 255u) << 16));
                        e = NB_MAX * CE + j;
                    }
                    en[0] = en[1]; en[1] = en[2]; en[2] = en[3]; en[3] = e;
                    dv[0] = dv[1]; dv[1] = dv[2]; dv[2] = dv[3]; dv[3] = d;
                    ck[0] = ck[1]; ck[1] = ck[2]; ck[2] = ck[3];
                };
                if (v == 2) { step(); step(); step(); step(); }
                else {
                    #pragma unroll 1
                    for (int k = 0; k < 4; k++) step();
                }
            }
            #pragma unroll
            for (int k = 0; k < 4; k++)
                asm volatile("st.shared.u16 [%0], %1;" :: "r"(sbase + SM_P1 + en[k] * 2), "r"(dv[k]) : "memory");
        }
    }
    if (warp == 15) {
        #pragma unroll
        for (int v = 0; v < EPT / 4; v++) sts128(sbase + SM_ENT + v * 512 + lane * 16, make_uint4(ent[4*v], ent[4*v+1], ent[4*v+2], ent[4*v+3]));
    }
    asm volatile("fence.proxy.async.shared::cta;" ::: "memory");
    WS(5);
    __syncthreads();
    if (warp == 15) {
        w_inc(gbar + 1);
        const uint32_t n = __reduce_or_sync(~0u, lds32(su + SM_MISC + 8));
        if (__builtin_expect(n > 15, 0)) {
            const uint2 r = lds64(su + SM_L1 + lane * 8);
            uint32_t m = lane < 8 ? 0 : (r.x >> 24 ? 0 : bin_bits(r.x >> 16)) | (r.y >> 24 ? 0 : bin_bits(r.y >> 16));
            m = n > 62 ? 0x7FFF3FFFu : __reduce_or_sync(~0u, m);
            sts32(su + SM_L1 + 60, m | 0x80000000u | (tag << 14));
            asm volatile("fence.proxy.async.shared::cta;" ::: "memory");
            __syncwarp();
        }
        w_st(gs + G_H1 + b * 64, su + SM_L1, 64);
        w_box_st(&tm1, b * (CE / 2), su + SM_P1);
        w_st(gs + G_L + b * 512, su + SM_L1, 256);
        asm volatile("cp.async.bulk.commit_group;" ::: "memory");
    } else {
        mbar_wait_c(su + SM_ABAR, 0);
        auto put = [&](uint32_t off, const uint32_t* uu) {
            if (off < (uint32_t)cnt) {
                const uint4 sv = lds128(sbase + SM_XU + off * 4);
                const uint32_t ss[4] = {sv.x, sv.y, sv.z, sv.w};
                #pragma unroll
                for (int k = 0; k < 4; k++) sts32(sbase + SM_P2 + uu[k] * 4, (ss[k] & 0xFFFF) | (((off + k) << 19) + (tag << 16)));
            }
        };
        #pragma unroll
        for (int v = 0; v < EPT / 4; v++) { if (v) mbar_wait_c(su + SM_ABAR + v * 8, 0); put(v * (THREADS * 4) + tid * 4, ent + 4 * v); }
        if (wg == 3) {
            const uint4 e = lds128(sbase + SM_ENT + w * 512 + lane * 16);
            const uint32_t uu[4] = {e.x, e.y, e.z, e.w};
            put(w * (THREADS * 4) + (480 + lane) * 4, uu);
        }
        asm volatile("fence.proxy.async.shared::cta;" ::: "memory");
        WS(7);
        __syncwarp();
        asm volatile("bar.arrive 12, 512;" ::: "memory");
    }
    WS(8);

    const int ngroups = (nn + 3) >> 2;
    if (warp < 12) {
        asm volatile("setmaxnreg.inc.sync.aligned.u32 152;");
        const uint32_t ab = su + SM_ABAR;
        uint32_t wf[40], wn[16];
        const uint32_t mo = sbase + (8 * (lane >> 4) + (lane & 7)) * 128 + (((2 * w + ((lane >> 3) & 1)) ^ (lane & 7)) << 4);
        const uint32_t wca = __shfl_sync(~0u, sbase + SM_WC + (16 * w + q) * 32 + t * 4 + ((q >> 2) << 4), lane), l16 = __shfl_sync(~0u, (lane & 15) * 16, lane);
        mbar_wait_c(ab + 24, 0);
        {
            #pragma unroll
            for (int ks = 0; ks < 4; ks++) { ldsm4t(wf + 4 * ks, mo + SM_WR + ks * 2048); ldsm4t(wf + 20 + 4 * ks, mo + SM_WR + 8192 + ks * 2048); ldsm4t(wn + 4 * ks, mo + SM_WR + 16384 + ks * 2048); }
            auto half = [](uint32_t& v) { asm("mul.rn.bf16x2 %0, %0, %1;" : "+r"(v) : "r"(0x3F003F00u)); };
            uint32_t z = 0;
            #pragma unroll
            for (int i = 0; i < 16; i++) { half(wf[i]); z ^= wf[i]; }
            sts32(sbase + SM_ES + lane * 4, z);
            if (wg == 2) {
                uint32_t f[4];
                ldsm4t(f, (mo ^ ((lane & 7) << 4)) + SM_WR + 24576);
                half(f[0]); half(f[1]); half(f[2]); half(f[3]);
                sts32(wca, f[0]); sts32(wca + 256, f[1]); sts32(wca ^ 16, f[2]); sts32((wca ^ 16) + 256, f[3]);
                asm volatile("fence.proxy.async.shared::cta;" ::: "memory");
            }
        }
        const uint64_t wcd = __reduce_or_sync(~0u, (((sbase + SM_WC) & 0x3FFFF) >> 4) | (8u << 16)) | EDHI;
        const uint32_t bar0 = __reduce_or_sync(~0u, sbase + SM_BARS + wg * 2 * STG);
        const uint32_t xd0 = __reduce_or_sync(~0u, (((sbase + SM_XS + wg * NSTAGE * XS_BYTES) & 0x3FFFF) >> 4) | (1u << 16));
        const uint32_t ed0 = __reduce_or_sync(~0u, (((sbase + SM_ES + wg * NSTAGE * ES_BYTES) & 0x3FFFF) >> 4) | (8u << 16));
        const uint64_t ohd = __reduce_or_sync(~0u, ((sbase + SM_OH) & 0x3FFFF) >> 4);
        const uint32_t tabx = __reduce_or_sync(~0u, sbase + SM_TAB + w * 128);
        const uint32_t bars = __reduce_or_sync(~0u, 2 * bar0 + STG), xds = __reduce_or_sync(~0u, 2 * xd0 + XS_BYTES / 16), eds = __reduce_or_sync(~0u, 2 * ed0 + ES_BYTES / 16);
        const uint32_t xuo = __reduce_or_sync(~0u, sbase + SM_XU + wg * 16384);
        { const uint2 z = lds64(sbase + SM_OH + 8); wf[38] = z.x; wf[39] = z.y; }
        WS(9);
        constexpr int NU = 6;
        const uint32_t dm = ((NPB_MAX + lane) * 4 | (tag << 14)) * 0x10001u;
        const uint32_t db = sbase + SM_DEG - (tag << 14);
        const char* const g1 = gs + (uint32_t)(b * (P1B + P2B) + tid * 8);
        int rk[NU][4];
        uint32_t spins = 0;
        {
            uint2 r1[NU];
            mbar_wait_c(ab + 80, 0);
            WS(2);
            #pragma unroll
            for (int i = 0; i < NU; i++) {
                r1[i] = make_uint2(dm, dm);
                if (NB_MIN * 16 >= 384 * (i + 1) || tid + 384 * i < nb * 16) r1[i] = lds64(sbase + SM_IDX + (tid + 384 * i) * 8);
            }
            #pragma unroll 1
            while (true) {
                uint32_t bad = 0;
                #pragma unroll
                for (int i = 0; i < NU; i++) bad |= r1[i].y ^ dm;
                if (__builtin_expect(!__any_sync(~0u, bad & 0xC000), 1)) break;
                #pragma unroll
                for (int i = 0; i < NU; i++) ld_unit(r1[i], g1 + 384 * 8 * i, (r1[i].y ^ dm) & 0xC000);
                if (++spins > (1u << 22)) break;
            }
            WS(3);
            #pragma unroll
            for (int i = 0; i < NU; i++) {
                rk[i][0] = r1[i].x & 0xFFFF; rk[i][1] = r1[i].x >> 16; rk[i][2] = r1[i].y & 0xFFFF; rk[i][3] = r1[i].y >> 16;
                #pragma unroll
                for (int k = 0; k < 4; k++) asm volatile("red.shared.add.u32 [%0], 1;" :: "r"(db + min((uint32_t)rk[i][k], NPB_MAX * 4 + (tag << 14))) : "memory");
            }
        }
        WS(10);
        asm volatile("bar.sync 11, 512;" ::: "memory");
        int mycls = 0, mycr = 0, dg = lds32(sbase + SM_DEG + tid * 4);
        if (tid < nn) {
            mycls = NCLS - 1 - (dg <= 40 ? dg : min(41 + ((dg - 41) >> 3), NCLS - 1)); mycr = atomicAdd(&cls[mycls], 1);
        }
        int s0 = 0;
        if (__builtin_expect(dg > 40, 0)) s0 = max(SLOT_CAP - ((dg + 1) & ~1) - atomicAdd(&misc[6], (dg + 1) & ~1), 0);
        asm volatile("bar.sync 1, 384;" ::: "memory");
        WS(12);
        {
            const uint2 c = lds64(sbase + SM_CLS + lane * 8);
            const int v0 = c.x * (lane > 11 ? ((64 - 2 * lane) << 16) + 1 : 1), v1 = c.y * (lane >= 11 ? ((62 - 2 * lane) << 16) + 1 : 1);
            int inc = v0 + v1;
            #pragma unroll
            for (int o = 1; o < 32; o <<= 1) { int y = __shfl_up_sync(~0u, inc, o); if (lane >= o) inc += y; }
            const int e0 = __shfl_sync(~0u, inc - v0 - v1, mycls >> 1), e1 = __shfl_sync(~0u, inc - v1, mycls >> 1);
            const int e = (mycls & 1) ? e1 : e0;
            if (tid < nn) {
                if (dg <= 40) s0 = min((e >> 16) + mycr * ((dg + 1) & ~1), SLOT_CAP - 40);
                sts32(sbase + SM_DEG + tid * 4, s0);
            }
            const uint32_t pos = tid < nn ? (e & 0xFFFF) + mycr : tid;
            sts32(sbase + SM_SORT + pos * 4, tid < nn ? (uint32_t)tid | ((uint32_t)s0 << 16) : NONE);
            asm volatile("st.shared.u16 [%0], %1;" :: "r"(sbase + SM_SDEG + pos * 2), "r"(min(dg, 65535)) : "memory");
            if (tid == 383) { misc[4] = (nn - c.y + 3) >> 2; if ((inc >> 16) + misc[6] > SLOT_CAP - 40) misc[1] = 1; }
        }
        asm volatile("bar.sync 1, 384;" ::: "memory");
        WS(13);
        const uint32_t sv = lds32(sbase + SM_SORT + tid * 4);
        const uint2 d4 = lds64(sbase + SM_SDEG + (tid >> 2) * 8);
        const uint32_t slow = lds32(sbase + SM_MISC + 4);
        #pragma unroll
        for (int i = 0; i < NU; i++) {
            #pragma unroll
            for (int k = 0; k < 4; k++) rk[i][k] = atoms_inc(db + rk[i][k]);
        }
        if (__reduce_or_sync(~0u, slow) == 0) {
            const uint32_t nd = sv & 0xFFFF;
            const int g = tid >> 2;
            dg = ((t & 2 ? d4.y : d4.x) >> (16 * (t & 1))) & 0xFFFF;
            const uint32_t hi2 = __vmaxu2(d4.x, d4.y), lo2 = __vminu2(d4.x, d4.y);
            const int mx = max(hi2 >> 16, hi2 & 0xFFFF), mn = min(lo2 >> 16, lo2 & 0xFFFF);
            int left = (mx + 1) >> 1;
            int tl = g, nx = ngroups + 4 + g, nt = left > NPMAX ? 2 : 1;
            const bool odd = left > 2 * NPMAX || (nt == 2 && nx >= TILE_CAP - TILE_X);
            if (__builtin_expect(__any_sync(~0u, odd), 0)) {
                if (odd) nt = (left + NPMAX - 1) / NPMAX;
                if (odd && t == 0) { asm volatile("atom.shared.add.u32 %0, [%1], %2;" : "=r"(nx) : "r"(sbase + SM_MISC + 20), "r"(nt - 1) : "memory"); if (nx + nt - 1 > TILE_CAP) misc[1] = 1; }
                nx = __shfl_sync(~0u, nx, lane & ~3);
                if (odd && nx + nt - 1 > TILE_CAP) left = 0;
            }
            const uint32_t w0 = tab_at(nd);
            if (g >= ngroups + 4) tl = ngroups;
            uint32_t cont = 0;
            int done = 0;
            bool act = true;
            do {
                int np = nt <= 2 ? (left + nt - 1) >> (nt - 1) : (left + nt - 1) / nt;
                left -= np; nt = max(nt - 1, 1);
                if (np) np = max(np, NPMIN);
                const int dv = min(max(dg - done, 0), 2 * np);
                uint32_t code = (uint32_t)np | cont | (left > 0 ? C_MORE : 0u);
                const bool gen = mn - done < 2 * np - (np == NPMIN ? 1 : 2);
                if (np == 0) code = 0;
                const uint32_t w1 = code | (dv == 2 * np ? 0x8000u : (2 * np - 1 - dv) << 8);
                if (act) *(uint2*)(smem + SM_TINFO + tl * 32 + t * 8) = make_uint2((dv ? (sv >> 16) + done : 0) | ((gen ? (np > 8 ? 15 : np > 5 ? 14 : 13) : np) << 16) | ((left > 0 ? nx : g >= ngroups - (KM + 3)) << 20) | ((uint32_t)dv << 27), w0 | (np == 0 ? 0u : w1 << 16));
                tl = nx++; cont = C_CONT; done += 2 * np; act = left > 0;
            } while (__any_sync(~0u, act));
        }
        __syncwarp();
        asm volatile("bar.arrive 4, 512;" ::: "memory");
        WS(14);
        wf[16] = lds32(wca); wf[17] = lds32(wca + 256); wf[18] = lds32(wca ^ 16); wf[19] = lds32((wca ^ 16) + 256);
        #pragma unroll
        for (int pc = 0; pc < 3; pc++) {
            uint4 r2[2];
            mbar_wait_c(ab + pc * 8, 1);
            if (pc == 0) WS(4); if (pc == 2) WS(16);
            #pragma unroll
            for (int k = 0; k < 2; k++) {
                r2[k] = lds128(sbase + SM_P2 + (tid + 384 * (2 * pc + k)) * 16);
                if (rk[2 * pc + k][0] < 0) r2[k].w = tag << 16;
            }
            while (__builtin_expect(__any_sync(~0u, ((r2[0].w ^ (tag << 16)) | (r2[1].w ^ (tag << 16))) & 0x30000), 0)) {
                #pragma unroll
                for (int k = 0; k < 2; k++)
                    ld_unit(r2[k], g1 + (uint32_t)(tid * 8) + (P1B + 384 * 16 * (2 * pc + k)), (r2[k].w ^ (tag << 16)) & 0x30000);
                if (++spins > (1u << 22)) break;
            }
            #pragma unroll
            for (int k = 0; k < 2; k++) {
                const int i = 2 * pc + k;
                const uint32_t eb = ((tid >> 4) + 24 * i) * ch;
                place(sbase, rk[i][0], r2[k].x, eb); place(sbase, rk[i][1], r2[k].y, eb); place(sbase, rk[i][2], r2[k].z, eb); place(sbase, rk[i][3], r2[k].w, eb);
            }
        }
        WGD();
        __syncwarp();
        asm volatile("bar.arrive 3, 480;" ::: "memory");
        float g[4 * NPMAX], h[4 * NPMAX];
        float4 cyr = make_float4(0.f, 0.f, 0.f, 0.f);
        WS(15); CG(1);
        mbar_wait_c(ab + 88 + wg * 8, 0);
        auto pack = [&](uint32_t* v, const float* u) {
            #pragma unroll
            for (int i = 0; i < 16; i++) v[i] = pack_bf16(u[2*i], u[2*i+1]);
        };
        auto rows_st = [&](uint32_t p, const uint32_t* v) {
            #pragma unroll
            for (int i = 0; i < 4; i++) stsm4t(p + i * 2048, v + 4 * i);
        };
        {
            const uint64_t d0 = desc_sw128(xuo), d1 = d0 + 512;
            const uint32_t mr = sbase + wg * 16384 + w * 128 + (tab_at(8 * (lane >> 4) + (lane & 7)) ^ ((lane & 8) << 1));
            uint32_t v[16];
            node_mma(g, wn, d0); node_mma(h, wn, d1);
            TileMMA<8>::wait_g(g);
            pack(v, g); rows_st(mr + SM_TAB, v);
            TileMMA<8>::wait_h(h);
            #pragma unroll
            for (int ks = 0; ks < 4; ks++) ldsm4t(wn + 4 * ks, mo + SM_WR + 40960 + ks * 2048);
            node_mma(g, wn, d0);
            if (wg == 2) asm volatile("bar.sync 5, 384;" ::: "memory"); else asm volatile("bar.arrive 5, 384;" ::: "memory");
            pack(v, h); rows_st(mr + SM_TAB + 8192, v);
            node_mma(h, wn, d1);
            __syncwarp();
            if (lane == 0) mbar_arrive(sbase + SM_ABAR + 112);
            TileMMA<8>::wait_g(g);
            pack(v, g);
            asm volatile("bar.sync %0, 128;" :: "r"(8 + wg) : "memory");
            rows_st(mr + SM_XU, v);
            TileMMA<8>::wait_h(h);
            pack(v, h);
            asm volatile("bar.sync %0, 128;" :: "r"(8 + wg) : "memory");
            rows_st(mr + SM_XU + 8192, v);
            __syncwarp();
            if (lane == 0) mbar_arrive(sbase + SM_ABAR + 72);
            mbar_wait_c(ab + 112, 0);
            __syncwarp();
            if (__builtin_expect(__reduce_or_sync(~0u, misc[1]) != 0, 0)) { slow_bin(x, ea, src, dst, wa, wb, wc, wu, wv, out, E, node0, nn, 384); asm volatile("exit;"); }
            WS(6);
        }
        uint32_t bar = bar0, xd = xd0, ed = ed0, ph = 0;
        float pn0 = 0.f, pd0 = 1.f, pn1 = 0.f, pd1 = 1.f;
        uint4 rc;
        rc.x = lds32(sbase + SM_TINFO + wg * 32 + ((lane >> 1) & 3) * 8 + 4);
        uint32_t code = __reduce_or_sync(~0u, rc.x >> 16);
        rc.x = (rc.x & 0xFFFF) ^ ((lane & 8) << 1);
        uint32_t pst = tabx + tab_at(NONE);
        auto fetch_a = [&]() {
            asm volatile("ldmatrix.sync.aligned.m8n8.x2.trans.shared.b16 {%0,%1}, [%2];" : "=r"(wf[36]), "=r"(wf[37]) : "r"(tabx + rc.x) : "memory");
        };
        auto emit = [&]() {
            asm volatile("stmatrix.sync.aligned.m8n8.x1.trans.shared.b16 [%0], {%1};" :: "r"(pst), "r"(pack_bf16(pn0 * rcpf(pd0), pn1 * rcpf(pd1))) : "memory");
        };
        auto carry = [&]() {
            if (rc.z & C_CONT) { pn0 += cyr.x; pd0 += cyr.y; pn1 += cyr.z; pd1 += cyr.w; }
            if (rc.z & C_MORE) { cyr = make_float4(pn0, pd0 - EPS2, pn1, pd1 - EPS2); pn0 = pn1 = 0.f; pst = tabx + tab_at(NONE); }
        };
        fetch_a();
        while (true) {
            switch (code & 15) {
                default: goto finished;
#define TILE(P) { \
                    bool ok; float dmin; \
                    do { \
                        mbar_wait_c(bar, ph); \
                        TileMMA<P>::issue(g, h, wf, xd, ed | EDHI, ohd, wcd); \
                        const uint32_t eb = bar + 8; \
                        ph ^= bar != bar0; bar = bars - bar; xd = xds - xd; ed = eds - ed; \
                          \
                        asm volatile("{\n.reg .pred p;\nsetp.eq.u32 p, %0, 77;\n@p trap;\n}" :: "r"(xds) : "memory"); \
                        rc = lds128(eb + 8 + l16); \
                        TileMMA<P>::wait_g(g); \
                        fetch_a(); emit(); \
                        TileMMA<P>::wait_h(h); \
                        mbar_arrive(eb); \
                        asm volatile("add.u32 %0, %1, %2;" : "=r"(pst) : "r"(rc.y), "r"(tabx)); \
                        ok = epi_fast<P>(g, h, __uint_as_float(rc.z), __uint_as_float(rc.w), pn0, pd0, pn1, pd1, dmin); \
                    } while (__all_sync(~0u, ok)); \
                    code = __reduce_or_sync(~0u, rc.w); \
                    if (__builtin_expect(__any_sync(~0u, ((rc.z & 0x1F00) != 0) | (dmin < TAU * 2 * P)), 0)) { \
                        int dv; \
                        const bool on = unpad(rc.z, P, g[4 * P - 4], g[4 * P - 2], pd0, pd1, dv); \
                        const uint32_t bad = __ballot_sync(~0u, on); \
                        if (__builtin_expect(bad != 0, 0)) { \
                            const float4 r = epi_exact<P>(g, h, bad, on, dv, su + SM_COPY, l16); \
                            if (on) { pn0 = r.x; pd0 = r.y; pn1 = r.z; pd1 = r.w; } \
                        } \
                    } \
                    if (code & C_BRK) { carry(); if (P != 11 && (code & 15) == P) goto L##P; } \
                    if (P == 11) {         \
                        wf[16] = lds32(wca); wf[17] = lds32(wca + 256); wf[18] = lds32(wca ^ 16); wf[19] = lds32((wca ^ 16) + 256); \
                    } }
#define CASE(P, UP, DN) case P: L##P: TILE(P) \
                    if (P > NPMIN && (code & 15) == P - 1) goto L##DN; \
                    if ((code & 15) == UP) goto L##UP; \
                    break;
                CASE(11, 11, 10) CASE(10, 11, 9) CASE(9, 10, 8) CASE(8, 9, 7) CASE(7, 8, 6) CASE(6, 7, 5) CASE(5, 6, 5)
#undef CASE
#undef TILE
            }
        }
finished:
        emit();
        __syncwarp();
        if (lane == 0) mbar_arrive(sbase + SM_ABAR + 48 + wg * 8);
    } else {
        asm volatile("setmaxnreg.dec.sync.aligned.u32 56;");
        auto x_ld = [&](int i0, int i1) {
            #pragma unroll
            for (int i = i0; i < i1; i++) w_box_ld(su + SM_XU + i * 8192, &tmx, node0 + i * 64, su + SM_ABAR + 88 + (i >> 1) * 8);
        };
        if (w < 3) {
            #pragma unroll
            for (int i = 0; i < 2; i++) { w_init(su + SM_BARS + (w * 2 + i) * STG, 64); w_init(su + SM_BARS + (w * 2 + i) * STG + 8, 128); }
            w_init(su + SM_ABAR + 48 + w * 8, 4);
            w_init(su + (w == 0 ? SM_GBAR + 99 * 8 : w == 1 ? SM_ABAR + 72 : SM_ABAR + 112), w == 0 ? 32 : 12);
        } else {
            #pragma unroll
            for (int i = 0; i < 4; i++) { w_init(su + SM_ABAR + (i < 3 ? 88 + i * 8 : 40), 1); w_expect(su + SM_ABAR + (i < 3 ? 88 + i * 8 : 40), i < 3 ? 16384 : nb * 64); }
            asm volatile("fence.mbarrier_init.release.cluster;" ::: "memory");
            w_hint(gbar + 1, all);
            asm volatile("cp.async.bulk.wait_group.read 0;" ::: "memory");
            WS(2);
            w_ld(su + SM_IDX, gs + b * (P1B + P2B), nb * (CE * 2), su + SM_ABAR + 80);
            w_ld(su + SM_H1, gs + G_H1, nb * 64, su + SM_ABAR + 120);
            asm volatile("bar.sync 12, 512;" ::: "memory");
            w_box_st(&tm2, P1B / 4 + b * CE, su + SM_P2);
            w_st(gs + G_H2 + b * 64, su + SM_P2 + P2B, 64);
            w_st(gs + G_L + b * 512 + 256, su + SM_P2 + P2B, 256);
            w_sent(gbar + 4, su + SM_MISC + 32);
            asm volatile("cp.async.bulk.commit_group;" ::: "memory");
        }
        const uint32_t ab = su + SM_ABAR;
        uint32_t todo = 0;
        const uint32_t mb = (lane & 3) == 3 ? bin_bits(b) : ~0u;
        WS(12);
        mbar_wait_c(ab + 120, 0);
        WS(13);
        {
            uint4 r[5];
            #pragma unroll
            for (int i = 0; i < 5; i++) r[i] = lds128(sbase + SM_H1 + (tid - 384 + 128 * i) * 16);
            #pragma unroll
            for (int i = 0; i < 5; i++) {
                const uint32_t bb = b << 16;
                const uint32_t m = min(min(r[i].x ^ bb, r[i].y ^ bb), min(r[i].z ^ bb, r[i].w ^ bb)) >> 16;
                if ((m == 0) | (((r[i].w ^ (tag << 14)) & 0xC000) != 0) | ((~r[i].w & mb) == 0)) todo |= 1 << i;
            }
            todo &= tid - 384 + 512 < nb * 4 ? 31 : tid - 384 + 384 < nb * 4 ? 15 : 7;
        }
        #pragma unroll 1
        for (int put = 0; put < 2; put++) {
            uint32_t any = __reduce_or_sync(~0u, todo), m = 0, u = 0;
            #pragma unroll 1
            while (any | m) {
                uint4 r = make_uint4(0, 0, 0, 0), r2 = r;
                uint32_t s, go, gd;
                bool on;
                if (__builtin_expect(m == 0, 1)) {
                    const uint32_t i = __ffs(any) - 1;
                    any &= any - 1; u = tid - 384 + 128 * i; on = (todo >> i) & 1;
                    r = lds128(sbase + SM_H1 + u * 16); r2 = lds128(sbase + SM_H2 + u * 16);
                    s = u >> 2; go = G_H1 + u * 16; gd = HB;
                } else {
                    s = ((u & ~31) + __ffs(m) - 1) >> 2; m &= m - 1; on = lane < 12;
                    go = G_L + s * 512 + 64 + lane * 16; gd = 256;
                }
                #pragma unroll 1
                for (int n = 0; n < (1 << 22); n++) {
                    const bool b1 = on && ((r.w >> 14) & 3) != tag, b2 = on && put && ((r2.w >> 16) & 3) != tag;
                    if (__builtin_expect(!__any_sync(~0u, b1 | b2), 1)) break;
                    ld_unit(r, gs + go, b1); ld_unit(r2, gs + go + gd, b2);
                }
                if (gd == HB) m = __ballot_sync(~0u, on && (~r.w & mb) == 0);
                if (on && r.w >> 16 == 255) sts32(sbase + SM_MISC + 4, 1);
                const uint32_t e[4] = {r.x, r.y, r.z, r.w}, v[4] = {r2.x, r2.y, r2.z, r2.w};
                uint32_t slot[4];
                #pragma unroll
                for (int k = 0; k < 4; k++) slot[k] = atoms_inc(sbase + SM_DEG + (on && e[k] >> 16 == (uint32_t)b ? (e[k] & 0x3FFF) : (NPB_MAX + lane) * 4));
                if (put) {
                    #pragma unroll
                    for (int k = 0; k < 4; k++) place(sbase, slot[k], v[k], s * ch);
                }
            }
            if (put == 0) {
                WS(4);
                asm volatile("bar.arrive 11, 512;" ::: "memory");
                if (w == 3) {
                    x_ld(0, 1);
                    w_expect(su + SM_ABAR, 12288); w_expect(su + SM_ABAR + 8, 12288); w_expect(su + SM_ABAR + 16, nb * (CE * 4) - 24576);
                    w_hint(gbar + 4, all);
                    asm volatile("cp.async.bulk.wait_group.read 0;" ::: "memory");
                    WS(3);
                    const char* g2 = gs + b * (P1B + P2B) + P1B;
                    w_ld(su + SM_P2, g2, 12288, su + SM_ABAR);
                    w_ld(su + SM_P2 + 12288, g2 + 12288, 12288, su + SM_ABAR + 8);
                    w_ld(su + SM_P2 + 24576, g2 + 24576, nb * (CE * 4) - 24576, su + SM_ABAR + 16);
                    w_ld(su + SM_H2, gs + G_H2, nb * 64, su + SM_ABAR + 40);
                    x_ld(1, 2);
                    mbar_wait_c(ab, 1);
                    x_ld(2, 6);
                } else {
                    #pragma unroll 11
                    for (int i = 0; i < 33; i++) w_init(su + SM_GBAR + (w * 33 + i) * 8, 32);
                    w_init(su + SM_GBAR + GD * 8, 32);
                }
                asm volatile("bar.sync 4, 512;" ::: "memory");
                mbar_wait_c(ab + 40, 0);
            }
        }
        __syncwarp();
        WS(10);
        WGD();
        const uint32_t scr = sbase + SM_PAIR + (tid & 127) * 8;
        const int r4 = lane >> 3, c8 = lane & 7;
        const uint32_t sb = su;
        const uint32_t tk = ((c8 & 1) << 4) | ((c8 >> 1) << 7);
        if (w < 3) {
            const char* gx = as_pair((const char*)x + c8 * 16, scr);
            const char* ge = as_pair((const char*)ea + (lane & 1) * 16, scr);
            const uint32_t gx0 = (uint32_t)(uint64_t)gx, ge0 = (uint32_t)(uint64_t)ge, hi = (uint64_t)gx >> 32, he = (uint64_t)ge >> 32;
            const int s = (lane >> 1) & 3;
            const uint32_t xs0 = sb + SM_XS + w * NSTAGE * XS_BYTES;
            const uint32_t es0 = sb + SM_ES + w * NSTAGE * ES_BYTES + r4 * 64 + (((lane ^ (r4 >> 1)) & 1) << 4) + (s >> 1) * 256 + (s & 1) * 32;
            const uint32_t bars = sb + SM_BARS + w * 2 * STG;
            const uint32_t xoffA = (2 * r4) * 128 + ((c8 ^ (2 * r4)) << 4);
            uint64_t pol;
            asm volatile("createpolicy.fractional.L2::evict_first.b64 %0, 1.0;" : "=l"(pol));
            asm volatile("bar.sync 6, 128;" ::: "memory");
            WS(15);
            uint32_t ph = 1, cur = w;
            uint32_t hist = GD * 0x010101u;
            auto done3 = [&]() { uint32_t v = (hist >> 16) & 0xFF; asm("" : "+r"(v)); mbar_arrive(sb + SM_GBAR + v * 8); };
            const bool go = __reduce_or_sync(~0u, misc[1] == 0 && nn > 0);
            const uint32_t ra = __shfl_sync(~0u, (lane & 15) * 16 + 32, lane), k15 = __shfl_sync(~0u, 15 | (lane & 1) << 7, lane), ca = SM_CLAIM + min(lane, 30) * 4, pa = sb + SM_TINFO + r4 * 8;
            const uint32_t pb = sb + SM_TINFO + s * 8 + 4, pc = sb + SM_TINFO + (lane & 3) * 8 + 6, xl = (lane & 8) << 1, xs = ra & 16;
            auto row_of = [&](uint32_t o) { uint32_t v; asm volatile("ld.shared.u16 %0, [%1];" : "=r"(v) : "r"(pb + o) : "memory"); return v; };
            auto code_of = [&](uint32_t o) { uint32_t v; asm volatile("ld.shared.s16 %0, [%1];" : "=r"(v) : "r"(pc + o) : "memory"); return v; };
            uint32_t pw = lds32(pa + w * 32), pt = __reduce_or_sync(~0u, pw), cont = 1;
            uint4 rc = make_uint4(0, row_of(w * 32) ^ xs, code_of(w * 32) & (ONE_F | 0x1FFFu), 0);
            const uint32_t se0 = sb + SM_EID + s * 4, brs = 2 * bars + STG;
            uint32_t br = bars, da = xs0 + xoffA, de = es0, ue = ES_BYTES;
            #pragma unroll 1
            while (go) {
                uint32_t se, sx;
                asm("dp2a.lo.u32.u32 %0, %1, 4, %2;" : "=r"(se) : "r"(pw), "r"(se0));
                asm("dp2a.lo.u32.u32 %0, %1, 2, %2;" : "=r"(sx) : "r"(pw), "r"(sb + SM_SRC));
                const int dv = pw >> 27;
                const uint32_t db = da ^ 0x90;
                const uint32_t sel = (pt >> 16) & 15, nf = (pt >> 15) & (127 << 5), nx = nf == 32 ? 0u : nf;
                uint32_t g;
                auto claim = [&]() { asm volatile("atom.shared.add.u32 %0, [%1], %2;" : "=r"(g) : "r"(ca + (nx == 0 ? sb : sb + 4)), "r"(ra) : "memory"); };
                if (sel == 0) break;
                if ((cont & 1) | (nf ^ nx)) {
                    if (cont & 1) asm volatile("bar.sync 3, 480;" ::: "memory");
                    if (nf != nx) mbar_wait_c(sb + SM_ABAR + 32, 0);
                }
                switch (sel) {
#define CASE(L, P, GEN) case L: { \
                        uint32_t oe[(P + 1) / 2], o[P]; \
                        _Pragma("unroll") for (int j = 0; j < (P + 1) / 2; j++) oe[j] = lds32(se + j * 16); \
                        _Pragma("unroll") for (int j = 0; j < P; j++) o[j] = lds32(sx + j * 4); \
                        mbar_wait_h(br + 8, ph); \
                        _Pragma("unroll") for (int j = 0; j < (P + 1) / 2; j++) \
                            if (LO32) { if (!GEN && 2 * j + 2 < P) cpe<false>(he, de + j * 512, oe[j], ge0, 0, 0, pol); \
                                else if (2 * j + 1 < NPMAX || s < 2) cpe<true>(he, de + j * 512, oe[j], ge0, 4 * j + s, dv, pol); } \
                            else if (!GEN && 2 * j + 2 < P) cp16e(de + j * 512, ge, oe[j], pol); else if (2 * j + 1 < NPMAX || s < 2) cp16z<32>(de + j * 512, ge, oe[j], 4 * j + s, dv, pol); \
                        _Pragma("unroll") for (int j = 0; j < P - 1; j++) { \
                            if (LO32) { cpx<0, GEN>(hi, da + j * 1024, o[j], gx0, 2 * j, dv); cpx<1, GEN>(hi, db + j * 1024, o[j], gx0, 2 * j + 1, dv); } \
                            else if (GEN) { cp16z<128>(da + j * 1024, gx, o[j] & 0xFFFFu, 2 * j, dv, 0); cp16z<128>(db + j * 1024, gx, o[j] >> 16, 2 * j + 1, dv, 0); } \
                            else { cp16i<128>(da + j * 1024, gx, o[j] & 0xFFFFu); cp16i<128>(db + j * 1024, gx, o[j] >> 16); } } \
                        if (LO32) { cpx<0, true>(hi, da + (P - 1) * 1024, o[P - 1], gx0, 2 * P - 2, dv); cpx<1, true>(hi, db + (P - 1) * 1024, o[P - 1], gx0, 2 * P - 1, dv); } \
                        else { cp16z<128>(da + (P - 1) * 1024, gx, o[P - 1] & 0xFFFFu, 2 * P - 2, dv, 0); cp16z<128>(db + (P - 1) * 1024, gx, o[P - 1] >> 16, 2 * P - 1, dv, 0); } \
                    } break;
                    CASE(11, 11, false) CASE(6, 6, false) CASE(7, 7, false) CASE(8, 8, false) CASE(9, 9, false) CASE(10, 10, false)
                    CASE(15, NPMAX, true) CASE(14, 8, true) default: CASE(13, 5, true)
#undef CASE
                }
                claim();
                mbar_cp_arrive(br);
                done3();
                g = __reduce_min_sync(~0u, g);
                {
                    const uint32_t o = nx == 0 ? g : nx;
                    pw = lds32(pa + o);
                    const uint32_t ya = row_of(o), yb = code_of(o);
                    pt = __reduce_or_sync(~0u, pw);
                    const uint32_t brk = (cont | nx) > 1 ? C_BRK : 0u;
                    rc.x = ya ^ xl;
                    const uint32_t lv = brk | ((sel + (15 - NPMAX)) & 16) | (((pt >> 16) & 15) ^ sel);
                    rc.w = (yb & k15) | (lv ? 0x70000000u | brk : TAU_BITS);
                    asm volatile("st.shared.v4.u32 [%2], {%3, %0, %1, %4};\nxor.b32 %0, %5, %6;\nand.b32 %1, %7, %8;"
                                 : "+r"(rc.y), "+r"(rc.z) : "r"(br + ra - 16), "r"(rc.x), "r"(rc.w), "r"(ya), "r"(xs), "r"(yb), "n"(ONE_F | 0x1FFFu) : "memory");
                    cont = nx;
                }
                mbar_arrive(br);
                hist = (hist << 8) | (nx == 0 ? cur : (uint32_t)GD);
                cur = nx == 0 ? g >> 5 : cur;
                da += ue * 4; de += ue; ue = -ue;
                ph ^= br != bars; br = brs - br;
            }
            if (cont & 1) asm volatile("bar.sync 3, 480;" ::: "memory");
            if (go) {
                mbar_wait(sb + SM_ABAR + 32, 0);
                const int g0 = 3 * max((misc[7] + 2) / 3 - TR, 0) + w;
                uint32_t ro[TR], gb[TR]; uint4 xv[TR], xu[TR]; char* op[TR];
                const int gz = misc[4];
                #pragma unroll
                for (int k = 0; k < TR; k++) {
                    uint32_t nd;
                    asm volatile("ld.shared.u16 %0, [%1];" : "=r"(nd) : "r"(pa + (g0 + 3 * k) * 32 + 4) : "memory");
                    uint32_t rb = node0 * 128 + row_bytes(nd);
                    if (g0 + 3 * k >= ngroups) rb = misc[16 + ((g0 + 3 * k - ngroups) & 3) * 4 + r4];
                    if (nd == tab_at(NONE)) rb = 0;
                    xv[k] = __ldg((const uint4*)(gx + rb));
                    op[k] = nd == tab_at(NONE) ? nullptr : (char*)out + rb + c8 * 16;
                    ro[k] = sb + (nd ^ tk);
                    xu[k] = lds128(ro[k] + SM_XU);
                    gb[k] = __reduce_or_sync(~0u, g0 + 3 * k < gz ? sb + SM_GBAR + (g0 + 3 * k) * 8 : 0u);
                }
                #pragma unroll 1
                for (int k = 0; k < 3; k++) {
                    mbar_wait(k < 2 ? br + 8 : sb + SM_ABAR + 48 + w * 8, k < 2 ? ph : 0);
                    done3(); hist <<= 8;
                    ph ^= br != bars; br = brs - br;
                }
                #pragma unroll
                for (int k = 0; k < TR; k++) {
                    uint4 a = make_uint4(0, 0, 0, 0);
                    if (gb[k]) { mbar_wait(gb[k], 0); a = lds128(ro[k] + SM_TAB); }
                    finish(a, xu[k], xv[k]);
                    if (op[k]) *(uint4*)op[k] = a;
                }
            }
            cp_wait<0>();
        } else {
            const int r4 = (lane >> 1) & 3, c8 = (lane >> 3) * 2 + (lane & 1);
            const uint32_t tk = ((c8 & 1) << 4) | ((c8 >> 1) << 7);
            const char* gx = as_pair((const char*)x + (size_t)node0 * 128 + c8 * 16, scr);
            const char* ob = as_pair((const char*)out + (size_t)node0 * 128 + c8 * 16, scr);
            asm volatile("bar.sync 6, 128;" ::: "memory");
            WS(15);
            if (b == 0 && lane == 0) asm volatile("red.relaxed.gpu.global.add.u32 [%0], 1;" :: "l"(gbar) : "memory");
            if (misc[1] == 0) mbar_wait(sb + SM_ABAR + 72, 0);
            if (npb <= NPB_MAX - 4) sts32(sb + SM_MISC + 12, 0);
            int rounds = misc[1] ? 0 : max((ngroups + 2) / 3 - TR, 0);
            const int gz = misc[4];
            int fast = __reduce_min_sync(~0u, min(rounds, gz / 3));
            const uint32_t wl = SM_TINFO + r4 * 8 + 4;
            uint32_t ko = sb;
            auto row_at = [&](uint32_t a) { uint32_t n; asm volatile("ld.shared.u16 %0, [%1];" : "=r"(n) : "r"(a) : "memory"); return n; };
            auto fetch = [&](uint32_t n, uint4& v) {
                asm volatile("{\n.reg .b64 p;\ncvt.u64.u32 p, %5;\nadd.u64 p, p, %4;\nld.global.nc.L1::no_allocate.v4.u32 {%0,%1,%2,%3}, [p];\n}"
                             : "=r"(v.x), "=r"(v.y), "=r"(v.z), "=r"(v.w) : "l"(gx), "r"(n));
            };
            auto store = [&](uint32_t n, const uint4& a) {
                asm volatile("{\n.reg .b64 p;\ncvt.u64.u32 p, %1;\nadd.u64 p, p, %0;\nst.global.v4.u32 [p], {%2,%3,%4,%5};\n}" :: "l"(ob), "r"(n), "r"(a.x), "r"(a.y), "r"(a.z), "r"(a.w) : "memory");
            };
            const uint32_t tw = __shfl_sync(~0u, tk, lane);
            int step = fast > R3 + PMIN && gz == ngroups ? -1 : -2, k = 0;
            #pragma unroll 1
            do {
                const int gn = __reduce_max_sync(~0u, balance(step, gs, all, ngroups, npb));
                if (step == R3) fast = rounds = (gn + 2) / 3 - TR;
                const bool pub = step < 0 && gn;
                step = gn == 0 || step == R3 ? fast - 1 : step < 0 ? R2 : R3;
                const uint32_t lim = step == fast - 1 ? ~0u : (ngroups - (KM + 3)) * 32;
                if (fast == 0) break;
                uint32_t n0[3], o0[3]; uint4 x0[3];
                #pragma unroll
                for (int r = 0; r < 3; r++) { const uint32_t v = row_at(wl + ko + r * 32); n0[r] = row_bytes(v); o0[r] = v ^ tw; fetch(n0[r], x0[r]); }
                #pragma unroll 1
                for (; k <= step; k++) {
                    const uint32_t wn = k < step ? ko + 96 : ko, gbar = sb + SM_GBAR + k * 24;
                    uint4 xu[3], a[3]; uint32_t v[3], ok;
                    #pragma unroll
                    for (int r = 0; r < 3; r++) { xu[r] = lds128(sb + o0[r] + SM_XU); v[r] = row_at(wl + wn + r * 32); }
#define TRY(o) "mbarrier.try_wait.parity.shared.b64 p, [%1 + " o "], 0, 4000;\n@p bra A_%=;\n"
#define NEXT(o) TRY(o) TRY(o) TRY(o) "bra B_%=;\n"
                    asm volatile("{\n.reg .pred p, q, r;\n.reg .b32 c, n;\nmov.u32 n, 0;\n"
                                 "A_%=:\nmbarrier.test_wait.parity.shared.b64 p, [%1], 0;\nmbarrier.test_wait.parity.shared.b64 q, [%1 + 8], 0;\nmbarrier.test_wait.parity.shared.b64 r, [%1 + 16], 0;\n"
                                 "@!r bra W2_%=;\n@!q bra W1_%=;\n@p bra D_%=;\n"
                                 NEXT("0") "W1_%=:\n" NEXT("8") "W2_%=:\n" NEXT("16")
                                 "B_%=:\nld.volatile.shared.u32 c, [%2];\nadd.u32 n, n, 1;\nsetp.gt.u32 q, n, 0x100000;\n@q trap;\nsetp.le.u32 q, c, %3;\n@q bra A_%=;\n"
                                 "D_%=:\nselp.u32 %0, 1, 0, p;\n}" : "=r"(ok) : "r"(gbar), "r"(sb + SM_CLAIM), "r"(lim) : "memory");
#undef NEXT
#undef TRY
                    if (!ok) break;
                    #pragma unroll
                    for (int r = 0; r < 3; r++) a[r] = lds128(sb + o0[r] + SM_TAB);
                    #pragma unroll
                    for (int r = 0; r < 3; r++) {
                        finish(a[r], xu[r], x0[r]);
                        const uint32_t nd = n0[r];
                        n0[r] = row_bytes(v[r]); o0[r] = v[r] ^ tw;
                        fetch(n0[r], x0[r]);
                        store(nd, a[r]);
                    }
                    ko += 96;
                    if (pub && k == R1) {
                        uint32_t now; asm volatile("mov.u32 %0, %%globaltimer_lo;" : "=r"(now));
                        now = __reduce_max_sync(~0u, (((now + lds32(sb + SM_MISC + 48)) << 6) & ~511u) | 256);
                        sts32(sb + SM_MISC + 48, now);
                        asm volatile(ELECT "st.relaxed.gpu.global.v2.u32 [%0], {%1, %2};\n}" :: "l"(gs + G_F + b * 8), "r"(now), "r"(all) : "memory");
                    }
                }
                if (k <= R1) step = -2;
            } while (k < fast);
            #pragma unroll 1
            for (int g = 3 * fast; g < 3 * rounds; g++) {
                const uint32_t v = row_at(sb + SM_TINFO + r4 * 8 + 4 + g * 32), nd = row_bytes(v), ro = sb + (v ^ tw);
                uint4 xv, a = make_uint4(0, 0, 0, 0);
                fetch(nd, xv);
                if (g < gz) { mbar_wait(sb + SM_GBAR + g * 8, 0); a = lds128(ro + SM_TAB); }
                finish(a, lds128(ro + SM_XU), xv);
                store(nd, a);
            }
        }
    }
    WS(17); WG1(); CG(2);
}

}

extern "C" void kernel_launch(void* const* d_in, const int* in_sizes, int n_in, void* d_out, int out_size) {
    const __nv_bfloat16* x = (const __nv_bfloat16*)d_in[0];
    const __nv_bfloat16* ea = (const __nv_bfloat16*)d_in[1];
    const int* src = (const int*)d_in[2];
    const int* dst = (const int*)d_in[3];
    const __nv_bfloat16* wa = (const __nv_bfloat16*)d_in[4];
    const __nv_bfloat16* wb = (const __nv_bfloat16*)d_in[5];
    const __nv_bfloat16* wc = (const __nv_bfloat16*)d_in[6];
    const __nv_bfloat16* wu = (const __nv_bfloat16*)d_in[7];
    const __nv_bfloat16* wv = (const __nv_bfloat16*)d_in[8];
    __nv_bfloat16* out = (__nv_bfloat16*)d_out;
    int N = in_sizes[0] / 64, E = in_sizes[2];
    static int sms = 0;
    static CUtensorMap tm1, tm2, tmw, tmx;
    static bool tm_ok = false;
    static void* gp = nullptr; static void* gb = nullptr;
    typedef CUresult (*EncFn)(CUtensorMap*, CUtensorMapDataType, cuuint32_t, void*, const cuuint64_t*, const cuuint64_t*, const cuuint32_t*,
                              const cuuint32_t*, CUtensorMapInterleave, CUtensorMapSwizzle, CUtensorMapL2promotion, CUtensorMapFloatOOBfill);
    static void* fn = nullptr;
    auto enc = [&](CUtensorMap* tm, const void* base, cuuint64_t cols, cuuint64_t rows, cuuint32_t bc, cuuint32_t br, CUtensorMapSwizzle sw) {
        cuuint64_t g2[2] = {cols, rows}, gs[1] = {cols * 4};
        cuuint32_t b2[2] = {bc, br}, es[2] = {1, 1};
        return ((EncFn)fn)(tm, CU_TENSOR_MAP_DATA_TYPE_UINT32, 2, (void*)base, g2, gs, b2, es, CU_TENSOR_MAP_INTERLEAVE_NONE, sw,
                           CU_TENSOR_MAP_L2_PROMOTION_NONE, CU_TENSOR_MAP_FLOAT_OOB_FILL_NONE) == CUDA_SUCCESS;
    };
    if (!sms) {
        cudaDeviceGetAttribute(&sms, cudaDevAttrMultiProcessorCount, 0);
        cudaDriverEntryPointQueryResult qr;
        cudaGetDriverEntryPoint("cuTensorMapEncodeTiled", &fn, cudaEnableDefault, &qr);
        cudaGetSymbolAddress(&gp, g_str); cudaGetSymbolAddress(&gb, g_bar);
        if (fn && gp && gb) {
            const cuuint32_t rows = sms < NB_MAX ? sms : NB_MAX;
            tm_ok = enc(&tm1, gp, (P1B + P2B) / 4, NB_MAX, CE / 2, rows, CU_TENSOR_MAP_SWIZZLE_NONE) && enc(&tm2, gp, (P1B + P2B) / 4, NB_MAX, CE, rows, CU_TENSOR_MAP_SWIZZLE_NONE);
        }
        cudaFuncSetAttribute(gcn_kernel<true>, cudaFuncAttributeMaxDynamicSharedMemorySize, SMEM_LAUNCH);
        cudaFuncSetAttribute(gcn_kernel<false>, cudaFuncAttributeMaxDynamicSharedMemorySize, SMEM_LAUNCH);
    }
    int nb = sms < NB_MAX ? sms : NB_MAX;
    int npb = (N + nb - 1) / nb;
    int ch = (((E + nb - 1) / nb) + 3) & ~3;
    const uintptr_t wp[4] = {(uintptr_t)wb, (uintptr_t)wv, (uintptr_t)wa, (uintptr_t)wu};
    uintptr_t wlo = wp[0], whi = wp[0], wal = 0;
    for (int i = 0; i < 4; i++) { wlo = wp[i] < wlo ? wp[i] : wlo; whi = wp[i] > whi ? wp[i] : whi; wal |= wp[i] - wp[0]; }
    bool ok = tm_ok && nb >= NB_MIN && npb < NPB_MAX && ch <= CH_MAX && !(E & 3) && N <= 65535 && npb >= 2 && !(wal & 127) && (whi - wlo) >> 7 < (1u << 30) &&
              !(((uintptr_t)src | (uintptr_t)dst | (uintptr_t)x | (uintptr_t)wb | (uintptr_t)wc) & 15);
    ok = ok && enc(&tmw, (const void*)wlo, 32, ((whi - wlo) >> 7) + 64, 32, 64, CU_TENSOR_MAP_SWIZZLE_128B) && enc(&tmx, x, 32, N, 32, 64, CU_TENSOR_MAP_SWIZZLE_128B);
    if (!ok) {
        int g = 1024, p = (N + g - 1) / g;
        slow_kernel<<<g, 256>>>(x, ea, src, dst, wa, wb, wc, wu, wv, out, N, E, p < 1 ? 1 : p);
        return;
    }
    int4 wrow = make_int4((int)((wp[0] - wlo) >> 7), (int)((wp[1] - wlo) >> 7), (int)((wp[2] - wlo) >> 7), (int)((wp[3] - wlo) >> 7));
    uint32_t magic = (uint32_t)((1ull << 32) / (uint32_t)npb) + 1u;
    void* args[] = {&dst, &gb, &gp, &src, &E, &ch, &N, &npb, &magic, &x, &ea, &wa, &wb, &wc, &wu, &wv, &out, &wrow, &tm1, &tm2, &tmw, &tmx};
    const bool lo32 = ((uintptr_t)x >> 32) == (((uintptr_t)x + (size_t)N * 128 - 1) >> 32) && ((uintptr_t)ea >> 32) == (((uintptr_t)ea + (size_t)E * 32 - 1) >> 32);
    cudaLaunchCooperativeKernel(lo32 && !FORCE64 ? (const void*)gcn_kernel<true> : (const void*)gcn_kernel<false>, dim3(nb), dim3(THREADS), args, SMEM_LAUNCH, cudaStreamPerThread);
}
```

```cpp
#include <cuda_runtime.h>
#include <cuda.h>
#include <cuda_bf16.h>
#include <stdint.h>

namespace {

constexpr int N_MAX = 65536;
constexpr int NPMAX = 11;
constexpr int NPMIN = 5;
constexpr int THREADS = 512;
constexpr int EPT = 12;
constexpr int CH_MAX = THREADS * EPT;
constexpr int NB_MAX = 134, NB_MIN = 120;
constexpr int CE = 64;
constexpr int P1B = NB_MAX * CE * 2;
constexpr int P2B = NB_MAX * CE * 4;
constexpr int HB = NB_MAX * 64;
constexpr int G_H1 = NB_MAX * (P1B + P2B), G_H2 = G_H1 + HB, G_L = G_H2 + HB, G_F = G_L + NB_MAX * 512;
constexpr int KM = 4, GRP_B = 1536, G_R = G_F + 2048, G_P = G_R + 2048, G_END = G_P + NB_MAX * KM * GRP_B;
#define BAL 1
#define PMIN 8
constexpr int R1 = 9, R2 = 11, R3 = 14;
constexpr int GD = 100;
constexpr int NPB_MAX = 384;
constexpr int SLOT_CAP = 6784;
constexpr int TILE_CAP = 123;
constexpr int TILE_X = 8;
constexpr int NCLS = 64;
constexpr int NSTAGE = 2;
constexpr int PD = 300;
constexpr int TR = 2;
constexpr float LOG2E = 1.4426950408889634f;

__device__ __align__(256) uint4 g_str[G_END / 16];
__device__ __align__(128) unsigned g_bar[8];
__device__ float g_slow[N_MAX * 128];
__device__ float4 g_copy[NB_MAX * 384 * 2 * NPMAX];

#define WS(k)
#define WGD()
#define WG0()
#define WG1()
#define CG(k)
#define SMEM_LAUNCH SMEM_BYTES
#define FORCE64 0
#define EDHI ((16ull << 32) | (3ull << 62))
template<int NP> struct TileMMA;
template<> struct TileMMA<5> {
  static __device__ __forceinline__ void issue(float* g, float* h, const uint32_t* w, uint32_t dx, uint64_t de, uint64_t dh, uint64_t dc) {
    asm volatile(
      "{\n.reg .b64 dx0, dx1, dx2, dx3;\n.reg .b32 l1, l2, l3, hx;\nmov.b32 hx, 0x40000040;\n"
      "add.u32 l1, %80, 2;\nadd.u32 l2, %80, 4;\nadd.u32 l3, %80, 6;\n"
      "mov.b64 dx0, {%80, hx};\nmov.b64 dx1, {l1, hx};\nmov.b64 dx2, {l2, hx};\nmov.b64 dx3, {l3, hx};\n"
      "wgmma.fence.sync.aligned;\n"
      "wgmma.mma_async.sync.aligned.m64n40k16.f32.bf16.bf16 {%0, %1, %2, %3, %4, %5, %6, %7, %8, %9, %10, %11, %12, %13, %14, %15, %16, %17, %18, %19}, {%76, %77, %78, %79}, %82, 0, 1, 1, 0;\n"
      "wgmma.mma_async.sync.aligned.m64n40k16.f32.bf16.bf16 {%0, %1, %2, %3, %4, %5, %6, %7, %8, %9, %10, %11, %12, %13, %14, %15, %16, %17, %18, %19}, {%56, %57, %58, %59}, %81, 1, 1, 1, 0;\n"
      "wgmma.mma_async.sync.aligned.m64n40k16.f32.bf16.bf16 {%0, %1, %2, %3, %4, %5, %6, %7, %8, %9, %10, %11, %12, %13, %14, %15, %16, %17, %18, %19}, {%40, %41, %42, %43}, dx0, 1, 1, 1, 0;\n"
      "wgmma.mma_async.sync.aligned.m64n40k16.f32.bf16.bf16 {%0, %1, %2, %3, %4, %5, %6, %7, %8, %9, %10, %11, %12, %13, %14, %15, %16, %17, %18, %19}, {%44, %45, %46, %47}, dx1, 1, 1, 1, 0;\n"
      "wgmma.mma_async.sync.aligned.m64n40k16.f32.bf16.bf16 {%0, %1, %2, %3, %4, %5, %6, %7, %8, %9, %10, %11, %12, %13, %14, %15, %16, %17, %18, %19}, {%48, %49, %50, %51}, dx2, 1, 1, 1, 0;\n"
      "wgmma.mma_async.sync.aligned.m64n40k16.f32.bf16.bf16 {%0, %1, %2, %3, %4, %5, %6, %7, %8, %9, %10, %11, %12, %13, %14, %15, %16, %17, %18, %19}, {%52, %53, %54, %55}, dx3, 1, 1, 1, 0;\n"
      "wgmma.commit_group.sync.aligned;\n"
      "wgmma.mma_async.sync.aligned.m64n40k16.f32.bf16.bf16 {%20, %21, %22, %23, %24, %25, %26, %27, %28, %29, %30, %31, %32, %33, %34, %35, %36, %37, %38, %39}, {%60, %61, %62, %63}, dx0, 0, 1, 1, 0;\n"
      "wgmma.mma_async.sync.aligned.m64n40k16.f32.bf16.bf16 {%20, %21, %22, %23, %24, %25, %26, %27, %28, %29, %30, %31, %32, %33, %34, %35, %36, %37, %38, %39}, {%64, %65, %66, %67}, dx1, 1, 1, 1, 0;\n"
      "wgmma.mma_async.sync.aligned.m64n40k16.f32.bf16.bf16 {%20, %21, %22, %23, %24, %25, %26, %27, %28, %29, %30, %31, %32, %33, %34, %35, %36, %37, %38, %39}, {%68, %69, %70, %71}, dx2, 1, 1, 1, 0;\n"
      "wgmma.mma_async.sync.aligned.m64n40k16.f32.bf16.bf16 {%20, %21, %22, %23, %24, %25, %26, %27, %28, %29, %30, %31, %32, %33, %34, %35, %36, %37, %38, %39}, {%72, %73, %74, %75}, dx3, 1, 1, 1, 0;\n"
      "wgmma.commit_group.sync.aligned;\n}\n"
      : "=f"(g[0]), "=f"(g[1]), "=f"(g[2]), "=f"(g[3]), "=f"(g[4]), "=f"(g[5]), "=f"(g[6]), "=f"(g[7]), "=f"(g[8]), "=f"(g[9]), "=f"(g[10]), "=f"(g[11]), "=f"(g[12]), "=f"(g[13]), "=f"(g[14]), "=f"(g[15]), "=f"(g[16]), "=f"(g[17]), "=f"(g[18]), "=f"(g[19]),
        "=f"(h[0]), "=f"(h[1]), "=f"(h[2]), "=f"(h[3]), "=f"(h[4]), "=f"(h[5]), "=f"(h[6]), "=f"(h[7]), "=f"(h[8]), "=f"(h[9]), "=f"(h[10]), "=f"(h[11]), "=f"(h[12]), "=f"(h[13]), "=f"(h[14]), "=f"(h[15]), "=f"(h[16]), "=f"(h[17]), "=f"(h[18]), "=f"(h[19])
      : "r"(w[0]), "r"(w[1]), "r"(w[2]), "r"(w[3]), "r"(w[4]), "r"(w[5]), "r"(w[6]), "r"(w[7]), "r"(w[8]), "r"(w[9]), "r"(w[10]), "r"(w[11]), "r"(w[12]), "r"(w[13]), "r"(w[14]), "r"(w[15]), "r"(w[16]), "r"(w[17]), "r"(w[18]), "r"(w[19]), "r"(w[20]), "r"(w[21]), "r"(w[22]), "r"(w[23]), "r"(w[24]), "r"(w[25]), "r"(w[26]), "r"(w[27]), "r"(w[28]), "r"(w[29]), "r"(w[30]), "r"(w[31]), "r"(w[32]), "r"(w[33]), "r"(w[34]), "r"(w[35]), "r"(w[36]), "r"(w[37]), "r"(w[38]), "r"(w[39]), "r"(dx), "l"(de), "l"(dh)
      : "memory");
  }
  static __device__ __forceinline__ void wait_g(float* g) {
    asm volatile("wgmma.wait_group.sync.aligned 1;\n"
      : "+f"(g[0]), "+f"(g[1]), "+f"(g[2]), "+f"(g[3]), "+f"(g[4]), "+f"(g[5]), "+f"(g[6]), "+f"(g[7]), "+f"(g[8]), "+f"(g[9]), "+f"(g[10]), "+f"(g[11]), "+f"(g[12]), "+f"(g[13]), "+f"(g[14]), "+f"(g[15]), "+f"(g[16]), "+f"(g[17]), "+f"(g[18]), "+f"(g[19])
      :: "memory");
  }
  static __device__ __forceinline__ void wait_h(float* h) {
    asm volatile("wgmma.wait_group.sync.aligned 0;\n"
      : "+f"(h[0]), "+f"(h[1]), "+f"(h[2]), "+f"(h[3]), "+f"(h[4]), "+f"(h[5]), "+f"(h[6]), "+f"(h[7]), "+f"(h[8]), "+f"(h[9]), "+f"(h[10]), "+f"(h[11]), "+f"(h[12]), "+f"(h[13]), "+f"(h[14]), "+f"(h[15]), "+f"(h[16]), "+f"(h[17]), "+f"(h[18]), "+f"(h[19])
      :: "memory");
  }
};
template<> struct TileMMA<6> {
  static __device__ __forceinline__ void issue(float* g, float* h, const uint32_t* w, uint32_t dx, uint64_t de, uint64_t dh, uint64_t dc) {
    asm volatile(
      "{\n.reg .b64 dx0, dx1, dx2, dx3;\n.reg .b32 l1, l2, l3, hx;\nmov.b32 hx, 0x40000040;\n"
      "add.u32 l1, %88, 2;\nadd.u32 l2, %88, 4;\nadd.u32 l3, %88, 6;\n"
      "mov.b64 dx0, {%88, hx};\nmov.b64 dx1, {l1, hx};\nmov.b64 dx2, {l2, hx};\nmov.b64 dx3, {l3, hx};\n"
      "wgmma.fence.sync.aligned;\n"
      "wgmma.mma_async.sync.aligned.m64n48k16.f32.bf16.bf16 {%0, %1, %2, %3, %4, %5, %6, %7, %8, %9, %10, %11, %12, %13, %14, %15, %16, %17, %18, %19, %20, %21, %22, %23}, {%84, %85, %86, %87}, %90, 0, 1, 1, 0;\n"
      "wgmma.mma_async.sync.aligned.m64n48k16.f32.bf16.bf16 {%0, %1, %2, %3, %4, %5, %6, %7, %8, %9, %10, %11, %12, %13, %14, %15, %16, %17, %18, %19, %20, %21, %22, %23}, {%64, %65, %66, %67}, %89, 1, 1, 1, 0;\n"
      "wgmma.mma_async.sync.aligned.m64n48k16.f32.bf16.bf16 {%0, %1, %2, %3, %4, %5, %6, %7, %8, %9, %10, %11, %12, %13, %14, %15, %16, %17, %18, %19, %20, %21, %22, %23}, {%48, %49, %50, %51}, dx0, 1, 1, 1, 0;\n"
      "wgmma.mma_async.sync.aligned.m64n48k16.f32.bf16.bf16 {%0, %1, %2, %3, %4, %5, %6, %7, %8, %9, %10, %11, %12, %13, %14, %15, %16, %17, %18, %19, %20, %21, %22, %23}, {%52, %53, %54, %55}, dx1, 1, 1, 1, 0;\n"
      "wgmma.mma_async.sync.aligned.m64n48k16.f32.bf16.bf16 {%0, %1, %2, %3, %4, %5, %6, %7, %8, %9, %10, %11, %12, %13, %14, %15, %16, %17, %18, %19, %20, %21, %22, %23}, {%56, %57, %58, %59}, dx2, 1, 1, 1, 0;\n"
      "wgmma.mma_async.sync.aligned.m64n48k16.f32.bf16.bf16 {%0, %1, %2, %3, %4, %5, %6, %7, %8, %9, %10, %11, %12, %13, %14, %15, %16, %17, %18, %19, %20, %21, %22, %23}, {%60, %61, %62, %63}, dx3, 1, 1, 1, 0;\n"
      "wgmma.commit_group.sync.aligned;\n"
      "wgmma.mma_async.sync.aligned.m64n48k16.f32.bf16.bf16 {%24, %25, %26, %27, %28, %29, %30, %31, %32, %33, %34, %35, %36, %37, %38, %39, %40, %41, %42, %43, %44, %45, %46, %47}, {%68, %69, %70, %71}, dx0, 0, 1, 1, 0;\n"
      "wgmma.mma_async.sync.aligned.m64n48k16.f32.bf16.bf16 {%24, %25, %26, %27, %28, %29, %30, %31, %32, %33, %34, %35, %36, %37, %38, %39, %40, %41, %42, %43, %44, %45, %46, %47}, {%72, %73, %74, %75}, dx1, 1, 1, 1, 0;\n"
      "wgmma.mma_async.sync.aligned.m64n48k16.f32.bf16.bf16 {%24, %25, %26, %27, %28, %29, %30, %31, %32, %33, %34, %35, %36, %37, %38, %39, %40, %41, %42, %43, %44, %45, %46, %47}, {%76, %77, %78, %79}, dx2, 1, 1, 1, 0;\n"
      "wgmma.mma_async.sync.aligned.m64n48k16.f32.bf16.bf16 {%24, %25, %26, %27, %28, %29, %30, %31, %32, %33, %34, %35, %36, %37, %38, %39, %40, %41, %42, %43, %44, %45, %46, %47}, {%80, %81, %82, %83}, dx3, 1, 1, 1, 0;\n"
      "wgmma.commit_group.sync.aligned;\n}\n"
      : "=f"(g[0]), "=f"(g[1]), "=f"(g[2]), "=f"(g[3]), "=f"(g[4]), "=f"(g[5]), "=f"(g[6]), "=f"(g[7]), "=f"(g[8]), "=f"(g[9]), "=f"(g[10]), "=f"(g[11]), "=f"(g[12]), "=f"(g[13]), "=f"(g[14]), "=f"(g[15]), "=f"(g[16]), "=f"(g[17]), "=f"(g[18]), "=f"(g[19]), "=f"(g[20]), "=f"(g[21]), "=f"(g[22]), "=f"(g[23]),
        "=f"(h[0]), "=f"(h[1]), "=f"(h[2]), "=f"(h[3]), "=f"(h[4]), "=f"(h[5]), "=f"(h[6]), "=f"(h[7]), "=f"(h[8]), "=f"(h[9]), "=f"(h[10]), "=f"(h[11]), "=f"(h[12]), "=f"(h[13]), "=f"(h[14]), "=f"(h[15]), "=f"(h[16]), "=f"(h[17]), "=f"(h[18]), "=f"(h[19]), "=f"(h[20]), "=f"(h[21]), "=f"(h[22]), "=f"(h[23])
      : "r"(w[0]), "r"(w[1]), "r"(w[2]), "r"(w[3]), "r"(w[4]), "r"(w[5]), "r"(w[6]), "r"(w[7]), "r"(w[8]), "r"(w[9]), "r"(w[10]), "r"(w[11]), "r"(w[12]), "r"(w[13]), "r"(w[14]), "r"(w[15]), "r"(w[16]), "r"(w[17]), "r"(w[18]), "r"(w[19]), "r"(w[20]), "r"(w[21]), "r"(w[22]), "r"(w[23]), "r"(w[24]), "r"(w[25]), "r"(w[26]), "r"(w[27]), "r"(w[28]), "r"(w[29]), "r"(w[30]), "r"(w[31]), "r"(w[32]), "r"(w[33]), "r"(w[34]), "r"(w[35]), "r"(w[36]), "r"(w[37]), "r"(w[38]), "r"(w[39]), "r"(dx), "l"(de), "l"(dh)
      : "memory");
  }
  static __device__ __forceinline__ void wait_g(float* g) {
    asm volatile("wgmma.wait_group.sync.aligned 1;\n"
      : "+f"(g[0]), "+f"(g[1]), "+f"(g[2]), "+f"(g[3]), "+f"(g[4]), "+f"(g[5]), "+f"(g[6]), "+f"(g[7]), "+f"(g[8]), "+f"(g[9]), "+f"(g[10]), "+f"(g[11]), "+f"(g[12]), "+f"(g[13]), "+f"(g[14]), "+f"(g[15]), "+f"(g[16]), "+f"(g[17]), "+f"(g[18]), "+f"(g[19]), "+f"(g[20]), "+f"(g[21]), "+f"(g[22]), "+f"(g[23])
      :: "memory");
  }
  static __device__ __forceinline__ void wait_h(float* h) {
    asm volatile("wgmma.wait_group.sync.aligned 0;\n"
      : "+f"(h[0]), "+f"(h[1]), "+f"(h[2]), "+f"(h[3]), "+f"(h[4]), "+f"(h[5]), "+f"(h[6]), "+f"(h[7]), "+f"(h[8]), "+f"(h[9]), "+f"(h[10]), "+f"(h[11]), "+f"(h[12]), "+f"(h[13]), "+f"(h[14]), "+f"(h[15]), "+f"(h[16]), "+f"(h[17]), "+f"(h[18]), "+f"(h[19]), "+f"(h[20]), "+f"(h[21]), "+f"(h[22]), "+f"(h[23])
      :: "memory");
  }
};
template<> struct TileMMA<7> {
  static __device__ __forceinline__ void issue(float* g, float* h, const uint32_t* w, uint32_t dx, uint64_t de, uint64_t dh, uint64_t dc) {
    asm volatile(
      "{\n.reg .b64 dx0, dx1, dx2, dx3;\n.reg .b32 l1, l2, l3, hx;\nmov.b32 hx, 0x40000040;\n"
      "add.u32 l1, %96, 2;\nadd.u32 l2, %96, 4;\nadd.u32 l3, %96, 6;\n"
      "mov.b64 dx0, {%96, hx};\nmov.b64 dx1, {l1, hx};\nmov.b64 dx2, {l2, hx};\nmov.b64 dx3, {l3, hx};\n"
      "wgmma.fence.sync.aligned;\n"
      "wgmma.mma_async.sync.aligned.m64n56k16.f32.bf16.bf16 {%0, %1, %2, %3, %4, %5, %6, %7, %8, %9, %10, %11, %12, %13, %14, %15, %16, %17, %18, %19, %20, %21, %22, %23, %24, %25, %26, %27}, {%92, %93, %94, %95}, %98, 0, 1, 1, 0;\n"
      "wgmma.mma_async.sync.aligned.m64n56k16.f32.bf16.bf16 {%0, %1, %2, %3, %4, %5, %6, %7, %8, %9, %10, %11, %12, %13, %14, %15, %16, %17, %18, %19, %20, %21, %22, %23, %24, %25, %26, %27}, {%72, %73, %74, %75}, %97, 1, 1, 1, 0;\n"
      "wgmma.mma_async.sync.aligned.m64n56k16.f32.bf16.bf16 {%0, %1, %2, %3, %4, %5, %6, %7, %8, %9, %10, %11, %12, %13, %14, %15, %16, %17, %18, %19, %20, %21, %22, %23, %24, %25, %26, %27}, {%56, %57, %58, %59}, dx0, 1, 1, 1, 0;\n"
      "wgmma.mma_async.sync.aligned.m64n56k16.f32.bf16.bf16 {%0, %1, %2, %3, %4, %5, %6, %7, %8, %9, %10, %11, %12, %13, %14, %15, %16, %17, %18, %19, %20, %21, %22, %23, %24, %25, %26, %27}, {%60, %61, %62, %63}, dx1, 1, 1, 1, 0;\n"
      "wgmma.mma_async.sync.aligned.m64n56k16.f32.bf16.bf16 {%0, %1, %2, %3, %4, %5, %6, %7, %8, %9, %10, %11, %12, %13, %14, %15, %16, %17, %18, %19, %20, %21, %22, %23, %24, %25, %26, %27}, {%64, %65, %66, %67}, dx2, 1, 1, 1, 0;\n"
      "wgmma.mma_async.sync.aligned.m64n56k16.f32.bf16.bf16 {%0, %1, %2, %3, %4, %5, %6, %7, %8, %9, %10, %11, %12, %13, %14, %15, %16, %17, %18, %19, %20, %21, %22, %23, %24, %25, %26, %27}, {%68, %69, %70, %71}, dx3, 1, 1, 1, 0;\n"
      "wgmma.commit_group.sync.aligned;\n"
      "wgmma.mma_async.sync.aligned.m64n56k16.f32.bf16.bf16 {%28, %29, %30, %31, %32, %33, %34, %35, %36, %37, %38, %39, %40, %41, %42, %43, %44, %45, %46, %47, %48, %49, %50, %51, %52, %53, %54, %55}, {%76, %77, %78, %79}, dx0, 0, 1, 1, 0;\n"
      "wgmma.mma_async.sync.aligned.m64n56k16.f32.bf16.bf16 {%28, %29, %30, %31, %32, %33, %34, %35, %36, %37, %38, %39, %40, %41, %42, %43, %44, %45, %46, %47, %48, %49, %50, %51, %52, %53, %54, %55}, {%80, %81, %82, %83}, dx1, 1, 1, 1, 0;\n"
      "wgmma.mma_async.sync.aligned.m64n56k16.f32.bf16.bf16 {%28, %29, %30, %31, %32, %33, %34, %35, %36, %37, %38, %39, %40, %41, %42, %43, %44, %45, %46, %47, %48, %49, %50, %51, %52, %53, %54, %55}, {%84, %85, %86, %87}, dx2, 1, 1, 1, 0;\n"
      "wgmma.mma_async.sync.aligned.m64n56k16.f32.bf16.bf16 {%28, %29, %30, %31, %32, %33, %34, %35, %36, %37, %38, %39, %40, %41, %42, %43, %44, %45, %46, %47, %48, %49, %50, %51, %52, %53, %54, %55}, {%88, %89, %90, %91}, dx3, 1, 1, 1, 0;\n"
      "wgmma.commit_group.sync.aligned;\n}\n"
      : "=f"(g[0]), "=f"(g[1]), "=f"(g[2]), "=f"(g[3]), "=f"(g[4]), "=f"(g[5]), "=f"(g[6]), "=f"(g[7]), "=f"(g[8]), "=f"(g[9]), "=f"(g[10]), "=f"(g[11]), "=f"(g[12]), "=f"(g[13]), "=f"(g[14]), "=f"(g[15]), "=f"(g[16]), "=f"(g[17]), "=f"(g[18]), "=f"(g[19]), "=f"(g[20]), "=f"(g[21]), "=f"(g[22]), "=f"(g[23]), "=f"(g[24]), "=f"(g[25]), "=f"(g[26]), "=f"(g[27]),
        "=f"(h[0]), "=f"(h[1]), "=f"(h[2]), "=f"(h[3]), "=f"(h[4]), "=f"(h[5]), "=f"(h[6]), "=f"(h[7]), "=f"(h[8]), "=f"(h[9]), "=f"(h[10]), "=f"(h[11]), "=f"(h[12]), "=f"(h[13]), "=f"(h[14]), "=f"(h[15]), "=f"(h[16]), "=f"(h[17]), "=f"(h[18]), "=f"(h[19]), "=f"(h[20]), "=f"(h[21]), "=f"(h[22]), "=f"(h[23]), "=f"(h[24]), "=f"(h[25]), "=f"(h[26]), "=f"(h[27])
      : "r"(w[0]), "r"(w[1]), "r"(w[2]), "r"(w[3]), "r"(w[4]), "r"(w[5]), "r"(w[6]), "r"(w[7]), "r"(w[8]), "r"(w[9]), "r"(w[10]), "r"(w[11]), "r"(w[12]), "r"(w[13]), "r"(w[14]), "r"(w[15]), "r"(w[16]), "r"(w[17]), "r"(w[18]), "r"(w[19]), "r"(w[20]), "r"(w[21]), "r"(w[22]), "r"(w[23]), "r"(w[24]), "r"(w[25]), "r"(w[26]), "r"(w[27]), "r"(w[28]), "r"(w[29]), "r"(w[30]), "r"(w[31]), "r"(w[32]), "r"(w[33]), "r"(w[34]), "r"(w[35]), "r"(w[36]), "r"(w[37]), "r"(w[38]), "r"(w[39]), "r"(dx), "l"(de), "l"(dh)
      : "memory");
  }
  static __device__ __forceinline__ void wait_g(float* g) {
    asm volatile("wgmma.wait_group.sync.aligned 1;\n"
      : "+f"(g[0]), "+f"(g[1]), "+f"(g[2]), "+f"(g[3]), "+f"(g[4]), "+f"(g[5]), "+f"(g[6]), "+f"(g[7]), "+f"(g[8]), "+f"(g[9]), "+f"(g[10]), "+f"(g[11]), "+f"(g[12]), "+f"(g[13]), "+f"(g[14]), "+f"(g[15]), "+f"(g[16]), "+f"(g[17]), "+f"(g[18]), "+f"(g[19]), "+f"(g[20]), "+f"(g[21]), "+f"(g[22]), "+f"(g[23]), "+f"(g[24]), "+f"(g[25]), "+f"(g[26]), "+f"(g[27])
      :: "memory");
  }
  static __device__ __forceinline__ void wait_h(float* h) {
    asm volatile("wgmma.wait_group.sync.aligned 0;\n"
      : "+f"(h[0]), "+f"(h[1]), "+f"(h[2]), "+f"(h[3]), "+f"(h[4]), "+f"(h[5]), "+f"(h[6]), "+f"(h[7]), "+f"(h[8]), "+f"(h[9]), "+f"(h[10]), "+f"(h[11]), "+f"(h[12]), "+f"(h[13]), "+f"(h[14]), "+f"(h[15]), "+f"(h[16]), "+f"(h[17]), "+f"(h[18]), "+f"(h[19]), "+f"(h[20]), "+f"(h[21]), "+f"(h[22]), "+f"(h[23]), "+f"(h[24]), "+f"(h[25]), "+f"(h[26]), "+f"(h[27])
      :: "memory");
  }
};
template<> struct TileMMA<8> {
  static __device__ __forceinline__ void issue(float* g, float* h, const uint32_t* w, uint32_t dx, uint64_t de, uint64_t dh, uint64_t dc) {
    asm volatile(
      "{\n.reg .b64 dx0, dx1, dx2, dx3;\n.reg .b32 l1, l2, l3, hx;\nmov.b32 hx, 0x40000040;\n"
      "add.u32 l1, %104, 2;\nadd.u32 l2, %104, 4;\nadd.u32 l3, %104, 6;\n"
      "mov.b64 dx0, {%104, hx};\nmov.b64 dx1, {l1, hx};\nmov.b64 dx2, {l2, hx};\nmov.b64 dx3, {l3, hx};\n"
      "wgmma.fence.sync.aligned;\n"
      "wgmma.mma_async.sync.aligned.m64n64k16.f32.bf16.bf16 {%0, %1, %2, %3, %4, %5, %6, %7, %8, %9, %10, %11, %12, %13, %14, %15, %16, %17, %18, %19, %20, %21, %22, %23, %24, %25, %26, %27, %28, %29, %30, %31}, {%100, %101, %102, %103}, %106, 0, 1, 1, 0;\n"
      "wgmma.mma_async.sync.aligned.m64n64k16.f32.bf16.bf16 {%0, %1, %2, %3, %4, %5, %6, %7, %8, %9, %10, %11, %12, %13, %14, %15, %16, %17, %18, %19, %20, %21, %22, %23, %24, %25, %26, %27, %28, %29, %30, %31}, {%80, %81, %82, %83}, %105, 1, 1, 1, 0;\n"
      "wgmma.mma_async.sync.aligned.m64n64k16.f32.bf16.bf16 {%0, %1, %2, %3, %4, %5, %6, %7, %8, %9, %10, %11, %12, %13, %14, %15, %16, %17, %18, %19, %20, %21, %22, %23, %24, %25, %26, %27, %28, %29, %30, %31}, {%64, %65, %66, %67}, dx0, 1, 1, 1, 0;\n"
      "wgmma.mma_async.sync.aligned.m64n64k16.f32.bf16.bf16 {%0, %1, %2, %3, %4, %5, %6, %7, %8, %9, %10, %11, %12, %13, %14, %15, %16, %17, %18, %19, %20, %21, %22, %23, %24, %25, %26, %27, %28, %29, %30, %31}, {%68, %69, %70, %71}, dx1, 1, 1, 1, 0;\n"
      "wgmma.mma_async.sync.aligned.m64n64k16.f32.bf16.bf16 {%0, %1, %2, %3, %4, %5, %6, %7, %8, %9, %10, %11, %12, %13, %14, %15, %16, %17, %18, %19, %20, %21, %22, %23, %24, %25, %26, %27, %28, %29, %30, %31}, {%72, %73, %74, %75}, dx2, 1, 1, 1, 0;\n"
      "wgmma.mma_async.sync.aligned.m64n64k16.f32.bf16.bf16 {%0, %1, %2, %3, %4, %5, %6, %7, %8, %9, %10, %11, %12, %13, %14, %15, %16, %17, %18, %19, %20, %21, %22, %23, %24, %25, %26, %27, %28, %29, %30, %31}, {%76, %77, %78, %79}, dx3, 1, 1, 1, 0;\n"
      "wgmma.commit_group.sync.aligned;\n"
      "wgmma.mma_async.sync.aligned.m64n64k16.f32.bf16.bf16 {%32, %33, %34, %35, %36, %37, %38, %39, %40, %41, %42, %43, %44, %45, %46, %47, %48, %49, %50, %51, %52, %53, %54, %55, %56, %57, %58, %59, %60, %61, %62, %63}, {%84, %85, %86, %87}, dx0, 0, 1, 1, 0;\n"
      "wgmma.mma_async.sync.aligned.m64n64k16.f32.bf16.bf16 {%32, %33, %34, %35, %36, %37, %38, %39, %40, %41, %42, %43, %44, %45, %46, %47, %48, %49, %50, %51, %52, %53, %54, %55, %56, %57, %58, %59, %60, %61, %62, %63}, {%88, %89, %90, %91}, dx1, 1, 1, 1, 0;\n"
      "wgmma.mma_async.sync.aligned.m64n64k16.f32.bf16.bf16 {%32, %33, %34, %35, %36, %37, %38, %39, %40, %41, %42, %43, %44, %45, %46, %47, %48, %49, %50, %51, %52, %53, %54, %55, %56, %57, %58, %59, %60, %61, %62, %63}, {%92, %93, %94, %95}, dx2, 1, 1, 1, 0;\n"
      "wgmma.mma_async.sync.aligned.m64n64k16.f32.bf16.bf16 {%32, %33, %34, %35, %36, %37, %38, %39, %40, %41, %42, %43, %44, %45, %46, %47, %48, %49, %50, %51, %52, %53, %54, %55, %56, %57, %58, %59, %60, %61, %62, %63}, {%96, %97, %98, %99}, dx3, 1, 1, 1, 0;\n"
      "wgmma.commit_group.sync.aligned;\n}\n"
      : "=f"(g[0]), "=f"(g[1]), "=f"(g[2]), "=f"(g[3]), "=f"(g[4]), "=f"(g[5]), "=f"(g[6]), "=f"(g[7]), "=f"(g[8]), "=f"(g[9]), "=f"(g[10]), "=f"(g[11]), "=f"(g[12]), "=f"(g[13]), "=f"(g[14]), "=f"(g[15]), "=f"(g[16]), "=f"(g[17]), "=f"(g[18]), "=f"(g[19]), "=f"(g[20]), "=f"(g[21]), "=f"(g[22]), "=f"(g[23]), "=f"(g[24]), "=f"(g[25]), "=f"(g[26]), "=f"(g[27]), "=f"(g[28]), "=f"(g[29]), "=f"(g[30]), "=f"(g[31]),
        "=f"(h[0]), "=f"(h[1]), "=f"(h[2]), "=f"(h[3]), "=f"(h[4]), "=f"(h[5]), "=f"(h[6]), "=f"(h[7]), "=f"(h[8]), "=f"(h[9]), "=f"(h[10]), "=f"(h[11]), "=f"(h[12]), "=f"(h[13]), "=f"(h[14]), "=f"(h[15]), "=f"(h[16]), "=f"(h[17]), "=f"(h[18]), "=f"(h[19]), "=f"(h[20]), "=f"(h[21]), "=f"(h[22]), "=f"(h[23]), "=f"(h[24]), "=f"(h[25]), "=f"(h[26]), "=f"(h[27]), "=f"(h[28]), "=f"(h[29]), "=f"(h[30]), "=f"(h[31])
      : "r"(w[0]), "r"(w[1]), "r"(w[2]), "r"(w[3]), "r"(w[4]), "r"(w[5]), "r"(w[6]), "r"(w[7]), "r"(w[8]), "r"(w[9]), "r"(w[10]), "r"(w[11]), "r"(w[12]), "r"(w[13]), "r"(w[14]), "r"(w[15]), "r"(w[16]), "r"(w[17]), "r"(w[18]), "r"(w[19]), "r"(w[20]), "r"(w[21]), "r"(w[22]), "r"(w[23]), "r"(w[24]), "r"(w[25]), "r"(w[26]), "r"(w[27]), "r"(w[28]), "r"(w[29]), "r"(w[30]), "r"(w[31]), "r"(w[32]), "r"(w[33]), "r"(w[34]), "r"(w[35]), "r"(w[36]), "r"(w[37]), "r"(w[38]), "r"(w[39]), "r"(dx), "l"(de), "l"(dh)
      : "memory");
  }
  static __device__ __forceinline__ void wait_g(float* g) {
    asm volatile("wgmma.wait_group.sync.aligned 1;\n"
      : "+f"(g[0]), "+f"(g[1]), "+f"(g[2]), "+f"(g[3]), "+f"(g[4]), "+f"(g[5]), "+f"(g[6]), "+f"(g[7]), "+f"(g[8]), "+f"(g[9]), "+f"(g[10]), "+f"(g[11]), "+f"(g[12]), "+f"(g[13]), "+f"(g[14]), "+f"(g[15]), "+f"(g[16]), "+f"(g[17]), "+f"(g[18]), "+f"(g[19]), "+f"(g[20]), "+f"(g[21]), "+f"(g[22]), "+f"(g[23]), "+f"(g[24]), "+f"(g[25]), "+f"(g[26]), "+f"(g[27]), "+f"(g[28]), "+f"(g[29]), "+f"(g[30]), "+f"(g[31])
      :: "memory");
  }
  static __device__ __forceinline__ void wait_h(float* h) {
    asm volatile("wgmma.wait_group.sync.aligned 0;\n"
      : "+f"(h[0]), "+f"(h[1]), "+f"(h[2]), "+f"(h[3]), "+f"(h[4]), "+f"(h[5]), "+f"(h[6]), "+f"(h[7]), "+f"(h[8]), "+f"(h[9]), "+f"(h[10]), "+f"(h[11]), "+f"(h[12]), "+f"(h[13]), "+f"(h[14]), "+f"(h[15]), "+f"(h[16]), "+f"(h[17]), "+f"(h[18]), "+f"(h[19]), "+f"(h[20]), "+f"(h[21]), "+f"(h[22]), "+f"(h[23]), "+f"(h[24]), "+f"(h[25]), "+f"(h[26]), "+f"(h[27]), "+f"(h[28]), "+f"(h[29]), "+f"(h[30]), "+f"(h[31])
      :: "memory");
  }
};
template<> struct TileMMA<9> {
  static __device__ __forceinline__ void issue(float* g, float* h, const uint32_t* w, uint32_t dx, uint64_t de, uint64_t dh, uint64_t dc) {
    asm volatile(
      "{\n.reg .b64 dx0, dx1, dx2, dx3;\n.reg .b32 l1, l2, l3, hx;\nmov.b32 hx, 0x40000040;\n"
      "add.u32 l1, %112, 2;\nadd.u32 l2, %112, 4;\nadd.u32 l3, %112, 6;\n"
      "mov.b64 dx0, {%112, hx};\nmov.b64 dx1, {l1, hx};\nmov.b64 dx2, {l2, hx};\nmov.b64 dx3, {l3, hx};\n"
      "wgmma.fence.sync.aligned;\n"
      "wgmma.mma_async.sync.aligned.m64n72k16.f32.bf16.bf16 {%0, %1, %2, %3, %4, %5, %6, %7, %8, %9, %10, %11, %12, %13, %14, %15, %16, %17, %18, %19, %20, %21, %22, %23, %24, %25, %26, %27, %28, %29, %30, %31, %32, %33, %34, %35}, {%108, %109, %110, %111}, %114, 0, 1, 1, 0;\n"
      "wgmma.mma_async.sync.aligned.m64n72k16.f32.bf16.bf16 {%0, %1, %2, %3, %4, %5, %6, %7, %8, %9, %10, %11, %12, %13, %14, %15, %16, %17, %18, %19, %20, %21, %22, %23, %24, %25, %26, %27, %28, %29, %30, %31, %32, %33, %34, %35}, {%88, %89, %90, %91}, %113, 1, 1, 1, 0;\n"
      "wgmma.mma_async.sync.aligned.m64n72k16.f32.bf16.bf16 {%0, %1, %2, %3, %4, %5, %6, %7, %8, %9, %10, %11, %12, %13, %14, %15, %16, %17, %18, %19, %20, %21, %22, %23, %24, %25, %26, %27, %28, %29, %30, %31, %32, %33, %34, %35}, {%72, %73, %74, %75}, dx0, 1, 1, 1, 0;\n"
      "wgmma.mma_async.sync.aligned.m64n72k16.f32.bf16.bf16 {%0, %1, %2, %3, %4, %5, %6, %7, %8, %9, %10, %11, %12, %13, %14, %15, %16, %17, %18, %19, %20, %21, %22, %23, %24, %25, %26, %27, %28, %29, %30, %31, %32, %33, %34, %35}, {%76, %77, %78, %79}, dx1, 1, 1, 1, 0;\n"
      "wgmma.mma_async.sync.aligned.m64n72k16.f32.bf16.bf16 {%0, %1, %2, %3, %4, %5, %6, %7, %8, %9, %10, %11, %12, %13, %14, %15, %16, %17, %18, %19, %20, %21, %22, %23, %24, %25, %26, %27, %28, %29, %30, %31, %32, %33, %34, %35}, {%80, %81, %82, %83}, dx2, 1, 1, 1, 0;\n"
      "wgmma.mma_async.sync.aligned.m64n72k16.f32.bf16.bf16 {%0, %1, %2, %3, %4, %5, %6, %7, %8, %9, %10, %11, %12, %13, %14, %15, %16, %17, %18, %19, %20, %21, %22, %23, %24, %25, %26, %27, %28, %29, %30, %31, %32, %33, %34, %35}, {%84, %85, %86, %87}, dx3, 1, 1, 1, 0;\n"
      "wgmma.commit_group.sync.aligned;\n"
      "wgmma.mma_async.sync.aligned.m64n72k16.f32.bf16.bf16 {%36, %37, %38, %39, %40, %41, %42, %43, %44, %45, %46, %47, %48, %49, %50, %51, %52, %53, %54, %55, %56, %57, %58, %59, %60, %61, %62, %63, %64, %65, %66, %67, %68, %69, %70, %71}, {%92, %93, %94, %95}, dx0, 0, 1, 1, 0;\n"
      "wgmma.mma_async.sync.aligned.m64n72k16.f32.bf16.bf16 {%36, %37, %38, %39, %40, %41, %42, %43, %44, %45, %46, %47, %48, %49, %50, %51, %52, %53, %54, %55, %56, %57, %58, %59, %60, %61, %62, %63, %64, %65, %66, %67, %68, %69, %70, %71}, {%96, %97, %98, %99}, dx1, 1, 1, 1, 0;\n"
      "wgmma.mma_async.sync.aligned.m64n72k16.f32.bf16.bf16 {%36, %37, %38, %39, %40, %41, %42, %43, %44, %45, %46, %47, %48, %49, %50, %51, %52, %53, %54, %55, %56, %57, %58, %59, %60, %61, %62, %63, %64, %65, %66, %67, %68, %69, %70, %71}, {%100, %101, %102, %103}, dx2, 1, 1, 1, 0;\n"
      "wgmma.mma_async.sync.aligned.m64n72k16.f32.bf16.bf16 {%36, %37, %38, %39, %40, %41, %42, %43, %44, %45, %46, %47, %48, %49, %50, %51, %52, %53, %54, %55, %56, %57, %58, %59, %60, %61, %62, %63, %64, %65, %66, %67, %68, %69, %70, %71}, {%104, %105, %106, %107}, dx3, 1, 1, 1, 0;\n"
      "wgmma.commit_group.sync.aligned;\n}\n"
      : "=f"(g[0]), "=f"(g[1]), "=f"(g[2]), "=f"(g[3]), "=f"(g[4]), "=f"(g[5]), "=f"(g[6]), "=f"(g[7]), "=f"(g[8]), "=f"(g[9]), "=f"(g[10]), "=f"(g[11]), "=f"(g[12]), "=f"(g[13]), "=f"(g[14]), "=f"(g[15]), "=f"(g[16]), "=f"(g[17]), "=f"(g[18]), "=f"(g[19]), "=f"(g[20]), "=f"(g[21]), "=f"(g[22]), "=f"(g[23]), "=f"(g[24]), "=f"(g[25]), "=f"(g[26]), "=f"(g[27]), "=f"(g[28]), "=f"(g[29]), "=f"(g[30]), "=f"(g[31]), "=f"(g[32]), "=f"(g[33]), "=f"(g[34]), "=f"(g[35]),
        "=f"(h[0]), "=f"(h[1]), "=f"(h[2]), "=f"(h[3]), "=f"(h[4]), "=f"(h[5]), "=f"(h[6]), "=f"(h[7]), "=f"(h[8]), "=f"(h[9]), "=f"(h[10]), "=f"(h[11]), "=f"(h[12]), "=f"(h[13]), "=f"(h[14]), "=f"(h[15]), "=f"(h[16]), "=f"(h[17]), "=f"(h[18]), "=f"(h[19]), "=f"(h[20]), "=f"(h[21]), "=f"(h[22]), "=f"(h[23]), "=f"(h[24]), "=f"(h[25]), "=f"(h[26]), "=f"(h[27]), "=f"(h[28]), "=f"(h[29]), "=f"(h[30]), "=f"(h[31]), "=f"(h[32]), "=f"(h[33]), "=f"(h[34]), "=f"(h[35])
      : "r"(w[0]), "r"(w[1]), "r"(w[2]), "r"(w[3]), "r"(w[4]), "r"(w[5]), "r"(w[6]), "r"(w[7]), "r"(w[8]), "r"(w[9]), "r"(w[10]), "r"(w[11]), "r"(w[12]), "r"(w[13]), "r"(w[14]), "r"(w[15]), "r"(w[16]), "r"(w[17]), "r"(w[18]), "r"(w[19]), "r"(w[20]), "r"(w[21]), "r"(w[22]), "r"(w[23]), "r"(w[24]), "r"(w[25]), "r"(w[26]), "r"(w[27]), "r"(w[28]), "r"(w[29]), "r"(w[30]), "r"(w[31]), "r"(w[32]), "r"(w[33]), "r"(w[34]), "r"(w[35]), "r"(w[36]), "r"(w[37]), "r"(w[38]), "r"(w[39]), "r"(dx), "l"(de), "l"(dh)
      : "memory");
  }
  static __device__ __forceinline__ void wait_g(float* g) {
    asm volatile("wgmma.wait_group.sync.aligned 1;\n"
      : "+f"(g[0]), "+f"(g[1]), "+f"(g[2]), "+f"(g[3]), "+f"(g[4]), "+f"(g[5]), "+f"(g[6]), "+f"(g[7]), "+f"(g[8]), "+f"(g[9]), "+f"(g[10]), "+f"(g[11]), "+f"(g[12]), "+f"(g[13]), "+f"(g[14]), "+f"(g[15]), "+f"(g[16]), "+f"(g[17]), "+f"(g[18]), "+f"(g[19]), "+f"(g[20]), "+f"(g[21]), "+f"(g[22]), "+f"(g[23]), "+f"(g[24]), "+f"(g[25]), "+f"(g[26]), "+f"(g[27]), "+f"(g[28]), "+f"(g[29]), "+f"(g[30]), "+f"(g[31]), "+f"(g[32]), "+f"(g[33]), "+f"(g[34]), "+f"(g[35])
      :: "memory");
  }
  static __device__ __forceinline__ void wait_h(float* h) {
    asm volatile("wgmma.wait_group.sync.aligned 0;\n"
      : "+f"(h[0]), "+f"(h[1]), "+f"(h[2]), "+f"(h[3]), "+f"(h[4]), "+f"(h[5]), "+f"(h[6]), "+f"(h[7]), "+f"(h[8]), "+f"(h[9]), "+f"(h[10]), "+f"(h[11]), "+f"(h[12]), "+f"(h[13]), "+f"(h[14]), "+f"(h[15]), "+f"(h[16]), "+f"(h[17]), "+f"(h[18]), "+f"(h[19]), "+f"(h[20]), "+f"(h[21]), "+f"(h[22]), "+f"(h[23]), "+f"(h[24]), "+f"(h[25]), "+f"(h[26]), "+f"(h[27]), "+f"(h[28]), "+f"(h[29]), "+f"(h[30]), "+f"(h[31]), "+f"(h[32]), "+f"(h[33]), "+f"(h[34]), "+f"(h[35])
      :: "memory");
  }
};
template<> struct TileMMA<10> {
  static __device__ __forceinline__ void issue(float* g, float* h, const uint32_t* w, uint32_t dx, uint64_t de, uint64_t dh, uint64_t dc) {
    asm volatile(
      "{\n.reg .b64 dx0, dx1, dx2, dx3;\n.reg .b32 l1, l2, l3, hx;\nmov.b32 hx, 0x40000040;\n"
      "add.u32 l1, %120, 2;\nadd.u32 l2, %120, 4;\nadd.u32 l3, %120, 6;\n"
      "mov.b64 dx0, {%120, hx};\nmov.b64 dx1, {l1, hx};\nmov.b64 dx2, {l2, hx};\nmov.b64 dx3, {l3, hx};\n"
      "wgmma.fence.sync.aligned;\n"
      "wgmma.mma_async.sync.aligned.m64n80k16.f32.bf16.bf16 {%0, %1, %2, %3, %4, %5, %6, %7, %8, %9, %10, %11, %12, %13, %14, %15, %16, %17, %18, %19, %20, %21, %22, %23, %24, %25, %26, %27, %28, %29, %30, %31, %32, %33, %34, %35, %36, %37, %38, %39}, {%116, %117, %118, %119}, %122, 0, 1, 1, 0;\n"
      "wgmma.mma_async.sync.aligned.m64n80k16.f32.bf16.bf16 {%0, %1, %2, %3, %4, %5, %6, %7, %8, %9, %10, %11, %12, %13, %14, %15, %16, %17, %18, %19, %20, %21, %22, %23, %24, %25, %26, %27, %28, %29, %30, %31, %32, %33, %34, %35, %36, %37, %38, %39}, {%96, %97, %98, %99}, %121, 1, 1, 1, 0;\n"
      "wgmma.mma_async.sync.aligned.m64n80k16.f32.bf16.bf16 {%0, %1, %2, %3, %4, %5, %6, %7, %8, %9, %10, %11, %12, %13, %14, %15, %16, %17, %18, %19, %20, %21, %22, %23, %24, %25, %26, %27, %28, %29, %30, %31, %32, %33, %34, %35, %36, %37, %38, %39}, {%80, %81, %82, %83}, dx0, 1, 1, 1, 0;\n"
      "wgmma.mma_async.sync.aligned.m64n80k16.f32.bf16.bf16 {%0, %1, %2, %3, %4, %5, %6, %7, %8, %9, %10, %11, %12, %13, %14, %15, %16, %17, %18, %19, %20, %21, %22, %23, %24, %25, %26, %27, %28, %29, %30, %31, %32, %33, %34, %35, %36, %37, %38, %39}, {%84, %85, %86, %87}, dx1, 1, 1, 1, 0;\n"
      "wgmma.mma_async.sync.aligned.m64n80k16.f32.bf16.bf16 {%0, %1, %2, %3, %4, %5, %6, %7, %8, %9, %10, %11, %12, %13, %14, %15, %16, %17, %18, %19, %20, %21, %22, %23, %24, %25, %26, %27, %28, %29, %30, %31, %32, %33, %34, %35, %36, %37, %38, %39}, {%88, %89, %90, %91}, dx2, 1, 1, 1, 0;\n"
      "wgmma.mma_async.sync.aligned.m64n80k16.f32.bf16.bf16 {%0, %1, %2, %3, %4, %5, %6, %7, %8, %9, %10, %11, %12, %13, %14, %15, %16, %17, %18, %19, %20, %21, %22, %23, %24, %25, %26, %27, %28, %29, %30, %31, %32, %33, %34, %35, %36, %37, %38, %39}, {%92, %93, %94, %95}, dx3, 1, 1, 1, 0;\n"
      "wgmma.commit_group.sync.aligned;\n"
      "wgmma.mma_async.sync.aligned.m64n80k16.f32.bf16.bf16 {%40, %41, %42, %43, %44, %45, %46, %47, %48, %49, %50, %51, %52, %53, %54, %55, %56, %57, %58, %59, %60, %61, %62, %63, %64, %65, %66, %67, %68, %69, %70, %71, %72, %73, %74, %75, %76, %77, %78, %79}, {%100, %101, %102, %103}, dx0, 0, 1, 1, 0;\n"
      "wgmma.mma_async.sync.aligned.m64n80k16.f32.bf16.bf16 {%40, %41, %42, %43, %44, %45, %46, %47, %48, %49, %50, %51, %52, %53, %54, %55, %56, %57, %58, %59, %60, %61, %62, %63, %64, %65, %66, %67, %68, %69, %70, %71, %72, %73, %74, %75, %76, %77, %78, %79}, {%104, %105, %106, %107}, dx1, 1, 1, 1, 0;\n"
      "wgmma.mma_async.sync.aligned.m64n80k16.f32.bf16.bf16 {%40, %41, %42, %43, %44, %45, %46, %47, %48, %49, %50, %51, %52, %53, %54, %55, %56, %57, %58, %59, %60, %61, %62, %63, %64, %65, %66, %67, %68, %69, %70, %71, %72, %73, %74, %75, %76, %77, %78, %79}, {%108, %109, %110, %111}, dx2, 1, 1, 1, 0;\n"
      "wgmma.mma_async.sync.aligned.m64n80k16.f32.bf16.bf16 {%40, %41, %42, %43, %44, %45, %46, %47, %48, %49, %50, %51, %52, %53, %54, %55, %56, %57, %58, %59, %60, %61, %62, %63, %64, %65, %66, %67, %68, %69, %70, %71, %72, %73, %74, %75, %76, %77, %78, %79}, {%112, %113, %114, %115}, dx3, 1, 1, 1, 0;\n"
      "wgmma.commit_group.sync.aligned;\n}\n"
      : "=f"(g[0]), "=f"(g[1]), "=f"(g[2]), "=f"(g[3]), "=f"(g[4]), "=f"(g[5]), "=f"(g[6]), "=f"(g[7]), "=f"(g[8]), "=f"(g[9]), "=f"(g[10]), "=f"(g[11]), "=f"(g[12]), "=f"(g[13]), "=f"(g[14]), "=f"(g[15]), "=f"(g[16]), "=f"(g[17]), "=f"(g[18]), "=f"(g[19]), "=f"(g[20]), "=f"(g[21]), "=f"(g[22]), "=f"(g[23]), "=f"(g[24]), "=f"(g[25]), "=f"(g[26]), "=f"(g[27]), "=f"(g[28]), "=f"(g[29]), "=f"(g[30]), "=f"(g[31]), "=f"(g[32]), "=f"(g[33]), "=f"(g[34]), "=f"(g[35]), "=f"(g[36]), "=f"(g[37]), "=f"(g[38]), "=f"(g[39]),
        "=f"(h[0]), "=f"(h[1]), "=f"(h[2]), "=f"(h[3]), "=f"(h[4]), "=f"(h[5]), "=f"(h[6]), "=f"(h[7]), "=f"(h[8]), "=f"(h[9]), "=f"(h[10]), "=f"(h[11]), "=f"(h[12]), "=f"(h[13]), "=f"(h[14]), "=f"(h[15]), "=f"(h[16]), "=f"(h[17]), "=f"(h[18]), "=f"(h[19]), "=f"(h[20]), "=f"(h[21]), "=f"(h[22]), "=f"(h[23]), "=f"(h[24]), "=f"(h[25]), "=f"(h[26]), "=f"(h[27]), "=f"(h[28]), "=f"(h[29]), "=f"(h[30]), "=f"(h[31]), "=f"(h[32]), "=f"(h[33]), "=f"(h[34]), "=f"(h[35]), "=f"(h[36]), "=f"(h[37]), "=f"(h[38]), "=f"(h[39])
      : "r"(w[0]), "r"(w[1]), "r"(w[2]), "r"(w[3]), "r"(w[4]), "r"(w[5]), "r"(w[6]), "r"(w[7]), "r"(w[8]), "r"(w[9]), "r"(w[10]), "r"(w[11]), "r"(w[12]), "r"(w[13]), "r"(w[14]), "r"(w[15]), "r"(w[16]), "r"(w[17]), "r"(w[18]), "r"(w[19]), "r"(w[20]), "r"(w[21]), "r"(w[22]), "r"(w[23]), "r"(w[24]), "r"(w[25]), "r"(w[26]), "r"(w[27]), "r"(w[28]), "r"(w[29]), "r"(w[30]), "r"(w[31]), "r"(w[32]), "r"(w[33]), "r"(w[34]), "r"(w[35]), "r"(w[36]), "r"(w[37]), "r"(w[38]), "r"(w[39]), "r"(dx), "l"(de), "l"(dh)
      : "memory");
  }
  static __device__ __forceinline__ void wait_g(float* g) {
    asm volatile("wgmma.wait_group.sync.aligned 1;\n"
      : "+f"(g[0]), "+f"(g[1]), "+f"(g[2]), "+f"(g[3]), "+f"(g[4]), "+f"(g[5]), "+f"(g[6]), "+f"(g[7]), "+f"(g[8]), "+f"(g[9]), "+f"(g[10]), "+f"(g[11]), "+f"(g[12]), "+f"(g[13]), "+f"(g[14]), "+f"(g[15]), "+f"(g[16]), "+f"(g[17]), "+f"(g[18]), "+f"(g[19]), "+f"(g[20]), "+f"(g[21]), "+f"(g[22]), "+f"(g[23]), "+f"(g[24]), "+f"(g[25]), "+f"(g[26]), "+f"(g[27]), "+f"(g[28]), "+f"(g[29]), "+f"(g[30]), "+f"(g[31]), "+f"(g[32]), "+f"(g[33]), "+f"(g[34]), "+f"(g[35]), "+f"(g[36]), "+f"(g[37]), "+f"(g[38]), "+f"(g[39])
      :: "memory");
  }
  static __device__ __forceinline__ void wait_h(float* h) {
    asm volatile("wgmma.wait_group.sync.aligned 0;\n"
      : "+f"(h[0]), "+f"(h[1]), "+f"(h[2]), "+f"(h[3]), "+f"(h[4]), "+f"(h[5]), "+f"(h[6]), "+f"(h[7]), "+f"(h[8]), "+f"(h[9]), "+f"(h[10]), "+f"(h[11]), "+f"(h[12]), "+f"(h[13]), "+f"(h[14]), "+f"(h[15]), "+f"(h[16]), "+f"(h[17]), "+f"(h[18]), "+f"(h[19]), "+f"(h[20]), "+f"(h[21]), "+f"(h[22]), "+f"(h[23]), "+f"(h[24]), "+f"(h[25]), "+f"(h[26]), "+f"(h[27]), "+f"(h[28]), "+f"(h[29]), "+f"(h[30]), "+f"(h[31]), "+f"(h[32]), "+f"(h[33]), "+f"(h[34]), "+f"(h[35]), "+f"(h[36]), "+f"(h[37]), "+f"(h[38]), "+f"(h[39])
      :: "memory");
  }
};
template<> struct TileMMA<11> {
  static __device__ __forceinline__ void issue(float* g, float* h, const uint32_t* w, uint32_t dx, uint64_t de, uint64_t dh, uint64_t dc) {
    asm volatile(
      "{\n.reg .b64 dx0, dx1, dx2, dx3;\n.reg .b32 l1, l2, l3, hx;\nmov.b32 hx, 0x40000040;\n"
      "add.u32 l1, %124, 2;\nadd.u32 l2, %124, 4;\nadd.u32 l3, %124, 6;\n"
      "mov.b64 dx0, {%124, hx};\nmov.b64 dx1, {l1, hx};\nmov.b64 dx2, {l2, hx};\nmov.b64 dx3, {l3, hx};\n"
      "wgmma.fence.sync.aligned;\n"
      "wgmma.mma_async.sync.aligned.m64n88k16.f32.bf16.bf16 {%0, %1, %2, %3, %4, %5, %6, %7, %8, %9, %10, %11, %12, %13, %14, %15, %16, %17, %18, %19, %20, %21, %22, %23, %24, %25, %26, %27, %28, %29, %30, %31, %32, %33, %34, %35, %36, %37, %38, %39, %40, %41, %42, %43}, {%120, %121, %122, %123}, %126, 0, 1, 1, 0;\n"
      "wgmma.mma_async.sync.aligned.m64n88k16.f32.bf16.bf16 {%0, %1, %2, %3, %4, %5, %6, %7, %8, %9, %10, %11, %12, %13, %14, %15, %16, %17, %18, %19, %20, %21, %22, %23, %24, %25, %26, %27, %28, %29, %30, %31, %32, %33, %34, %35, %36, %37, %38, %39, %40, %41, %42, %43}, %127, %125, 1, 1, 1, 0, 0;\n"
      "wgmma.mma_async.sync.aligned.m64n88k16.f32.bf16.bf16 {%0, %1, %2, %3, %4, %5, %6, %7, %8, %9, %10, %11, %12, %13, %14, %15, %16, %17, %18, %19, %20, %21, %22, %23, %24, %25, %26, %27, %28, %29, %30, %31, %32, %33, %34, %35, %36, %37, %38, %39, %40, %41, %42, %43}, {%88, %89, %90, %91}, dx0, 1, 1, 1, 0;\n"
      "wgmma.mma_async.sync.aligned.m64n88k16.f32.bf16.bf16 {%0, %1, %2, %3, %4, %5, %6, %7, %8, %9, %10, %11, %12, %13, %14, %15, %16, %17, %18, %19, %20, %21, %22, %23, %24, %25, %26, %27, %28, %29, %30, %31, %32, %33, %34, %35, %36, %37, %38, %39, %40, %41, %42, %43}, {%92, %93, %94, %95}, dx1, 1, 1, 1, 0;\n"
      "wgmma.mma_async.sync.aligned.m64n88k16.f32.bf16.bf16 {%0, %1, %2, %3, %4, %5, %6, %7, %8, %9, %10, %11, %12, %13, %14, %15, %16, %17, %18, %19, %20, %21, %22, %23, %24, %25, %26, %27, %28, %29, %30, %31, %32, %33, %34, %35, %36, %37, %38, %39, %40, %41, %42, %43}, {%96, %97, %98, %99}, dx2, 1, 1, 1, 0;\n"
      "wgmma.mma_async.sync.aligned.m64n88k16.f32.bf16.bf16 {%0, %1, %2, %3, %4, %5, %6, %7, %8, %9, %10, %11, %12, %13, %14, %15, %16, %17, %18, %19, %20, %21, %22, %23, %24, %25, %26, %27, %28, %29, %30, %31, %32, %33, %34, %35, %36, %37, %38, %39, %40, %41, %42, %43}, {%100, %101, %102, %103}, dx3, 1, 1, 1, 0;\n"
      "wgmma.commit_group.sync.aligned;\n"
      "wgmma.mma_async.sync.aligned.m64n88k16.f32.bf16.bf16 {%44, %45, %46, %47, %48, %49, %50, %51, %52, %53, %54, %55, %56, %57, %58, %59, %60, %61, %62, %63, %64, %65, %66, %67, %68, %69, %70, %71, %72, %73, %74, %75, %76, %77, %78, %79, %80, %81, %82, %83, %84, %85, %86, %87}, {%104, %105, %106, %107}, dx0, 0, 1, 1, 0;\n"
      "wgmma.mma_async.sync.aligned.m64n88k16.f32.bf16.bf16 {%44, %45, %46, %47, %48, %49, %50, %51, %52, %53, %54, %55, %56, %57, %58, %59, %60, %61, %62, %63, %64, %65, %66, %67, %68, %69, %70, %71, %72, %73, %74, %75, %76, %77, %78, %79, %80, %81, %82, %83, %84, %85, %86, %87}, {%108, %109, %110, %111}, dx1, 1, 1, 1, 0;\n"
      "wgmma.mma_async.sync.aligned.m64n88k16.f32.bf16.bf16 {%44, %45, %46, %47, %48, %49, %50, %51, %52, %53, %54, %55, %56, %57, %58, %59, %60, %61, %62, %63, %64, %65, %66, %67, %68, %69, %70, %71, %72, %73, %74, %75, %76, %77, %78, %79, %80, %81, %82, %83, %84, %85, %86, %87}, {%112, %113, %114, %115}, dx2, 1, 1, 1, 0;\n"
      "wgmma.mma_async.sync.aligned.m64n88k16.f32.bf16.bf16 {%44, %45, %46, %47, %48, %49, %50, %51, %52, %53, %54, %55, %56, %57, %58, %59, %60, %61, %62, %63, %64, %65, %66, %67, %68, %69, %70, %71, %72, %73, %74, %75, %76, %77, %78, %79, %80, %81, %82, %83, %84, %85, %86, %87}, {%116, %117, %118, %119}, dx3, 1, 1, 1, 0;\n"
      "wgmma.commit_group.sync.aligned;\n}\n"
      : "=f"(g[0]), "=f"(g[1]), "=f"(g[2]), "=f"(g[3]), "=f"(g[4]), "=f"(g[5]), "=f"(g[6]), "=f"(g[7]), "=f"(g[8]), "=f"(g[9]), "=f"(g[10]), "=f"(g[11]), "=f"(g[12]), "=f"(g[13]), "=f"(g[14]), "=f"(g[15]), "=f"(g[16]), "=f"(g[17]), "=f"(g[18]), "=f"(g[19]), "=f"(g[20]), "=f"(g[21]), "=f"(g[22]), "=f"(g[23]), "=f"(g[24]), "=f"(g[25]), "=f"(g[26]), "=f"(g[27]), "=f"(g[28]), "=f"(g[29]), "=f"(g[30]), "=f"(g[31]), "=f"(g[32]), "=f"(g[33]), "=f"(g[34]), "=f"(g[35]), "=f"(g[36]), "=f"(g[37]), "=f"(g[38]), "=f"(g[39]), "=f"(g[40]), "=f"(g[41]), "=f"(g[42]), "=f"(g[43]),
        "=f"(h[0]), "=f"(h[1]), "=f"(h[2]), "=f"(h[3]), "=f"(h[4]), "=f"(h[5]), "=f"(h[6]), "=f"(h[7]), "=f"(h[8]), "=f"(h[9]), "=f"(h[10]), "=f"(h[11]), "=f"(h[12]), "=f"(h[13]), "=f"(h[14]), "=f"(h[15]), "=f"(h[16]), "=f"(h[17]), "=f"(h[18]), "=f"(h[19]), "=f"(h[20]), "=f"(h[21]), "=f"(h[22]), "=f"(h[23]), "=f"(h[24]), "=f"(h[25]), "=f"(h[26]), "=f"(h[27]), "=f"(h[28]), "=f"(h[29]), "=f"(h[30]), "=f"(h[31]), "=f"(h[32]), "=f"(h[33]), "=f"(h[34]), "=f"(h[35]), "=f"(h[36]), "=f"(h[37]), "=f"(h[38]), "=f"(h[39]), "=f"(h[40]), "=f"(h[41]), "=f"(h[42]), "=f"(h[43])
      : "r"(w[0]), "r"(w[1]), "r"(w[2]), "r"(w[3]), "r"(w[4]), "r"(w[5]), "r"(w[6]), "r"(w[7]), "r"(w[8]), "r"(w[9]), "r"(w[10]), "r"(w[11]), "r"(w[12]), "r"(w[13]), "r"(w[14]), "r"(w[15]), "r"(w[20]), "r"(w[21]), "r"(w[22]), "r"(w[23]), "r"(w[24]), "r"(w[25]), "r"(w[26]), "r"(w[27]), "r"(w[28]), "r"(w[29]), "r"(w[30]), "r"(w[31]), "r"(w[32]), "r"(w[33]), "r"(w[34]), "r"(w[35]), "r"(w[36]), "r"(w[37]), "r"(w[38]), "r"(w[39]), "r"(dx), "l"(de), "l"(dh), "l"(dc)
      : "memory");
  }
  static __device__ __forceinline__ void wait_g(float* g) {
    asm volatile("wgmma.wait_group.sync.aligned 1;\n"
      : "+f"(g[0]), "+f"(g[1]), "+f"(g[2]), "+f"(g[3]), "+f"(g[4]), "+f"(g[5]), "+f"(g[6]), "+f"(g[7]), "+f"(g[8]), "+f"(g[9]), "+f"(g[10]), "+f"(g[11]), "+f"(g[12]), "+f"(g[13]), "+f"(g[14]), "+f"(g[15]), "+f"(g[16]), "+f"(g[17]), "+f"(g[18]), "+f"(g[19]), "+f"(g[20]), "+f"(g[21]), "+f"(g[22]), "+f"(g[23]), "+f"(g[24]), "+f"(g[25]), "+f"(g[26]), "+f"(g[27]), "+f"(g[28]), "+f"(g[29]), "+f"(g[30]), "+f"(g[31]), "+f"(g[32]), "+f"(g[33]), "+f"(g[34]), "+f"(g[35]), "+f"(g[36]), "+f"(g[37]), "+f"(g[38]), "+f"(g[39]), "+f"(g[40]), "+f"(g[41]), "+f"(g[42]), "+f"(g[43])
      :: "memory");
  }
  static __device__ __forceinline__ void wait_h(float* h) {
    asm volatile("wgmma.wait_group.sync.aligned 0;\n"
      : "+f"(h[0]), "+f"(h[1]), "+f"(h[2]), "+f"(h[3]), "+f"(h[4]), "+f"(h[5]), "+f"(h[6]), "+f"(h[7]), "+f"(h[8]), "+f"(h[9]), "+f"(h[10]), "+f"(h[11]), "+f"(h[12]), "+f"(h[13]), "+f"(h[14]), "+f"(h[15]), "+f"(h[16]), "+f"(h[17]), "+f"(h[18]), "+f"(h[19]), "+f"(h[20]), "+f"(h[21]), "+f"(h[22]), "+f"(h[23]), "+f"(h[24]), "+f"(h[25]), "+f"(h[26]), "+f"(h[27]), "+f"(h[28]), "+f"(h[29]), "+f"(h[30]), "+f"(h[31]), "+f"(h[32]), "+f"(h[33]), "+f"(h[34]), "+f"(h[35]), "+f"(h[36]), "+f"(h[37]), "+f"(h[38]), "+f"(h[39]), "+f"(h[40]), "+f"(h[41]), "+f"(h[42]), "+f"(h[43])
      :: "memory");
  }
};
__device__ __forceinline__ void node_mma(float* g, const uint32_t* w, uint64_t dx) {
    asm volatile(
      "{\n.reg .b64 dx1, dx2, dx3;\n"
      "add.s64 dx1, %48, 2;\nadd.s64 dx2, %48, 4;\nadd.s64 dx3, %48, 6;\n"
      "wgmma.fence.sync.aligned;\n"
      "wgmma.mma_async.sync.aligned.m64n64k16.f32.bf16.bf16 {%0, %1, %2, %3, %4, %5, %6, %7, %8, %9, %10, %11, %12, %13, %14, %15, %16, %17, %18, %19, %20, %21, %22, %23, %24, %25, %26, %27, %28, %29, %30, %31}, {%32, %33, %34, %35}, %48, 0, 1, 1, 0;\n"
      "wgmma.mma_async.sync.aligned.m64n64k16.f32.bf16.bf16 {%0, %1, %2, %3, %4, %5, %6, %7, %8, %9, %10, %11, %12, %13, %14, %15, %16, %17, %18, %19, %20, %21, %22, %23, %24, %25, %26, %27, %28, %29, %30, %31}, {%36, %37, %38, %39}, dx1, 1, 1, 1, 0;\n"
      "wgmma.mma_async.sync.aligned.m64n64k16.f32.bf16.bf16 {%0, %1, %2, %3, %4, %5, %6, %7, %8, %9, %10, %11, %12, %13, %14, %15, %16, %17, %18, %19, %20, %21, %22, %23, %24, %25, %26, %27, %28, %29, %30, %31}, {%40, %41, %42, %43}, dx2, 1, 1, 1, 0;\n"
      "wgmma.mma_async.sync.aligned.m64n64k16.f32.bf16.bf16 {%0, %1, %2, %3, %4, %5, %6, %7, %8, %9, %10, %11, %12, %13, %14, %15, %16, %17, %18, %19, %20, %21, %22, %23, %24, %25, %26, %27, %28, %29, %30, %31}, {%44, %45, %46, %47}, dx3, 1, 1, 1, 0;\n"
      "wgmma.commit_group.sync.aligned;\n}\n"
      : "=f"(g[0]), "=f"(g[1]), "=f"(g[2]), "=f"(g[3]), "=f"(g[4]), "=f"(g[5]), "=f"(g[6]), "=f"(g[7]), "=f"(g[8]), "=f"(g[9]), "=f"(g[10]), "=f"(g[11]), "=f"(g[12]), "=f"(g[13]), "=f"(g[14]), "=f"(g[15]), "=f"(g[16]), "=f"(g[17]), "=f"(g[18]), "=f"(g[19]), "=f"(g[20]), "=f"(g[21]), "=f"(g[22]), "=f"(g[23]), "=f"(g[24]), "=f"(g[25]), "=f"(g[26]), "=f"(g[27]), "=f"(g[28]), "=f"(g[29]), "=f"(g[30]), "=f"(g[31])
      : "r"(w[0]), "r"(w[1]), "r"(w[2]), "r"(w[3]), "r"(w[4]), "r"(w[5]), "r"(w[6]), "r"(w[7]), "r"(w[8]), "r"(w[9]), "r"(w[10]), "r"(w[11]), "r"(w[12]), "r"(w[13]), "r"(w[14]), "r"(w[15]), "l"(dx)
      : "memory");
}

__device__ __forceinline__ uint32_t smem_u32(const void* p) { return (uint32_t)__cvta_generic_to_shared(p); }
__device__ __forceinline__ float ex2f(float x) { float y; asm("ex2.approx.ftz.f32 %0, %1;" : "=f"(y) : "f"(x)); return y; }
__device__ __forceinline__ float rcpf(float x) { float y; asm("rcp.approx.ftz.f32 %0, %1;" : "=f"(y) : "f"(x)); return y; }
__device__ __forceinline__ uint32_t pack_bf16(float lo, float hi) {
    uint32_t r; asm("cvt.rn.bf16x2.f32 %0, %1, %2;" : "=r"(r) : "f"(hi), "f"(lo)); return r;
}
__device__ __forceinline__ float bf_lo(uint32_t v) { return __uint_as_float(v << 16); }
__device__ __forceinline__ float bf_hi(uint32_t v) { return __uint_as_float(v & 0xFFFF0000u); }
template<int STRIDE>
__device__ __forceinline__ void cp16i(uint32_t dst, const char* base, uint32_t idx) {
    asm volatile("{\n.reg .b64 a;\nmad.wide.u32 a, %2, %3, %1;\ncp.async.cg.shared.global [%0], [a], 16;\n}\n" :: "r"(dst), "l"(base), "r"(idx), "n"(STRIDE) : "memory");
}
__device__ __forceinline__ void cp16e(uint32_t dst, const char* base, uint32_t idx, uint64_t pol) {
    asm volatile("{\n.reg .b64 a;\nmad.wide.u32 a, %2, 32, %1;\ncp.async.cg.shared.global.L2::cache_hint [%0], [a], 16, %3;\n}\n" :: "r"(dst), "l"(base), "r"(idx), "l"(pol) : "memory");
}
template<int STRIDE>
__device__ __forceinline__ void cp16z(uint32_t dst, const char* base, uint32_t idx, int k, int n, uint64_t pol) {
    if (STRIDE == 32)
        asm volatile("{\n.reg .b64 a;\n.reg .pred p;\nsetp.ge.s32 p, %3, %4;\nmad.wide.u32 a, %2, 32, %1;\ncp.async.cg.shared.global.L2::cache_hint [%0], [a], 16, p, %5;\n}\n"
                     :: "r"(dst), "l"(base), "r"(idx), "r"(k), "r"(n), "l"(pol) : "memory");
    else
        asm volatile("{\n.reg .b64 a;\n.reg .pred p;\nsetp.ge.s32 p, %3, %4;\nmad.wide.u32 a, %2, 128, %1;\ncp.async.cg.shared.global [%0], [a], 16, p;\n}\n"
                     :: "r"(dst), "l"(base), "r"(idx), "r"(k), "r"(n) : "memory");
}
template<int HI, bool Z>
__device__ __forceinline__ void cpx(uint32_t hi, uint32_t dst, uint32_t p, uint32_t lo, int k, int n) {
    if (Z) asm volatile("{\n.reg .b32 l;\n.reg .b64 a;\n.reg .pred q;\nsetp.ge.s32 q, %5, %6;\ndp2a.lo.u32.u32 l, %1, %2, %3;\nmov.b64 a, {l, %0};\ncp.async.cg.shared.global [%4], [a], 16, q;\n}\n"
                        :: "r"(hi), "r"(p), "r"(HI ? 0x8000u : 0x80u), "r"(lo), "r"(dst), "r"(k), "r"(n) : "memory");
    else asm volatile("{\n.reg .b32 l;\n.reg .b64 a;\ndp2a.lo.u32.u32 l, %1, %2, %3;\nmov.b64 a, {l, %0};\ncp.async.cg.shared.global [%4], [a], 16;\n}\n"
                      :: "r"(hi), "r"(p), "r"(HI ? 0x8000u : 0x80u), "r"(lo), "r"(dst) : "memory");
}
template<bool Z>
__device__ __forceinline__ void cpe(uint32_t hi, uint32_t dst, uint32_t idx, uint32_t lo, int k, int n, uint64_t pol) {
    if (Z) asm volatile("{\n.reg .b32 l;\n.reg .b64 a;\n.reg .pred q;\nsetp.ge.s32 q, %5, %6;\nmad.lo.u32 l, %1, 32, %2;\nmov.b64 a, {l, %0};\ncp.async.cg.shared.global.L2::cache_hint [%3], [a], 16, q, %4;\n}\n"
                        :: "r"(hi), "r"(idx), "r"(lo), "r"(dst), "l"(pol), "r"(k), "r"(n) : "memory");
    else asm volatile("{\n.reg .b32 l;\n.reg .b64 a;\nmad.lo.u32 l, %1, 32, %2;\nmov.b64 a, {l, %0};\ncp.async.cg.shared.global.L2::cache_hint [%3], [a], 16, %4;\n}\n"
                      :: "r"(hi), "r"(idx), "r"(lo), "r"(dst), "l"(pol) : "memory");
}
__device__ __forceinline__ void cp_commit() { asm volatile("cp.async.commit_group;" ::: "memory"); }
template<int N> __device__ __forceinline__ void cp_wait() { asm volatile("cp.async.wait_group %0;" :: "n"(N) : "memory"); }
__device__ __forceinline__ void mbar_arrive(uint32_t bar) { asm volatile("mbarrier.arrive.shared.b64 _, [%0];" :: "r"(bar) : "memory"); }
__device__ __forceinline__ void mbar_cp_arrive(uint32_t bar) { asm volatile("cp.async.mbarrier.arrive.noinc.shared.b64 [%0];" :: "r"(bar) : "memory"); }
__device__ __forceinline__ void mbar_wait(uint32_t bar, uint32_t parity) {
    asm volatile("{\n.reg .pred p;\n.reg .u32 n;\nmbarrier.try_wait.parity.shared.b64 p, [%0], %1;\n@p bra DONE_%=;\nmov.u32 n, 0;\n"
                 "WAIT_%=:\nmbarrier.try_wait.parity.shared.b64 p, [%0], %1, 0x100000;\n@p bra DONE_%=;\n"
                 "add.u32 n, n, 1;\nsetp.lt.u32 p, n, 0x400000;\n@p bra WAIT_%=;\ntrap;\nDONE_%=:\n}\n"
                 :: "r"(bar), "r"(parity) : "memory");
}
__device__ __forceinline__ void mbar_wait_c(uint32_t bar, uint32_t parity) {
    asm volatile("{\n.reg .pred p;\nWAIT_%=:\nmbarrier.try_wait.parity.shared.b64 p, [%0], %1;\n@p bra DONE_%=;\nbra WAIT_%=;\nDONE_%=:\n}\n"
                 :: "r"(bar), "r"(parity) : "memory");
}
__device__ __forceinline__ void mbar_wait_h(uint32_t bar, uint32_t parity) {
    asm volatile("{\n.reg .pred p;\nWAIT_%=:\nmbarrier.try_wait.parity.shared.b64 p, [%0], %1, 0x100000;\n@p bra DONE_%=;\nbra WAIT_%=;\nDONE_%=:\n}\n"
                 :: "r"(bar), "r"(parity) : "memory");
}
__device__ __forceinline__ uint32_t lds32(uint32_t a) { uint32_t v; asm volatile("ld.shared.u32 %0, [%1];" : "=r"(v) : "r"(a) : "memory"); return v; }
__device__ __forceinline__ void sts32(uint32_t a, uint32_t v) { asm volatile("st.shared.u32 [%0], %1;" :: "r"(a), "r"(v) : "memory"); }
__device__ __forceinline__ uint2 lds64(uint32_t a) { uint2 v; asm volatile("ld.shared.v2.u32 {%0,%1}, [%2];" : "=r"(v.x), "=r"(v.y) : "r"(a) : "memory"); return v; }
__device__ __forceinline__ void sts64(uint32_t a, uint32_t x, uint32_t y) { asm volatile("st.shared.v2.u32 [%0], {%1,%2};" :: "r"(a), "r"(x), "r"(y) : "memory"); }
__device__ __forceinline__ uint4 lds128(uint32_t a) { uint4 v; asm volatile("ld.shared.v4.u32 {%0,%1,%2,%3}, [%4];" : "=r"(v.x), "=r"(v.y), "=r"(v.z), "=r"(v.w) : "r"(a) : "memory"); return v; }
__device__ __forceinline__ void sts128(uint32_t a, uint4 v) { asm volatile("st.shared.v4.u32 [%0], {%1,%2,%3,%4};" :: "r"(a), "r"(v.x), "r"(v.y), "r"(v.z), "r"(v.w) : "memory"); }
__device__ __forceinline__ void ldsm4t(uint32_t* v, uint32_t a) {
    asm volatile("ldmatrix.sync.aligned.m8n8.x4.trans.shared.b16 {%0,%1,%2,%3}, [%4];" : "=r"(v[0]), "=r"(v[1]), "=r"(v[2]), "=r"(v[3]) : "r"(a) : "memory");
}
__device__ __forceinline__ void stsm4t(uint32_t a, const uint32_t* v) {
    asm volatile("stmatrix.sync.aligned.m8n8.x4.trans.shared.b16 [%0], {%1,%2,%3,%4};" :: "r"(a), "r"(v[0]), "r"(v[1]), "r"(v[2]), "r"(v[3]) : "memory");
}
__device__ __forceinline__ int atoms_inc(uint32_t a) { int v; asm volatile("atom.shared.add.u32 %0, [%1], 1;" : "=r"(v) : "r"(a) : "memory"); return v; }
__device__ __forceinline__ float tanhf_a(float x) { float y; asm("tanh.approx.f32 %0, %1;" : "=f"(y) : "f"(x)); return y; }
__device__ __forceinline__ const char* as_pair(const void* p, uint32_t scratch) {
    const char* r;
    asm volatile("st.shared.u64 [%1], %2;\nld.volatile.shared.u64 %0, [%1];" : "=l"(r) : "r"(scratch), "l"(p) : "memory");
    return r;
}
__device__ __forceinline__ void ld_unit(uint4& v, const char* p, bool ok) {
    asm volatile("{\n.reg .pred q;\nsetp.ne.u32 q, %5, 0;\n@q ld.relaxed.gpu.global.v4.u32 {%0,%1,%2,%3}, [%4];\n}"
                 : "+r"(v.x), "+r"(v.y), "+r"(v.z), "+r"(v.w) : "l"(p), "r"((uint32_t)ok) : "memory");
}
__device__ __forceinline__ void ld_unit(uint2& v, const char* p, bool ok) {
    asm volatile("{\n.reg .pred q;\nsetp.ne.u32 q, %3, 0;\n@q ld.relaxed.gpu.global.v2.u32 {%0,%1}, [%2];\n}"
                 : "+r"(v.x), "+r"(v.y) : "l"(p), "r"((uint32_t)ok) : "memory");
}
#define ELECT "{\n.reg .pred p;\nelect.sync _|p, 0xffffffff;\n@p "
__device__ __forceinline__ void w_init(uint32_t bar, int n) { asm volatile(ELECT "mbarrier.init.shared.b64 [%0], %1;\n}" :: "r"(bar), "r"(n) : "memory"); }
__device__ __forceinline__ void w_expect(uint32_t bar, uint32_t bytes) { asm volatile(ELECT "mbarrier.arrive.expect_tx.shared.b64 _, [%0], %1;\n}" :: "r"(bar), "r"(bytes) : "memory"); }
__device__ __forceinline__ void w_ld(uint32_t dst, const void* src, int bytes, uint32_t bar) {
    asm volatile(ELECT "cp.async.bulk.shared::cluster.global.mbarrier::complete_tx::bytes [%0], [%1], %2, [%3];\n}" :: "r"(dst), "l"(src), "r"(bytes), "r"(bar) : "memory");
}
__device__ __forceinline__ void w_box_ld(uint32_t dst, const CUtensorMap* tm, int row, uint32_t bar) {
    asm volatile(ELECT "cp.async.bulk.tensor.2d.shared::cluster.global.mbarrier::complete_tx::bytes [%0], [%1, {%3, %4}], [%2];\n}"
        :: "r"(dst), "l"((uint64_t)tm), "r"(bar), "r"(0), "r"(row) : "memory");
}
__device__ __forceinline__ void w_st(void* dst, uint32_t src, int bytes) {
    asm volatile(ELECT "cp.async.bulk.global.shared::cta.bulk_group [%0], [%1], %2;\n}" :: "l"(dst), "r"(src), "r"(bytes) : "memory");
}
__device__ __forceinline__ void w_box_st(const CUtensorMap* tm, int col, uint32_t src) {
    asm volatile(ELECT "cp.async.bulk.tensor.2d.global.shared::cta.bulk_group [%0, {%2, %3}], [%1];\n}" :: "l"((uint64_t)tm), "r"(src), "r"(col), "r"(0) : "memory");
}
__device__ __forceinline__ void w_sent(unsigned* p, uint32_t src) {
    asm volatile(ELECT "cp.reduce.async.bulk.global.shared::cta.bulk_group.add.u32 [%0], [%1], 16;\n}" :: "l"(p), "r"(src) : "memory");
}
__device__ __forceinline__ void w_inc(unsigned* p) { asm volatile(ELECT "red.relaxed.gpu.global.add.u32 [%0], 1;\n}" :: "l"(p) : "memory"); }
__device__ __forceinline__ void w_hint(unsigned* p, uint32_t all) {
    #pragma unroll 1
    for (int i = 0; i < 4096; i++) {
        uint32_t v; asm volatile("ld.relaxed.gpu.global.u32 %0, [%1];" : "=r"(v) : "l"(p) : "memory");
        if (__all_sync(~0u, (int)(v - all) >= 0)) break;
    }
}

__device__ __forceinline__ void finish(uint4& a, const uint4& xu, const uint4& xv) {
    asm("{\n.reg .b32 z;\nfma.rn.relu.bf16x2 z, %0, %3, %1;\nadd.rn.bf16x2 %0, z, %2;\n}" : "+r"(a.x) : "r"(xu.x), "r"(xv.x), "r"(0x3F803F80u));
    asm("{\n.reg .b32 z;\nfma.rn.relu.bf16x2 z, %0, %3, %1;\nadd.rn.bf16x2 %0, z, %2;\n}" : "+r"(a.y) : "r"(xu.y), "r"(xv.y), "r"(0x3F803F80u));
    asm("{\n.reg .b32 z;\nfma.rn.relu.bf16x2 z, %0, %3, %1;\nadd.rn.bf16x2 %0, z, %2;\n}" : "+r"(a.z) : "r"(xu.z), "r"(xv.z), "r"(0x3F803F80u));
    asm("{\n.reg .b32 z;\nfma.rn.relu.bf16x2 z, %0, %3, %1;\nadd.rn.bf16x2 %0, z, %2;\n}" : "+r"(a.w) : "r"(xu.w), "r"(xv.w), "r"(0x3F803F80u));
}

constexpr float EPS2 = 2e-6f;
constexpr float TAU = 2.5e-5f;

constexpr uint32_t TAU_BITS = 0x3A103000u;
template<int NP>
__device__ __forceinline__ bool epi_fast(const float* g, const float* h, float m2, float tau, float& n0, float& d0, float& n1, float& d1, float& dmin)
{
    constexpr int JC = NP >= 6 ? NP - 3 : NP - 2;
    bool ok;
    #pragma unroll
    for (int j = 0; j < NP; j++) {
        float t0 = tanhf_a(g[4*j+0]), t1 = tanhf_a(g[4*j+1]), t2 = tanhf_a(g[4*j+2]), t3 = tanhf_a(g[4*j+3]);
        auto add_d = [&]() {
            if (j == 0) { d0 = t0 + (2.f * (JC + 1) + EPS2); d1 = t2 + (2.f * (JC + 1) + EPS2); } else { d0 += t0; d1 += t2; }
            d0 += t1; d1 += t3;
        };
        if (j <= JC) add_d();
        if (j == 0) { n0 = fmaf(t0, h[0], h[0]); n1 = fmaf(t2, h[2], h[2]); }
        t0 += 1.f; t2 += 1.f;
        if (j == NP - 1) { t1 = fmaf(t1, m2, m2); t3 = fmaf(t3, m2, m2); } else { t1 += 1.f; t3 += 1.f; }
        if (j > JC) add_d();
        if (j > 0) { n0 = fmaf(t0, h[4*j], n0); n1 = fmaf(t2, h[4*j+2], n1); }
        n0 = fmaf(t1, h[4*j+1], n0); n1 = fmaf(t3, h[4*j+3], n1);
        if (j == JC) { dmin = fminf(d0, d1); ok = dmin >= tau; }
    }
    return ok;
}

__device__ __noinline__ void slow_bin(const __nv_bfloat16* x, const __nv_bfloat16* ea, const int* src, const int* dst,
                                      const __nv_bfloat16* wa, const __nv_bfloat16* wb, const __nv_bfloat16* wc,
                                      const __nv_bfloat16* wu, const __nv_bfloat16* wv, __nv_bfloat16* out,
                                      int E, int node0, int nn, int nthr)
{
    const int tid = threadIdx.x, lane = tid & 31;
    for (int i = tid; i < nn * 128; i += nthr) g_slow[(size_t)node0 * 128 + i] = 0.f;
    asm volatile("bar.sync 1, %0;" :: "r"(nthr) : "memory");
    for (int e0 = (tid >> 5) * 32; e0 < E; e0 += nthr) {
        int d = (e0 + lane < E) ? dst[e0 + lane] - node0 : -1;
        unsigned m = __ballot_sync(~0u, d >= 0 && d < nn);
        while (m) {
            int l = __ffs(m) - 1; m &= m - 1;
            int e = e0 + l, n = node0 + __shfl_sync(~0u, d, l), s = src[e];
            float g0 = 0, g1 = 0, h0 = 0, h1 = 0;
            for (int k = 0; k < 64; k++) {
                float xs = __bfloat162float(x[(size_t)s * 64 + k]), xd = __bfloat162float(x[(size_t)n * 64 + k]);
                uint32_t b2 = *(const uint32_t*)(wb + k * 64 + 2 * lane), v2 = *(const uint32_t*)(wv + k * 64 + 2 * lane);
                uint32_t a2 = *(const uint32_t*)(wa + k * 64 + 2 * lane);
                g0 = fmaf(xs, bf_lo(b2), fmaf(xd, bf_lo(a2), g0)); g1 = fmaf(xs, bf_hi(b2), fmaf(xd, bf_hi(a2), g1));
                h0 = fmaf(xs, bf_lo(v2), h0); h1 = fmaf(xs, bf_hi(v2), h1);
            }
            for (int k = 0; k < 16; k++) {
                float ev = __bfloat162float(ea[(size_t)e * 16 + k]);
                uint32_t c2 = *(const uint32_t*)(wc + k * 64 + 2 * lane);
                g0 = fmaf(ev, bf_lo(c2), g0); g1 = fmaf(ev, bf_hi(c2), g1);
            }
            float s0 = rcpf(1.f + ex2f(-LOG2E * g0)), s1 = rcpf(1.f + ex2f(-LOG2E * g1));
            float* acc = g_slow + (size_t)n * 128 + 4 * lane;
            atomicAdd(acc + 0, s0 * h0); atomicAdd(acc + 1, s0);
            atomicAdd(acc + 2, s1 * h1); atomicAdd(acc + 3, s1);
        }
    }
    __threadfence();
    asm volatile("bar.sync 1, %0;" :: "r"(nthr) : "memory");
    for (int i = tid; i < nn * 32; i += nthr) {
        int n = node0 + (i >> 5), cp = i & 31;
        float4 a = __ldcg((const float4*)(g_slow + (size_t)n * 128 + 4 * cp));
        float u0 = 0, u1 = 0;
        for (int k = 0; k < 64; k++) {
            float xd = __bfloat162float(x[(size_t)n * 64 + k]);
            uint32_t w2 = *(const uint32_t*)(wu + k * 64 + 2 * cp);
            u0 = fmaf(xd, bf_lo(w2), u0); u1 = fmaf(xd, bf_hi(w2), u1);
        }
        uint32_t xv = *(const uint32_t*)(x + (size_t)n * 64 + 2 * cp);
        float z0 = u0 + a.x / (a.y + 1e-6f), z1 = u1 + a.z / (a.w + 1e-6f);
        *(uint32_t*)(out + (size_t)n * 64 + 2 * cp) = pack_bf16(bf_lo(xv) + fmaxf(z0, 0.f), bf_hi(xv) + fmaxf(z1, 0.f));
    }
}

__global__ void __launch_bounds__(256) slow_kernel(const __nv_bfloat16* x, const __nv_bfloat16* ea, const int* src, const int* dst,
        const __nv_bfloat16* wa, const __nv_bfloat16* wb, const __nv_bfloat16* wc, const __nv_bfloat16* wu, const __nv_bfloat16* wv,
        __nv_bfloat16* out, int N, int E, int npb)
{
    int node0 = blockIdx.x * npb;
    slow_bin(x, ea, src, dst, wa, wb, wc, wu, wv, out, E, node0, max(0, min(npb, N - node0)), 256);
}

constexpr int XS_BYTES = NPMAX * 1024;
constexpr int ES_BYTES = NPMAX * 256;
constexpr int SM_XS = 0;
constexpr int SM_XU = SM_XS + 3 * NSTAGE * XS_BYTES;
constexpr int SM_TAB = SM_XU + NPB_MAX * 128;
constexpr int SM_ES = SM_TAB + NPB_MAX * 128;
constexpr int SM_WC = SM_ES + 3 * NSTAGE * ES_BYTES;
constexpr int SM_OH = SM_WC + 2048;
constexpr int SM_EID = SM_OH + 128;
constexpr int SM_SRC = SM_EID + SLOT_CAP * 4;
constexpr int SM_TINFO = SM_SRC + SLOT_CAP * 2;
constexpr int SM_MISC = SM_TINFO + TILE_CAP * 32;
constexpr int SM_CLAIM = SM_MISC + 32 * 4;
constexpr int STG = 272;
constexpr int SM_BARS = SM_CLAIM + 32 * 4;
constexpr int SM_ABAR = SM_BARS + 6 * STG;
constexpr int SM_GBAR = SM_ABAR + 16 * 8;
constexpr int SMEM_BYTES = SM_GBAR + (GD + 1) * 8;
constexpr int SM_P2 = 0, SM_P1 = P2B + 256;
constexpr int SM_L1 = SM_P1 + P1B + 128;
constexpr int SM_DEG = SM_L1 + 256;
constexpr int SM_CLS = SM_DEG + 512 * 4;
constexpr int SM_HIST = SM_CLS + NCLS * 4;
constexpr int SM_XLIST = SM_HIST + NB_MAX * 4;
constexpr int SM_SORT = SM_XLIST + 8;
constexpr int SM_SDEG = SM_SORT + NPB_MAX * 4;
constexpr int SM_PAIR = SM_SDEG + NPB_MAX * 2;
constexpr int SM_ENT = SM_ES + 1024;
constexpr int SM_H1 = SM_P1 + HB, SM_H2 = SM_P1;
constexpr int SM_IDX = SM_EID;
constexpr int SM_WR = SM_TAB;
static_assert(TILE_CAP <= 128 && TR >= 2 && SM_ES % 256 == 0 && NSTAGE == 2 && SM_BARS % 16 == 0 && SM_TINFO % 16 == 0 && SM_EID % 128 == 0 && SM_TAB % 1024 == 0 && SM_XU % 1024 == 0 && SM_TINFO % 8 == 0 && SM_OH % 16 == 0 && SM_XLIST % 8 == 0 && SM_PAIR % 8 == 0, "align");
static_assert(SM_P1 % 128 == 0 && P1B + HB <= SM_SRC - SM_EID && 2 * HB <= P1B && SM_H1 + 5 * 128 * 16 <= SM_XU && NB_MAX * (CE / 4) <= 6 * 384 && NB_MAX * 4 <= 5 * 128 && NB_MIN * 4 >= 3 * 128 && SM_PAIR + 128 * 8 <= SM_XU && CH_MAX * 4 <= SM_SRC - SM_EID && SM_DEG >= 3 << 14, "alias");
static_assert(KM == 4 && CE == 64 && SMEM_BYTES <= 232448, "smem");
constexpr uint32_t C_BRK = 16  , C_CONT = 32, C_MORE = 64;
constexpr uint32_t ONE_F = 0x3F800000u;
constexpr int NONE = NPB_MAX - 1;
__host__ __device__ constexpr uint32_t tab_at(uint32_t n) { return (n >> 2) * 512 + (n & 3) * 32 + ((n >> 2) & 1) * 16; }

__device__ __forceinline__ bool unpad(uint32_t w1, int np, float ga, float gb, float& d0, float& d1, int& dv) {
    const int pad = (w1 >> 8) & 31;
    dv = 2 * np - 1 - pad + (w1 >= ONE_F);
    float t0 = TAU * 2 * np, t1 = t0;
    if (pad) {
        t0 = fmaxf(t0, d0 * (1.f / 16384)); t1 = fmaxf(t1, d1 * (1.f / 16384));
        asm volatile("tanh.approx.f32 %0, %0;\ntanh.approx.f32 %1, %1;" : "+f"(ga), "+f"(gb));
        d0 -= pad * (1.f + ga); d1 -= pad * (1.f + gb);
    }
    if (dv == 0) { d0 = d1 = EPS2; t0 = t1 = 0.f; }
    return d0 < t0 || d1 < t1;
}
constexpr int SM_COPY = SM_XU + tab_at(NPB_MAX - 4) - 16;
__device__ __forceinline__ void exact_quad(const float4 g, const float4 h, int k, int dv, float4& r) {
    const float e0 = 2.f * rcpf(1.f + ex2f(-2.f * LOG2E * g.x)), e1 = 2.f * rcpf(1.f + ex2f(-2.f * LOG2E * g.y));
    const float e2 = 2.f * rcpf(1.f + ex2f(-2.f * LOG2E * g.z)), e3 = 2.f * rcpf(1.f + ex2f(-2.f * LOG2E * g.w));
    if (k < dv) { r.y += e0; r.x = fmaf(e0, h.x, r.x); r.w += e2; r.z = fmaf(e2, h.z, r.z); }
    if (k + 1 < dv) { r.y += e1; r.x = fmaf(e1, h.y, r.x); r.w += e3; r.z = fmaf(e3, h.w, r.z); }
}
__device__ __forceinline__ float4 ldsf4(uint32_t a) { const uint4 v = lds128(a); return make_float4(__uint_as_float(v.x), __uint_as_float(v.y), __uint_as_float(v.z), __uint_as_float(v.w)); }
__device__ __noinline__ float4 exact_1(uint32_t sa, uint32_t l16, int np, uint32_t own)
{
    const uint32_t n16 = np * 16, slot = (l16 >= n16) + (l16 >= 2 * n16);
    __syncwarp();
    const float4 g = ldsf4(sa + l16), h = ldsf4(sa + 240 + l16);
    float4 r = make_float4(0.f, 0.f, 0.f, 0.f);
    exact_quad(g, h, (l16 - slot * n16) >> 3, lds32(sa + 496 + slot * 4), r);
    __syncwarp();
    sts128(sa + l16, make_uint4(__float_as_uint(r.x), __float_as_uint(r.y), __float_as_uint(r.z), __float_as_uint(r.w)));
    __syncwarp();
    r = make_float4(0.f, EPS2, 0.f, EPS2);
    #pragma unroll
    for (int j = 0; j < NPMAX; j++) {
        const float4 v = ldsf4(own + j * 16);
        if (j < NPMIN || j < np) { r.x += v.x; r.y += v.y; r.z += v.z; r.w += v.w; }
    }
    __syncwarp();
    sts32(sa + (SM_MISC + 12 - SM_COPY), 0);
    return r;
}
__device__ __noinline__ float4* exact_copy() { return g_copy + (blockIdx.x * 12 + (threadIdx.x >> 5)) * (64 * NPMAX) + (threadIdx.x & 31); }
__device__ __noinline__ float4 exact_all(const float4* gh, int np, int dv)
{
    float4 r = make_float4(0.f, EPS2, 0.f, EPS2);
    #pragma unroll 1
    for (int j = 0; j < np; j++, gh += 32) exact_quad(gh[0], gh[32 * NPMAX], 2 * j, dv, r);
    return r;
}
template<int NP>
__device__ __forceinline__ float4 epi_exact(const float* g, const float* h, uint32_t bad, bool on, int dv, uint32_t sa, uint32_t l16) {
    uint32_t old = 1;
    const uint32_t b1 = bad & (bad - 1), b2 = b1 & (b1 - 1);
    uint32_t slot = 0;
    if (15 / NP > 1) {
        uint32_t lt; asm("mov.u32 %0, %%lanemask_lt;" : "=r"(lt));
        slot = on ? ((bad & lt) != 0) + ((b1 & lt) != 0) : 0;
    }
    const uint32_t own = sa + slot * (NP * 16);
    if ((15 / NP > 2 ? b2 & (b2 - 1) : 15 / NP > 1 ? b2 : b1) == 0) {
        #pragma unroll 1
        for (int n = 0; n < 12; n++) {
            asm volatile(ELECT "atom.shared.or.b32 %0, [%1], 1;\n}" : "+r"(old) : "r"(sa + (SM_MISC + 12 - SM_COPY)) : "memory");
            if (__any_sync(~0u, old != 1)) break;
        }
    }
    if (__any_sync(~0u, old == 0)) {
        #pragma unroll
        for (int i = 0; i < 2 * NP; i++) {
            const float* v = i < NP ? g + 4 * i : h + 4 * (i - NP);
            asm volatile("{\n.reg .pred p;\nsetp.ne.u32 p, %5, 0;\n@p st.shared.v4.f32 [%0], {%1,%2,%3,%4};\n}"
                         :: "r"(own + (i < NP ? i : 15 + i - NP) * 16), "f"(v[0]), "f"(v[1]), "f"(v[2]), "f"(v[3]), "r"((uint32_t)on) : "memory");
        }
        asm volatile("{\n.reg .pred p;\nsetp.ne.u32 p, %2, 0;\n@p st.shared.u32 [%0], %1;\n}" :: "r"(sa + 496 + slot * 4), "r"(dv), "r"((uint32_t)on) : "memory");
        return exact_1(sa, l16, NP, own);
    }
    float4* gh = exact_copy();
    #pragma unroll
    for (int i = 0; i < 2 * NP; i++) {
        const float* v = i < NP ? g + 4 * i : h + 4 * (i - NP);
        asm volatile("st.global.v4.f32 [%0], {%1,%2,%3,%4};" :: "l"(gh + (i < NP ? i : NPMAX + i - NP) * 32), "f"(v[0]), "f"(v[1]), "f"(v[2]), "f"(v[3]) : "memory");
    }
    return exact_all(gh, NP, dv);
}
__device__ __forceinline__ uint32_t row_bytes(uint32_t o) { return (o & 0xFE00) | ((o << 2) & 0x180); }

__device__ __noinline__ int balance(int step, char* gs, uint32_t id, int ng, int npb)
{
    extern __shared__ __align__(1024) uint8_t smem[];
    const uint32_t sb = smem_u32(smem), lane = threadIdx.x & 31, b = blockIdx.x, r4 = lane >> 3;
    const uint32_t tw = ((lane & 1) << 4) | ((lane & 6) << 6), ti = sb + SM_TINFO + r4 * 8, st = sb + SM_MISC + 48;
    uint32_t now; asm volatile("mov.u32 %0, %%globaltimer_lo;" : "=r"(now));
    auto put = [&](uint32_t a, uint32_t v) { if (lane == 0) asm volatile("st.relaxed.gpu.global.v2.u32 [%0], {%1, %2};" :: "l"(gs + a), "r"(v), "r"(id) : "memory"); };
    auto get = [&](uint32_t a) {
        uint2 v;
        #pragma unroll 1
        for (uint32_t n = 0; ; n++) {
            asm volatile("ld.acquire.gpu.global.v2.u32 {%0, %1}, [%2];" : "=r"(v.x), "=r"(v.y) : "l"(gs + a) : "memory");
            if (__all_sync(~0u, v.y == id)) break;
            if (n > (1u << 22)) __trap();
        }
        return v.x;
    };
    int gn = ng;
    if (step < 0) {
        if (BAL && step == -1) {
            const uint32_t e = lds32(sb + SM_TINFO + (3 * R1 + 3) * 32);
            if ((e & 0xFFFF) >= KM * 64 && ((e >> 20) & 127) < 2 && ((lds32(sb + SM_TINFO + (ng - KM) * 32 + 4) >> 16) & 15) <= 8 && lds32(sb + SM_MISC + 24) == 0) {
                #pragma unroll 1
                for (int j = 0; j < KM; j++) {
                    const uint32_t ta = (ng - 1 - j) * 32, s0 = lds32(sb + SM_TINFO + ta) & 0xFFFF;
                    const uint2 e = lds64(ti + ta);
                    char* p = gs + G_P + (b * KM + j) * GRP_B;
                    const uint32_t ro = sb + ((e.y & 0xFFFF) ^ tw);
                    *(uint4*)(p + lane * 16) = lds128(ro + SM_TAB);
                    *(uint4*)(p + 512 + lane * 16) = lds128(ro + SM_XU);
                    *(uint2*)(p + 1024 + lane * 8) = lds64(sb + SM_EID + s0 * 4 + lane * 8);
                    *(uint32_t*)(p + 1280 + lane * 4) = lds32(sb + SM_SRC + s0 * 2 + lane * 4);
                    *(uint2*)(p + 1408 + r4 * 8) = make_uint2(e.x >> 27 ? e.x - s0 : e.x, e.y);
                }
                uint32_t c = 0;
                #pragma unroll 1
                for (int g = 3 * R1 + 3 + lane; g < ng; g += 32) c += 93 + ((lds32(sb + SM_TINFO + g * 32 + 4) >> 16) & 15) * 42;
                sts32(st, (__reduce_add_sync(~0u, c) * 595) >> 10);
                asm volatile("fence.acq_rel.gpu;" ::: "memory");
                __syncwarp();
                return 1;
            }
        }
        put(G_F + b * 8, (now << 6) & ~511u);
    } else if (step == R2) {
        uint2 v[5];
        #pragma unroll 1
        for (uint32_t n = 0; ; n++) {
            bool ok = true;
            #pragma unroll
            for (int i = 0; i < 5; i++) asm volatile("ld.relaxed.gpu.global.v2.u32 {%0, %1}, [%2];" : "=r"(v[i].x), "=r"(v[i].y) : "l"(gs + G_F + min(lane + 32 * i, gridDim.x - 1) * 8) : "memory");
            #pragma unroll
            for (int i = 0; i < 5; i++) ok &= v[i].y == id;
            if (__all_sync(~0u, ok)) break;
            if (n > (1u << 22)) __trap();
        }
        const uint32_t ref = __shfl_sync(~0u, v[0].x, 0) - 0x80000000u, key = ((lds32(st) - ref) & ~511u) | b;
        uint32_t c = 0;
        #pragma unroll
        for (int i = 0; i < 5; i++) if (lane + 32 * i < gridDim.x && (v[i].x & 256)) c += 0x10000 + ((((v[i].x - ref) & ~511u) | (lane + 32 * i)) < key);
        c = __reduce_add_sync(~0u, c);
        const uint32_t kf = key | (ng % 3 == 0 ? 256 : 0);
        put(G_R + (c & 0xFFFF) * 8, kf);
        sts64(st, kf, (c >> 16) - 1 - (c & 0xFFFF));
        __syncwarp();
        return gn;
    } else {
        const uint32_t pk = get(G_R + lds32(st + 4) * 8);
        const uint32_t key = lds32(st);
        const int df = (int)(pk >> 9) - (int)(key >> 9), m = min((abs(df) * 8 + 175) / 350, (df < 0 ? pk : key) & 256 ? 3 : KM);
        gn += df < 0 ? -m : m;
        #pragma unroll 1
        for (int i0 = 0; i0 < gn - ng; i0 += 2) {
            uint4 ra[2], ru[2]; uint2 le[2], e[2]; uint32_t ls[2];
            #pragma unroll
            for (int i = 0; i < 2; i++) {
                const char* p = gs + G_P + ((pk & 255) * KM + i0 + i) * GRP_B;
                ra[i] = __ldcg((const uint4*)(p + lane * 16)); ru[i] = __ldcg((const uint4*)(p + 512 + lane * 16));
                le[i] = __ldcg((const uint2*)(p + 1024 + lane * 8)); e[i] = __ldcg((const uint2*)(p + 1408 + r4 * 8));
                ls[i] = __ldcg((const uint32_t*)(p + 1280 + lane * 4));
            }
            #pragma unroll
            for (int i = 0; i < 2; i++) {
                const int j = (m - 1 - i0 - i) & 3;
                const bool some = (e[i].y & 0xFFFF) != tab_at(NONE);
                const uint32_t row = some ? lds32(ti + (i0 + i) * 32 + 4) & 0xFFFF : tab_at(NONE);
                if (some) { sts128(sb + (row ^ tw) + SM_TAB, ra[i]); sts128(sb + (row ^ tw) + SM_XU, ru[i]); }
                sts64(sb + SM_EID + (i0 + i) * 256 + lane * 8, le[i].x, le[i].y);
                sts32(sb + SM_SRC + (i0 + i) * 128 + lane * 4, ls[i]);
                sts32(sb + SM_MISC + 64 + j * 16 + r4 * 4, (pk & 255) * npb * 128 + row_bytes(e[i].y & 0xFFFF));
                sts64(ti + (ng + j) * 32, ((e[i].x & 0xF800FFFFu) + (i0 + i) * 64) | (((e[i].y >> 16) & 15) > 5 ? 14u << 16 : 13u << 16), (e[i].y & 0xFFFF0000u) | row);
            }
        }
        __syncwarp();
        sts32(sb + SM_TINFO + gn * 32 + lane * 4, lane & 1 ? tab_at(NONE) : 0);
        sts32(sb + SM_MISC + 16, gn);
    }
    sts32(sb + SM_MISC + 28, gn);
    __syncwarp();
    if (lane == 0) mbar_arrive(sb + SM_ABAR + 32);
    return step < 0 ? 0 : gn;
}
__device__ __forceinline__ uint32_t bin_bits(uint32_t b) { return (1u << (b & 7)) | ((b < 48 ? 0x100u : 0x400u) << (b >> 3)); }
__device__ __forceinline__ void place(uint32_t sbase, uint32_t slot, uint32_t v, uint32_t eb) {
    asm volatile("{\n.reg .pred p;\nsetp.lt.u32 p, %0, %5;\n@p st.shared.u32 [%1], %2;\n@p st.shared.u16 [%3], %4;\n}"
                 :: "r"(slot), "r"(sbase + SM_EID + slot * 4), "r"(eb + (v >> 19)), "r"(sbase + SM_SRC + slot * 2), "r"(v), "n"(SLOT_CAP) : "memory");
}
__device__ __forceinline__ uint64_t desc_sw128(uint32_t a) {
    return (uint64_t)((a & 0x3FFFF) >> 4) | ((uint64_t)1 << 16) | ((uint64_t)64 << 32) | ((uint64_t)1 << 62);
}

template<bool LO32>
__global__ void __launch_bounds__(THREADS, 1)
gcn_kernel(const int* __restrict__ dst, unsigned* gbar, char* gs, const int* __restrict__ src, int E, int ch, int N, int npb, uint32_t magic,
           const __nv_bfloat16* __restrict__ x, const __nv_bfloat16* __restrict__ ea,
           const __nv_bfloat16* __restrict__ wa, const __nv_bfloat16* __restrict__ wb, const __nv_bfloat16* __restrict__ wc,
           const __nv_bfloat16* __restrict__ wu, const __nv_bfloat16* __restrict__ wv,
           __nv_bfloat16* out, int4 wrow, const __grid_constant__ CUtensorMap tm1, const __grid_constant__ CUtensorMap tm2,
           const __grid_constant__ CUtensorMap tmw, const __grid_constant__ CUtensorMap tmx)
{
    extern __shared__ __align__(1024) uint8_t smem[];
    int* cls = (int*)(smem + SM_CLS);
    int* misc = (int*)(smem + SM_MISC);
    WG0(); WS(0); CG(0);
    const uint32_t sbase = smem_u32(smem);
    const int tid = threadIdx.x, lane = tid & 31;
    const int b = blockIdx.x, nb = gridDim.x;
    const int cnt = max(0, min(ch, E - b * ch));
    const int node0 = b * npb;
    uint32_t tag = 0;
    if (tid < 384) asm volatile("ld.relaxed.gpu.global.u32 %0, [%1];" : "=r"(tag) : "l"(gbar) : "memory");
    auto dst_ld = [&](int v, uint32_t n) {
        const uint32_t off = v * (THREADS * 4) + tid * 4;
        asm volatile("{\n.reg .pred q;\nsetp.lt.u32 q, %2, %3;\n@q cp.async.cg.shared.global [%0], [%1], 16;\n}"
                     :: "r"(sbase + SM_IDX + off * 4), "l"(dst + (uint32_t)(b * ch + off)), "r"(off), "r"(n) : "memory");
    };
    dst_ld(0, min(cnt, 384 * 4));
    const int warp = (int)__reduce_max_sync(~0u, (unsigned)tid >> 5);
    const uint32_t su = __reduce_or_sync(~0u, sbase);
    if (warp >= 12) {
        const int v = warp & 3;
        const uint32_t a1 = su + SM_ABAR + (v == 0 ? 80 : v == 1 ? 120 : v == 2 ? 32 : 40);
        w_init(su + SM_ABAR + v * 8, 1); w_init(a1, 1);
        w_expect(su + SM_ABAR + v * 8, v < 3 ? min(max(cnt * 4 - v * 8192, 0), 8192) : 4 * 8192 + 2048);
        if (v < 2) w_expect(a1, v == 0 ? nb * (CE * 2) : nb * 64);
        asm volatile("fence.mbarrier_init.release.cluster;" ::: "memory");
        dst_ld(0, cnt);
    }
    #pragma unroll
    for (int v = 0; v < EPT / 4; v++) {
        if (v) {
            uint32_t c0, c1; asm volatile("mov.u32 %0, %%clock;" : "=r"(c0)); do { asm volatile("mov.u32 %0, %%clock;" : "=r"(c1)); } while (__all_sync(~0u, c1 - c0 < PD));
            dst_ld(v, cnt);
        }
        cp_commit();
    }
    if (warp == 15) {
        w_box_ld(su + SM_WR, &tmw, wrow.x, su + SM_ABAR + 24); w_box_ld(su + SM_WR + 8192, &tmw, wrow.y, su + SM_ABAR + 24);
        w_box_ld(su + SM_WR + 16384, &tmw, wrow.z, su + SM_ABAR + 24); w_ld(su + SM_WR + 24576, wc, 2048, su + SM_ABAR + 24);
        w_box_ld(su + SM_WR + 40960, &tmw, wrow.w, su + SM_ABAR + 24);
    }
    const int wg = warp >> 2, w = warp & 3;
    const int q = lane >> 2, t = lane & 3;
    const int nn = max(0, min(npb, N - node0));
    if (sbase & 1023) __trap();

    sts32(sbase + SM_DEG + tid * 4, tid < NPB_MAX ? 0 : 0x80000000u);
    if (tid < NCLS + NB_MAX) cls[tid] = tid < NCLS ? 0 : ((tid - NCLS) * 20) & 63;
    else if (warp == 8) sts32(sbase + SM_OH + lane * 4, t != (q >> 1) ? 0u : 0x00003F00u);
    else if (warp == 11) misc[lane] = lane == 5 ? TILE_CAP - TILE_X : lane == 3 ? 3 : lane == 8;
    if (warp == 14) sts32(sbase + SM_TINFO + 96 * 32 + lane * 4, lane & 1 ? tab_at(NONE) : 0);
    if (warp == 15) sts32(sbase + SM_CLAIM + lane * 4, lane == 0 ? 3 * 32 : 0x40000000);
    if (tid == 0) sts32(sbase + SM_XLIST, tag);
    tag = (tag & 1) | 2;
    if (wg < 3) {
        const uint32_t d0 = ((NPB_MAX + ((2 * lane) & 15) + 16 * (b & 1)) * 4 | (tag << 14)) * 0x10001u, d1 = d0 + 0x40004u, d2 = tag << 16;
        #pragma unroll 1
        for (int i = tid; i < (P1B + 384) / 16; i += 384) {
            sts128(sbase + SM_P1 + i * 16, make_uint4(d0, d0, d1, i == P1B / 16 + 11 ? 0x80000000u | (tag << 14) : d1));
            sts128(sbase + SM_P2 + i * 16, make_uint4(d2, d2, d2, d2)); sts128(sbase + SM_P2 + P1B - 128 + i * 16, make_uint4(d2, d2, d2, d2));
        }
    }
    WS(1);
    __syncthreads();
    if (wg == 3) tag = lds32(sbase + SM_P2) >> 16;
    uint32_t all = 0;
    if (wg == 3) all = (lds32(sbase + SM_XLIST) + 1) * nb;
    if (tid == 128) {
        asm volatile("prefetch.tensormap [%0];" :: "l"((uint64_t)&tm1) : "memory");
        asm volatile("prefetch.tensormap [%0];" :: "l"((uint64_t)&tm2) : "memory");
        asm volatile("prefetch.tensormap [%0];" :: "l"((uint64_t)&tmx) : "memory");
    }
    const uint32_t m4 = __reduce_or_sync(~0u, -4 * npb);
    uint32_t ent[EPT];
    #pragma unroll
    for (int v = 0; v < EPT / 4; v++) {
        if (v == 0) cp_wait<2>(); else if (v == 1) cp_wait<1>(); else cp_wait<0>();
        if (v == 0 && wg == 2 && w < 3) {
            const int n = min(cnt * 4 - w * 8192, 8192);
            if (n > 0) w_ld(su + SM_XU + w * 8192, src + b * ch + w * 2048, n, su + SM_ABAR + w * 8);
        }
        const uint32_t off = v * (THREADS * 4) + tid * 4;
        if (off < (uint32_t)cnt) {
            const uint4 u = lds128(sbase + SM_IDX + off * 4);
            uint32_t dv[4] = {u.x, u.y, u.z, u.w}, ps[4], ck[4];
            uint32_t* en = ent + 4 * v;
            #pragma unroll
            for (int k = 0; k < 4; k++) {
                dv[k] = min(dv[k], (uint32_t)(nb * npb - 1));
                ps[k] = __umulhi(dv[k], magic);
                asm volatile("atom.shared.add.u32 %0, [%1], 0x10001;" : "=r"(ck[k]) : "r"(sbase + SM_HIST + ps[k] * 4) : "memory");
            }
            #pragma unroll
            for (int k = 0; k < 4; k++) {
                dv[k] = ps[k] * m4 + (dv[k] * 4 + (tag << 14));
                en[k] = (ck[k] & 63) + ps[k] * CE;
            }
            if (__builtin_expect(max(max(ck[0], ck[1]), max(ck[2], ck[3])) >= CE << 16, 0)) {
                auto step = [&]() {
                    uint32_t e = en[0];
                    const uint32_t d = dv[0];
                    if (ck[0] >= CE << 16) {
                        uint32_t j; asm volatile("atom.shared.inc.u32 %0, [%1], 0x7fffffff;" : "=r"(j) : "r"(sbase + SM_MISC + 8) : "memory");
                        j = min(j + (j >= 15), 63u);
                        sts32(sbase + SM_L1 + j * 4, d | ((j < 63 ? e / CE : 255u) << 16));
                        e = NB_MAX * CE + j;
                    }
                    en[0] = en[1]; en[1] = en[2]; en[2] = en[3]; en[3] = e;
                    dv[0] = dv[1]; dv[1] = dv[2]; dv[2] = dv[3]; dv[3] = d;
                    ck[0] = ck[1]; ck[1] = ck[2]; ck[2] = ck[3];
                };
                if (v == 2) { step(); step(); step(); step(); }
                else {
                    #pragma unroll 1
                    for (int k = 0; k < 4; k++) step();
                }
            }
            #pragma unroll
            for (int k = 0; k < 4; k++)
                asm volatile("st.shared.u16 [%0], %1;" :: "r"(sbase + SM_P1 + en[k] * 2), "r"(dv[k]) : "memory");
        }
    }
    if (warp == 15) {
        #pragma unroll
        for (int v = 0; v < EPT / 4; v++) sts128(sbase + SM_ENT + v * 512 + lane * 16, make_uint4(ent[4*v], ent[4*v+1], ent[4*v+2], ent[4*v+3]));
    }
    asm volatile("fence.proxy.async.shared::cta;" ::: "memory");
    WS(5);
    __syncthreads();
    if (warp == 15) {
        w_inc(gbar + 1);
        const uint32_t n = __reduce_or_sync(~0u, lds32(su + SM_MISC + 8));
        if (__builtin_expect(n > 15, 0)) {
            const uint2 r = lds64(su + SM_L1 + lane * 8);
            uint32_t m = lane < 8 ? 0 : (r.x >> 24 ? 0 : bin_bits(r.x >> 16)) | (r.y >> 24 ? 0 : bin_bits(r.y >> 16));
            m = n > 62 ? 0x7FFF3FFFu : __reduce_or_sync(~0u, m);
            sts32(su + SM_L1 + 60, m | 0x80000000u | (tag << 14));
            asm volatile("fence.proxy.async.shared::cta;" ::: "memory");
            __syncwarp();
        }
        w_st(gs + G_H1 + b * 64, su + SM_L1, 64);
        w_box_st(&tm1, b * (CE / 2), su + SM_P1);
        w_st(gs + G_L + b * 512, su + SM_L1, 256);
        asm volatile("cp.async.bulk.commit_group;" ::: "memory");
    } else {
        mbar_wait_c(su + SM_ABAR, 0);
        auto put = [&](uint32_t off, const uint32_t* uu) {
            if (off < (uint32_t)cnt) {
                const uint4 sv = lds128(sbase + SM_XU + off * 4);
                const uint32_t ss[4] = {sv.x, sv.y, sv.z, sv.w};
                #pragma unroll
                for (int k = 0; k < 4; k++) sts32(sbase + SM_P2 + uu[k] * 4, (ss[k] & 0xFFFF) | (((off + k) << 19) + (tag << 16)));
            }
        };
        #pragma unroll
        for (int v = 0; v < EPT / 4; v++) { if (v) mbar_wait_c(su + SM_ABAR + v * 8, 0); put(v * (THREADS * 4) + tid * 4, ent + 4 * v); }
        if (wg == 3) {
            const uint4 e = lds128(sbase + SM_ENT + w * 512 + lane * 16);
            const uint32_t uu[4] = {e.x, e.y, e.z, e.w};
            put(w * (THREADS * 4) + (480 + lane) * 4, uu);
        }
        asm volatile("fence.proxy.async.shared::cta;" ::: "memory");
        WS(7);
        __syncwarp();
        asm volatile("bar.arrive 12, 512;" ::: "memory");
    }
    WS(8);

    const int ngroups = (nn + 3) >> 2;
    if (warp < 12) {
        asm volatile("setmaxnreg.inc.sync.aligned.u32 152;");
        const uint32_t ab = su + SM_ABAR;
        uint32_t wf[40], wn[32];
        const uint32_t mo = su + (8 * (lane >> 4) + (lane & 7)) * 128 + (((2 * w + ((lane >> 3) & 1)) ^ (lane & 7)) << 4);
        const uint32_t wca = __shfl_sync(~0u, su + SM_WC + (16 * w + q) * 32 + t * 4 + ((q >> 2) << 4), lane), l16 = __shfl_sync(~0u, (lane & 15) * 16, lane);
        mbar_wait_c(ab + 24, 0);
        {
            #pragma unroll
            for (int ks = 0; ks < 4; ks++) { ldsm4t(wf + 4 * ks, mo + SM_WR + ks * 2048); ldsm4t(wf + 20 + 4 * ks, mo + SM_WR + 8192 + ks * 2048); ldsm4t(wn + 4 * ks, mo + SM_WR + 16384 + ks * 2048); ldsm4t(wn + 16 + 4 * ks, mo + SM_WR + 40960 + ks * 2048); }
            auto half = [](uint32_t& v) { asm("mul.rn.bf16x2 %0, %0, %1;" : "+r"(v) : "r"(0x3F003F00u)); };
            uint32_t z = 0;
            #pragma unroll
            for (int i = 0; i < 16; i++) { half(wf[i]); z ^= wf[i]; }
            sts32(su + SM_ES + lane * 4, z);
            if (wg == 2) {
                uint32_t f[4];
                ldsm4t(f, (mo ^ ((lane & 7) << 4)) + SM_WR + 24576);
                half(f[0]); half(f[1]); half(f[2]); half(f[3]);
                sts32(wca, f[0]); sts32(wca + 256, f[1]); sts32(wca ^ 16, f[2]); sts32((wca ^ 16) + 256, f[3]);
                asm volatile("fence.proxy.async.shared::cta;" ::: "memory");
            }
        }
        const uint64_t wcd = __reduce_or_sync(~0u, (((su + SM_WC) & 0x3FFFF) >> 4) | (8u << 16)) | EDHI;
        const uint32_t bar0 = __reduce_or_sync(~0u, su + SM_BARS + wg * 2 * STG);
        const uint32_t xd0 = __reduce_or_sync(~0u, (((su + SM_XS + wg * NSTAGE * XS_BYTES) & 0x3FFFF) >> 4) | (1u << 16));
        const uint32_t ed0 = __reduce_or_sync(~0u, (((su + SM_ES + wg * NSTAGE * ES_BYTES) & 0x3FFFF) >> 4) | (8u << 16));
        const uint64_t ohd = __reduce_or_sync(~0u, ((su + SM_OH) & 0x3FFFF) >> 4);
        const uint32_t tabx = __reduce_or_sync(~0u, su + SM_TAB + w * 128);
        const uint32_t bars = __reduce_or_sync(~0u, 2 * bar0 + STG), xds = __reduce_or_sync(~0u, 2 * xd0 + XS_BYTES / 16), eds = __reduce_or_sync(~0u, 2 * ed0 + ES_BYTES / 16);
        const uint32_t xuo = __reduce_or_sync(~0u, su + SM_XU + wg * 16384);
        WS(9);
        constexpr int NU = 6;
        const uint32_t dm = ((NPB_MAX + lane) * 4 | (tag << 14)) * 0x10001u;
        const uint32_t db = su + SM_DEG - (tag << 14);
        const char* const g1 = gs + (uint32_t)(b * (P1B + P2B) + tid * 8);
        int rk[NU][4];
        uint32_t spins = 0;
        {
            uint2 r1[NU];
            mbar_wait_c(ab + 80, 0);
            WS(2);
            #pragma unroll
            for (int i = 0; i < NU; i++) {
                r1[i] = make_uint2(dm, dm);
                if (NB_MIN * 16 >= 384 * (i + 1) || tid + 384 * i < nb * 16) r1[i] = lds64(su + SM_IDX + (tid + 384 * i) * 8);
            }
            #pragma unroll 1
            while (true) {
                uint32_t bad = 0;
                #pragma unroll
                for (int i = 0; i < NU; i++) bad |= r1[i].y ^ dm;
                if (__builtin_expect(!__any_sync(~0u, bad & 0xC000), 1)) break;
                #pragma unroll
                for (int i = 0; i < NU; i++) ld_unit(r1[i], g1 + 384 * 8 * i, (r1[i].y ^ dm) & 0xC000);
                if (++spins > (1u << 22)) break;
            }
            WS(3);
            #pragma unroll
            for (int i = 0; i < NU; i++) {
                rk[i][0] = r1[i].x & 0xFFFF; rk[i][1] = r1[i].x >> 16; rk[i][2] = r1[i].y & 0xFFFF; rk[i][3] = r1[i].y >> 16;
                #pragma unroll
                for (int k = 0; k < 4; k++) asm volatile("red.shared.add.u32 [%0], 1;" :: "r"(db + min((uint32_t)rk[i][k], NPB_MAX * 4 + (tag << 14))) : "memory");
            }
        }
        WS(10);
        asm volatile("bar.sync 11, 512;" ::: "memory");
        int mycls = 0, mycr = 0, dg = lds32(su + SM_DEG + tid * 4);
        if (tid < nn) {
            mycls = NCLS - 1 - (dg <= 40 ? dg : min(41 + ((dg - 41) >> 3), NCLS - 1)); mycr = atomicAdd(&cls[mycls], 1);
        }
        int s0 = 0;
        if (__builtin_expect(dg > 40, 0)) s0 = max(SLOT_CAP - ((dg + 1) & ~1) - atomicAdd(&misc[6], (dg + 1) & ~1), 0);
        asm volatile("bar.sync 1, 384;" ::: "memory");
        WS(12);
        {
            const uint2 c = lds64(su + SM_CLS + lane * 8);
            const int v0 = c.x * (lane > 11 ? ((64 - 2 * lane) << 16) + 1 : 1), v1 = c.y * (lane >= 11 ? ((62 - 2 * lane) << 16) + 1 : 1);
            int inc = v0 + v1;
            #pragma unroll
            for (int o = 1; o < 32; o <<= 1) { int y = __shfl_up_sync(~0u, inc, o); if (lane >= o) inc += y; }
            const int e0 = __shfl_sync(~0u, inc - v0 - v1, mycls >> 1), e1 = __shfl_sync(~0u, inc - v1, mycls >> 1);
            const int e = (mycls & 1) ? e1 : e0;
            if (tid < nn) {
                if (dg <= 40) s0 = min((e >> 16) + mycr * ((dg + 1) & ~1), SLOT_CAP - 40);
                sts32(su + SM_DEG + tid * 4, s0);
            }
            const uint32_t pos = tid < nn ? (e & 0xFFFF) + mycr : tid;
            sts32(su + SM_SORT + pos * 4, tid < nn ? (uint32_t)tid | ((uint32_t)s0 << 16) : NONE);
            asm volatile("st.shared.u16 [%0], %1;" :: "r"(su + SM_SDEG + pos * 2), "r"(min(dg, 65535)) : "memory");
            if (tid == 383) { misc[4] = (nn - c.y + 3) >> 2; if ((inc >> 16) + misc[6] > SLOT_CAP - 40) misc[1] = 1; }
        }
        asm volatile("bar.sync 1, 384;" ::: "memory");
        WS(13);
        const uint32_t sv = lds32(su + SM_SORT + tid * 4);
        const uint2 d4 = lds64(su + SM_SDEG + (tid >> 2) * 8);
        const uint32_t slow = lds32(su + SM_MISC + 4);
        #pragma unroll
        for (int i = 0; i < NU; i++) {
            #pragma unroll
            for (int k = 0; k < 4; k++) rk[i][k] = atoms_inc(db + rk[i][k]);
        }
        if (__reduce_or_sync(~0u, slow) == 0) {
            const uint32_t nd = sv & 0xFFFF;
            const int g = tid >> 2;
            dg = ((t & 2 ? d4.y : d4.x) >> (16 * (t & 1))) & 0xFFFF;
            const uint32_t hi2 = __vmaxu2(d4.x, d4.y), lo2 = __vminu2(d4.x, d4.y);
            const int mx = max(hi2 >> 16, hi2 & 0xFFFF), mn = min(lo2 >> 16, lo2 & 0xFFFF);
            int left = (mx + 1) >> 1;
            int tl = g, nx = ngroups + 4 + g, nt = left > NPMAX ? 2 : 1;
            const bool odd = left > 2 * NPMAX || (nt == 2 && nx >= TILE_CAP - TILE_X);
            if (__builtin_expect(__any_sync(~0u, odd), 0)) {
                if (odd) nt = (left + NPMAX - 1) / NPMAX;
                if (odd && t == 0) { asm volatile("atom.shared.add.u32 %0, [%1], %2;" : "=r"(nx) : "r"(su + SM_MISC + 20), "r"(nt - 1) : "memory"); if (nx + nt - 1 > TILE_CAP) misc[1] = 1; }
                nx = __shfl_sync(~0u, nx, lane & ~3);
                if (odd && nx + nt - 1 > TILE_CAP) left = 0;
            }
            const uint32_t w0 = tab_at(nd);
            if (g >= ngroups + 4) tl = ngroups;
            uint32_t cont = 0;
            int done = 0;
            bool act = true;
            do {
                int np = nt <= 2 ? (left + nt - 1) >> (nt - 1) : (left + nt - 1) / nt;
                left -= np; nt = max(nt - 1, 1);
                if (np) np = max(np, NPMIN);
                const int dv = min(max(dg - done, 0), 2 * np);
                uint32_t code = (uint32_t)np | cont | (left > 0 ? C_MORE : 0u);
                const bool gen = mn - done < 2 * np - (np == NPMIN ? 1 : 2);
                if (np == 0) code = 0;
                const uint32_t w1 = code | (dv == 2 * np ? 0x8000u : (2 * np - 1 - dv) << 8);
                if (act) *(uint2*)(smem + SM_TINFO + tl * 32 + t * 8) = make_uint2((dv ? (sv >> 16) + done : 0) | ((gen ? (np > 8 ? 15 : np > 5 ? 14 : 13) : np) << 16) | ((left > 0 ? nx : g >= ngroups - (KM + 3)) << 20) | ((uint32_t)dv << 27), w0 | (np == 0 ? 0u : w1 << 16));
                tl = nx++; cont = C_CONT; done += 2 * np; act = left > 0;
            } while (__any_sync(~0u, act));
        }
        __syncwarp();
        asm volatile("bar.arrive 4, 512;" ::: "memory");
        WS(14);
        #pragma unroll
        for (int pc = 0; pc < 3; pc++) {
            uint4 r2[2];
            mbar_wait_c(ab + pc * 8, 1);
            if (pc == 0) WS(4); if (pc == 2) WS(16);
            #pragma unroll
            for (int k = 0; k < 2; k++) {
                r2[k] = lds128(su + SM_P2 + (tid + 384 * (2 * pc + k)) * 16);
                if (rk[2 * pc + k][0] < 0) r2[k].w = tag << 16;
            }
            while (__builtin_expect(__any_sync(~0u, ((r2[0].w ^ (tag << 16)) | (r2[1].w ^ (tag << 16))) & 0x30000), 0)) {
                #pragma unroll
                for (int k = 0; k < 2; k++)
                    ld_unit(r2[k], g1 + (uint32_t)(tid * 8) + (P1B + 384 * 16 * (2 * pc + k)), (r2[k].w ^ (tag << 16)) & 0x30000);
                if (++spins > (1u << 22)) break;
            }
            #pragma unroll
            for (int k = 0; k < 2; k++) {
                const int i = 2 * pc + k;
                const uint32_t eb = ((tid >> 4) + 24 * i) * ch;
                place(su, rk[i][0], r2[k].x, eb); place(su, rk[i][1], r2[k].y, eb); place(su, rk[i][2], r2[k].z, eb); place(su, rk[i][3], r2[k].w, eb);
            }
        }
        WGD();
        __syncwarp();
        asm volatile("bar.arrive 3, 480;" ::: "memory");
        float g[4 * NPMAX], h[4 * NPMAX];
        float4 cyr = make_float4(0.f, 0.f, 0.f, 0.f);
        WS(15); CG(1);
        mbar_wait_c(ab + 88 + wg * 8, 0);
        auto pack = [&](uint32_t* v, const float* u) {
            #pragma unroll
            for (int i = 0; i < 16; i++) v[i] = pack_bf16(u[2*i], u[2*i+1]);
        };
        auto rows_st = [&](uint32_t p, const uint32_t* v) {
            #pragma unroll
            for (int i = 0; i < 4; i++) stsm4t(p + i * 2048, v + 4 * i);
        };
        {
            const uint64_t d0 = desc_sw128(xuo), d1 = d0 + 512;
            const uint32_t mr = su + wg * 16384 + w * 128 + (tab_at(8 * (lane >> 4) + (lane & 7)) ^ ((lane & 8) << 1));
            uint32_t v[16];
            node_mma(g, wn, d0); node_mma(h, wn, d1);
            TileMMA<8>::wait_g(g);
            pack(v, g); rows_st(mr + SM_TAB, v);
            node_mma(g, wn + 16, d0);
            TileMMA<8>::wait_g(h);
            pack(v, h); rows_st(mr + SM_TAB + 8192, v);
            node_mma(h, wn + 16, d1);
            __syncwarp();
            if (lane == 0) mbar_arrive(su + SM_ABAR + 112);
            TileMMA<8>::wait_g(g);
            pack(v, g);
            asm volatile("bar.sync %0, 128;" :: "r"(8 + wg) : "memory");
            rows_st(mr + SM_XU, v);
            TileMMA<8>::wait_h(h);
            pack(v, h);
            asm volatile("bar.sync %0, 128;" :: "r"(8 + wg) : "memory");
            rows_st(mr + SM_XU + 8192, v);
            wf[16] = lds32(wca); wf[17] = lds32(wca + 256); wf[18] = lds32(wca ^ 16); wf[19] = lds32((wca ^ 16) + 256);
            { const uint2 z = lds64(su + SM_OH + 8); wf[38] = z.x; wf[39] = z.y; }
            #pragma unroll
            for (int i = 32; i < 36; i++) wf[i] ^= wf[38];
            __syncwarp();
            if (lane == 0) mbar_arrive(su + SM_ABAR + 72);
            mbar_wait_c(ab + 112, 0);
            __syncwarp();
            if (__builtin_expect(__reduce_or_sync(~0u, lds32(su + SM_MISC + 4)) != 0, 0)) { slow_bin(x, ea, src, dst, wa, wb, wc, wu, wv, out, E, node0, nn, 384); asm volatile("exit;"); }
            WS(6);
        }
        uint32_t bar = bar0, xd = xd0, ed = ed0, ph = 0;
        float pn0 = 0.f, pd0 = 1.f, pn1 = 0.f, pd1 = 1.f;
        uint4 rc;
        rc.x = lds32(su + SM_TINFO + wg * 32 + ((lane >> 1) & 3) * 8 + 4);
        uint32_t code = __reduce_or_sync(~0u, rc.x >> 16);
        rc.x = (rc.x & 0xFFFF) ^ ((lane & 8) << 1);
        uint32_t pst = tabx + tab_at(NONE);
        auto fetch_a = [&]() {
            asm volatile("ldmatrix.sync.aligned.m8n8.x2.trans.shared.b16 {%0,%1}, [%2];" : "=r"(wf[36]), "=r"(wf[37]) : "r"(tabx + rc.x) : "memory");
        };
        auto emit = [&]() {
            asm volatile("stmatrix.sync.aligned.m8n8.x1.trans.shared.b16 [%0], {%1};" :: "r"(pst), "r"(pack_bf16(pn0 * rcpf(pd0), pn1 * rcpf(pd1))) : "memory");
        };
        auto carry = [&]() {
            if (rc.z & C_CONT) { pn0 += cyr.x; pd0 += cyr.y; pn1 += cyr.z; pd1 += cyr.w; }
            if (rc.z & C_MORE) { cyr = make_float4(pn0, pd0 - EPS2, pn1, pd1 - EPS2); pn0 = pn1 = 0.f; pst = tabx + tab_at(NONE); }
        };
        fetch_a();
        while (true) {
            switch (code & 15) {
                default: goto finished;
#define TILE(P) { \
                    bool ok; float dmin; \
                    do { \
                        mbar_wait_c(bar, ph); \
                        TileMMA<P>::issue(g, h, wf, xd, ed | EDHI, ohd, wcd); \
                        const uint32_t eb = bar + 8; \
                        ph ^= bar != bar0; bar = bars - bar; xd = xds - xd; ed = eds - ed; \
                          \
                        asm volatile("{\n.reg .pred p;\nsetp.eq.u32 p, %0, 77;\n@p trap;\n}" :: "r"(xds) : "memory"); \
                        rc = lds128(eb + 8 + l16); \
                        TileMMA<P>::wait_g(g); \
                        fetch_a(); emit(); \
                        TileMMA<P>::wait_h(h); \
                        mbar_arrive(eb); \
                        asm volatile("add.u32 %0, %1, %2;" : "=r"(pst) : "r"(rc.y), "r"(tabx)); \
                        ok = epi_fast<P>(g, h, __uint_as_float(rc.z), __uint_as_float(rc.w), pn0, pd0, pn1, pd1, dmin); \
                    } while (__all_sync(~0u, ok)); \
                    code = __reduce_or_sync(~0u, rc.w); \
                    if (__builtin_expect(__any_sync(~0u, ((rc.z & 0x1F00) != 0) | (dmin < TAU * 2 * P)), 0)) { \
                        int dv; \
                        const bool on = unpad(rc.z, P, g[4 * P - 4], g[4 * P - 2], pd0, pd1, dv); \
                        const uint32_t bad = __ballot_sync(~0u, on); \
                        if (__builtin_expect(bad != 0, 0)) { \
                            const float4 r = epi_exact<P>(g, h, bad, on, dv, su + SM_COPY, l16); \
                            if (on) { pn0 = r.x; pd0 = r.y; pn1 = r.z; pd1 = r.w; } \
                        } \
                    } \
                    if (code & C_BRK) { carry(); if (P != 11 && (code & 15) == P) goto L##P; } \
                    if (P == 11) {         \
                        wf[16] = lds32(wca); wf[17] = lds32(wca + 256); wf[18] = lds32(wca ^ 16); wf[19] = lds32((wca ^ 16) + 256); \
                    } }
#define CASE(P, UP, DN) case P: L##P: TILE(P) \
                    if (P > NPMIN && (code & 15) == P - 1) goto L##DN; \
                    if ((code & 15) == UP) goto L##UP; \
                    break;
                CASE(11, 11, 10) CASE(10, 11, 9) CASE(9, 10, 8) CASE(8, 9, 7) CASE(7, 8, 6) CASE(6, 7, 5) CASE(5, 6, 5)
#undef CASE
#undef TILE
            }
        }
finished:
        emit();
        __syncwarp();
        if (lane == 0) mbar_arrive(su + SM_ABAR + 48 + wg * 8);
    } else {
        asm volatile("setmaxnreg.dec.sync.aligned.u32 56;");
        auto x_ld = [&](int i0, int i1) {
            #pragma unroll
            for (int i = i0; i < i1; i++) w_box_ld(su + SM_XU + i * 8192, &tmx, node0 + i * 64, su + SM_ABAR + 88 + (i >> 1) * 8);
        };
        if (w < 3) {
            #pragma unroll
            for (int i = 0; i < 2; i++) { w_init(su + SM_BARS + (w * 2 + i) * STG, 64); w_init(su + SM_BARS + (w * 2 + i) * STG + 8, 128); }
            w_init(su + SM_ABAR + 48 + w * 8, 4);
            w_init(su + (w == 0 ? SM_GBAR + 99 * 8 : w == 1 ? SM_ABAR + 72 : SM_ABAR + 112), w == 0 ? 32 : 12);
        } else {
            #pragma unroll
            for (int i = 0; i < 4; i++) { w_init(su + SM_ABAR + (i < 3 ? 88 + i * 8 : 40), 1); w_expect(su + SM_ABAR + (i < 3 ? 88 + i * 8 : 40), i < 3 ? 16384 : nb * 64); }
            asm volatile("fence.mbarrier_init.release.cluster;" ::: "memory");
            w_hint(gbar + 1, all);
            asm volatile("cp.async.bulk.wait_group.read 0;" ::: "memory");
            WS(2);
            w_ld(su + SM_IDX, gs + b * (P1B + P2B), nb * (CE * 2), su + SM_ABAR + 80);
            w_ld(su + SM_H1, gs + G_H1, nb * 64, su + SM_ABAR + 120);
            asm volatile("bar.sync 12, 512;" ::: "memory");
            w_box_st(&tm2, P1B / 4 + b * CE, su + SM_P2);
            w_st(gs + G_H2 + b * 64, su + SM_P2 + P2B, 64);
            w_st(gs + G_L + b * 512 + 256, su + SM_P2 + P2B, 256);
            w_sent(gbar + 4, su + SM_MISC + 32);
            asm volatile("cp.async.bulk.commit_group;" ::: "memory");
        }
        const uint32_t ab = su + SM_ABAR;
        uint32_t todo = 0;
        const uint32_t mb = (lane & 3) == 3 ? bin_bits(b) : ~0u;
        WS(12);
        mbar_wait_c(ab + 120, 0);
        WS(13);
        {
            uint4 r[5];
            #pragma unroll
            for (int i = 0; i < 5; i++) r[i] = lds128(sbase + SM_H1 + (tid - 384 + 128 * i) * 16);
            #pragma unroll
            for (int i = 0; i < 5; i++) {
                const uint32_t bb = b << 16;
                const uint32_t m = min(min(r[i].x ^ bb, r[i].y ^ bb), min(r[i].z ^ bb, r[i].w ^ bb)) >> 16;
                if ((m == 0) | (((r[i].w ^ (tag << 14)) & 0xC000) != 0) | ((~r[i].w & mb) == 0)) todo |= 1 << i;
            }
            todo &= tid - 384 + 512 < nb * 4 ? 31 : tid - 384 + 384 < nb * 4 ? 15 : 7;
        }
        #pragma unroll 1
        for (int put = 0; put < 2; put++) {
            uint32_t any = __reduce_or_sync(~0u, todo), m = 0, u = 0;
            #pragma unroll 1
            while (any | m) {
                uint4 r = make_uint4(0, 0, 0, 0), r2 = r;
                uint32_t s, go, gd;
                bool on;
                if (__builtin_expect(m == 0, 1)) {
                    const uint32_t i = __ffs(any) - 1;
                    any &= any - 1; u = tid - 384 + 128 * i; on = (todo >> i) & 1;
                    r = lds128(sbase + SM_H1 + u * 16); r2 = lds128(sbase + SM_H2 + u * 16);
                    s = u >> 2; go = G_H1 + u * 16; gd = HB;
                } else {
                    s = ((u & ~31) + __ffs(m) - 1) >> 2; m &= m - 1; on = lane < 12;
                    go = G_L + s * 512 + 64 + lane * 16; gd = 256;
                }
                #pragma unroll 1
                for (int n = 0; n < (1 << 22); n++) {
                    const bool b1 = on && ((r.w >> 14) & 3) != tag, b2 = on && put && ((r2.w >> 16) & 3) != tag;
                    if (__builtin_expect(!__any_sync(~0u, b1 | b2), 1)) break;
                    ld_unit(r, gs + go, b1); ld_unit(r2, gs + go + gd, b2);
                }
                if (gd == HB) m = __ballot_sync(~0u, on && (~r.w & mb) == 0);
                if (on && r.w >> 16 == 255) sts32(sbase + SM_MISC + 4, 1);
                const uint32_t e[4] = {r.x, r.y, r.z, r.w}, v[4] = {r2.x, r2.y, r2.z, r2.w};
                uint32_t slot[4];
                #pragma unroll
                for (int k = 0; k < 4; k++) slot[k] = atoms_inc(sbase + SM_DEG + (on && e[k] >> 16 == (uint32_t)b ? (e[k] & 0x3FFF) : (NPB_MAX + lane) * 4));
                if (put) {
                    #pragma unroll
                    for (int k = 0; k < 4; k++) place(sbase, slot[k], v[k], s * ch);
                }
            }
            if (put == 0) {
                WS(4);
                asm volatile("bar.arrive 11, 512;" ::: "memory");
                if (w == 3) {
                    x_ld(0, 1);
                    w_expect(su + SM_ABAR, 12288); w_expect(su + SM_ABAR + 8, 12288); w_expect(su + SM_ABAR + 16, nb * (CE * 4) - 24576);
                    w_hint(gbar + 4, all);
                    asm volatile("cp.async.bulk.wait_group.read 0;" ::: "memory");
                    WS(3);
                    const char* g2 = gs + b * (P1B + P2B) + P1B;
                    w_ld(su + SM_P2, g2, 12288, su + SM_ABAR);
                    w_ld(su + SM_P2 + 12288, g2 + 12288, 12288, su + SM_ABAR + 8);
                    w_ld(su + SM_P2 + 24576, g2 + 24576, nb * (CE * 4) - 24576, su + SM_ABAR + 16);
                    w_ld(su + SM_H2, gs + G_H2, nb * 64, su + SM_ABAR + 40);
                    x_ld(1, 2);
                    mbar_wait_c(ab, 1);
                    x_ld(2, 6);
                } else {
                    #pragma unroll 11
                    for (int i = 0; i < 33; i++) w_init(su + SM_GBAR + (w * 33 + i) * 8, 32);
                    w_init(su + SM_GBAR + GD * 8, 32);
                }
                asm volatile("bar.sync 4, 512;" ::: "memory");
                mbar_wait_c(ab + 40, 0);
            }
        }
        __syncwarp();
        WS(10);
        WGD();
        const uint32_t scr = sbase + SM_PAIR + (tid & 127) * 8;
        const int r4 = lane >> 3, c8 = lane & 7;
        const uint32_t sb = su;
        const uint32_t tk = ((c8 & 1) << 4) | ((c8 >> 1) << 7);
        if (w < 3) {
            const char* gx = as_pair((const char*)x + c8 * 16, scr);
            const char* ge = as_pair((const char*)ea + (lane & 1) * 16, scr);
            const uint32_t gx0 = (uint32_t)(uint64_t)gx, ge0 = (uint32_t)(uint64_t)ge, hi = (uint64_t)gx >> 32, he = (uint64_t)ge >> 32;
            const int s = (lane >> 1) & 3;
            const uint32_t xs0 = sb + SM_XS + w * NSTAGE * XS_BYTES;
            const uint32_t es0 = sb + SM_ES + w * NSTAGE * ES_BYTES + r4 * 64 + (((lane ^ (r4 >> 1)) & 1) << 4) + (s >> 1) * 256 + (s & 1) * 32;
            const uint32_t bars = sb + SM_BARS + w * 2 * STG;
            const uint32_t xoffA = (2 * r4) * 128 + ((c8 ^ (2 * r4)) << 4);
            uint64_t pol;
            asm volatile("createpolicy.fractional.L2::evict_first.b64 %0, 1.0;" : "=l"(pol));
            asm volatile("bar.sync 6, 128;" ::: "memory");
            WS(15);
            uint32_t ph = 1, cur = w;
            uint32_t hist = GD * 0x010101u;
            auto done3 = [&]() { uint32_t v = (hist >> 16) & 0xFF; asm("" : "+r"(v)); mbar_arrive(sb + SM_GBAR + v * 8); };
            const bool go = __reduce_or_sync(~0u, misc[1] == 0 && nn > 0);
            const uint32_t ra = __shfl_sync(~0u, (lane & 15) * 16 + 32, lane), k15 = __shfl_sync(~0u, 15 | (lane & 1) << 7, lane), ca = SM_CLAIM + min(lane, 30) * 4, pa = sb + SM_TINFO + r4 * 8;
            const uint32_t pb = sb + SM_TINFO + s * 8 + 4, pc = sb + SM_TINFO + (lane & 3) * 8 + 6, xl = (lane & 8) << 1, xs = ra & 16;
            auto row_of = [&](uint32_t o) { uint32_t v; asm volatile("ld.shared.u16 %0, [%1];" : "=r"(v) : "r"(pb + o) : "memory"); return v; };
            auto code_of = [&](uint32_t o) { uint32_t v; asm volatile("ld.shared.s16 %0, [%1];" : "=r"(v) : "r"(pc + o) : "memory"); return v; };
            uint32_t pw = lds32(pa + w * 32), pt = __reduce_or_sync(~0u, pw), cont = 1;
            uint4 rc = make_uint4(0, row_of(w * 32) ^ xs, code_of(w * 32) & (ONE_F | 0x1FFFu), 0);
            const uint32_t se0 = sb + SM_EID + s * 4, brs = 2 * bars + STG;
            uint32_t br = bars, da = xs0 + xoffA, de = es0, ue = ES_BYTES;
            #pragma unroll 1
            while (go) {
                uint32_t se, sx;
                asm("dp2a.lo.u32.u32 %0, %1, 4, %2;" : "=r"(se) : "r"(pw), "r"(se0));
                asm("dp2a.lo.u32.u32 %0, %1, 2, %2;" : "=r"(sx) : "r"(pw), "r"(sb + SM_SRC));
                const int dv = pw >> 27;
                const uint32_t db = da ^ 0x90;
                const uint32_t sel = (pt >> 16) & 15, nf = (pt >> 15) & (127 << 5), nx = nf == 32 ? 0u : nf;
                uint32_t g;
                auto claim = [&]() { asm volatile("atom.shared.add.u32 %0, [%1], %2;" : "=r"(g) : "r"(ca + (nx == 0 ? sb : sb + 4)), "r"(ra) : "memory"); };
                if (sel == 0) break;
                if ((cont & 1) | (nf ^ nx)) {
                    if (cont & 1) asm volatile("bar.sync 3, 480;" ::: "memory");
                    if (nf != nx) mbar_wait_c(sb + SM_ABAR + 32, 0);
                }
                switch (sel) {
#define CASE(L, P, GEN) case L: { \
                        uint32_t oe[(P + 1) / 2], o[P]; \
                        _Pragma("unroll") for (int j = 0; j < (P + 1) / 2; j++) oe[j] = lds32(se + j * 16); \
                        _Pragma("unroll") for (int j = 0; j < P; j++) o[j] = lds32(sx + j * 4); \
                        mbar_wait_h(br + 8, ph); \
                        _Pragma("unroll") for (int j = 0; j < (P + 1) / 2; j++) \
                            if (LO32) { if (!GEN && 2 * j + 2 < P) cpe<false>(he, de + j * 512, oe[j], ge0, 0, 0, pol); \
                                else if (2 * j + 1 < NPMAX || s < 2) cpe<true>(he, de + j * 512, oe[j], ge0, 4 * j + s, dv, pol); } \
                            else if (!GEN && 2 * j + 2 < P) cp16e(de + j * 512, ge, oe[j], pol); else if (2 * j + 1 < NPMAX || s < 2) cp16z<32>(de + j * 512, ge, oe[j], 4 * j + s, dv, pol); \
                        _Pragma("unroll") for (int j = 0; j < P - 1; j++) { \
                            if (LO32) { cpx<0, GEN>(hi, da + j * 1024, o[j], gx0, 2 * j, dv); cpx<1, GEN>(hi, db + j * 1024, o[j], gx0, 2 * j + 1, dv); } \
                            else if (GEN) { cp16z<128>(da + j * 1024, gx, o[j] & 0xFFFFu, 2 * j, dv, 0); cp16z<128>(db + j * 1024, gx, o[j] >> 16, 2 * j + 1, dv, 0); } \
                            else { cp16i<128>(da + j * 1024, gx, o[j] & 0xFFFFu); cp16i<128>(db + j * 1024, gx, o[j] >> 16); } } \
                        if (LO32) { cpx<0, true>(hi, da + (P - 1) * 1024, o[P - 1], gx0, 2 * P - 2, dv); cpx<1, true>(hi, db + (P - 1) * 1024, o[P - 1], gx0, 2 * P - 1, dv); } \
                        else { cp16z<128>(da + (P - 1) * 1024, gx, o[P - 1] & 0xFFFFu, 2 * P - 2, dv, 0); cp16z<128>(db + (P - 1) * 1024, gx, o[P - 1] >> 16, 2 * P - 1, dv, 0); } \
                    } break;
                    CASE(11, 11, false) CASE(6, 6, false) CASE(7, 7, false) CASE(8, 8, false) CASE(9, 9, false) CASE(10, 10, false)
                    CASE(15, NPMAX, true) CASE(14, 8, true) default: CASE(13, 5, true)
#undef CASE
                }
                claim();
                mbar_cp_arrive(br);
                done3();
                g = __reduce_min_sync(~0u, g);
                {
                    const uint32_t o = nx == 0 ? g : nx;
                    pw = lds32(pa + o);
                    const uint32_t ya = row_of(o), yb = code_of(o);
                    pt = __reduce_or_sync(~0u, pw);
                    const uint32_t brk = (cont | nx) > 1 ? C_BRK : 0u;
                    rc.x = ya ^ xl;
                    const uint32_t lv = brk | ((sel + (15 - NPMAX)) & 16) | (((pt >> 16) & 15) ^ sel);
                    rc.w = (yb & k15) | (lv ? 0x70000000u | brk : TAU_BITS);
                    asm volatile("st.shared.v4.u32 [%2], {%3, %0, %1, %4};\nxor.b32 %0, %5, %6;\nand.b32 %1, %7, %8;"
                                 : "+r"(rc.y), "+r"(rc.z) : "r"(br + ra - 16), "r"(rc.x), "r"(rc.w), "r"(ya), "r"(xs), "r"(yb), "n"(ONE_F | 0x1FFFu) : "memory");
                    cont = nx;
                }
                mbar_arrive(br);
                hist = (hist << 8) | (nx == 0 ? cur : (uint32_t)GD);
                cur = nx == 0 ? g >> 5 : cur;
                da += ue * 4; de += ue; ue = -ue;
                ph ^= br != bars; br = brs - br;
            }
            if (cont & 1) asm volatile("bar.sync 3, 480;" ::: "memory");
            if (go) {
                mbar_wait(sb + SM_ABAR + 32, 0);
                const int g0 = 3 * max((misc[7] + 2) / 3 - TR, 0) + w;
                uint32_t ro[TR], gb[TR]; uint4 xv[TR], xu[TR]; char* op[TR];
                const int gz = misc[4];
                #pragma unroll
                for (int k = 0; k < TR; k++) {
                    uint32_t nd;
                    asm volatile("ld.shared.u16 %0, [%1];" : "=r"(nd) : "r"(pa + (g0 + 3 * k) * 32 + 4) : "memory");
                    uint32_t rb = node0 * 128 + row_bytes(nd);
                    if (g0 + 3 * k >= ngroups) rb = misc[16 + ((g0 + 3 * k - ngroups) & 3) * 4 + r4];
                    if (nd == tab_at(NONE)) rb = 0;
                    xv[k] = __ldg((const uint4*)(gx + rb));
                    op[k] = nd == tab_at(NONE) ? nullptr : (char*)out + rb + c8 * 16;
                    ro[k] = sb + (nd ^ tk);
                    xu[k] = lds128(ro[k] + SM_XU);
                    gb[k] = __reduce_or_sync(~0u, g0 + 3 * k < gz ? sb + SM_GBAR + (g0 + 3 * k) * 8 : 0u);
                }
                #pragma unroll 1
                for (int k = 0; k < 3; k++) {
                    mbar_wait(k < 2 ? br + 8 : sb + SM_ABAR + 48 + w * 8, k < 2 ? ph : 0);
                    done3(); hist <<= 8;
                    ph ^= br != bars; br = brs - br;
                }
                #pragma unroll
                for (int k = 0; k < TR; k++) {
                    uint4 a = make_uint4(0, 0, 0, 0);
                    if (gb[k]) { mbar_wait(gb[k], 0); a = lds128(ro[k] + SM_TAB); }
                    finish(a, xu[k], xv[k]);
                    if (op[k]) *(uint4*)op[k] = a;
                }
            }
            cp_wait<0>();
        } else {
            const int r4 = (lane >> 1) & 3, c8 = (lane >> 3) * 2 + (lane & 1);
            const uint32_t tk = ((c8 & 1) << 4) | ((c8 >> 1) << 7);
            const char* gx = (const char*)x + (size_t)node0 * 128;
            const char* ob = (const char*)out + (size_t)node0 * 128;
            const uint32_t c16 = __shfl_sync(~0u, c8 * 16, lane);
            auto row_bytes = [&](uint32_t o) { return (o & 0xFE00) | (((o << 2) & 0x180) | c16); };
            asm volatile("bar.sync 6, 128;" ::: "memory");
            WS(15);
            if (b == 0 && lane == 0) asm volatile("red.relaxed.gpu.global.add.u32 [%0], 1;" :: "l"(gbar) : "memory");
            if (misc[1] == 0) mbar_wait(sb + SM_ABAR + 72, 0);
            if (npb <= NPB_MAX - 4) sts32(sb + SM_MISC + 12, 0);
            int rounds = misc[1] ? 0 : max((ngroups + 2) / 3 - TR, 0);
            const int gz = misc[4];
            int fast = __reduce_min_sync(~0u, min(rounds, gz / 3));
            const uint32_t wl = SM_TINFO + r4 * 8 + 4;
            uint32_t ko = sb;
            auto row_at = [&](uint32_t a) { uint32_t n; asm volatile("ld.shared.u16 %0, [%1];" : "=r"(n) : "r"(a) : "memory"); return n; };
            auto fetch = [&](uint32_t n, uint4& v) {
                asm volatile("{\n.reg .b64 p;\ncvt.u64.u32 p, %5;\nadd.u64 p, p, %4;\nld.global.nc.L1::no_allocate.v4.u32 {%0,%1,%2,%3}, [p];\n}"
                             : "=r"(v.x), "=r"(v.y), "=r"(v.z), "=r"(v.w) : "l"(gx), "r"(n));
            };
            auto store = [&](uint32_t n, const uint4& a) {
                asm volatile("{\n.reg .b64 p;\ncvt.u64.u32 p, %1;\nadd.u64 p, p, %0;\nst.global.v4.u32 [p], {%2,%3,%4,%5};\n}" :: "l"(ob), "r"(n), "r"(a.x), "r"(a.y), "r"(a.z), "r"(a.w) : "memory");
            };
            const uint32_t tw = __shfl_sync(~0u, tk, lane);
            int step = fast > R3 + PMIN && gz == ngroups ? -1 : -2, k = 0;
            #pragma unroll 1
            do {
                const int gn = __reduce_max_sync(~0u, balance(step, gs, all, ngroups, npb));
                if (step == R3) fast = rounds = (gn + 2) / 3 - TR;
                const bool pub = step < 0 && gn;
                step = gn == 0 || step == R3 ? fast - 1 : step < 0 ? R2 : R3;
                const uint32_t lim = step == fast - 1 ? ~0u : (ngroups - (KM + 3)) * 32;
                if (fast == 0) break;
                uint32_t n0[3], o0[3]; uint4 x0[3];
                #pragma unroll
                for (int r = 0; r < 3; r++) { const uint32_t v = row_at(wl + ko + r * 32); n0[r] = row_bytes(v); o0[r] = v ^ tw; fetch(n0[r], x0[r]); }
                #pragma unroll 1
                for (; k <= step; k++) {
                    const uint32_t wn = k < step ? ko + 96 : ko, gbar = sb + SM_GBAR + k * 24;
                    uint4 xu[3], a[3]; uint32_t v[3], ok;
                    #pragma unroll
                    for (int r = 0; r < 3; r++) { xu[r] = lds128(sb + o0[r] + SM_XU); v[r] = row_at(wl + wn + r * 32); }
#define TRY(o) "mbarrier.try_wait.parity.shared.b64 p, [%1 + " o "], 0, 4000;\n@p bra A_%=;\n"
#define NEXT(o) TRY(o) TRY(o) TRY(o) "bra B_%=;\n"
                    asm volatile("{\n.reg .pred p, q, r;\n.reg .b32 c, n;\nmov.u32 n, 0;\n"
                                 "A_%=:\nmbarrier.test_wait.parity.shared.b64 p, [%1], 0;\nmbarrier.test_wait.parity.shared.b64 q, [%1 + 8], 0;\nmbarrier.test_wait.parity.shared.b64 r, [%1 + 16], 0;\n"
                                 "@!r bra W2_%=;\n@!q bra W1_%=;\n@p bra D_%=;\n"
                                 NEXT("0") "W1_%=:\n" NEXT("8") "W2_%=:\n" NEXT("16")
                                 "B_%=:\nld.volatile.shared.u32 c, [%2];\nadd.u32 n, n, 1;\nsetp.gt.u32 q, n, 0x100000;\n@q trap;\nsetp.le.u32 q, c, %3;\n@q bra A_%=;\n"
                                 "D_%=:\nselp.u32 %0, 1, 0, p;\n}" : "=r"(ok) : "r"(gbar), "r"(sb + SM_CLAIM), "r"(lim) : "memory");
#undef NEXT
#undef TRY
                    if (!ok) break;
                    #pragma unroll
                    for (int r = 0; r < 3; r++) a[r] = lds128(sb + o0[r] + SM_TAB);
                    #pragma unroll
                    for (int r = 0; r < 3; r++) {
                        finish(a[r], xu[r], x0[r]);
                        const uint32_t nd = n0[r];
                        n0[r] = row_bytes(v[r]); o0[r] = v[r] ^ tw;
                        fetch(n0[r], x0[r]);
                        store(nd, a[r]);
                    }
                    ko += 96;
                    if (pub && k == R1) {
                        uint32_t now; asm volatile("mov.u32 %0, %%globaltimer_lo;" : "=r"(now));
                        now = __reduce_max_sync(~0u, (((now + lds32(sb + SM_MISC + 48)) << 6) & ~511u) | 256);
                        sts32(sb + SM_MISC + 48, now);
                        asm volatile(ELECT "st.relaxed.gpu.global.v2.u32 [%0], {%1, %2};\n}" :: "l"(gs + G_F + b * 8), "r"(now), "r"(all) : "memory");
                    }
                }
                if (k <= R1) step = -2;
            } while (k < fast);
            #pragma unroll 1
            for (int g = 3 * fast; g < 3 * rounds; g++) {
                const uint32_t v = row_at(sb + SM_TINFO + r4 * 8 + 4 + g * 32), nd = row_bytes(v), ro = sb + (v ^ tw);
                uint4 xv, a = make_uint4(0, 0, 0, 0);
                fetch(nd, xv);
                if (g < gz) { mbar_wait(sb + SM_GBAR + g * 8, 0); a = lds128(ro + SM_TAB); }
                finish(a, lds128(ro + SM_XU), xv);
                store(nd, a);
            }
        }
    }
    WS(17); WG1(); CG(2);
}

}

extern "C" void kernel_launch(void* const* d_in, const int* in_sizes, int n_in, void* d_out, int out_size) {
    const __nv_bfloat16* x = (const __nv_bfloat16*)d_in[0];
    const __nv_bfloat16* ea = (const __nv_bfloat16*)d_in[1];
    const int* src = (const int*)d_in[2];
    const int* dst = (const int*)d_in[3];
    const __nv_bfloat16* wa = (const __nv_bfloat16*)d_in[4];
    const __nv_bfloat16* wb = (const __nv_bfloat16*)d_in[5];
    const __nv_bfloat16* wc = (const __nv_bfloat16*)d_in[6];
    const __nv_bfloat16* wu = (const __nv_bfloat16*)d_in[7];
    const __nv_bfloat16* wv = (const __nv_bfloat16*)d_in[8];
    __nv_bfloat16* out = (__nv_bfloat16*)d_out;
    int N = in_sizes[0] / 64, E = in_sizes[2];
    static int sms = 0;
    static CUtensorMap tm1, tm2, tmw, tmx;
    static bool tm_ok = false;
    static void* gp = nullptr; static void* gb = nullptr;
    typedef CUresult (*EncFn)(CUtensorMap*, CUtensorMapDataType, cuuint32_t, void*, const cuuint64_t*, const cuuint64_t*, const cuuint32_t*,
                              const cuuint32_t*, CUtensorMapInterleave, CUtensorMapSwizzle, CUtensorMapL2promotion, CUtensorMapFloatOOBfill);
    static void* fn = nullptr;
    auto enc = [&](CUtensorMap* tm, const void* base, cuuint64_t cols, cuuint64_t rows, cuuint32_t bc, cuuint32_t br, CUtensorMapSwizzle sw) {
        cuuint64_t g2[2] = {cols, rows}, gs[1] = {cols * 4};
        cuuint32_t b2[2] = {bc, br}, es[2] = {1, 1};
        return ((EncFn)fn)(tm, CU_TENSOR_MAP_DATA_TYPE_UINT32, 2, (void*)base, g2, gs, b2, es, CU_TENSOR_MAP_INTERLEAVE_NONE, sw,
                           CU_TENSOR_MAP_L2_PROMOTION_NONE, CU_TENSOR_MAP_FLOAT_OOB_FILL_NONE) == CUDA_SUCCESS;
    };
    if (!sms) {
        cudaDeviceGetAttribute(&sms, cudaDevAttrMultiProcessorCount, 0);
        cudaDriverEntryPointQueryResult qr;
        cudaGetDriverEntryPoint("cuTensorMapEncodeTiled", &fn, cudaEnableDefault, &qr);
        cudaGetSymbolAddress(&gp, g_str); cudaGetSymbolAddress(&gb, g_bar);
        if (fn && gp && gb) {
            const cuuint32_t rows = sms < NB_MAX ? sms : NB_MAX;
            tm_ok = enc(&tm1, gp, (P1B + P2B) / 4, NB_MAX, CE / 2, rows, CU_TENSOR_MAP_SWIZZLE_NONE) && enc(&tm2, gp, (P1B + P2B) / 4, NB_MAX, CE, rows, CU_TENSOR_MAP_SWIZZLE_NONE);
        }
        cudaFuncSetAttribute(gcn_kernel<true>, cudaFuncAttributeMaxDynamicSharedMemorySize, SMEM_LAUNCH);
        cudaFuncSetAttribute(gcn_kernel<false>, cudaFuncAttributeMaxDynamicSharedMemorySize, SMEM_LAUNCH);
    }
    int nb = sms < NB_MAX ? sms : NB_MAX;
    int npb = (N + nb - 1) / nb;
    int ch = (((E + nb - 1) / nb) + 3) & ~3;
    const uintptr_t wp[4] = {(uintptr_t)wb, (uintptr_t)wv, (uintptr_t)wa, (uintptr_t)wu};
    uintptr_t wlo = wp[0], whi = wp[0], wal = 0;
    for (int i = 0; i < 4; i++) { wlo = wp[i] < wlo ? wp[i] : wlo; whi = wp[i] > whi ? wp[i] : whi; wal |= wp[i] - wp[0]; }
    bool ok = tm_ok && nb >= NB_MIN && npb < NPB_MAX && ch <= CH_MAX && !(E & 3) && N <= 65535 && npb >= 2 && !(wal & 127) && (whi - wlo) >> 7 < (1u << 30) &&
              !(((uintptr_t)src | (uintptr_t)dst | (uintptr_t)x | (uintptr_t)wb | (uintptr_t)wc) & 15);
    ok = ok && enc(&tmw, (const void*)wlo, 32, ((whi - wlo) >> 7) + 64, 32, 64, CU_TENSOR_MAP_SWIZZLE_128B) && enc(&tmx, x, 32, N, 32, 64, CU_TENSOR_MAP_SWIZZLE_128B);
    if (!ok) {
        int g = 1024, p = (N + g - 1) / g;
        slow_kernel<<<g, 256>>>(x, ea, src, dst, wa, wb, wc, wu, wv, out, N, E, p < 1 ? 1 : p);
        return;
    }
    int4 wrow = make_int4((int)((wp[0] - wlo) >> 7), (int)((wp[1] - wlo) >> 7), (int)((wp[2] - wlo) >> 7), (int)((wp[3] - wlo) >> 7));
    uint32_t magic = (uint32_t)((1ull << 32) / (uint32_t)npb) + 1u;
    void* args[] = {&dst, &gb, &gp, &src, &E, &ch, &N, &npb, &magic, &x, &ea, &wa, &wb, &wc, &wu, &wv, &out, &wrow, &tm1, &tm2, &tmw, &tmx};
    const bool lo32 = ((uintptr_t)x >> 32) == (((uintptr_t)x + (size_t)N * 128 - 1) >> 32) && ((uintptr_t)ea >> 32) == (((uintptr_t)ea + (size_t)E * 32 - 1) >> 32);
    cudaLaunchCooperativeKernel(lo32 && !FORCE64 ? (const void*)gcn_kernel<true> : (const void*)gcn_kernel<false>, dim3(nb), dim3(THREADS), args, SMEM_LAUNCH, cudaStreamPerThread);
}
```
